```python
import torch

def _softmax(x, axis=-1):
    return torch.softmax(x, dim=axis)

def _gelu(x):
    return torch.nn.functional.gelu(x, approximate='tanh')

def _silu(x):
    return torch.nn.functional.silu(x)

def _sigmoid(x):
    return torch.sigmoid(x)

def _layernorm(x, axis=-1, eps=1e-05):
    m = x.mean(dim=axis, keepdim=True)
    v = x.var(dim=axis, keepdim=True, unbiased=False)
    return (x - m) / torch.sqrt(v + eps)

def _scatter_add(tgt, idx, src, axis=0):
    return tgt.clone().index_add_(axis, idx, src)

def _segment_sum(src, seg, n):
    out = torch.zeros((n,) + src.shape[1:], dtype=src.dtype)
    return out.index_add_(0, seg, src)

def _pad(x, pw):
    flat = tuple((v for pair in reversed(pw) for v in pair))
    return torch.nn.functional.pad(x, flat)
kernel_name = 'adaLN_cond__memory_aug_recurrent_mem_tr__mixer_s_mlp__prompt'

def setup_inputs():

    _w = lambda a: (lambda t: t.to(torch.bfloat16) if t.is_floating_point() else t)(torch.as_tensor(a))

    def _A_setup():
        B, S, Dm = (1, 2048, 1024)
        H, Dh = (32, 128)
        M, seg = (8, 32)
        seg = min(seg, S)
        S = S // seg * seg
        return {'x': _w((lambda *s: torch.randn(*s, dtype=torch.bfloat16) * 0.05)(B, S, Dm)), 'mem0': _w((lambda *s: torch.randn(*s, dtype=torch.bfloat16) * 0.4)(B, M, Dm)), 'Wq': _w((lambda *s: torch.randn(*s, dtype=torch.bfloat16) * 3.2)(Dm, H, Dh) * Dm ** (-0.5)), 'Wk': _w((lambda *s: torch.randn(*s, dtype=torch.bfloat16) * 3.2)(Dm, H, Dh) * Dm ** (-0.5)), 'Wv': _w((lambda *s: torch.randn(*s, dtype=torch.bfloat16) * 0.4)(Dm, H, Dh) * Dm ** (-0.5)), 'Wo': _w((lambda *s: torch.randn(*s, dtype=torch.bfloat16) * 0.4)(H, Dh, Dm) * (H * Dh) ** (-0.5)), 'seg_len': seg}
    _A_in = _A_setup()

    def _B_setup():
        B, S, D, F = (1, 2048, 1024, 3584)
        return {'x': _w((lambda *s: torch.randn(*s, dtype=torch.bfloat16) * 0.05)(B, S, D)), 'w1': _w((lambda *s: torch.randn(*s, dtype=torch.bfloat16) * 3.2)(D, D) * D ** (-0.5)), 'w2': _w((lambda *s: torch.randn(*s, dtype=torch.bfloat16) * 3.2)(D, D) * D ** (-0.5)), 'w3': _w((lambda *s: torch.randn(*s, dtype=torch.bfloat16) * 3.2)(D, F) * D ** (-0.5)), 'w4': _w((lambda *s: torch.randn(*s, dtype=torch.bfloat16) * 3.2)(F, D) * F ** (-0.5))}
    _B_in = _B_setup()
    return {'A_x': _A_in['x'], 'A_mem0': _A_in['mem0'], 'A_Wq': _A_in['Wq'], 'A_Wk': _A_in['Wk'], 'A_Wv': _A_in['Wv'], 'A_Wo': _A_in['Wo'], 'A_seg_len': _A_in['seg_len'], 'B_x': _B_in['x'], 'B_w1': _B_in['w1'], 'B_w2': _B_in['w2'], 'B_w3': _B_in['w3'], 'B_w4': _B_in['w4'], 'c': _w((lambda *s: torch.randn(*s, dtype=torch.bfloat16) * 0.1)(1, 1024) * 8.0), 'w_mod': _w((lambda *s: torch.randn(*s, dtype=torch.bfloat16) * 0.1)(1024, 6 * 1024) * 1024 ** (-0.5) * 8.0)}

def reference(A_x, A_mem0, A_Wq, A_Wk, A_Wv, A_Wo, A_seg_len, B_x, B_w1, B_w2, B_w3, B_w4, c, w_mod):

    def _A_ref(x, mem0, Wq, Wk, Wv, Wo, seg_len):
        B, S, Dm = x.shape
        H, Dh = (Wq.shape[1], Wq.shape[2])
        M = mem0.shape[1]
        scale = Dh ** (-0.5)
        n_seg = S // seg_len
        L = M + seg_len
        idx = torch.arange(L)
        mask = (idx[:, None] < M) | (idx[:, None] >= idx[None, :])
        mem = mem0
        outs = []
        for s in range(n_seg):
            xs = x[:, s * seg_len:(s + 1) * seg_len, :].clone()
            h = torch.concatenate([mem, xs], axis=1)
            q = torch.einsum('btd,dhe->bhte', h, Wq)
            k = torch.einsum('btd,dhe->bhte', h, Wk)
            v = torch.einsum('btd,dhe->bhte', h, Wv)
            scores = torch.einsum('bhqe,bhke->bhqk', q, k) * scale
            scores = torch.where(mask[None, None], scores, -1000000000.0)
            p = _softmax(scores, axis=-1)
            o = torch.einsum('bhqk,bhke->bhqe', p, v)
            o = torch.einsum('bhte,hed->btd', o, Wo)
            mem = o[:, :M, :].clone()
            outs.append(o[:, M:, :])
        return torch.concatenate(outs, axis=1)

    def _B_ref(x, w1, w2, w3, w4):
        B, S, D = x.shape
        h = _gelu(_layernorm(x, axis=-1) @ w1)
        c = D // 4
        g0 = _pad(h[:, :, 0 * c:1 * c], ((0, 0), (1, 0), (0, 0)))[:, :S, :]
        g1 = _pad(h[:, :, 1 * c:2 * c], ((0, 0), (0, 1), (0, 0)))[:, 1:, :]
        g2 = _pad(h[:, :, 2 * c:3 * c], ((0, 0), (2, 0), (0, 0)))[:, :S, :]
        g3 = _pad(h[:, :, 3 * c:], ((0, 0), (0, 2), (0, 0)))[:, 2:, :]
        hs = torch.concatenate([g0, g1, g2, g3], axis=-1) @ w2
        x1 = x + hs
        h2 = _gelu(_layernorm(x1, axis=-1) @ w3) @ w4
        return x1 + h2
    x = A_x
    mod = (_silu(c) @ w_mod).reshape(c.shape[0], 6, 1, -1)
    sa, ca, ga, sb, cb, gb = (mod[:, 0].clone(), mod[:, 1].clone(), mod[:, 2].clone(), mod[:, 3].clone(), mod[:, 4].clone(), mod[:, 5].clone())
    h = _layernorm(x, axis=-1) * (1 + ca) + sa
    x = x + ga * _A_ref(h, A_mem0, A_Wq, A_Wk, A_Wv, A_Wo, A_seg_len)
    h = _layernorm(x, axis=-1) * (1 + cb) + sb
    x = x + gb * _B_ref(h, B_w1, B_w2, B_w3, B_w4)
    return x
```

```cpp
#include <cuda_runtime.h>
#include <cuda.h>
#include <cuda_bf16.h>
#include <stdint.h>
#include <limits.h>

typedef __nv_bfloat16 bf16;

constexpr int S_ = 2048, DM = 1024, NH = 32, DH = 128, NSEG = 64, FF = 3584;
constexpr int SPIN_LIMIT = 1 << 22;
#define W_INFL 2
#define XP 0
#define H_PIECES 4
#define NPROBE 3

__device__ uint8_t g_arena[10 << 20];
__device__ uint32_t g_tick[64];
__device__ __align__(16) uint32_t g_modp[8 * 2 * DM];
__host__ __device__ constexpr uint32_t blk(uint32_t lb, uint32_t par) {
    return (lb << 13) | ((((lb) ^ (lb >> 3) ^ (lb >> 4) ^ (lb >> 6) ^ par) & 1) << 12);
}
__host__ __device__ constexpr uint32_t lb_x2(uint32_t h) { return (h & 1) | ((h >> 1) << 3); }
__host__ __device__ constexpr uint32_t mem_row(uint32_t kh, uint32_t b, uint32_t r) { return blk(128 | b, kh) + r * 1024; }
__device__ __forceinline__ uint32_t mem_slot(uint32_t s) { return ((s & 1) << 15) | ((s & 2) << 17); }
constexpr uint32_t CNT1 = 0x3d80, CNT_ALL = 0x4000;
constexpr uint32_t LB_PROBE = 6 | 64, LB_TIME = 6;
__host__ __device__ constexpr uint32_t lb_tok(uint32_t h) { return (h & 1) | ((h >> 1) << 3); }
__device__ float g_mod[6 * DM];
__device__ __align__(1024) bf16 g_himg[(S_ + 32) * DM];
__device__ __align__(1024) bf16 g_O[S_ * NH * DH];
__device__ __align__(1024) bf16 g_y[S_ * DM];
__device__ __align__(1024) bf16 g_g[S_ * DM];
__device__ __align__(1024) bf16 g_x1[S_ * DM];
__device__ __align__(16) float g_st[4 * S_ * 2];
__device__ float g_vec[3 * DM + FF];
__device__ float g_cst[8];
__device__ uint32_t g_pcnt[2 * 32 * 8], g_pflag[6 * 32 * 8];
__device__ __align__(1024) bf16 g_u[S_ * FF];

#define TL(i) {}
#define TLC(i) {}
__device__ __forceinline__ uint32_t smem_u32(const void* p) { return (uint32_t)__cvta_generic_to_shared(p); }
__device__ __forceinline__ void spin_guard(int it) {
    asm volatile("{.reg .pred p; setp.gt.s32 p, %0, %1; @p st.global.u32 [%2], %0;}" ::"r"(it), "n"(SPIN_LIMIT), "l"(1ull));
}
__device__ __forceinline__ void wg_fence() { asm volatile("wgmma.fence.sync.aligned;" ::: "memory"); }
__device__ __forceinline__ void wg_commit() { asm volatile("wgmma.commit_group.sync.aligned;" ::: "memory"); }
template <int N> __device__ __forceinline__ void wg_wait() { asm volatile("wgmma.wait_group.sync.aligned %0;" ::"n"(N) : "memory"); }
__host__ __device__ constexpr uint64_t mkdesc(uint32_t addr, uint32_t lbo, uint32_t sbo, uint32_t swz) {
    return (uint64_t)((addr & 0x3FFFF) >> 4) | ((uint64_t)(lbo >> 4) << 16) | ((uint64_t)(sbo >> 4) << 32) | ((uint64_t)swz << 62);
}
__device__ __forceinline__ uint64_t dadd(uint64_t d, uint32_t o) { return (d & 0xffffffff00000000ull) | (uint32_t)((uint32_t)d + o); }
__device__ __forceinline__ void mbar_init(uint32_t b, uint32_t c) { asm volatile("mbarrier.init.shared.b64 [%0], %1;" ::"r"(b), "r"(c) : "memory"); }
__device__ __forceinline__ void mbar_expect(uint32_t b, uint32_t tx) { asm volatile("mbarrier.arrive.expect_tx.shared.b64 _, [%0], %1;" ::"r"(b), "r"(tx) : "memory"); }
__device__ __forceinline__ void mbar_arrive(uint32_t b) { asm volatile("mbarrier.arrive.shared.b64 _, [%0];" ::"r"(b) : "memory"); }
__device__ __forceinline__ void mbar_arrive_cluster(uint32_t b, uint32_t cta) {
    asm volatile("{.reg .b32 r; mapa.shared::cluster.u32 r, %0, %1; mbarrier.arrive.shared::cluster.b64 _, [r];}" ::"r"(b), "r"(cta) : "memory");
}
__device__ __forceinline__ bool mbar_try(uint32_t b, uint32_t par) {
    uint32_t ok;
    asm volatile("{.reg .pred p; mbarrier.try_wait.parity.shared.b64 p, [%1], %2; selp.u32 %0, 1, 0, p;}" : "=r"(ok) : "r"(b), "r"(par) : "memory");
    return ok;
}
__device__ __forceinline__ void mbar_wait(uint32_t b, uint32_t par) {
    int it = 0;
#pragma unroll 1
    while (!mbar_try(b, par)) { spin_guard(++it); }
}
__device__ __forceinline__ void mbar_wait_w(uint32_t b, uint32_t par) {
    int it = 0;
    bool ok;
#pragma unroll 1
    do { ok = __all_sync(~0u, mbar_try(b, par)); spin_guard(++it); } while (!ok);
}
__device__ __forceinline__ void mbar_wait_cluster(uint32_t b, uint32_t par) {
    int it = 0;
    while (true) {
        uint32_t ok;
        asm volatile("{.reg .pred p; mbarrier.try_wait.parity.acquire.cluster.shared::cta.b64 p, [%1], %2; selp.u32 %0, 1, 0, p;}" : "=r"(ok) : "r"(b), "r"(par) : "memory");
        if (ok) break;
        spin_guard(++it);
    }
}
__device__ __forceinline__ void tma2d(uint32_t dst, const CUtensorMap* m, int c0, int c1, uint32_t bar) {
    asm volatile("cp.async.bulk.tensor.2d.shared::cluster.global.mbarrier::complete_tx::bytes [%0], [%1, {%3, %4}], [%2];" ::"r"(dst), "l"(m), "r"(bar), "r"(c0), "r"(c1) : "memory");
}
__device__ __forceinline__ void tma2d_mc(uint32_t dst, const CUtensorMap* m, int c0, int c1, uint32_t bar, uint16_t mask) {
    asm volatile("cp.async.bulk.tensor.2d.shared::cluster.global.mbarrier::complete_tx::bytes.multicast::cluster [%0], [%1, {%3, %4}], [%2], %5;" ::"r"(dst), "l"(m), "r"(bar), "r"(c0), "r"(c1), "h"(mask) : "memory");
}
__device__ __forceinline__ void bulk_g2s(uint32_t dst, const void* src, uint32_t bytes, uint32_t bar) {
    asm volatile("cp.async.bulk.shared::cluster.global.mbarrier::complete_tx::bytes [%0], [%1], %2, [%3];" ::"r"(dst), "l"(src), "r"(bytes), "r"(bar) : "memory");
}
__device__ __forceinline__ void bar_sync(int id, int n) { asm volatile("bar.sync %0, %1;" ::"r"(id), "r"(n) : "memory"); }
__device__ __forceinline__ void bar_arrive(int id, int n) { asm volatile("bar.arrive %0, %1;" ::"r"(id), "r"(n) : "memory"); }
__device__ __forceinline__ void cluster_sync_all() { asm volatile("barrier.cluster.arrive.aligned; barrier.cluster.wait.aligned;" ::: "memory"); }
__device__ __forceinline__ void fence_async_smem() { asm volatile("fence.proxy.async.shared::cta;" ::: "memory"); }
__device__ __forceinline__ void ldsm4t(uint32_t* r, uint32_t a) {
    asm volatile("ldmatrix.sync.aligned.m8n8.x4.trans.shared.b16 {%0,%1,%2,%3}, [%4];" : "=r"(r[0]), "=r"(r[1]), "=r"(r[2]), "=r"(r[3]) : "r"(a) : "memory");
}
__device__ __forceinline__ void ldsm4(uint32_t* r, uint32_t a) {
    asm volatile("ldmatrix.sync.aligned.m8n8.x4.shared.b16 {%0,%1,%2,%3}, [%4];" : "=r"(r[0]), "=r"(r[1]), "=r"(r[2]), "=r"(r[3]) : "r"(a) : "memory");
}
__device__ __forceinline__ uint32_t movm(uint32_t a) {
    uint32_t d; asm volatile("movmatrix.sync.aligned.m8n8.trans.b16 %0, %1;" : "=r"(d) : "r"(a)); return d;
}
__device__ __forceinline__ void mma16816(float* d, uint32_t a0, uint32_t a1, uint32_t a2, uint32_t a3, uint32_t b0, uint32_t b1) {
    asm volatile("mma.sync.aligned.m16n8k16.row.col.f32.bf16.bf16.f32 {%0,%1,%2,%3},{%4,%5,%6,%7},{%8,%9},{%0,%1,%2,%3};"
                 : "+f"(d[0]), "+f"(d[1]), "+f"(d[2]), "+f"(d[3]) : "r"(a0), "r"(a1), "r"(a2), "r"(a3), "r"(b0), "r"(b1));
}
__device__ __forceinline__ void mma16816z(float* d, const uint32_t* a, uint32_t b0, uint32_t b1) {
    asm volatile("mma.sync.aligned.m16n8k16.row.col.f32.bf16.bf16.f32 {%0,%1,%2,%3},{%4,%5,%6,%7},{%8,%9},{%10,%10,%10,%10};"
                 : "=f"(d[0]), "=f"(d[1]), "=f"(d[2]), "=f"(d[3]) : "r"(a[0]), "r"(a[1]), "r"(a[2]), "r"(a[3]), "r"(b0), "r"(b1), "f"(0.f));
}
__device__ __forceinline__ void mma1688(float* d, uint32_t a0, uint32_t a1, uint32_t b0) {
    asm volatile("mma.sync.aligned.m16n8k8.row.col.f32.bf16.bf16.f32 {%0,%1,%2,%3},{%4,%5},{%6},{%0,%1,%2,%3};"
                 : "+f"(d[0]), "+f"(d[1]), "+f"(d[2]), "+f"(d[3]) : "r"(a0), "r"(a1), "r"(b0));
}
__device__ __forceinline__ uint32_t pack2(float lo, float hi) {
    uint32_t r; asm("cvt.rn.bf16x2.f32 %0, %1, %2;" : "=r"(r) : "f"(hi), "f"(lo)); return r;
}
__device__ __forceinline__ uint32_t hadd2(uint32_t a, uint32_t b) {
    uint32_t r; asm("add.rn.bf16x2 %0, %1, %2;" : "=r"(r) : "r"(a), "r"(b)); return r;
}
__device__ __forceinline__ float bflo(uint32_t u) { return __uint_as_float(u << 16); }
__device__ __forceinline__ float bfhi(uint32_t u) { return __uint_as_float(u & 0xffff0000u); }
__device__ __forceinline__ float ex2(float x) { float r; asm("ex2.approx.ftz.f32 %0, %1;" : "=f"(r) : "f"(x)); return r; }
__device__ __forceinline__ uint4 ldg_rlx4(const void* p) {
    uint4 v; asm volatile("ld.relaxed.gpu.global.v4.u32 {%0,%1,%2,%3}, [%4];" : "=r"(v.x), "=r"(v.y), "=r"(v.z), "=r"(v.w) : "l"(p) : "memory"); return v;
}
__device__ __forceinline__ uint2 ldg_rlx2(const void* p) {
    unsigned long long v; asm volatile("ld.relaxed.gpu.global.b64 %0, [%1];" : "=l"(v) : "l"(p) : "memory");
    return make_uint2((uint32_t)v, (uint32_t)(v >> 32));
}
__device__ __forceinline__ uint32_t ldg_rlx1(const void* p) {
    uint32_t v; asm volatile("ld.relaxed.gpu.global.u32 %0, [%1];" : "=r"(v) : "l"(p) : "memory"); return v;
}
__device__ __forceinline__ void stg_rlx1(void* p, uint32_t v) { asm volatile("st.relaxed.gpu.global.u32 [%0], %1;" ::"l"(p), "r"(v) : "memory"); }
__device__ __forceinline__ void stg_rlx2(void* p, uint32_t x, uint32_t y) {
    unsigned long long v = (unsigned long long)x | ((unsigned long long)y << 32);
    asm volatile("st.relaxed.gpu.global.b64 [%0], %1;" ::"l"(p), "l"(v) : "memory");
}
__device__ __forceinline__ void stg_rlx4(void* p, uint32_t x, uint32_t y, uint32_t z, uint32_t w) {
    asm volatile("st.relaxed.gpu.global.v4.u32 [%0], {%1,%2,%3,%4};" ::"l"(p), "r"(x), "r"(y), "r"(z), "r"(w) : "memory");
}
__device__ __forceinline__ void sts4(uint32_t a, uint32_t x, uint32_t y, uint32_t z, uint32_t w) {
    asm volatile("st.shared.v4.u32 [%0], {%1,%2,%3,%4};" ::"r"(a), "r"(x), "r"(y), "r"(z), "r"(w) : "memory");
}
__device__ __forceinline__ uint4 lds4(uint32_t a) {
    uint4 v; asm volatile("ld.shared.v4.u32 {%0,%1,%2,%3}, [%4];" : "=r"(v.x), "=r"(v.y), "=r"(v.z), "=r"(v.w) : "r"(a) : "memory"); return v;
}
__device__ __forceinline__ void st_async4(uint32_t a, float x, float y, float z, float w, uint32_t bar) {
    asm volatile("st.async.shared::cluster.mbarrier::complete_tx::bytes.v4.f32 [%0], {%1,%2,%3,%4}, [%5];" ::"r"(a), "f"(x), "f"(y), "f"(z), "f"(w), "r"(bar) : "memory");
}
#define F4(d, i) "+f"(d[i]), "+f"(d[i + 1]), "+f"(d[i + 2]), "+f"(d[i + 3])
__device__ __forceinline__ void wgmma_rs32(float* d, const uint32_t* a, uint64_t b, int sc) {
    asm volatile("{.reg .pred p; setp.ne.b32 p, %21, 0;\n wgmma.mma_async.sync.aligned.m64n32k16.f32.bf16.bf16 {%0,%1,%2,%3,%4,%5,%6,%7,%8,%9,%10,%11,%12,%13,%14,%15}, {%16,%17,%18,%19}, %20, p, 1, 1, 0;}"
                 : F4(d, 0), F4(d, 4), F4(d, 8), F4(d, 12) : "r"(a[0]), "r"(a[1]), "r"(a[2]), "r"(a[3]), "l"(b), "r"(sc));
}
__device__ __forceinline__ void wgmma_ss32(float* d, uint64_t a, uint64_t b, int sc) {
    asm volatile("{.reg .pred p; setp.ne.b32 p, %18, 0;\n wgmma.mma_async.sync.aligned.m64n32k16.f32.bf16.bf16 {%0,%1,%2,%3,%4,%5,%6,%7,%8,%9,%10,%11,%12,%13,%14,%15}, %16, %17, p, 1, 1, 1, 0;}"
                 : F4(d, 0), F4(d, 4), F4(d, 8), F4(d, 12) : "l"(a), "l"(b), "r"(sc));
}
__device__ __forceinline__ void wgmma_rs40(float* d, const uint32_t* a, uint64_t b, int sc) {
    asm volatile("{.reg .pred p; setp.ne.b32 p, %25, 0;\n wgmma.mma_async.sync.aligned.m64n40k16.f32.bf16.bf16 {%0,%1,%2,%3,%4,%5,%6,%7,%8,%9,%10,%11,%12,%13,%14,%15,%16,%17,%18,%19}, {%20,%21,%22,%23}, %24, p, 1, 1, 0;}"
                 : F4(d, 0), F4(d, 4), F4(d, 8), F4(d, 12), F4(d, 16) : "r"(a[0]), "r"(a[1]), "r"(a[2]), "r"(a[3]), "l"(b), "r"(sc));
}
__device__ __forceinline__ void wgmma_ss40(float* d, uint64_t a, uint64_t b, int sc) {
    asm volatile("{.reg .pred p; setp.ne.b32 p, %22, 0;\n wgmma.mma_async.sync.aligned.m64n40k16.f32.bf16.bf16 {%0,%1,%2,%3,%4,%5,%6,%7,%8,%9,%10,%11,%12,%13,%14,%15,%16,%17,%18,%19}, %20, %21, p, 1, 1, 1, 0;}"
                 : F4(d, 0), F4(d, 4), F4(d, 8), F4(d, 12), F4(d, 16) : "l"(a), "l"(b), "r"(sc));
}
#define F16(d, i) F4(d, i), F4(d, i + 4), F4(d, i + 8), F4(d, i + 12)
template <int TA>
__device__ __forceinline__ void wgmma_ss128(float* d, uint64_t a, uint64_t b, int sc) {
    asm volatile("{.reg .pred p; setp.ne.b32 p, %66, 0;\n wgmma.mma_async.sync.aligned.m64n128k16.f32.bf16.bf16 "
                 "{%0,%1,%2,%3,%4,%5,%6,%7,%8,%9,%10,%11,%12,%13,%14,%15,%16,%17,%18,%19,%20,%21,%22,%23,%24,%25,%26,%27,%28,%29,%30,%31,"
                 "%32,%33,%34,%35,%36,%37,%38,%39,%40,%41,%42,%43,%44,%45,%46,%47,%48,%49,%50,%51,%52,%53,%54,%55,%56,%57,%58,%59,%60,%61,%62,%63}, %64, %65, p, 1, 1, %67, 1;}"
                 : F16(d, 0), F16(d, 16), F16(d, 32), F16(d, 48) : "l"(a), "l"(b), "r"(sc), "n"(TA));
}

__device__ __forceinline__ float warp_sum(float v) {
#pragma unroll
    for (int o = 16; o; o >>= 1) v += __shfl_xor_sync(~0u, v, o);
    return v;
}
__device__ __forceinline__ float bfround(float x) { return __bfloat162float(__float2bfloat16(x)); }

__device__ __forceinline__ void wait_count1(const uint32_t* p, uint32_t target) {
    int it = 0;
#pragma unroll 1
    while (true) {
        uint32_t v;
        asm volatile("ld.acquire.gpu.global.u32 %0, [%1];" : "=r"(v) : "l"(p) : "memory");
        if (v >= target) break;
        spin_guard(++it);
    }
}
__device__ __forceinline__ void red2(float* p, float a, float b) {
    asm volatile("red.relaxed.gpu.global.add.v2.f32 [%0], {%1, %2};" ::"l"(p), "f"(a), "f"(b) : "memory");
}
__device__ __forceinline__ void l2_prefetch(const void* p, uint32_t bytes) {
    asm volatile("cp.async.bulk.prefetch.L2.global [%0], %1;" ::"l"(p), "r"(bytes) : "memory");
}
__device__ __forceinline__ void signal_count(uint32_t* p) { asm volatile("red.release.gpu.global.add.u32 [%0], 1;" ::"l"(p) : "memory"); }
__device__ __forceinline__ void e_expect(uint32_t b, uint32_t tx) {
    asm volatile("{.reg .pred p; elect.sync _|p, 0xffffffff; @p mbarrier.arrive.expect_tx.shared.b64 _, [%0], %1;}" ::"r"(b), "r"(tx) : "memory");
}
__device__ __forceinline__ void e_tma2d(uint32_t dst, const CUtensorMap* m, int c0, int c1, uint32_t bar) {
    asm volatile("{.reg .pred p; elect.sync _|p, 0xffffffff;\n @p cp.async.bulk.tensor.2d.shared::cluster.global.mbarrier::complete_tx::bytes [%0], [%1, {%3, %4}], [%2];}"
                 ::"r"(dst), "l"(m), "r"(bar), "r"(c0), "r"(c1) : "memory");
}
__device__ __forceinline__ void e_tma2d_mc(uint32_t dst, const CUtensorMap* m, int c0, int c1, uint32_t bar) {
    asm volatile("{.reg .pred p; elect.sync _|p, 0xffffffff;\n @p cp.async.bulk.tensor.2d.shared::cluster.global.mbarrier::complete_tx::bytes.multicast::cluster [%0], [%1, {%3, %4}], [%2], %5;}"
                 ::"r"(dst), "l"(m), "r"(bar), "r"(c0), "r"(c1), "h"((uint16_t)3) : "memory");
}
__device__ __forceinline__ void e_prefetch(const void* p, uint32_t bytes) {
    asm volatile("{.reg .pred p; elect.sync _|p, 0xffffffff; @p cp.async.bulk.prefetch.L2.global [%0], %1;}" ::"l"(p), "r"(bytes) : "memory");
}
__device__ __forceinline__ void wait_count_w(const uint32_t* p, uint32_t target) {
    int it = 0;
#pragma unroll 1
    while (true) {
        uint32_t v;
        asm volatile("ld.acquire.gpu.global.u32 %0, [%1];" : "=r"(v) : "l"(p) : "memory");
        if (__all_sync(~0u, v >= target)) break;
        spin_guard(++it);
    }
}

__device__ __forceinline__ void ln_row(float* x) {
    float s = 0;
#pragma unroll
    for (int i = 0; i < 32; i++) s += x[i];
    float m = warp_sum(s) * (1.0f / DM);
    float q = 0;
#pragma unroll
    for (int i = 0; i < 32; i++) { x[i] -= m; q += x[i] * x[i]; }
    float r = rsqrtf(warp_sum(q) * (1.0f / DM) + 1e-5f);
#pragma unroll
    for (int i = 0; i < 32; i++) x[i] *= r;
}
__device__ __forceinline__ uint4 pack8(const float* x) {
    return make_uint4(pack2(x[0], x[1]), pack2(x[2], x[3]), pack2(x[4], x[5]), pack2(x[6], x[7]));
}
#define NL 6
constexpr uint32_t SM_HB = 16384, HBK = 5120, SM_SX = 57344, SM_OX = 122880, SM_PX = 124928, SM_PA = 126976, SM_WO = 147456,
                   SM_TAB = 212992, SM_PRE = SM_TAB, SM_BAR = 227328, SM_REC_TOTAL = 227328 + 256;
constexpr uint32_t SB0 = 1024;
constexpr int B_WO = 0, B_HE = 1, B_ROLE = 2, B_HB = 3, B_W = 5;
constexpr int NB_MEM = 1, NB_QK = 2, NB_X1 = 3, NB_X2 = 4, NB_WIN = 5, NB_WG = 6, NB_KDONE = 7, NB_FIN0 = 8, NB_P = 9, NB_PX = 10, NB_G = 11, NB_A = 12, NB_B = 13, NB_C = 14, NB_S = 15;
#define SPF 33
#define SPF_AT 52
#define SPF_NS 150
#define D_TPV 100
#define V_POS 2
#define D_X2 450
#define D_TV 50
#define D_V 400
#define D_NEAR 1800
#define D_FAR (D_NEAR - 140)
#define E_MUL 28
#define D_WF 60
#define NE 0
#define D_H 0
#define D_W2 150
#define SETTLE 0
#define TV_POS 1
#define D_PA 0
#define NE1 10
#define H_POS 0
#define PA_POS 1
#define G_AT 24
#define W0_AT 4
#define W0_RS (NL - 1)
#define P_GATE 0
#define NPF (NL + 6)

struct Delays { uint32_t near, far, x2, v, w2, pa, wf, tv; };
#define MISS(i, v)
#define MISS_INIT
#define MISS_OUT
#define HT(i)
#define PROF_INIT
#define PROF(i)
#define PROFV(i, v)
#define PROF_OUT

__device__ __forceinline__ uint32_t clk32() { uint32_t t; asm volatile("mov.u32 %0, %%clock;" : "=r"(t) :: "memory"); return t; }
__device__ __forceinline__ uint32_t gtime() { uint32_t t; asm volatile("mov.u32 %0, %%globaltimer_lo;" : "=r"(t) :: "memory"); return t; }
__device__ __forceinline__ void spin_until(uint32_t t0, uint32_t d) { while (clk32() - t0 < d) {} }
template <int N> __device__ __forceinline__ uint32_t delay(uint32_t zero) {
    float x = __uint_as_float(clk32());
#pragma unroll
    for (int i = 0; i < N; i++) asm volatile("ex2.approx.ftz.f32 %0, %0;" : "+f"(x));
    return __float_as_uint(x) & zero;
}
__device__ __forceinline__ uint32_t opaque(uint32_t v) { return __shfl_sync(~0u, v, threadIdx.x & 31); }
__device__ __forceinline__ uint32_t xor_or(uint32_t a, uint32_t b, uint32_t t) {
    uint32_t r; asm volatile("lop3.b32 %0, %1, %2, %3, 0x7E;" : "=r"(r) : "r"(a), "r"(b), "r"(t)); return r;
}
__device__ __forceinline__ uint32_t or3(uint32_t a, uint32_t b, uint32_t c) {
    uint32_t r; asm volatile("lop3.b32 %0, %1, %2, %3, 0xFE;" : "=r"(r) : "r"(a), "r"(b), "r"(c)); return r;
}
__device__ __forceinline__ uint32_t settag(uint32_t v, uint32_t tag) {
    uint32_t r; asm("lop3.b32 %0, %1, 1, %2, 0xB8;" : "=r"(r) : "r"(v), "r"(tag)); return r;
}
__device__ __forceinline__ void ldg4_if(uint4& v, const void* p, bool c) {
    asm volatile("{.reg .pred p; setp.ne.u32 p, %5, 0; @p ld.relaxed.gpu.global.v4.u32 {%0,%1,%2,%3}, [%4];}"
                 : "+r"(v.x), "+r"(v.y), "+r"(v.z), "+r"(v.w) : "l"(p), "r"((uint32_t)c) : "memory");
}
__device__ __forceinline__ uint4 ldg_rlx2x2(const void* p) {
    unsigned long long a, b;
    asm volatile("ld.relaxed.gpu.global.v2.b64 {%0,%1}, [%2];" : "=l"(a), "=l"(b) : "l"(p) : "memory");
    return make_uint4((uint32_t)a, (uint32_t)(a >> 32), (uint32_t)b, (uint32_t)(b >> 32));
}
__device__ __forceinline__ void stg_rlx2x2(void* p, uint32_t x, uint32_t y, uint32_t z, uint32_t w) {
    asm volatile("{.reg .b64 a, b; mov.b64 a, {%1,%2}; mov.b64 b, {%3,%4}; st.relaxed.gpu.global.v2.b64 [%0], {a, b};}" ::"l"(p), "r"(x), "r"(y), "r"(z), "r"(w) : "memory");
}
__device__ __forceinline__ void ldg1_if(uint32_t& v, const void* p, bool c) {
    asm volatile("{.reg .pred p; setp.ne.u32 p, %2, 0; @p ld.relaxed.gpu.global.u32 %0, [%1];}" : "+r"(v) : "l"(p), "r"((uint32_t)c) : "memory");
}
__device__ __forceinline__ void sts2(uint32_t a, float x, float y) { asm volatile("st.shared.v2.f32 [%0], {%1,%2};" ::"r"(a), "f"(x), "f"(y) : "memory"); }
__device__ __forceinline__ void sts4f(uint32_t a, float x, float y, float z, float w) {
    asm volatile("st.shared.v4.f32 [%0], {%1,%2,%3,%4};" ::"r"(a), "f"(x), "f"(y), "f"(z), "f"(w) : "memory");
}
__device__ __forceinline__ void sts1(uint32_t a, uint32_t x) { asm volatile("st.shared.u32 [%0], %1;" ::"r"(a), "r"(x) : "memory"); }
__device__ __forceinline__ uint32_t lds1(uint32_t a) { uint32_t v; asm volatile("ld.shared.u32 %0, [%1];" : "=r"(v) : "r"(a) : "memory"); return v; }
__device__ __forceinline__ float4 lds4f(uint32_t a) {
    float4 v; asm volatile("ld.shared.v4.f32 {%0,%1,%2,%3}, [%4];" : "=f"(v.x), "=f"(v.y), "=f"(v.z), "=f"(v.w) : "r"(a) : "memory"); return v;
}
__device__ __forceinline__ float2 lds2f(uint32_t a) {
    float2 v; asm volatile("ld.shared.v2.f32 {%0,%1}, [%2];" : "=f"(v.x), "=f"(v.y) : "r"(a) : "memory"); return v;
}
__device__ __forceinline__ bool any_bit0(uint32_t x) {
    uint32_t r;
    asm volatile("{.reg .pred p, q; .reg .b32 t; and.b32 t, %1, 1; setp.ne.u32 p, t, 0; vote.sync.any.pred q, p, 0xffffffff; selp.u32 %0, 1, 0, q;}" : "=r"(r) : "r"(x));
    return r;
}
__device__ __forceinline__ float rcp_fast(float x) { float r; asm("rcp.approx.ftz.f32 %0, %1;" : "=f"(r) : "f"(x)); return r; }
__device__ __forceinline__ void stsm4(uint32_t a, uint32_t r0, uint32_t r1, uint32_t r2, uint32_t r3) {
    asm volatile("stmatrix.sync.aligned.m8n8.x4.shared.b16 [%0], {%1,%2,%3,%4};" ::"r"(a), "r"(r0), "r"(r1), "r"(r2), "r"(r3) : "memory");
}
__device__ __forceinline__ void stsm4t(uint32_t a, uint32_t r0, uint32_t r1, uint32_t r2, uint32_t r3) {
    asm volatile("stmatrix.sync.aligned.m8n8.x4.trans.shared.b16 [%0], {%1,%2,%3,%4};" ::"r"(a), "r"(r0), "r"(r1), "r"(r2), "r"(r3) : "memory");
}
__device__ __forceinline__ uint32_t and3(uint32_t a, uint32_t b, uint32_t c) {
    uint32_t r; asm("lop3.b32 %0, %1, %2, %3, 0x80;" : "=r"(r) : "r"(a), "r"(b), "r"(c)); return r;
}
__device__ __forceinline__ void red_mem(void* p, uint32_t x, uint32_t y, uint32_t z, uint32_t w, void* q, uint32_t e) {
    asm volatile("red.relaxed.gpu.global.add.noftz.v4.bf16x2 [%0], {%1,%2,%3,%4}; red.relaxed.gpu.global.add.noftz.bf16x2 [%5], %6;"
                 ::"l"(p), "r"(x), "r"(y), "r"(z), "r"(w), "l"(q), "r"(e) : "memory");
}
__device__ __forceinline__ void stg4_if(bool c, void* p, uint32_t x) {
    asm volatile("{.reg .pred p; setp.ne.u32 p, %2, 0; @p st.relaxed.gpu.global.v4.u32 [%0], {%1,%1,%1,%1};}" ::"l"(p), "r"(x), "r"((uint32_t)c) : "memory");
}
__device__ __forceinline__ uint32_t max3u(uint32_t a, uint32_t b, uint32_t c) { return __vimax3_u32(a, b, c); }
__device__ __forceinline__ void fence_gpu() { asm volatile("fence.acq_rel.gpu;" ::: "memory"); }

__device__ __forceinline__ void h_load(uint32_t sb, const uint8_t* hsrc, int pass, uint32_t rank, uint32_t rot) {
    const uint8_t* src = hsrc + (size_t)pass * 65536;
    const uint32_t bar = sb + SM_BAR + 8 * (B_HB + (pass & 1)), dst = sb + SM_HB + (pass & 1) * 65536 + rank * 4 * HBK;
    e_expect(bar, 32768);
#pragma unroll 1
    for (int i = 0; i < H_PIECES; i++) {
        const uint32_t o = ((i + rot) & (H_PIECES - 1)) * (16384 / H_PIECES);
        asm volatile("{.reg .pred p; elect.sync _|p, 0xffffffff;\n"
                     " @p cp.async.bulk.shared::cluster.global.mbarrier::complete_tx::bytes.multicast::cluster [%0], [%1], %4, [%2], %3;}"
                     ::"r"(dst + o + (o >> 12) * 1024), "l"(src + o), "r"(bar), "h"((uint16_t)3), "n"(16384 / H_PIECES) : "memory");
    }
}
__device__ __forceinline__ uint4 ldg_b128(const void* p) {
    uint4 v;
    asm volatile("{.reg .b128 t; .reg .b64 a, b; ld.relaxed.gpu.global.b128 t, [%4]; mov.b128 {a, b}, t; mov.b64 {%0,%1}, a; mov.b64 {%2,%3}, b;}"
                 : "=r"(v.x), "=r"(v.y), "=r"(v.z), "=r"(v.w) : "l"(p) : "memory");
    return v;
}
__device__ __forceinline__ void ldg_b128_into(uint4& v, const void* p) {
    asm volatile("{.reg .b128 t; .reg .b64 a, b; ld.relaxed.gpu.global.b128 t, [%4]; mov.b128 {a, b}, t; mov.b64 {%0,%1}, a; mov.b64 {%2,%3}, b;}"
                 : "+r"(v.x), "+r"(v.y), "+r"(v.z), "+r"(v.w) : "l"(p) : "memory");
}
__device__ __forceinline__ void stg_b128_if(bool c, void* p, uint32_t x, uint32_t y, uint32_t z, uint32_t w) {
    asm volatile("{.reg .pred p; .reg .b128 t; .reg .b64 a, b; setp.ne.u32 p, %5, 0; mov.b64 a, {%1,%2}; mov.b64 b, {%3,%4}; mov.b128 t, {a, b}; @p st.relaxed.gpu.global.b128 [%0], t;}"
                 ::"l"(p), "r"(x), "r"(y), "r"(z), "r"(w), "r"((uint32_t)c) : "memory");
}
__device__ __forceinline__ float pretag(float x, uint32_t add, uint32_t keep) { return __uint_as_float((__float_as_uint(x) + add) & keep); }

template <class F, class G>
__device__ __forceinline__ void softmax_rows(uint32_t src, uint32_t dst, uint32_t g16, int row0, F ready, G mid) {
    const uint32_t u = (g16 >> 7) & 3, e = ((g16 >> 9) << 3) | ((g16 >> 4) & 7);
    uint32_t se = src + e * 8, su = se + u * 1088, d0 = dst + e * 16 + u * 4, d1 = dst + 512 + e * 4;
    int vis = row0 + (e >> 2) - 2 * (e & 3) - 8 * u;
    asm volatile("" : "+r"(se), "+r"(su), "+r"(d0), "+r"(d1), "+r"(vis));
    ready();
    const float2 p0 = lds2f(su), p1 = lds2f(su + 256), p2 = lds2f(su + 512), p3 = lds2f(su + 768);
    const float2 m0 = lds2f(se + 4352), m1 = lds2f(se + 4352 + 256), m2 = lds2f(se + 4352 + 512), m3 = lds2f(se + 4352 + 768);
    float a0 = (p0.x + p1.x) + (p2.x + p3.x), a1 = (p0.y + p1.y) + (p2.y + p3.y);
    const float a2 = (m0.x + m1.x) + (m2.x + m3.x), a3 = (m0.y + m1.y) + (m2.y + m3.y);
    if (vis < 0) a0 = -1e9f / 0.08838834764831845f;
    if (vis < 1) a1 = -1e9f / 0.08838834764831845f;
    int k = __float_as_int(fmaxf(fmaxf(a0, a1), fmaxf(a2, a3)));
    k ^= (k >> 31) & 0x7fffffff;
    const bool hi = g16 & 64;
    const int k0 = __reduce_max_sync(~0u, hi ? INT_MIN : k), k1 = __reduce_max_sync(~0u, hi ? k : INT_MIN);
    mid();
    k = hi ? k1 : k0;
    const float m = __int_as_float(k ^ ((k >> 31) & 0x7fffffff));
    const float sl2 = 0.08838834764831845f * 1.4426950408889634f, mb = -m * sl2;
    sts1(d0, pack2(ex2(fmaf(a0, sl2, mb)), ex2(fmaf(a1, sl2, mb))));
    sts1(d1, pack2(ex2(fmaf(a2, sl2, mb)), ex2(fmaf(a3, sl2, mb))));
}

__device__ __forceinline__ uint32_t pack_h2(float lo, float hi) {
    uint32_t r; asm("cvt.rn.satfinite.f16x2.f32 %0, %1, %2;" : "=r"(r) : "f"(hi), "f"(lo)); return r;
}
__device__ __forceinline__ float2 unpack_h2(uint32_t u) {
    float2 r; asm("{.reg .b16 l, h; mov.b32 {l, h}, %2; cvt.f32.f16 %0, l; cvt.f32.f16 %1, h;}" : "=f"(r.x), "=f"(r.y) : "r"(u)); return r;
}
__device__ __forceinline__ uint32_t add_h2(uint32_t a, uint32_t b) { uint32_t r; asm("add.rn.f16x2 %0, %1, %2;" : "=r"(r) : "r"(a), "r"(b)); return r; }
__device__ __forceinline__ uint32_t max_h2(uint32_t a, uint32_t b) { uint32_t r; asm("max.f16x2 %0, %1, %2;" : "=r"(r) : "r"(a), "r"(b)); return r; }
__device__ __forceinline__ void stg2_if(bool c, void* p, uint32_t x, uint32_t y) {
    asm volatile("{.reg .pred p; .reg .b64 v; setp.ne.u32 p, %3, 0; mov.b64 v, {%1, %2}; @p st.relaxed.gpu.global.b64 [%0], v;}" ::"l"(p), "r"(x), "r"(y), "r"((uint32_t)c) : "memory");
}
__device__ __forceinline__ void stg1_if(bool c, void* p, uint32_t x) {
    asm volatile("{.reg .pred p; setp.ne.u32 p, %2, 0; @p st.relaxed.gpu.global.u32 [%0], %1;}" ::"l"(p), "r"(x), "r"((uint32_t)c) : "memory");
}
struct U2 { uint32_t x, y; };
__device__ __forceinline__ U2 ldg_u2(const void* p) {
    U2 v; asm volatile("{.reg .b64 t; ld.relaxed.gpu.global.b64 t, [%2]; mov.b64 {%0, %1}, t;}" : "=r"(v.x), "=r"(v.y) : "l"(p) : "memory"); return v;
}
constexpr int POLL_LIMIT = 1 << 16;
constexpr float SM_L2E = 0.08838834764831845f * 1.4426950408889634f;
template <int V> struct IC { static constexpr int value = V; };
typedef unsigned long long u64;
__device__ __forceinline__ uint32_t lo32(u64 v) { return (uint32_t)v; }
__device__ __forceinline__ uint32_t hi32(u64 v) { return (uint32_t)(v >> 32); }
__device__ __forceinline__ u64 ldg_u64(const void* p) { u64 v; asm volatile("ld.relaxed.gpu.global.b64 %0, [%1];" : "=l"(v) : "l"(p) : "memory"); return v; }
__device__ __forceinline__ void ldg_u64_if(u64& v, const void* p, bool c) {
    asm volatile("{.reg .pred p; setp.ne.u32 p, %2, 0; @p ld.relaxed.gpu.global.b64 %0, [%1];}" : "+l"(v) : "l"(p), "r"((uint32_t)c) : "memory");
}
__device__ __forceinline__ void rec_main(uint32_t sb, const CUtensorMap* tWo, uint8_t* arena, int role, int hinfo, int wg, uint32_t zero, const Delays& dly) {
    const int hA = hinfo & 255;
    const int tid = threadIdx.x, t = tid & 127, lane = tid & 31, wi = t >> 5;
    const uint32_t bars = sb + SM_BAR;
    const int head = role >> 2, qd = role & 3, j = blockIdx.x & 1, kh = role & 1;
    const uint32_t mypar = head >= hA;
    const bool warp0 = __all_sync(~0u, wi == 0), warp1 = __all_sync(~0u, wi == 1);
    const uint8_t* hsrc = (const uint8_t*)g_himg + kh * 32768 + j * 16384;
    auto tokbase = [&](int ty) { return ((ty + 1) << 21) + blk(lb_tok(head), mypar ^ ((hinfo >> (8 + ty)) & 1)); };
    const uint32_t tbw = tokbase(wg), tbq = tokbase(0) + (qd >> 1) * 2048 + (qd & 1) * 8;
    uint32_t w[32 - NL][4];
    const uint32_t frow = ((lane >> 4) * 8 + (lane & 7)) * 128, fx = ((lane >> 3) & 1) ^ (lane & 7);
    const uint32_t wl0 = sb + wg * 65536 + frow + ((fx ^ (2 * wi)) << 4);
    {
#pragma unroll 1
        for (int i = 0; i < 4; i++) mbar_wait_w(bars + 8 * (B_W + (wg == 2 ? 8 + i : 2 * i + wg)), 0);
#pragma unroll
        for (int p = NL; p < 32; p++) ldsm4t(w[p - NL], wl0 + p * 2048);
        fence_async_smem();
        if (wg < 2) bar_sync(NB_WG, 256);
        if (wg > 0) wait_count_w(&g_tick[32 + (lane & 3) * 8], 1);
        if (wg == 1 && warp0) {
            if (lane == 0) mbar_arrive_cluster(bars + 8 * B_HE, j ^ 1);
            asm volatile("fence.proxy.async.global;" ::: "memory");
            mbar_wait_w(bars + 8 * B_HE, 0);
#pragma unroll 1
            for (int i = 0; i < 2; i++) h_load(sb, hsrc, i, j, head);
        }
        TL(3 + wg)
    }
    const uint32_t g16 = opaque(t * 16), sbl = sb - __reduce_max_sync(~0u, wi) * 512;
    {
        const uint32_t c16 = kh * 2048 + ((2 * j + (wi >> 1)) * 32 + lane) * 16;
        const uint32_t xso = blk(lb_x2(head), mypar), r8 = lane & 7;
        const uint32_t mrow = wg < 2 ? mem_row(wi >> 1, wg * 2 + (wi & 1), qd) : mem_row(kh, wi, 0);
        const uint32_t a0 = wg < 2 ? wl0 : mem_row(role >> 6, (role >> 4) & 3, (role >> 2) & 3) + (lane < 8 ? qd * 128 + lane * 16 : 512 + qd * 32 + (lane & 1) * 16);
        const uint32_t a3 = wg < 2 ? sb + SM_WO + wi * 16384 + frow + ((fx ^ (2 * wg)) << 4) : qd * 65536 + head * 2048 + wi * 512 + lane * 4;
        const uint32_t a4 = sb + SM_HB + 4096 + r8 * 128 +
                            (wg < 2 ? ((lane >> 3) ^ r8) << 4 : (wi & 1) * HBK + ((((wi & 2) + (lane >> 4) * 4 + ((lane >> 3) & 1)) ^ r8) << 4));
        bar_sync(NB_X2, 384);
        if (wg == 0 && lane == 0) {
            mbar_expect(bars + 8 * B_WO, 16384);
            tma2d(sb + SM_WO + wi * 16384, tWo, (wi >> 1) * 512 + qd * 128 + (wi & 1) * 64, head * DH, bars + 8 * B_WO);
            tma2d(sb + SM_WO + wi * 16384 + 8192, tWo, (wi >> 1) * 512 + qd * 128 + (wi & 1) * 64, head * DH + 64, bars + 8 * B_WO);
        }
        __syncwarp();
        if (wg == 2) {
            const uint32_t ch = (((wi & 2) + 5) ^ r8) << 4;
            sts1(sb + SM_TAB + 12288 + t * 4, sb + ch + (lane & 1 ? SM_HB + 4096 + r8 * 128 + ((wi & 1) + (lane >> 3) * 2) * HBK : SM_HB - 128));
        }
        const uint32_t to = tbw + (wi & 1) * 16384 + c16;
        sts4(sb + SM_TAB + wg * 4096 + g16, wg < 2 ? a3 : a0, xso + wg * 16384 + (wi & 1) * 2048 + (c16 >> 1), xso + (wg == 2 ? 32768 : 0) + t * 8, wg < 2 ? a4 : to);
        sts4(sb + SM_TAB + wg * 4096 + 2048 + g16, mrow + lane * 16, mrow + 512 + lane * 4, wg < 2 ? a0 : a3, wg < 2 ? to : a4);
    }
    PROF_INIT
    MISS_INIT
#define HB(ks) dadd(mkdesc(SB0 + SM_HB + ((ks) >> 2) * HBK + ((ks) & 3) * 32, 16, 1024, 1), hbo)
#define STEP_CONSTS                                                                                  \
    const uint32_t tag = (s & 1) ^ 1, ttag = ((s >> 1) & 1) ^ 1, tso = (s & 1) * 32768;              \
    const int p = s + 2, b = p & 1;                                                                  \
    uint32_t hbo = b * 4096, fz[5] = {0, 0, 0, 0, 0};                                                \
    const uint32_t ftag = (((p - 1) >> 1) & 1) ^ 1, ptag = ((p >> 1) & 1) ^ 1;                       \
    const uint32_t pso = tbw + (1 << 20) + (b ^ 1) * 32768 + j * 16384 + kh * 2048;
#define SCHED_FENCE(i) fz[i] = clk32();
#define FZ ((fz[0] | fz[1] | fz[2] | fz[3] | fz[4]) & zero)
#define BLOCK_FENCE asm volatile("pmevent 0;" ::: "memory");
    constexpr int GAP = 32 / NL;
    const uint32_t l16 = sbl + g16, g8 = g16 >> 1;
    uint4 u, v;
    uint8_t *pdst, *fdst;
    auto tok_pack = [&](int ty, const float* acc, uint32_t ftag, uint32_t ptag) {
        const bool tg = ty == 2 || !(g16 & 64);
        const uint32_t add = tg ? (ftag ^ 1) << 16 : 0u, keep = tg ? 0xfffe0000u : ~0u;
        const uint32_t add1 = ty == 2 ? 0u : add, keep1 = ty == 2 ? ~0u : keep;
        const uint32_t add2 = ty == 0 ? add : 0u, keep2 = ty == 0 ? keep : ~0u;
        v = {pack2(pretag(acc[0], add, keep), pretag(acc[1], add1, keep1)), pack2(acc[2], acc[3]),
             pack2(pretag(acc[4], add2, keep2), pretag(acc[5], add2, keep2)), pack2(acc[6], acc[7])};
        if (ty < 2) { v.x = movm(v.x); v.z = movm(v.z); v.y = movm(v.y); v.w = movm(v.w); }
        u = {pack2(pretag(acc[8], (ptag ^ 1) << 16, 0xfffe0000u), acc[9]) | ptag, pack2(acc[10], acc[11]), pack2(acc[12], acc[13]), pack2(acc[14], acc[15])};
        v.x = settag(v.x, ftag);
        if (ty == 0) v.z = settag(v.z, ftag);
    };

#pragma unroll 1
    for (int s = -2; s < 0; s++) {
        STEP_CONSTS
        (void)tag; (void)ttag; (void)tso; (void)fz;
        float acc[16];
        mbar_wait_w(bars + 8 * (B_HB + b), 0);
        wg_fence();
#pragma unroll
        for (int i = 0; i < 32; i++) {
            if (i < NL) wgmma_ss32(acc, dadd(mkdesc(SB0 + i * 2048, 8192, 1024, 1), wg * 4096), HB(i), i != 0);
            else wgmma_rs32(acc, w[i < NL ? 0 : i - NL], HB(i), 1);
        }
        wg_commit();
        uint4 pa;
        int it = 0;
#pragma unroll 1
        do pa = ldg_b128(arena + (pso + g16)); while ((p > 0) & any_bit0(pa.x ^ ftag) & (++it < POLL_LIMIT));
        pdst = arena + ((pso ^ (32768 + 2048)) + g16);
        fdst = arena + ((b ^ 1) * 32768 + lds1(sb + SM_TAB + wg * 4096 + (wg < 2 ? 2060 : 12) + g16));
        wg_wait<0>();
#pragma unroll
        for (int k = 0; k < 4; k++) { acc[2 * k] += bflo((&pa.x)[k]); acc[2 * k + 1] += bfhi((&pa.x)[k]); }
        tok_pack(wg, acc, ftag, ptag);
        stg_b128_if(true, pdst, u.x, u.y, u.z, u.w);
        stg_b128_if(p > 0, fdst, v.x, v.y, v.z, v.w);
        if (p == 0) {
            TL(2)
            bar_sync(NB_MEM, 384);
            if (wg == 1 && warp0) {
                if (g16 == 0) mbar_arrive_cluster(bars + 8 * B_HE, j ^ 1);
                mbar_wait_w(bars + 8 * B_HE, 1);
                h_load(sb, hsrc, 2, j, head);
            }
        }
    }

    auto qk_loop = [&](auto wgc) {
        constexpr int WG = decltype(wgc)::value;
        const uint32_t tabw = sb + SM_TAB + WG * 4096;
        uint32_t w0[NL][4], lm0;
        auto w0_load = [&](uint32_t wl) {
            lm0 = lds1(tabw + 12 + g16);
#pragma unroll
            for (int k = 0; k < NL; k++) ldsm4t(w0[k], wl + k * 2048);
        };
        w0_load(lds1(tabw + 2056 + g16));
#pragma unroll 1
        for (int s = 0;; s++) {
            STEP_CONSTS
            uint32_t wz0 = zero;
#pragma unroll
            for (int k = 0; k < NL; k += 2) wz0 = and3(wz0, w0[k][0], w0[k + 1 < NL ? k + 1 : k][0]);
            const uint32_t lm = lm0 + b * 65536 + wz0, lm1 = lm ^ 64;
            const bool fst = XP & 8 ? s == 99 : true, pst = XP & 8 ? s == 99 : s + 1 < NSEG;
            uint4 pa, t1;
            float acc[16];
            auto acc_init = [&]() {
#pragma unroll
                for (int k = 0; k < 4; k++) { acc[2 * k] = bflo((&pa.x)[k]); acc[2 * k + 1] = bfhi((&pa.x)[k]); acc[8 + 2 * k] = __uint_as_float((&pa.x)[k] & zero); acc[9 + 2 * k] = __uint_as_float(~(&pa.x)[k] & zero); }
            };
            BLOCK_FENCE
            if (P_GATE >= 0) bar_sync(NB_P, 384);
            stg_b128_if(fst, fdst, v.x, v.y, v.z, v.w);
            stg_b128_if(pst, pdst, u.x, u.y, u.z, u.w);
            bar_sync(NB_MEM, 384);
            PROF(1)
            { const int s_ = s; { const int s = s_ - 1; (void)s; PROF(16) } }
            uint32_t tq0;
            {
                float c[4][4];
                uint32_t xo;
#pragma unroll
                for (int it = 0; it < 16; it++) {
                    uint32_t bfr[4];
                    if (it == 10) xo = lds1(tabw + 4 + g16);
                    ldsm4(bfr, (it & 1 ? lm1 : lm) + (it >> 1) * HBK);
                    const uint32_t* wa = 2 * it < NL ? w0[2 * it < NL ? 2 * it : 0] : w[2 * it < NL ? 0 : 2 * it - NL];
                    const uint32_t* wb = 2 * it + 1 < NL ? w0[2 * it + 1 < NL ? 2 * it + 1 : 0] : w[2 * it + 1 < NL ? 0 : 2 * it + 1 - NL];
                    float *ca = c[(2 * it) & 3], *cb = c[(2 * it + 1) & 3];
                    if (it < 2) { mma16816z(ca, wa, bfr[0], bfr[1]); mma16816z(cb, wb, bfr[2], bfr[3]); }
                    else { mma16816(ca, wa[0], wa[1], wa[2], wa[3], bfr[0], bfr[1]); mma16816(cb, wb[0], wb[1], wb[2], wb[3], bfr[2], bfr[3]); }
                }
                const uint32_t r0 = pack2((c[0][0] + c[1][0]) + (c[2][0] + c[3][0]), (c[0][1] + c[1][1]) + (c[2][1] + c[3][1]));
                const uint32_t r1 = pack2((c[0][2] + c[1][2]) + (c[2][2] + c[3][2]), (c[0][3] + c[1][3]) + (c[2][3] + c[3][3]));
                const uint32_t m0 = movm(r0), m1 = movm(r1);
                tq0 = clk32();
                bar_arrive(NB_QK, 384);
                stg_rlx2(arena + xo, settag(m0, tag), m1);
            }
            PROF(2)
            uint32_t wf[NPF][4], a3;
#define WF(f) ((a3 ^ (((f) & 1) * 64)) + ((f) >> 1) * 2048)
            if (WG == 1) {
                float sc[5][4];
                int it = 0;
                bool bad;
#pragma unroll 1
                do {
                    uint4 kf[2][2];
                    U2 qf[2], x[8];
                    const uint32_t gz = g16 | (it & zero);
                    const uint8_t *ts = arena + (tso + tbw + gz), *tq = arena + (tso + tbq + gz), *xp = arena + lds1(tabw + 8 + gz);
#pragma unroll
                    for (int a = 0; a < 4; a++) kf[a >> 1][a & 1] = ldg_b128(ts + (a >> 1) * 16384 + (a & 1) * 2048);
#pragma unroll
                    for (int a = 0; a < 2; a++) qf[a] = ldg_u2(tq + a * 16384);
                    spin_until(tq0, dly.x2);
#pragma unroll
                    for (int i = 0; i < 8; i++) x[i] = ldg_u2(xp + (i >> 2) * 16384 + (i & 3) * 1024);
                    PROF(8)
                    const uint32_t q0[4] = {hadd2(x[0].x, x[1].x), qf[0].x, hadd2(x[0].y, x[1].y), qf[0].y};
                    const uint32_t q1[4] = {hadd2(x[2].x, x[3].x), qf[1].x, hadd2(x[2].y, x[3].y), qf[1].y};
                    PROFV(7, clk32() + (q0[0] & zero))
                    const uint32_t bt = ((qf[0].x ^ ttag) | (qf[1].x ^ ttag)) | ((kf[0][0].x ^ ttag) | (kf[0][1].x ^ ttag)) | ((kf[1][0].x ^ ttag) | (kf[1][1].x ^ ttag));
                    uint32_t bx = 0;
#pragma unroll
                    for (int i = 0; i < 8; i += 2) bx |= (x[i].x ^ tag) | (x[i + 1].x ^ tag);
                    mma16816z(sc[0], q0, kf[0][0].x, kf[0][0].y);
                    mma16816z(sc[1], q0, kf[0][0].z, kf[0][0].w);
                    mma16816z(sc[2], q0, kf[0][1].x, kf[0][1].y);
                    mma16816z(sc[3], q0, kf[0][1].z, kf[0][1].w);
                    mma16816z(sc[4], q0, hadd2(x[4].x, x[5].x), hadd2(x[4].y, x[5].y));
                    bad = any_bit0((XP & 8 ? bt & zero : bt) | bx) & (++it < POLL_LIMIT);
                    mma16816(sc[0], q1[0], q1[1], q1[2], q1[3], kf[1][0].x, kf[1][0].y);
                    mma16816(sc[1], q1[0], q1[1], q1[2], q1[3], kf[1][0].z, kf[1][0].w);
                    mma16816(sc[2], q1[0], q1[1], q1[2], q1[3], kf[1][1].x, kf[1][1].y);
                    mma16816(sc[3], q1[0], q1[1], q1[2], q1[3], kf[1][1].z, kf[1][1].w);
                    mma16816(sc[4], q1[0], q1[1], q1[2], q1[3], hadd2(x[6].x, x[7].x), hadd2(x[6].y, x[7].y));
                } while (bad);
                PROFV(13, it - 1) MISS(1, it - 1)
                const uint32_t sx = sb + SM_SX + (g16 & 0x1f0) * 5;
                constexpr float SH = SM_L2E / 64;
                sts4(sx + (g16 >> 5 & 0x30), pack_h2(sc[0][0] * SH, sc[0][1] * SH), pack_h2(sc[1][0] * SH, sc[1][1] * SH),
                     pack_h2(sc[2][0] * SH, sc[2][1] * SH), pack_h2(sc[3][0] * SH, sc[3][1] * SH));
                sts1(sx + 64 + (g16 >> 7 & 0xc), pack_h2(sc[4][0] * SH, sc[4][1] * SH));
                bar_arrive(NB_X1, 384);
#pragma unroll
                for (int n = 0; n < 5; n++) sts2(sb + SM_SX + 2560 + g8 + n * 1088, sc[n][2], sc[n][3]);
                PROF(3)
                a3 = lds1(tabw + g16);
                softmax_rows(sb + SM_SX + 2560, sb + SM_PX + 1024, g16 | (clk32() & zero), qd * 8, [&]() { BLOCK_FENCE bar_sync(NB_PX, 128); }, [&]() {
                    BLOCK_FENCE
#pragma unroll
                    for (int f = 0; f < NE1; f++) ldsm4t(wf[f], WF(f));
                    BLOCK_FENCE
                });
                PROF(4)
            } else {
                a3 = lds1(tabw + g16);
                spin_until(tq0, dly.pa);
                uint4 x, y;
                int it = 0;
#pragma unroll 1
                do { x = ldg_b128(arena + (pso + g16)); y = ldg_b128(arena + (pso + tokbase(1) - tokbase(0) + g16)); }
                while (!(XP & 8) & (p <= NSEG) & any_bit0(xor_or(x.x, y.x, ftag)) & (++it < POLL_LIMIT));
                sts4(sb + SM_PA + g16, x.x, x.y, x.z, x.w);
                sts4(sb + SM_PA + 2048 + g16, y.x, y.y, y.z, y.w);
                if (NE) spin_until(tq0, dly.wf);
#pragma unroll
                for (int f = 0; f < NE; f++) ldsm4t(wf[f], WF(f));
                bar_sync(NB_X1, 384);
                if (E_MUL && g16 < 32) asm volatile("red.relaxed.gpu.global.max.u32 [%0], %1; red.relaxed.gpu.global.add.u32 [%0+4], 1;"
                                                    ::"l"(arena + ((blk(LB_TIME, 0) ^ (g16 << 8)) + qd * 1024 + (tq0 & zero))), "r"(gtime()) : "memory");
                __syncwarp();
                const uint32_t tx = clk32();
                if (H_POS == 2 && !(XP & 1) && warp1 && s + 3 <= NSEG) h_load(sb, hsrc, s + 3, j, head);
                spin_until(tx, dly.w2);
            }
#pragma unroll
            for (int f = WG ? NE1 : NE; f < NPF; f++) ldsm4t(wf[f], WF(f));
            PROF(5)
            if (s + 1 == NSEG) { bar_arrive(NB_X2, 384); break; }
            const uint32_t oa = l16 + SM_OX, slot = mem_slot(s + 1);
            float c[4][4];
            uint32_t ob[4][4];
            uint32_t wz = zero;
#pragma unroll
            for (int f = 0; f < NPF; f += 2) wz = and3(wz, wf[f][0], wf[f + 1 < NPF ? f + 1 : f][0]);
            BLOCK_FENCE
            bar_sync(NB_X2 + (SETTLE ? wz : 0), 384);
            ldsm4t(ob[0], oa);
            ldsm4t(ob[1], oa + 512);
            SCHED_FENCE(0)
#pragma unroll
            for (int f = 0; f < 16; f++) {
                const uint32_t *a = wf[f % NPF], *o = ob[f >> 2] + (f & 2);
                if (f < 4) mma16816z(c[f], a, o[0], o[1]);
                else mma16816(c[f & 3], a[0], a[1], a[2], a[3], o[0], o[1]);
                if (f == 3) ldsm4t(ob[2], oa + 1024);
                if (f == 5) { ldsm4t(ob[3], oa + 1536); if (NPF < 16) ldsm4t(wf[0], WF(NPF)); }
                if (f == 7) {
#pragma unroll
                    for (int k = NPF + 1; k < 16; k++) ldsm4t(wf[k - NPF], WF(k));
                }
                if (f == 8) t1 = lds4(tabw + 2048 + g16);
                if (f == 9) { pa = lds4(sb + SM_PA + WG * 2048 + g16); SCHED_FENCE(4) }
                if (f == 3 || f == 5 || f == 7) SCHED_FENCE(f / 2)
            }
            acc_init();
            const float last = c[1][3] + c[3][3], one = __uint_as_float(CNT1 << 16);
            red_mem(arena + (t1.x + slot), pack2(c[0][0] + c[2][0], c[0][1] + c[2][1]), pack2(c[0][2] + c[2][2], c[0][3] + c[2][3]),
                    pack2(c[1][0] + c[3][0], c[1][1] + c[3][1]), pack2(c[1][2] + c[3][2], one),
                    arena + (t1.y + slot), pack2(one, last));
            hbo += FZ;
            PROF(6)
            constexpr int NS = WG ? NL : NL - W0_RS, GS = (32 - NL + NS) / NS;
            if (WG == 0) {
                bar_arrive(NB_WIN, 384);
                spin_until(clk32(), dly.tv);
                w0_load(t1.z);
            }
            asm volatile("" : F16(acc, 0));
            if (WG == 0) BLOCK_FENCE
            wg_fence();
            bar_sync(WG ? NB_WIN : NB_B, WG ? 384 : 256);
#pragma unroll
            for (int i = 0; i < 32; i++) {
                const int k = i / GS;
                if (i >= 32 - NL + NS) wgmma_rs32(acc, w0[i < 32 - NL + NS ? 0 : i - 32 + NL], HB(i - 32 + NL), 1);
                else if (i % GS == GS - 1 && k < NS) wgmma_ss32(acc, mkdesc(SB0 + WG * 65536 + k * 2048, 8192, 1024, 1), HB(k), 1);
                else wgmma_rs32(acc, w[i - (k < NS ? k : NS)], HB(NL + i - (k < NS ? k : NS)), 1);
                if (WG == 1 && i == G_AT) bar_arrive(NB_B, 256);
            }
            wg_commit();
            BLOCK_FENCE
            if (WG == 1) w0_load(t1.z);
            pdst = arena + ((pso ^ (32768 + 2048)) + g16);
            fdst = arena + ((b ^ 1) * 32768 + t1.w);
            BLOCK_FENCE
            wg_wait<0>();
            PROF(9)
            tok_pack(WG, acc, ftag, ptag);
            PROF(10) HT(6)
        }
    };
    if (wg == 0) {
        qk_loop(IC<0>());
    } else if (wg == 1) {
        qk_loop(IC<1>());
    } else {
        const uint32_t tabw = sb + SM_TAB + 8192, ONES = 0x3f803f80u;
        uint32_t ov[4] = {0, 0, 0, 0}, tw = 0, dl = 0, dx0 = lds1(sb + SM_TAB + 12288 + (g16 >> 2));
        uint4 t1 = lds4(tabw + 2048 + g16);
        uint8_t* od = (uint8_t*)g_O + t1.z;
        uint4 vf[2][2], pa;
        auto vf_fetch = [&](int s) {
            const uint8_t* ts = arena + ((s & 1) * 32768 + tbw + g16);
#pragma unroll
            for (int a = 0; a < 4; a++) vf[a >> 1][a & 1] = ldg_b128(ts + (a >> 1) * 16384 + (a & 1) * 2048);
        };
        auto tok_fetch = [&](int s) {
            if (TV_POS != 1) vf_fetch(s);
            pa = ldg_b128(arena + (tbw + (1 << 20) + (~s & 1) * 32768 + j * 16384 + kh * 2048 + g16));
        };
        if (PA_POS) tok_fetch(0);
        TL(9)
        mbar_wait_w(bars + 8 * B_WO, 0);
        TL(6)
#pragma unroll 1
        for (int s = 0; s < NSEG; s++) {
            STEP_CONSTS
#define VFBAD ((vf[0][0].x ^ ttag) | (vf[0][1].x ^ ttag) | (vf[1][0].x ^ ttag) | (vf[1][1].x ^ ttag))
#define TOKBAD ((TV_POS == 1 ? 0 : VFBAD) | (p <= NSEG ? pa.x ^ ftag : 0))
            {
                const uint32_t dst = t1.w + b * 65536, dx = dx0 + b * 65536;
                const uint8_t *ms = arena + (t1.x + mem_slot(s)), *me = arena + (t1.y + mem_slot(s));
                asm volatile("" : "+l"(ms), "+l"(me));
                spin_until(tw, dl);
                PROF(11)
                int it = 0;
                bool bad;
#pragma unroll 1
                do {
                    uint4 m[4];
                    uint32_t x[4];
#pragma unroll
                    for (int i = 0; i < 4; i++) m[i] = ldg_rlx4(ms + i * 1024);
#pragma unroll
                    for (int i = 0; i < 4; i++) x[i] = ldg_rlx1(me + i * 1024);
#pragma unroll
                    for (int i = 0; i < 4; i++) {
                        stsm4t(dst + i * 2 * HBK, m[i].x, m[i].y, m[i].z, m[i].w);
                        if (i == P_GATE) asm volatile("{.reg .pred p; setp.eq.s32 p, %0, 0; @p bar.arrive %1, 384;}" ::"r"(it), "n"(NB_P) : "memory");
                    }
                    BLOCK_FENCE
                    stsm4t(dx, x[0], x[1], x[2], x[3]);
                    asm volatile("" : "+r"(m[0].w));
                    const uint32_t c = and3((and3(m[0].w, m[1].w, m[2].w) & m[3].w) >> 16, x[0], x[1]);
                    bad = __any_sync(~0u, !(and3(c, x[2], x[3]) & CNT_ALL)) & (++it < POLL_LIMIT);
                } while (bad);
                PROFV(12, it - 1)
                bar_arrive(NB_MEM, 384);
                MISS(0, it - 1) HT(5)
                PROF(8)
            }
#pragma unroll
            for (int a = 0; a < 4; a++) stg_rlx1(od + a * 128, ov[a]);
            od = (uint8_t*)g_O + ((size_t)s * (32 * NH * DH * 2) + t1.z);
            const uint4 t0 = lds4(tabw + g16);
            if (s == 1) { TL(7) TLC(0) }
            if (s == 63) TLC(1)
            if (s == 0) TL(13)
            fence_async_smem();
            stg4_if(g16 < 160, arena + (t0.x + mem_slot(s + 3)), 0);
            int it = 0;
            if (!PA_POS) tok_fetch(s);
#pragma unroll 1
            while (!(XP & 8) & any_bit0(TOKBAD) & (++it < POLL_LIMIT)) tok_fetch(s + (it & zero));
            if (warp0 && ((s & 3) == 1 || s == 0)) {
                wait_count_w(&g_tick[32 + ((g16 >> 4) & 3) * 8], min((s + 3) / 4 + 1, 16));
                asm volatile("fence.proxy.async.global;" ::: "memory");
            }
            float acc[20];
#pragma unroll
            for (int k = 0; k < 4; k++) { acc[2 * k] = bflo((&pa.x)[k]); acc[2 * k + 1] = bfhi((&pa.x)[k]); acc[8 + 2 * k] = acc[9 + 2 * k] = acc[16 + k] = __uint_as_float(pa.x & zero); }
            if (XP & 1 ? s < 1 : p <= NSEG) mbar_wait_w(bars + 8 * (B_HB + b), (p >> 1) & 1);
            asm volatile("" : F16(acc, 0), F4(acc, 16));
            BLOCK_FENCE
            wg_fence();
            bar_sync(NB_QK, 384);
#pragma unroll
            for (int i = 0; i < 32; i++) {
                const int k = i / GAP;
                if (i % GAP == GAP - 1 && k < NL) wgmma_ss40(acc, mkdesc(SB0 + 131072 + k * 2048, 8192, 1024, 1), HB(k), 1);
                else wgmma_rs40(acc, w[i - (k < NL ? k : NL)], HB(NL + i - (k < NL ? k : NL)), 1);
            }
            wg_commit();
            uint8_t* vo = arena + t0.y;
            pdst = arena + ((pso ^ (32768 + 2048)) + g16);
            fdst = arena + ((b ^ 1) * 32768 + t0.w);
            BLOCK_FENCE
            wg_wait<0>();
            PROF(9)
            stg_rlx2(vo, settag(pack2(acc[16], acc[17]), tag), pack2(acc[18], acc[19]));
            const uint32_t tv = clk32();
            if (TV_POS == 1) vf_fetch(s);
            tok_pack(2, acc, ftag, ptag);
            stg_b128_if(XP & 8 ? s == 99 : p <= NSEG, fdst, v.x, v.y, v.z, v.w);
            stg_b128_if(XP & 8 ? s == 99 : p < NSEG, pdst, u.x, u.y, u.z, u.w);
            PROF(10)
            const uint8_t* xp = arena + t0.z;
            const uint32_t sxa = sb + SM_SX + (g16 & 0x1f0) * 5;
            uint32_t xv[4], gt = 0;
            auto pv = [&](uint32_t p0, uint32_t p1, uint32_t p2, uint32_t p3, uint32_t p4, auto getv) {
                float oc[2][4], lc[4] = {0.f, 0.f, 0.f, 0.f};
                mma16816(lc, ONES, ONES, ONES, ONES, p0, p1);
                mma16816z(oc[0], &vf[0][0].x, p0, p1);
                mma16816z(oc[1], &vf[1][0].x, p0, p1);
                mma16816(lc, ONES, ONES, ONES, ONES, p2, p3);
                mma16816(oc[0], vf[0][1].x, vf[0][1].y, vf[0][1].z, vf[0][1].w, p2, p3);
                mma16816(oc[1], vf[1][1].x, vf[1][1].y, vf[1][1].z, vf[1][1].w, p2, p3);
                mma1688(lc, ONES, ONES, p4);
                getv();
                mma1688(oc[0], xv[0], xv[1], p4);
                mma1688(oc[1], xv[2], xv[3], p4);
                const float r0 = rcp_fast(lc[0]), r1 = rcp_fast(lc[1]);
                ov[0] = pack2(oc[0][0] * r0, oc[0][1] * r1); ov[1] = pack2(oc[0][2] * r0, oc[0][3] * r1);
                ov[2] = pack2(oc[1][0] * r0, oc[1][1] * r1); ov[3] = pack2(oc[1][2] * r0, oc[1][3] * r1);
            };
            bool bad;
            it = 0;
#pragma unroll 1
            do {
                U2 xr[4];
                auto load_v = [&]() {
                    spin_until(tv, dly.v);
#pragma unroll
                    for (int i = 0; i < 4; i++) xr[i] = ldg_u2(xp + i * 1024);
                };
                if (TV_POS == 1 && it) {
                    const uint8_t* tz = arena + (tso + tbw + (g16 | (it & zero)));
#pragma unroll
                    for (int a = 0; a < 4; a++) ldg_b128_into(vf[a >> 1][a & 1], tz + (a >> 1) * 16384 + (a & 1) * 2048);
                }
                if (!V_POS) load_v();
                PROF(3)
                asm volatile("{.reg .pred p; setp.eq.s32 p, %0, 0; @p bar.sync %1, 384;}" ::"r"(it), "n"(NB_X1) : "memory");
                uint4 sx[5];
#pragma unroll
                for (int i = 0; i < 5; i++) sx[i] = lds4(sxa + i * 16);
                if (it == 0) { gt = gtime(); tw = clk32(); }
                if (V_POS == 2) load_v();
                uint32_t h[5];
#pragma unroll
                for (int n = 0; n < 4; n++) h[n] = add_h2(add_h2((&sx[0].x)[n], (&sx[1].x)[n]), add_h2((&sx[2].x)[n], (&sx[3].x)[n]));
                h[4] = add_h2(add_h2(sx[4].x, sx[4].y), add_h2(sx[4].z, sx[4].w));
                uint32_t hm = max_h2(max_h2(max_h2(h[0], h[1]), h[2]), max_h2(h[3], h[4]));
                hm = max_h2(hm, __byte_perm(hm, hm, 0x1032));
                const uint32_t m1 = __shfl_xor_sync(~0u, hm, 1), m2 = __shfl_xor_sync(~0u, hm, 2), m3 = __shfl_xor_sync(~0u, hm, 3);
                float2 a[5];
#pragma unroll
                for (int n = 0; n < 5; n++) a[n] = unpack_h2(h[n]);
                if (V_POS == 1) load_v(); else SCHED_FENCE(0)
                const float mb = -64.0f * unpack_h2(max_h2(max_h2(hm, m1), max_h2(m2, m3))).x;
                uint32_t pm[5];
#pragma unroll
                for (int n = 0; n < 5; n++) pm[n] = pack2(ex2(fmaf(a[n].x, 64.0f, mb)), ex2(fmaf(a[n].y, 64.0f, mb)));
                pv(pm[0], pm[1], pm[2], pm[3], pm[4], [&]() {
                    xv[0] = hadd2(xr[0].x, xr[1].x); xv[1] = hadd2(xr[0].y, xr[1].y);
                    xv[2] = hadd2(xr[2].x, xr[3].x); xv[3] = hadd2(xr[2].y, xr[3].y);
                });
                bad = any_bit0((TV_POS == 1 && !(XP & 8) ? VFBAD : 0) | (xr[0].x ^ tag) | (xr[1].x ^ tag) | (xr[2].x ^ tag) | (xr[3].x ^ tag)) & (++it < POLL_LIMIT);
                stsm4(sb + SM_OX + g16, ov[0], ov[1], ov[2], ov[3]);
            } while (bad);
            PROFV(14, it - 1) MISS(2, it - 1)
            PROF(5)
            bar_sync(NB_X2, 384);
            U2 tv2 = {0, 0};
            const uint8_t* tp = arena + (blk(LB_TIME, mypar) + (((g16 | (tw & zero)) << 6) & 0xc00));
            {
                const uint4 pp = lds4(l16 + SM_PX + 1024);
                const uint32_t p4 = lds1(sb + SM_PX + 512 + 1024 + ((g16 >> 2) & 0x7c));
                if (E_MUL) tv2 = ldg_u2(tp);
                if (H_POS == 0 && !(XP & 1) && warp0 && s + 3 <= NSEG) h_load(sb, hsrc, s + 3, j, head);
                pv(pp.x, pp.y, pp.z, pp.w, p4, []() {});
            }
            t1 = lds4(tabw + 2048 + g16);
            dx0 = lds1(sb + SM_TAB + 12288 + (g16 >> 2));
            PROF(6) HT(7)
            bar_arrive(NB_WIN + ((ov[0] | ov[3] | fz[0]) & zero), 384);
            BLOCK_FENCE
            if (H_POS == 1 && !(XP & 1) && warp0 && s + 3 <= NSEG) h_load(sb, hsrc, s + 3, j, head);
            asm volatile("" : "+r"(tv2.y));
            it = 0;
#pragma unroll 1
            while (E_MUL && __any_sync(~0u, tv2.y < 32 * (s + 1)) & (++it < 16)) tv2 = ldg_u2(tp);
            const uint32_t e = __reduce_max_sync(~0u, tv2.x) - gt;
            MISS(3, it - 1) MISS(4, gt)
            if (PA_POS) tok_fetch(s + 1);
            dl = (kh == mypar ? dly.near : dly.far) + (e > 4096 ? 0 : e * E_MUL >> 4);
        }
#pragma unroll
        for (int a = 0; a < 4; a++) stg_rlx1(od + a * 128, ov[a]);
        TL(8)
    }
    PROF_OUT
    MISS_OUT
}

struct RecMaps { CUtensorMap wq, wk, wv, wo; };
struct RecPtrs { const bf16 *x, *mem0, *c, *wmod, *w1, *w3; uint8_t* arena; uint32_t zero; const bf16 *w2, *w4, *wo; Delays dly; };

__device__ __forceinline__ float silu_bf(const bf16* c, int i) {
    const float v = __bfloat162float(c[i]);
    return bfround(__fdividef(v, 1.0f + __expf(-v)));
}
__device__ __noinline__ void rec_ln(float* coef, const RecPtrs& p, int id, int r0) {
    int r1 = 32;
    const int tid = threadIdx.x;
    const int lane = tid & 31, wid = tid >> 5;
    const uint32_t ring = smem_u32(coef) - SM_PRE + wid * 8192 + lane * 16;
    auto rowof = [&](int j) { return (j >> 1) * 64 + (id * 8 + wid) * 2 + (j & 1); };
    auto fetch = [&](int j) {
        if (j < 2 * r1) {
#pragma unroll
            for (int i = 0; i < 4; i++)
                asm volatile("cp.async.cg.shared.global [%0], [%1], 16;" ::"r"(ring + (j & 3) * 2048 + i * 512), "l"(p.x + (size_t)rowof(j) * DM + i * 256 + lane * 8) : "memory");
        }
        asm volatile("cp.async.commit_group;" ::: "memory");
    };
#pragma unroll 1
    for (int j = 2 * r0; j < 2 * r0 + 4; j++) fetch(j);
#pragma unroll 1
    for (int i = tid; i < 2 * DM / 4; i += 256) {
        uint4 v[8];
        int it = 0;
        uint32_t ok;
        do {
            ok = 1;
#pragma unroll
            for (int k = 0; k < 8; k++) v[k] = ldg_rlx4(g_modp + k * 2 * DM + i * 4);
#pragma unroll
            for (int k = 0; k < 8; k++) ok &= v[k].x & v[k].y & v[k].z & v[k].w;
            spin_guard(++it);
        } while (!ok);
        float t[4] = {0, 0, 0, 0};
#pragma unroll
        for (int k = 0; k < 8; k++) { t[0] += __uint_as_float(v[k].x); t[1] += __uint_as_float(v[k].y); t[2] += __uint_as_float(v[k].z); t[3] += __uint_as_float(v[k].w); }
#pragma unroll
        for (int j = 0; j < 4; j++) coef[i * 4 + j] = bfround(t[j]) + (i >= DM / 4 ? 1.0f : 0.0f);
    }
    bar_sync(NB_FIN0, 256);
    if (r0 == 0) {
        int v, it = 0;
#pragma unroll 1
        do { v = *(volatile int*)((uint8_t*)coef - SM_PRE + SM_BAR + 192); spin_guard(++it); } while (v == INT_MIN);
        if (v >= 0) r1 = 2;
    }
    if (tid == 0 && r0 == 0) TL(2)
#pragma unroll 1
    for (int j = 2 * r0; j < 2 * r1; j++) {
        float x[32];
        asm volatile("cp.async.wait_group 3;" ::: "memory");
#pragma unroll
        for (int i = 0; i < 4; i++) {
            const uint4 v = lds4(ring + (j & 3) * 2048 + i * 512);
            float* d = x + i * 8;
            d[0] = bflo(v.x); d[1] = bfhi(v.x); d[2] = bflo(v.y); d[3] = bfhi(v.y); d[4] = bflo(v.z); d[5] = bfhi(v.z); d[6] = bflo(v.w); d[7] = bfhi(v.w);
        }
        const int row = rowof(j), rr = row & 15;
        ln_row(x);
        fetch(j + 4);
#pragma unroll
        for (int i = 0; i < 4; i++) {
            float y[8];
            const float4* cf = (const float4*)(coef + i * 256 + lane * 8);
            const float4 s0 = cf[0], s1 = cf[1], c0 = cf[256], c1 = cf[257];
            const float sh[8] = {s0.x, s0.y, s0.z, s0.w, s1.x, s1.y, s1.z, s1.w}, sc[8] = {c0.x, c0.y, c0.z, c0.w, c1.x, c1.y, c1.z, c1.w};
#pragma unroll
            for (int e = 0; e < 8; e++) y[e] = fmaf(x[i * 8 + e], sc[e], sh[e]);
            const int own = ((row >> 4) & 1) == (i >> 1), c16 = i * 32 + lane;
            const uint32_t off = ((row >> 5) + own) * 65536 + (c16 >> 3) * 4096 + (rr + (own ? 0 : 16)) * 128 + (((c16 & 7) ^ (rr & 7)) << 4);
            *(uint4*)((uint8_t*)g_himg + off) = pack8(y);
        }
        if ((j & 3) != 3) continue;
        bar_sync(j == 3 ? NB_C : NB_FIN0, j == 3 ? 320 : 256);
        if (wid == 0) {
            if (j == 3) bar_arrive(NB_B, 64);
            if (lane == 0) { if (j == 7) wait_count1(&g_tick[32 + id * 8], 1); signal_count(&g_tick[32 + id * 8]); if (j < 8) TL(13) }
            __syncwarp();
        }
    }
}
#define SIDE_T 300
template <int NQ>
__device__ __forceinline__ void side_gemv(const bf16* w, int ld, int k0, int ks, const float* coef, uint32_t ring, float (*acc)[8]) {
#pragma unroll
    for (int q = 0; q < NQ; q++)
#pragma unroll
        for (int j = 0; j < 8; j++) acc[q][j] = 0.f;
    const uint32_t cs = smem_u32(coef);
    uint32_t wr = ring, t0 = clk32() + (threadIdx.x >> 5 & 3) * (SIDE_T / 4);
    w += (size_t)k0 * ld;
#pragma unroll 1
    for (int k = k0 - 16 * ks; k < DM; k += 8 * ks) {
        const uint32_t rd = wr == ring + 32768 ? ring : wr + 16384;
        asm volatile("cp.async.wait_group 1;" ::: "memory");
#pragma unroll 1
        for (int r = 0; r < 8; r += 4) {
            uint4 v[4];
            float cf[NQ][4];
#pragma unroll
            for (int h = 0; h < 4; h++) {
                v[h] = lds4(rd + (r + h) * 2048);
#pragma unroll
                for (int q = 0; q < NQ; q++) cf[q][h] = __uint_as_float(lds1(cs + (q * DM + max(k, 0) + (r + h) * ks) * 4));
            }
            if (k + 16 * ks < DM) {
#pragma unroll
                for (int h = 0; h < 4; h++) asm volatile("cp.async.cg.shared.global [%0], [%1], 16;" ::"r"(wr + (r + h) * 2048), "l"(w + h * ks * ld) : "memory");
                w += 4 * ks * ld;
            }
            if (k >= 0) {
#pragma unroll
                for (int h = 0; h < 4; h++) {
                    const float f[8] = {bflo(v[h].x), bfhi(v[h].x), bflo(v[h].y), bfhi(v[h].y), bflo(v[h].z), bfhi(v[h].z), bflo(v[h].w), bfhi(v[h].w)};
#pragma unroll
                    for (int q = 0; q < NQ; q++)
#pragma unroll
                        for (int j = 0; j < 8; j++) acc[q][j] = fmaf(cf[q][h], f[j], acc[q][j]);
                }
            }
            t0 += SIDE_T;
            while ((int)(clk32() - t0) < 0) {}
        }
        asm volatile("cp.async.commit_group;" ::: "memory");
        wr = rd;
    }
}
__device__ __noinline__ void rec_side(float* sm, const RecPtrs& p, int id) {
    const int tid = threadIdx.x;
    const uint32_t* steps = (const uint32_t*)(p.arena + (LB_TIME << 13) + 4);
    if (tid < 256) {
        if (blockIdx.x < 128) rec_ln(sm + SM_PRE / 4, p, id, 2);
        if (tid == 0) TL(14)
        for (int i = tid; i < 2 * S_; i += 256) g_st[id * 2 * S_ + i] = 0.f;
        if (id == 0 && tid < 64) g_pcnt[tid * 8] = 0;
        if (id == 1) for (int i = tid; i < 5 * 256; i += 256) g_pflag[i] = 0;
        int it = 0;
#pragma unroll 1
        while (ldg_rlx1(steps) < 32 * SPF_AT && ++it < POLL_LIMIT) __nanosleep(1000);
#pragma unroll 1
        for (int m = 0; m < 6; m++) {
            if (!((SPF >> m) & 1)) continue;
            const uint8_t* w = (const uint8_t*)(m == 0 ? p.wo : m == 1 ? p.w1 : m == 2 ? p.w2 : m == 3 ? p.w3 : m == 4 ? p.w4 : p.x);
            const int n = (m == 0 ? 4096 : m < 3 ? 1024 : m == 5 ? 2048 : FF) * 2048 / 4;
#pragma unroll 1
            for (int o = tid * 128; o < n; o += 256 * 128) {
                asm volatile("prefetch.global.L2 [%0];" ::"l"(w + id * n + o));
                __nanosleep(SPF_NS);
            }
        }
        return;
    }
    const int t = tid - 256;
    float *coef = sm + 32768, *red = coef + 3 * DM;
    const uint32_t ring = smem_u32(sm) + 65536 + t * 16;
    for (int i = t; i < DM; i += 128) { coef[i] = silu_bf(p.c, i); coef[2 * DM + i] = 1.0f; }
    if (t == 0) wait_count1(&g_tick[32 + id * 8], 2);
    bar_sync(NB_G, 128);
    float acc[3][8];
    side_gemv<1>(p.wmod + (2 + id) * DM + t * 8, 6 * DM, 0, 1, coef, ring, acc);
#pragma unroll
    for (int j = 0; j < 8; j++) g_mod[(2 + id) * DM + t * 8 + j] = bfround(acc[0][j]);
    bar_sync(NB_G, 128);
    if (t == 0) signal_count(&g_tick[8]);
    side_gemv<1>(p.w3 + id * (FF / 4) + min(t, FF / 32 - 1) * 8, FF, 0, 1, coef + 2 * DM, ring, acc);
    if (t < FF / 32) {
#pragma unroll
        for (int j = 0; j < 8; j++) g_vec[3 * DM + id * (FF / 4) + t * 8 + j] = acc[0][j];
    }
    if (t == 0) wait_count1(&g_tick[8], 4);
    bar_sync(NB_G, 128);
    for (int i = t; i < DM; i += 128) { coef[i] = 1.0f + __ldcg(g_mod + 4 * DM + i); coef[DM + i] = __ldcg(g_mod + 3 * DM + i); }
    bar_sync(NB_G, 128);
    if (id == 1 && t < 32) {
        float u[5] = {0, 0, 0, 0, 0};
        for (int i = t; i < DM; i += 32) {
            const float a = coef[i], b = coef[DM + i];
            u[0] += a; u[1] += a * a; u[2] += a * b; u[3] += b; u[4] += b * b;
        }
#pragma unroll
        for (int q = 0; q < 5; q++) { const float r = warp_sum(u[q]); if (t == 0) g_cst[q] = r * (1.0f / DM); }
    }
    side_gemv<3>(p.w1 + id * 256 + (t & 31) * 8, DM, t >> 5, 4, coef, ring, acc);
#pragma unroll
    for (int q = 0; q < 3; q++)
#pragma unroll
        for (int j = 0; j < 8; j++) red[((t >> 5) * 3 + q) * 256 + (t & 31) * 8 + j] = acc[q][j];
    bar_sync(NB_G, 128);
    for (int i = t; i < 768; i += 128) g_vec[(i >> 8) * DM + id * 256 + (i & 255)] = (red[i] + red[768 + i]) + (red[1536 + i] + red[2304 + i]);
    if (t == 0) TL(9)
}

__global__ void __cluster_dims__(2, 1, 1) __launch_bounds__(384, 1)
k_rec(const __grid_constant__ RecMaps mp, const __grid_constant__ RecPtrs p) {
    extern __shared__ uint8_t smraw[];
    const uint32_t sb = smem_u32(smraw);
    if ((sb & 0x3FFFF) != SB0) __trap();
    const uint32_t bars = sb + SM_BAR;
    const int tid = threadIdx.x, lane = tid & 31, b = blockIdx.x;
    const int wid = __reduce_max_sync(~0u, tid >> 5);
    const uint32_t rank = b & 1;
    uint8_t* arena = p.arena;
    volatile int* sinfo = (volatile int*)(smraw + SM_BAR + 192);
    if (tid == 0) TL(0)
    if (tid == 0) sinfo[0] = INT_MIN;
    if (tid == 352) {
        for (int i = 0; i < 17; i++) mbar_init(bars + 8 * i, i == B_WO ? 4 : 1);
        asm volatile("fence.mbarrier_init.release.cluster;" ::: "memory");
        mbar_expect(bars + 8 * B_ROLE, 8);

    }
    __syncwarp();
    asm volatile("barrier.cluster.arrive.relaxed.aligned;" ::: "memory");
    int pr = 0, hA = 0;
    if (wid < 8) {
        if (b < 128) {
            const int cb = (b & 15) * 128, k0 = (b >> 4) * 128 + (tid >> 4);
            uint4 v[8];
#pragma unroll
            for (int i = 0; i < 8; i++) v[i] = __ldg((const uint4*)(p.wmod + (size_t)(k0 + 16 * i) * (6 * DM) + cb + (tid & 15) * 8));
            float acc[8] = {0, 0, 0, 0, 0, 0, 0, 0};
#pragma unroll
            for (int i = 0; i < 8; i++) {
                const float sv = silu_bf(p.c, k0 + 16 * i);
                acc[0] += sv * bflo(v[i].x); acc[1] += sv * bfhi(v[i].x); acc[2] += sv * bflo(v[i].y); acc[3] += sv * bfhi(v[i].y);
                acc[4] += sv * bflo(v[i].z); acc[5] += sv * bfhi(v[i].z); acc[6] += sv * bflo(v[i].w); acc[7] += sv * bfhi(v[i].w);
            }
            float* red = (float*)(smraw + SM_PRE);
            *(float4*)(red + (tid >> 4) * 128 + (tid & 15) * 8) = make_float4(acc[0], acc[1], acc[2], acc[3]);
            *(float4*)(red + (tid >> 4) * 128 + (tid & 15) * 8 + 4) = make_float4(acc[4], acc[5], acc[6], acc[7]);
            bar_sync(NB_FIN0, 256);
            if (wid < 4) {
                float t = 0;
#pragma unroll
                for (int i = 0; i < 16; i++) t += red[i * 128 + tid];
                stg_rlx1(&g_modp[(b >> 4) * 2 * DM + cb + tid], __float_as_uint(t) | 1u);
            }
        } else {
            rec_ln((float*)(smraw + SM_PRE), p, b - 128, 0);
        }
    } else if (wid >= 10 && b >= 128) {
        {
            const int w = (b - 128) * 2 + wid - 10;
            const uint16_t* src = (const uint16_t*)p.mem0 + (lane & 3) * 2 * DM + (w >> 2) * 512 + (w & 1) * 64 + (w & 2) * 8 + (lane >> 2);
            uint32_t v[4][4];
#pragma unroll
            for (int i = 0; i < 16; i++) v[i >> 2][i & 3] = src[(i >> 2) * 128 + (i & 2) * 16 + (i & 1) * 8] | ((uint32_t)src[DM + (i >> 2) * 128 + (i & 2) * 16 + (i & 1) * 8] << 16);
            uint8_t* d = arena + mem_row(w >> 2, w & 3, 0);
            uint8_t* e = d + 512 + lane * 4;
            d += lane * 16;
#pragma unroll
            for (int i = 0; i < 4; i++, d += 1024, e += 1024) {
                stg_rlx4(d, v[i][0], v[i][1], v[i][2], (v[i][3] & 0xffff) | CNT_ALL << 16);
                stg_rlx4(d + mem_slot(1), 0, 0, 0, 0);
                stg_rlx4(d + mem_slot(2), 0, 0, 0, 0);
                stg_rlx1(e, (v[i][3] & 0xffff0000u) | CNT_ALL); stg_rlx1(e + mem_slot(1), 0); stg_rlx1(e + mem_slot(2), 0);
            }
            if (w == 0 && lane < 8) stg_rlx2(arena + (LB_TIME << 13) + lane * 1024, 0, 0);
            bar_arrive(NB_C, 320);
        }
    } else if (rank == 0) {
        uint32_t best = ~0u;
        const int pg = wid < 10 ? 0 : 1 + (b >> 1) % 3;
        uint32_t* q = (uint32_t*)(arena + (pg << 21) + (pg ? blk(b >> 1, wid & 1) : blk(LB_PROBE, wid & 1) + b * 16));
        if (lane < 8) stg_rlx1(q + lane, 0);
        uint2 tk2 = ldg_rlx2(&g_tick[0]);
        __syncwarp();
        if (lane == 0) {
            q += 3;
            uint32_t v = atomicAdd(q, 1u);
#pragma unroll 1
            for (int r = 0; r < NPROBE; r++) {
                const uint32_t t0 = clk32() + (v >> 8);
                v = atomicAdd(q + (v >> 8), 1u);
                uint32_t t1;
                asm volatile("{.reg .pred p; setp.eq.u32 p, %1, 0xffffffff; @p exit; mov.u32 %0, %%clock;}" : "=r"(t1) : "r"(v) : "memory");
                best = min(best, t1 - t0);
            }
            sinfo[wid - 6] = best;
        }
        bar_sync(NB_KDONE, b < 128 ? 128 : 64);
        if (wid == 8) {
            const int par = sinfo[2] <= sinfo[3] ? 0 : 1, ncl = gridDim.x >> 1;
            int tk = 0, it = 0;
            const uint32_t vote = b < 128 && (sinfo[4] <= sinfo[5] ? 0 : 1) != par ? 256u << (8 * ((b >> 1) % 3)) : 0u;
            if (b >= 128) {
#pragma unroll 1
                while (!__all_sync(~0u, (int)((tk2.x + tk2.y) & 255) >= ncl - 2)) { tk2 = ldg_rlx2(&g_tick[0]); spin_guard(++it); }
            }
            if (lane == 0) tk = atomicAdd(&g_tick[par], 1u + vote) & 255;
#pragma unroll 1
            while (!__all_sync(~0u, (int)((tk2.x + tk2.y) & 255) >= ncl)) { tk2 = ldg_rlx2(&g_tick[0]); spin_guard(++it); }
            tk = __shfl_sync(~0u, tk, 0);
            const int n0 = tk2.x & 255, n1 = tk2.y & 255;
            hA = min(n0 >> 1, NH);
            const int q0 = 2 * hA, q1 = 2 * NH - q0;
            const int over = tk - (par ? q1 : q0), lack = max(par ? q0 - n0 : q1 - n1, 0);
            if (over < 0) pr = par ? q0 + tk : tk;
            else if (over < lack) pr = (par ? n0 : q0 + n1) + over;
            else pr = -1 - (over - lack + (par ? max(n0 - q0, 0) : 0));
#pragma unroll
            for (int i = 0; i < 3; i++) hA |= (((tk2.x + tk2.y) >> (8 + 8 * i)) & 255) > 10 ? 256 << i : 0;
        }
    }
    asm volatile("barrier.cluster.wait.aligned;" ::: "memory");
    if (wid == 8) {
        if (rank == 0) {
            if (lane == 0) {
                uint32_t rsb;
                asm("mapa.shared::cluster.u32 %0, %1, 1;" : "=r"(rsb) : "r"(sb));
                asm volatile("st.async.shared::cluster.mbarrier::complete_tx::bytes.v2.u32 [%0], {%1, %2}, [%3];"
                             ::"r"(rsb + SM_BAR + 192), "r"(pr), "r"(hA), "r"(rsb + SM_BAR + 8 * B_ROLE) : "memory");
                sinfo[0] = pr; sinfo[1] = hA;
                if (b >= 128) atomicOr(&g_tick[4], (pr < 0 ? 4u : 1u) << ((b - 128) >> 1));
            }
        } else {
            mbar_wait_w(bars + 8 * B_ROLE, 0);
            pr = sinfo[0];
        }
        TL(1)
        __syncwarp();
        bar_arrive(NB_A, 288);
        bar_arrive(NB_S, 128);
        if (b >= 128 && pr < 0) bar_sync(NB_B, 64);
        if (pr >= 0) {
            const int pu = __reduce_max_sync(~0u, pr), c0 = (pu >> 1) * 128 + rank * 64, r0 = (pu & 1) * 512;
            bool fast = false;
#pragma unroll 1
            for (int n = 0; n < 12; n++) {
                const int rot = b >= 128 ? 8 : 0, i = (n + rot) % 12;
                if (rot && n == 4) bar_sync(NB_B, 64);
                if (n >= W_INFL && !fast) {
                    const uint32_t v = ldg_rlx1(&g_tick[32 + (lane & 3) * 8]);
                    mbar_wait_w(bars + 8 * (B_W + (n - W_INFL + rot) % 12), 0);
                    fast = __all_sync(~0u, v != 0);
                }
                const int m = i < 8 ? i & 1 : 2, k = i < 8 ? i >> 1 : i - 8;
                const uint32_t dst = sb + m * 65536 + k * 16384, br = bars + 8 * (B_W + i);
                if (lane == 0) {
                    mbar_expect(br, 16384);
                    tma2d(dst, &mp.wq + m, c0, r0 + k * 128, br);
                    tma2d(dst + 8192, &mp.wq + m, c0, r0 + k * 128 + 64, br);
                }
                __syncwarp();
            }
        }
    } else {
        bar_sync(wid < 8 ? NB_A : NB_S, wid < 8 ? 288 : 128);
    }
    const int prr = __reduce_max_sync(~0u, sinfo[0]);
    hA = __reduce_max_sync(~0u, sinfo[1]);
    if (prr < 0) {
        int j = (b - 128) >> 1;
        if (b < 128) {
            uint32_t v;
            int it = 0;
#pragma unroll 1
            do { v = __reduce_max_sync(~0u, ldg_rlx1(&g_tick[4])); spin_guard(++it); } while (__popc(v) < 2);
            j = v == 3 ? -1 - prr : (v & 1) ^ 1;
        }
        rec_side((float*)smraw, p, j * 2 + rank);
        return;
    }
    const int role = (prr >> 1) * 4 + rank * 2 + (prr & 1);
    rec_main(sb, &mp.wo, arena, role, hA, wid >> 2, p.zero, p.dly);
}

__device__ __forceinline__ void wgmma_ss192(float* d, uint64_t a, uint64_t b, int sc) {
    asm volatile("{.reg .pred p; setp.ne.b32 p, %98, 0;\n wgmma.mma_async.sync.aligned.m64n192k16.f32.bf16.bf16 "
                 "{%0,%1,%2,%3,%4,%5,%6,%7,%8,%9,%10,%11,%12,%13,%14,%15,%16,%17,%18,%19,%20,%21,%22,%23,%24,%25,%26,%27,%28,%29,%30,%31,%32,%33,%34,%35,%36,%37,%38,%39,%40,%41,%42,%43,%44,%45,%46,%47,%48,%49,%50,%51,%52,%53,%54,%55,%56,%57,%58,%59,%60,%61,%62,%63,%64,%65,%66,%67,%68,%69,%70,%71,%72,%73,%74,%75,%76,%77,%78,%79,%80,%81,%82,%83,%84,%85,%86,%87,%88,%89,%90,%91,%92,%93,%94,%95}, %96, %97, p, 1, 1, 0, 1;}"
                 : F16(d, 0), F16(d, 16), F16(d, 32), F16(d, 48), F16(d, 64), F16(d, 80) : "l"(a), "l"(b), "r"(sc));
}
__device__ __forceinline__ void wgmma_ss256(float* d, uint64_t a, uint64_t b, int sc) {
    asm volatile("{.reg .pred p; setp.ne.b32 p, %130, 0;\n wgmma.mma_async.sync.aligned.m64n256k16.f32.bf16.bf16 "
                 "{%0,%1,%2,%3,%4,%5,%6,%7,%8,%9,%10,%11,%12,%13,%14,%15,%16,%17,%18,%19,%20,%21,%22,%23,%24,%25,%26,%27,%28,%29,%30,%31,%32,%33,%34,%35,%36,%37,%38,%39,%40,%41,%42,%43,%44,%45,%46,%47,%48,%49,%50,%51,%52,%53,%54,%55,%56,%57,%58,%59,%60,%61,%62,%63,%64,%65,%66,%67,%68,%69,%70,%71,%72,%73,%74,%75,%76,%77,%78,%79,%80,%81,%82,%83,%84,%85,%86,%87,%88,%89,%90,%91,%92,%93,%94,%95,%96,%97,%98,%99,%100,%101,%102,%103,%104,%105,%106,%107,%108,%109,%110,%111,%112,%113,%114,%115,%116,%117,%118,%119,%120,%121,%122,%123,%124,%125,%126,%127}, %128, %129, p, 1, 1, 0, 1;}"
                 : F16(d, 0), F16(d, 16), F16(d, 32), F16(d, 48), F16(d, 64), F16(d, 80), F16(d, 96), F16(d, 112) : "l"(a), "l"(b), "r"(sc));
}

constexpr uint32_t P_VEC = 212992, P_ROW = P_VEC + 6144, P_BAR = P_ROW + 4096, P_SMEM = P_BAR + 256;
constexpr uint32_t P_OUT = 180224, P_OUT3 = 147456, P_OUT4 = 163840;
#define PPH 1
#define FLAG_ST "st.release.gpu.global.u32"
#define FLAG_LD "ld.acquire.gpu.global.u32"
#define BA3 2
#define BA 5
#define BA0 1
constexpr int P_SA = 5, P_SB = 3;
constexpr int PB_FA = 0, PB_EA = 5, PB_FB = 10, PB_EB = 13, PB_OUT = 16;
enum { C_Y = 0, C_G = 1, C_X1 = 2, C_U = 3, C_S1 = 8, C_S3 = 9 };
enum { V_GA = 0, V_A = 1, V_B = 2, V_GB = 3, V_VA = 4, V_VB = 5, V_VC = 6, V_C3 = 7 };
struct PostMaps { CUtensorMap o, wo, y, w1, g, w2, x1, w3, u, w4, out; };
struct PostPtrs { const bf16* x; };

struct GeluK { float k0, k1, kh; };
__device__ __forceinline__ GeluK gelu_k(float c) { return {0.7978845608028654f * c, 0.7978845608028654f * 0.044715f * c * c * c, 0.5f * c}; }
__device__ __forceinline__ float gelu_s(float t, const GeluK& k) {
    const float u = t * fmaf(t * t, k.k1, k.k0);
    float th; asm("tanh.approx.f32 %0, %1;" : "=f"(th) : "f"(u));
    const float hx = k.kh * t;
    return fmaf(hx, th, hx);
}
__device__ __forceinline__ float2 ldsv(uint32_t a) {
    float2 v; asm("ld.shared.v2.f32 {%0,%1}, [%2];" : "=f"(v.x), "=f"(v.y) : "r"(a)); return v;
}
__device__ __forceinline__ void wait_smem(uint32_t a, int target) {
    int it = 0;
#pragma unroll 1
    while (true) {
        int v;
        asm volatile("ld.acquire.cta.shared.u32 %0, [%1];" : "=r"(v) : "r"(a) : "memory");
        if (__all_sync(~0u, v >= target)) break;
        spin_guard(++it);
    }
}

#define PP(i)
#define PH_(c, w, i)
struct Pipe { int st, ph; };
template <int ST> __device__ __forceinline__ void adv(Pipe& p) { if (++p.st == ST) { p.st = 0; p.ph ^= 1; } }

__device__ __forceinline__ void post_produce(uint32_t sb, const PostMaps& mp, int mb, int nb, int rank) {
    const int rh = 2 * mb + rank, lane = threadIdx.x & 31;
    int st = 0, pp = 0, st2 = 0, pp2 = 0;
#pragma unroll 1
    for (int ph = 0; ph < 7; ph++) {
        const bool W = ph == 3 || ph == 4;
        if (ph == 3 || ph >= 5) {
            const int n = ph == 5 ? P_SB : P_SA;
            const uint32_t e = sb + P_BAR + 8 * (ph == 5 ? PB_EB : PB_EA);
#pragma unroll 1
            for (int i = 0; i < n; i++) mbar_wait_w(e + 8 * i, pp ^ (i >= st));
            if (ph == 6) break;
            if (ph == 5) wait_smem(sb + P_BAR + 8 * (PB_OUT + (lane & 1)), 4);
            int t = st; st = st2; st2 = t; t = pp; pp = pp2; pp2 = t;
        }
        const int ST = W ? P_SB : P_SA, NK = ph == 0 ? 64 : ph == 5 ? 56 : 16, NB = ph == 3 ? 4 : ph == 4 ? 3 : 2;
        const uint32_t SBYTES = W ? 49152 : 32768;
        const uint32_t full = sb + P_BAR + 8 * (W ? PB_FB : PB_FA), empty = sb + P_BAR + 8 * (W ? PB_EB : PB_EA);
        const CUtensorMap* ta = &mp.o + 2 * (ph > 3 ? ph - 1 : ph);
        const CUtensorMap* tb = ta + 1;
        const int n0 = ph == 3 ? nb * 256 : ph == 4 ? 2048 + nb * 192 : nb * 128;
        const int amul = ph == 0 ? 256 : 64, arow = ph == 0 ? rh * 8 : rh * 64;
        const uint32_t shifts = ph == 2 ? 0x04000301u : 0x02020202u;
        const uint32_t* fl = &g_pflag[(ph == 5 ? C_U + ((lane >> 3) & 1) : ph - 1) * 256 + (ph == 2 ? min(max(rh + min(lane >> 3, 2) - 1, 0), 31) : rh) * 8 + (lane & 7)];
        uint32_t have = ph == 0 || ph == 4 ? 9 : 0;
        auto order = [&](int i, int& need, int& grp) {
            need = 0; grp = i & 1;
            if (ph == 5) {
                const int q = i < 32 ? i >> 2 : ((i - 32) * 43) >> 7, src = (q + (nb & 6)) & 7;
                need = (i < 32 ? 1 : 256) << src; grp = i < 32 ? i & 3 : i - 32 - 3 * q;
                return i + (src - q) * (i < 32 ? 4 : 3);
            }
            if (ph == 0) return i;
            const int kb = (i + 2 * (nb & 6)) & 15;
            need = (ph == 2 ? 0x10101 : 1) << (kb >> 1);
            return kb;
        };
        PH_(ph == PPH, 0, 26) PH_(ph == PPH, 1, 26)
        int ib = 0, sB = st, pB = pp;
#pragma unroll 1
        for (int i = 0; i < NK; i++) {
            int need, grp;
#pragma unroll 1
            for (const int lim = i || ph > 3 ? i + 1 : ph == 3 ? BA3 : ph ? BA : BA0; ib < lim; ib++) {
                const int kb = order(ib, need, grp);
                const uint32_t a = sb + sB * SBYTES, f = full + 8 * sB;
                mbar_wait_w(empty + 8 * sB, pB ^ 1);
                e_expect(f, 16384 + NB * 8192);
                e_tma2d(a + 16384, tb, n0, kb * 64, f);
                e_tma2d(a + 24576, tb, n0 + 64, kb * 64, f);
                if (W) { e_tma2d(a + 32768, tb, n0 + 128, kb * 64, f); if (ph == 3) e_tma2d(a + 40960, tb, n0 + 192, kb * 64, f); }
                if (++sB == ST) { sB = 0; pB ^= 1; }
            }
            const int kb = order(i, need, grp);
            PH_(ph == PPH && i == 0, 0, 27) PH_(ph == PPH && i == 0, 1, 27)
            if (ph == 0 && i == 0) {
                asm volatile("barrier.cluster.wait.aligned;" ::: "memory");
                PH_(PPH == 0, 0, 25) PH_(PPH == 0, 1, 25)
            }
            if ((__ballot_sync(~0u, have > grp) & need) != need) {
                int it = 0;
#pragma unroll 1
                do {
                    asm volatile(FLAG_LD " %0, [%1];" : "=r"(have) : "l"(fl) : "memory");
                    spin_guard(++it);
                } while ((__ballot_sync(~0u, have > grp) & need) != need);
                PH_(ph == PPH && i == 0, 0, 23) PH_(ph == PPH, 0, 24) PH_(ph == PPH && i == 0, 1, 23) PH_(ph == PPH, 1, 24)
                asm volatile("fence.proxy.async.global;" ::: "memory");
                PH_(ph == PPH && i == 0, 0, 25) PH_(ph == PPH && i == 0, 1, 25)
            }
            e_tma2d_mc(sb + st * SBYTES + rank * 8192, ta, kb * amul, arow + (int)((shifts >> ((kb & 12) * 2)) & 7) - 2, full + 8 * st);
            if (++st == ST) { st = 0; pp ^= 1; }
        }
    }
}

template <int PH>
__device__ __forceinline__ void post_mma(uint32_t sb, float* acc, Pipe& p, int wg, bool lead, int pi) {
    constexpr bool W = PH == 3 || PH == 4;
    constexpr int ST = W ? P_SB : P_SA, SBYTES = W ? 49152 : 32768, NK = PH == 0 ? 64 : PH == 5 ? 56 : 16;
    const uint32_t full = sb + P_BAR + 8 * (W ? PB_FB : PB_FA), empty = sb + P_BAR + 8 * (W ? PB_EB : PB_EA);
    constexpr uint64_t DA = PH == 0 ? mkdesc(SB0, 128, 1024, 0) : mkdesc(SB0, 16, 1024, 1);
    constexpr uint64_t DB = mkdesc(SB0 + 16384, 8192, 1024, 1);
    auto release = [&](int st) { if (lead) { mbar_arrive_cluster(empty + 8 * st, 0); mbar_arrive_cluster(empty + 8 * st, 1); } };
    int prev = 0;
#pragma unroll 1
    for (int kb = 0; kb < NK; kb++) {
        mbar_wait_w(full + 8 * p.st, p.ph);
        const uint32_t so = p.st * (SBYTES >> 4);
        const uint32_t a = (uint32_t)DA + so + wg * 512, b = (uint32_t)DB + so;
        wg_fence();
#pragma unroll
        for (int k = 0; k < 4; k++) {
            const uint64_t da = (DA & 0xffffffff00000000ull) | (a + k * (PH == 0 ? 16 : 2)), db = (DB & 0xffffffff00000000ull) | (b + k * 128);
            if (PH == 3) wgmma_ss256(acc, da, db, (kb | k) != 0);
            else if (PH == 4) wgmma_ss192(acc, da, db, (kb | k) != 0);
            else wgmma_ss128<PH == 0>(acc, da, db, (kb | k) != 0);
        }
        wg_commit();
        if (kb == 0) { PP(pi) if (PH == 0 && wg == 0) TL(11) }
        wg_wait<1>();
        if (kb > 0) release(prev);
        prev = p.st;
        adv<ST>(p);
    }
    wg_wait<0>();
    release(prev);
    PP(pi + 1)
}

__global__ void __cluster_dims__(2, 1, 1) __launch_bounds__(384, 1)
k_post(const __grid_constant__ PostMaps mp, const __grid_constant__ PostPtrs pp) {
    extern __shared__ uint8_t smraw[];
    const uint32_t sb = smem_u32(smraw);
    if ((sb & 0x3FFFF) != SB0) __trap();
    const int tid = threadIdx.x, lane = tid & 31;
    const int mb = blockIdx.x >> 3, nb = blockIdx.x & 7, rank = blockIdx.x & 1;
    const uint32_t bars = sb + P_BAR;
    if (tid < PB_OUT) {
        mbar_init(bars + 8 * tid, (tid >= PB_EA && tid < PB_FB) || tid >= PB_EB ? 4 : 1);
        asm volatile("fence.mbarrier_init.release.cluster;" ::: "memory");
    }
    if (tid == 32) sts4(bars + 8 * PB_OUT, 0, 0, 0, 0);
    if (tid >= 256 && tid < 267) asm volatile("prefetch.tensormap [%0];" ::"l"(&mp.o + (tid - 256)) : "memory");
    __syncthreads();
    asm volatile("barrier.cluster.arrive.aligned;" ::: "memory");
    if (tid < 256 || tid >= 288) asm volatile("barrier.cluster.wait.aligned;" ::: "memory");
    if (tid >= 256) {
        asm volatile("setmaxnreg.dec.sync.aligned.u32 40;");
        const int w = __reduce_max_sync(~0u, (tid >> 5) - 8);
        if (w == 0) {
            post_produce(sb, mp, mb, nb, rank);
        } else if (w < 3) {
            const int wg = w - 1, rh = 2 * mb + wg;
            float* rowc = (float*)(smraw + P_ROW) + (wg * 64 + lane * 2) * 8;
            int nout = 0, sig = 0;
#pragma unroll 1
            for (int i = 0; i < 8; i++) {
                const int cnt = (0x54392180u >> (4 * i)) & 15;
                if (cnt < C_S1) {
                    const int ng = cnt == 3 ? 4 : cnt == 4 ? 3 : 2, c0 = cnt == 3 ? nb * 256 : cnt == 4 ? 2048 + nb * 192 : nb * 128;
                    const uint32_t src = sb + (cnt == 3 ? P_OUT3 : cnt == 4 ? P_OUT4 : P_OUT) + wg * ng * 8192;
                    uint32_t* fl = &g_pflag[cnt * 256 + rh * 8 + nb];
#pragma unroll 1
                    for (int j = 0; j < ng; j++) {
                        bar_sync(4 + 4 * wg + (sig++ & 3), 160);
                        if (lane == 0) {
                            PH_(cnt == PPH - 1, wg, 20)
                            asm volatile("cp.async.bulk.tensor.2d.global.shared::cta.bulk_group [%0, {%2, %3}], [%1]; cp.async.bulk.commit_group;"
                                         ::"l"(&mp.y + 2 * (cnt > 3 ? cnt - 1 : cnt)), "r"(src + j * 8192), "r"(c0 + j * 64), "r"(rh * 64) : "memory");
                        }
                        __syncwarp();
                    }
                    if (lane == 0) {
                        asm volatile("cp.async.bulk.wait_group 0; fence.proxy.async.global;" ::: "memory");
                        PH_(cnt == PPH - 1, wg, 21)
                        asm volatile(FLAG_ST " [%0], %1;" ::"l"(fl), "r"(ng) : "memory");
                        PH_(cnt == PPH - 1, wg, 22)
                        asm volatile("st.release.cta.shared.u32 [%0], %1;" ::"r"(bars + 8 * (PB_OUT + wg)), "r"(nout + 1) : "memory");
                    }
                    nout++;
                    __syncwarp();
                    continue;
                }
                bar_sync(4 + 4 * wg + (sig++ & 3), 160);
                uint32_t* c = &g_pcnt[(cnt - C_S1) * 256 + rh * 8];
                if (lane == 0) { signal_count(c); wait_count1(c, 8); }
                __syncwarp();
                const float4* sp = (const float4*)g_st + rh * 32 + lane;
                float4 u[3] = {__ldcg(sp + (cnt == C_S1 ? 0 : 3) * (S_ / 2)), __ldcg(sp + S_ / 2), __ldcg(sp + S_)};
#pragma unroll 1
                for (int h = 0; h < 2; h++) {
                    const float id = 1.0f / DM;
                    const float m = u[0].x * id, var = fmaxf(u[0].y * id - m * m, 0.f) + 1e-5f, r = rsqrtf(var);
                    float sc = r, m2 = 0.f;
                    if (cnt == C_S1) {
                        m2 = r * (u[1].x * id - m * g_cst[0]) + g_cst[3];
                        const float e2 = r * r * (u[2].x * id - 2.0f * m * u[1].y * id + m * m * g_cst[1]) + 2.0f * r * (u[2].y * id - m * g_cst[2]) + g_cst[4];
                        sc = r * rsqrtf(fmaxf(e2 - m2 * m2, 0.f) + 1e-5f);
                    }
                    const GeluK k = gelu_k(sc);
                    *(float4*)(rowc + h * 8) = make_float4(k.k0, k.k1, k.kh, -m);
                    *(float4*)(rowc + h * 8 + 4) = make_float4(var * r, -m2 * var * r, r, -m * r);
#pragma unroll
                    for (int q = 0; q < 3; q++) { u[q].x = u[q].z; u[q].y = u[q].w; }
                }
                bar_arrive(1 + wg, 160);
            }
        }
    } else {
        asm volatile("setmaxnreg.inc.sync.aligned.u32 232;");
        const bf16* xin = pp.x;
        const int wg = __reduce_max_sync(~0u, tid >> 7), wi = (tid >> 5) & 3, g = lane >> 2, tq = lane & 3;
        const int rh = 2 * mb + wg, row = rh * 64 + wi * 16 + g;
        const bool lead = (tid & 127) == 0;
        PP(0)
        if (tid == 0) TL(10)
        uint4 xg[8];
#pragma unroll
        for (int i = 0; i < 8; i++)
            xg[i] = __ldg((const uint4*)(xin + (size_t)(rh * 64 + wi * 16 + (i & 3) * 4 + (lane >> 3)) * DM + nb * 128 + (i >> 2) * 64 + (lane & 7) * 8));
        if (blockIdx.x < 64) g_modp[blockIdx.x * 256 + tid] = 0;
        if (blockIdx.x == 64 && tid < 64) g_tick[tid] = 0;
        {
            float* sv = (float*)(smraw + P_VEC);
            if (tid < 128) {
                const int c = nb * 128 + tid;
                sv[V_GA * 128 + tid] = __ldcg(&g_mod[2 * DM + c]); sv[V_A * 128 + tid] = 1.0f + __ldcg(&g_mod[4 * DM + c]);
                sv[V_B * 128 + tid] = __ldcg(&g_mod[3 * DM + c]); sv[V_GB * 128 + tid] = __ldcg(&g_mod[5 * DM + c]);
            } else {
                const int c = nb * 128 + tid - 128;
                sv[V_VA * 128 + tid - 128] = __ldcg(&g_vec[c]); sv[V_VB * 128 + tid - 128] = __ldcg(&g_vec[DM + c]); sv[V_VC * 128 + tid - 128] = __ldcg(&g_vec[2 * DM + c]);
            }
            sv[V_C3 * 128 + tid] = __ldcg(&g_vec[3 * DM + nb * 256 + tid]);
            if (tid < 192) sv[V_C3 * 128 + 256 + tid] = __ldcg(&g_vec[3 * DM + 2048 + nb * 192 + tid]);
            bar_sync(3, 256);
        }
        uint32_t vec = sb + P_VEC + tq * 8;
        asm volatile("" : "+r"(vec) :: "memory");
        const uint32_t stw = sb + (wi * 16 + ((lane >> 3) & 1) * 8 + (lane & 7)) * 128 + (((lane >> 4) ^ (lane & 7)) << 4);
        int sig = 0;
        auto signal = [&]() { bar_arrive(4 + 4 * wg + (sig++ & 3), 160); };
        auto put64 = [&](uint32_t o, const float* v) {
#pragma unroll
            for (int jj = 0; jj < 4; jj++, v += 8) stsm4((stw + o) ^ (jj << 5), pack2(v[0], v[1]), pack2(v[2], v[3]), pack2(v[4], v[5]), pack2(v[6], v[7]));
            fence_async_smem();
            signal();
        };
        auto out_free = [&](int n) { wait_smem(bars + 8 * (PB_OUT + (lane & 1)), n); };
        const uint32_t rowc = sb + P_ROW + (wg * 64 + wi * 16 + g) * 32, o128 = P_OUT + wg * 16384;
        Pipe pa = {0, 0}, pb = {0, 0};
        uint32_t keep[32];
#define KEEP(jn, e) (((e) & 1) ? bfhi(keep[2 * (jn) + ((e) >> 1)]) : bflo(keep[2 * (jn) + ((e) >> 1)]))
        float mu1[2], r1[2];
        {
            float acc[64];
            const uint32_t xo = sb + o128 + wi * 2048 + (lane >> 3) * 128;
#pragma unroll
            for (int i = 0; i < 8; i++) sts4(xo + (i >> 2) * 8192 + (i & 3) * 512 + (((lane & 7) ^ ((i & 1) * 4 + (lane >> 3))) << 4), xg[i].x, xg[i].y, xg[i].z, xg[i].w);
            __syncwarp();
#pragma unroll
            for (int jj = 0; jj < 8; jj++) ldsm4(keep + jj * 4, (stw + o128 + (jj >> 2) * 8192) ^ ((jj & 3) << 5));
            __syncwarp();
            post_mma<0>(sb, acc, pa, wg, lead, 1);
            float st[2][6];
#pragma unroll
            for (int q = 0; q < 6; q++) st[0][q] = st[1][q] = 0.f;
#pragma unroll
            for (int jn = 0; jn < 16; jn++) {
                const float2 ga = ldsv(vec + V_GA * 512 + jn * 32), a = ldsv(vec + V_A * 512 + jn * 32);
                float xa[4];
#pragma unroll
                for (int e = 0; e < 4; e++) {
                    xa[e] = fmaf((e & 1) ? ga.y : ga.x, acc[4 * jn + e], KEEP(jn, e));
                    st[e >> 1][0] += xa[e]; st[e >> 1][1] = fmaf(xa[e], xa[e], st[e >> 1][1]);
                    acc[4 * jn + e] = ((e & 1) ? a.y : a.x) * xa[e];
                }
                keep[2 * jn] = pack2(xa[0], xa[1]); keep[2 * jn + 1] = pack2(xa[2], xa[3]);
                if ((jn & 7) == 7) put64(o128 + (jn >> 3) * 8192, acc + 4 * jn - 28);
            }
            PP(3)
#pragma unroll
            for (int jn = 0; jn < 16; jn++) {
                const float2 a = ldsv(vec + V_A * 512 + jn * 32), b = ldsv(vec + V_B * 512 + jn * 32);
#pragma unroll
                for (int e = 0; e < 4; e++) {
                    const float y = acc[4 * jn + e], aa = (e & 1) ? a.y : a.x, bb = (e & 1) ? b.y : b.x;
                    float* s = st[e >> 1];
                    s[2] += y; s[3] = fmaf(aa, y, s[3]); s[4] = fmaf(y, y, s[4]); s[5] = fmaf(bb, y, s[5]);
                }
            }
#pragma unroll
            for (int h = 0; h < 2; h++)
#pragma unroll
                for (int q = 0; q < 6; q++) { st[h][q] += __shfl_xor_sync(~0u, st[h][q], 1); st[h][q] += __shfl_xor_sync(~0u, st[h][q], 2); }
            if (tq < 3) {
#pragma unroll
                for (int h = 0; h < 2; h++)
                    red2(g_st + (tq * S_ + row + h * 8) * 2, tq == 0 ? st[h][0] : tq == 1 ? st[h][2] : st[h][4], tq == 0 ? st[h][1] : tq == 1 ? st[h][3] : st[h][5]);
            }
            signal();
            PP(29)
        }
        {
            float acc[64];
            post_mma<1>(sb, acc, pa, wg, lead, 4);
            float c1[2], c2[2], c3[2];
            GeluK gk[2];
            bar_sync(1 + wg, 160);
#pragma unroll
            for (int h = 0; h < 2; h++) {
                const float4 a = lds4f(rowc + h * 256), b = lds4f(rowc + h * 256 + 16);
                gk[h] = {a.x, a.y, a.z}; c1[h] = a.w; c2[h] = b.x; c3[h] = b.y; mu1[h] = b.w; r1[h] = b.z;
            }
#pragma unroll
            for (int jn = 0; jn < 16; jn++) {
                const float2 va = ldsv(vec + V_VA * 512 + jn * 32), vb = ldsv(vec + V_VB * 512 + jn * 32), vc = ldsv(vec + V_VC * 512 + jn * 32);
#pragma unroll
                for (int e = 0; e < 4; e++) {
                    const int h = e >> 1;
                    const float t = fmaf(c1[h], (e & 1) ? va.y : va.x, fmaf(c2[h], (e & 1) ? vb.y : vb.x, fmaf(c3[h], (e & 1) ? vc.y : vc.x, acc[4 * jn + e])));
                    acc[4 * jn + e] = gelu_s(t, gk[h]);
                }
                if ((jn & 7) == 7) put64(o128 + (jn >> 3) * 8192, acc + 4 * jn - 28);
            }
            PP(6)
        }
        {
            float acc[64];
            post_mma<2>(sb, acc, pa, wg, lead, 7);
#pragma unroll
            for (int jn = 0; jn < 16; jn++) {
                const float2 a = ldsv(vec + V_A * 512 + jn * 32), b = ldsv(vec + V_B * 512 + jn * 32);
#pragma unroll
                for (int e = 0; e < 4; e++) {
                    const int h = e >> 1;
                    acc[4 * jn + e] += fmaf(fmaf(KEEP(jn, e), r1[h], mu1[h]), (e & 1) ? a.y : a.x, (e & 1) ? b.y : b.x);
                }
                if ((jn & 7) == 7) put64(o128 + (jn >> 3) * 8192, acc + 4 * jn - 28);
            }
            PP(9)
            float st[2][2] = {{0.f, 0.f}, {0.f, 0.f}};
#pragma unroll
            for (int jn = 0; jn < 16; jn++) {
                const float2 gb = ldsv(vec + V_GB * 512 + jn * 32);
                float z[4];
#pragma unroll
                for (int e = 0; e < 4; e++) {
                    const float x1 = acc[4 * jn + e];
                    st[e >> 1][0] += x1; st[e >> 1][1] = fmaf(x1, x1, st[e >> 1][1]);
                    z[e] = fmaf((e & 1) ? gb.y : gb.x, x1, KEEP(jn, e));
                }
                keep[2 * jn] = pack2(z[0], z[1]); keep[2 * jn + 1] = pack2(z[2], z[3]);
            }
#pragma unroll
            for (int h = 0; h < 2; h++)
#pragma unroll
                for (int q = 0; q < 2; q++) { st[h][q] += __shfl_xor_sync(~0u, st[h][q], 1); st[h][q] += __shfl_xor_sync(~0u, st[h][q], 2); }
            if (tq < 2) red2(g_st + (3 * S_ + row + tq * 8) * 2, tq ? st[1][0] : st[0][0], tq ? st[1][1] : st[0][1]);
            signal();
            PP(30)
        }
        {
            uint32_t v3 = vec + V_C3 * 512;
#pragma unroll 1
            for (int r = 0; r < 2; r++) {
                float acc[128];
#pragma unroll
                for (int i = 96; i < 128; i++) acc[i] = 0.f;
                if (r == 0) post_mma<3>(sb, acc, pb, wg, lead, 10);
                else post_mma<4>(sb, acc, pb, wg, lead, 13);
                float c1[2];
                GeluK gk[2];
                if (r == 0) bar_sync(1 + wg, 160);
                out_free(3 + r);
#pragma unroll
                for (int h = 0; h < 2; h++) { const float4 a = lds4f(rowc + h * 256); gk[h] = {a.x, a.y, a.z}; c1[h] = a.w; }
                uint32_t o = r ? P_OUT4 + wg * 24576 : P_OUT3 + wg * 32768;
#pragma unroll 1
                for (int left = 3 - r; left >= 0; left--) {
#pragma unroll
                    for (int jn = 0; jn < 8; jn++) {
                        const float2 vc = ldsv(v3 + jn * 32);
#pragma unroll
                        for (int e = 0; e < 4; e++) acc[4 * jn + e] = gelu_s(fmaf(c1[e >> 1], (e & 1) ? vc.y : vc.x, acc[4 * jn + e]), gk[e >> 1]);
                    }
                    put64(o, acc);
#pragma unroll
                    for (int i = 0; i < 32; i++) acc[i] = acc[32 + i];
                    if (left > 1) {
#pragma unroll
                        for (int i = 32; i < 64; i++) acc[i] = acc[32 + i];
                        if (left > 2) {
#pragma unroll
                            for (int i = 64; i < 96; i++) acc[i] = acc[32 + i];
                        }
                    }
                    o += 8192; v3 += 256;
                }
                PP(12 + 3 * r)
            }
        }
        {
            float acc[64];
            post_mma<5>(sb, acc, pa, wg, lead, 16);
#pragma unroll
            for (int jn = 0; jn < 16; jn++) {
                const float2 gb = ldsv(vec + V_GB * 512 + jn * 32);
#pragma unroll
                for (int e = 0; e < 4; e++) acc[4 * jn + e] = fmaf((e & 1) ? gb.y : gb.x, acc[4 * jn + e], KEEP(jn, e));
                if ((jn & 7) == 7) put64(o128 + (jn >> 3) * 8192, acc + 4 * jn - 28);
            }
            PP(18)
            if (tid == 0) TL(12)
        }
    }
}

typedef CUresult (*EncFn)(CUtensorMap*, CUtensorMapDataType, cuuint32_t, void*, const cuuint64_t*, const cuuint64_t*, const cuuint32_t*,
                          const cuuint32_t*, CUtensorMapInterleave, CUtensorMapSwizzle, CUtensorMapL2promotion, CUtensorMapFloatOOBfill);

static CUtensorMap make_map(EncFn enc, const void* p, uint64_t inner, uint64_t outer, uint32_t bi = 64) {
    CUtensorMap m;
    cuuint64_t dims[2] = {inner, outer};
    cuuint64_t str[1] = {inner * 2};
    cuuint32_t box[2] = {bi, 64};
    cuuint32_t es[2] = {1, 1};
    enc(&m, CU_TENSOR_MAP_DATA_TYPE_BFLOAT16, 2, (void*)p, dims, str, box, es, CU_TENSOR_MAP_INTERLEAVE_NONE,
        bi == 64 ? CU_TENSOR_MAP_SWIZZLE_128B : CU_TENSOR_MAP_SWIZZLE_64B, CU_TENSOR_MAP_L2_PROMOTION_L2_256B, CU_TENSOR_MAP_FLOAT_OOB_FILL_NONE);
    return m;
}
static CUtensorMap make_map_o(EncFn enc, const void* p) {
    CUtensorMap m;
    cuuint64_t dims[2] = {16384, 256};
    cuuint64_t str[1] = {65536};
    cuuint32_t box[2] = {256, 8};
    cuuint32_t es[2] = {1, 1};
    enc(&m, CU_TENSOR_MAP_DATA_TYPE_UINT32, 2, (void*)p, dims, str, box, es, CU_TENSOR_MAP_INTERLEAVE_NONE, CU_TENSOR_MAP_SWIZZLE_NONE,
        CU_TENSOR_MAP_L2_PROMOTION_L2_256B, CU_TENSOR_MAP_FLOAT_OOB_FILL_NONE);
    return m;
}
template <class T> static T* sym(T& s) { void* p = nullptr; cudaGetSymbolAddress(&p, s); return (T*)p; }

static const Delays h_dly = {D_NEAR, D_FAR, D_X2, D_V, D_W2, D_PA, D_WF, D_TV};
extern "C" void kernel_launch(void* const* d_in, const int* in_sizes, int n_in, void* d_out, int out_size) {
    const bf16* x = (const bf16*)d_in[0];
    const bf16* mem0 = (const bf16*)d_in[1];
    const bf16 *Wq = (const bf16*)d_in[2], *Wk = (const bf16*)d_in[3], *Wv = (const bf16*)d_in[4], *Wo = (const bf16*)d_in[5];
    const bf16 *w1 = (const bf16*)d_in[8], *w2 = (const bf16*)d_in[9], *w3 = (const bf16*)d_in[10], *w4 = (const bf16*)d_in[11];
    const bf16 *c = (const bf16*)d_in[12], *wmod = (const bf16*)d_in[13];
    bf16* out = (bf16*)d_out;

    EncFn enc = nullptr;
    cudaDriverEntryPointQueryResult qr;
    cudaGetDriverEntryPoint("cuTensorMapEncodeTiled", (void**)&enc, cudaEnableDefault, &qr);
    CUtensorMap tWq = make_map(enc, Wq, NH * DH, DM), tWk = make_map(enc, Wk, NH * DH, DM), tWv = make_map(enc, Wv, NH * DH, DM);
    PostMaps mp;
    mp.o = make_map_o(enc, sym(g_O)); mp.wo = make_map(enc, Wo, DM, NH * DH);
    mp.y = make_map(enc, sym(g_y), DM, S_); mp.w1 = make_map(enc, w1, DM, DM);
    mp.g = make_map(enc, sym(g_g), DM, S_); mp.w2 = make_map(enc, w2, DM, DM);
    mp.x1 = make_map(enc, sym(g_x1), DM, S_); mp.w3 = make_map(enc, w3, FF, DM);
    mp.u = make_map(enc, sym(g_u), FF, S_); mp.w4 = make_map(enc, w4, DM, FF);
    mp.out = make_map(enc, out, DM, S_);
    cudaFuncSetAttribute(k_rec, cudaFuncAttributeMaxDynamicSharedMemorySize, SM_REC_TOTAL + 2048);
    cudaFuncSetAttribute(k_post, cudaFuncAttributeMaxDynamicSharedMemorySize, P_SMEM);

    uint8_t* arena = (uint8_t*)(((uintptr_t)sym(g_arena) + (2u << 20) - 1) & ~(uintptr_t)((2u << 20) - 1));
    const PostPtrs pp = {x};
    const RecPtrs rp = {x, mem0, c, wmod, w1, w3, arena, 0u, w2, w4, Wo, h_dly};
    const RecMaps rm = {tWq, tWk, tWv, mp.wo};
    k_rec<<<132, 384, SM_REC_TOTAL + 2048>>>(rm, rp);
    k_post<<<128, 384, P_SMEM>>>(mp, pp);
}
```

```cpp
#include <cuda_runtime.h>
#include <cuda.h>
#include <cuda_bf16.h>
#include <stdint.h>
#include <limits.h>

typedef __nv_bfloat16 bf16;

constexpr int S_ = 2048, DM = 1024, NH = 32, DH = 128, NSEG = 64, FF = 3584;
constexpr int SPIN_LIMIT = 1 << 22;
#define W_INFL 2
#define XP 0
#define H_PIECES 4
#define NPROBE 3

__device__ uint8_t g_arena[10 << 20];
__device__ uint32_t g_tick[64];
__device__ __align__(16) uint32_t g_modp[8 * 2 * DM];
__host__ __device__ constexpr uint32_t blk(uint32_t lb, uint32_t par) {
    return (lb << 13) | ((((lb) ^ (lb >> 3) ^ (lb >> 4) ^ (lb >> 6) ^ par) & 1) << 12);
}
__host__ __device__ constexpr uint32_t lb_x2(uint32_t h) { return (h & 1) | ((h >> 1) << 3); }
__host__ __device__ constexpr uint32_t mem_row(uint32_t kh, uint32_t b, uint32_t r) { return blk(128 | b, kh) + r * 1024; }
__device__ __forceinline__ uint32_t mem_slot(uint32_t s) { return ((s & 1) << 15) | ((s & 2) << 17); }
constexpr uint32_t CNT1 = 0x3d80, CNT_ALL = 0x4000;
constexpr uint32_t LB_PROBE = 6 | 64, LB_TIME = 6;
__host__ __device__ constexpr uint32_t lb_tok(uint32_t h) { return (h & 1) | ((h >> 1) << 3); }
__device__ float g_mod[6 * DM];
__device__ __align__(1024) bf16 g_himg[(S_ + 32) * DM];
__device__ __align__(1024) bf16 g_O[S_ * NH * DH];
__device__ __align__(1024) bf16 g_y[S_ * DM];
__device__ __align__(1024) bf16 g_g[S_ * DM];
__device__ __align__(1024) bf16 g_x1[S_ * DM];
__device__ __align__(16) float g_st[4 * S_ * 2];
__device__ float g_vec[3 * DM + FF];
__device__ float g_cst[8];
__device__ uint32_t g_pcnt[2 * 32 * 8], g_pflag[6 * 32 * 8];
__device__ __align__(1024) bf16 g_u[S_ * FF];

#define TL(i) {}
#define TLC(i) {}
__device__ __forceinline__ uint32_t smem_u32(const void* p) { return (uint32_t)__cvta_generic_to_shared(p); }
__device__ __forceinline__ void spin_guard(int it) {
    asm volatile("{.reg .pred p; setp.gt.s32 p, %0, %1; @p st.global.u32 [%2], %0;}" ::"r"(it), "n"(SPIN_LIMIT), "l"(1ull));
}
__device__ __forceinline__ void wg_fence() { asm volatile("wgmma.fence.sync.aligned;" ::: "memory"); }
__device__ __forceinline__ void wg_commit() { asm volatile("wgmma.commit_group.sync.aligned;" ::: "memory"); }
template <int N> __device__ __forceinline__ void wg_wait() { asm volatile("wgmma.wait_group.sync.aligned %0;" ::"n"(N) : "memory"); }
__host__ __device__ constexpr uint64_t mkdesc(uint32_t addr, uint32_t lbo, uint32_t sbo, uint32_t swz) {
    return (uint64_t)((addr & 0x3FFFF) >> 4) | ((uint64_t)(lbo >> 4) << 16) | ((uint64_t)(sbo >> 4) << 32) | ((uint64_t)swz << 62);
}
__device__ __forceinline__ uint64_t dadd(uint64_t d, uint32_t o) { return (d & 0xffffffff00000000ull) | (uint32_t)((uint32_t)d + o); }
__device__ __forceinline__ void mbar_init(uint32_t b, uint32_t c) { asm volatile("mbarrier.init.shared.b64 [%0], %1;" ::"r"(b), "r"(c) : "memory"); }
__device__ __forceinline__ void mbar_expect(uint32_t b, uint32_t tx) { asm volatile("mbarrier.arrive.expect_tx.shared.b64 _, [%0], %1;" ::"r"(b), "r"(tx) : "memory"); }
__device__ __forceinline__ void mbar_arrive(uint32_t b) { asm volatile("mbarrier.arrive.shared.b64 _, [%0];" ::"r"(b) : "memory"); }
__device__ __forceinline__ void mbar_arrive_cluster(uint32_t b, uint32_t cta) {
    asm volatile("{.reg .b32 r; mapa.shared::cluster.u32 r, %0, %1; mbarrier.arrive.shared::cluster.b64 _, [r];}" ::"r"(b), "r"(cta) : "memory");
}
__device__ __forceinline__ bool mbar_try(uint32_t b, uint32_t par) {
    uint32_t ok;
    asm volatile("{.reg .pred p; mbarrier.try_wait.parity.shared.b64 p, [%1], %2; selp.u32 %0, 1, 0, p;}" : "=r"(ok) : "r"(b), "r"(par) : "memory");
    return ok;
}
__device__ __forceinline__ void mbar_wait(uint32_t b, uint32_t par) {
    int it = 0;
#pragma unroll 1
    while (!mbar_try(b, par)) { spin_guard(++it); }
}
__device__ __forceinline__ void mbar_wait_w(uint32_t b, uint32_t par) {
    int it = 0;
    bool ok;
#pragma unroll 1
    do { ok = __all_sync(~0u, mbar_try(b, par)); spin_guard(++it); } while (!ok);
}
__device__ __forceinline__ void mbar_wait_cluster(uint32_t b, uint32_t par) {
    int it = 0;
    while (true) {
        uint32_t ok;
        asm volatile("{.reg .pred p; mbarrier.try_wait.parity.acquire.cluster.shared::cta.b64 p, [%1], %2; selp.u32 %0, 1, 0, p;}" : "=r"(ok) : "r"(b), "r"(par) : "memory");
        if (ok) break;
        spin_guard(++it);
    }
}
__device__ __forceinline__ void tma2d(uint32_t dst, const CUtensorMap* m, int c0, int c1, uint32_t bar) {
    asm volatile("cp.async.bulk.tensor.2d.shared::cluster.global.mbarrier::complete_tx::bytes [%0], [%1, {%3, %4}], [%2];" ::"r"(dst), "l"(m), "r"(bar), "r"(c0), "r"(c1) : "memory");
}
__device__ __forceinline__ void tma2d_mc(uint32_t dst, const CUtensorMap* m, int c0, int c1, uint32_t bar, uint16_t mask) {
    asm volatile("cp.async.bulk.tensor.2d.shared::cluster.global.mbarrier::complete_tx::bytes.multicast::cluster [%0], [%1, {%3, %4}], [%2], %5;" ::"r"(dst), "l"(m), "r"(bar), "r"(c0), "r"(c1), "h"(mask) : "memory");
}
__device__ __forceinline__ void bulk_g2s(uint32_t dst, const void* src, uint32_t bytes, uint32_t bar) {
    asm volatile("cp.async.bulk.shared::cluster.global.mbarrier::complete_tx::bytes [%0], [%1], %2, [%3];" ::"r"(dst), "l"(src), "r"(bytes), "r"(bar) : "memory");
}
__device__ __forceinline__ void bar_sync(int id, int n) { asm volatile("bar.sync %0, %1;" ::"r"(id), "r"(n) : "memory"); }
__device__ __forceinline__ void bar_arrive(int id, int n) { asm volatile("bar.arrive %0, %1;" ::"r"(id), "r"(n) : "memory"); }
__device__ __forceinline__ void cluster_sync_all() { asm volatile("barrier.cluster.arrive.aligned; barrier.cluster.wait.aligned;" ::: "memory"); }
__device__ __forceinline__ void fence_async_smem() { asm volatile("fence.proxy.async.shared::cta;" ::: "memory"); }
__device__ __forceinline__ void ldsm4t(uint32_t* r, uint32_t a) {
    asm volatile("ldmatrix.sync.aligned.m8n8.x4.trans.shared.b16 {%0,%1,%2,%3}, [%4];" : "=r"(r[0]), "=r"(r[1]), "=r"(r[2]), "=r"(r[3]) : "r"(a) : "memory");
}
__device__ __forceinline__ void ldsm4(uint32_t* r, uint32_t a) {
    asm volatile("ldmatrix.sync.aligned.m8n8.x4.shared.b16 {%0,%1,%2,%3}, [%4];" : "=r"(r[0]), "=r"(r[1]), "=r"(r[2]), "=r"(r[3]) : "r"(a) : "memory");
}
__device__ __forceinline__ uint32_t movm(uint32_t a) {
    uint32_t d; asm volatile("movmatrix.sync.aligned.m8n8.trans.b16 %0, %1;" : "=r"(d) : "r"(a)); return d;
}
__device__ __forceinline__ void mma16816(float* d, uint32_t a0, uint32_t a1, uint32_t a2, uint32_t a3, uint32_t b0, uint32_t b1) {
    asm volatile("mma.sync.aligned.m16n8k16.row.col.f32.bf16.bf16.f32 {%0,%1,%2,%3},{%4,%5,%6,%7},{%8,%9},{%0,%1,%2,%3};"
                 : "+f"(d[0]), "+f"(d[1]), "+f"(d[2]), "+f"(d[3]) : "r"(a0), "r"(a1), "r"(a2), "r"(a3), "r"(b0), "r"(b1));
}
__device__ __forceinline__ void mma16816z(float* d, const uint32_t* a, uint32_t b0, uint32_t b1) {
    asm volatile("mma.sync.aligned.m16n8k16.row.col.f32.bf16.bf16.f32 {%0,%1,%2,%3},{%4,%5,%6,%7},{%8,%9},{%10,%10,%10,%10};"
                 : "=f"(d[0]), "=f"(d[1]), "=f"(d[2]), "=f"(d[3]) : "r"(a[0]), "r"(a[1]), "r"(a[2]), "r"(a[3]), "r"(b0), "r"(b1), "f"(0.f));
}
__device__ __forceinline__ void mma1688(float* d, uint32_t a0, uint32_t a1, uint32_t b0) {
    asm volatile("mma.sync.aligned.m16n8k8.row.col.f32.bf16.bf16.f32 {%0,%1,%2,%3},{%4,%5},{%6},{%0,%1,%2,%3};"
                 : "+f"(d[0]), "+f"(d[1]), "+f"(d[2]), "+f"(d[3]) : "r"(a0), "r"(a1), "r"(b0));
}
__device__ __forceinline__ uint32_t pack2(float lo, float hi) {
    uint32_t r; asm("cvt.rn.bf16x2.f32 %0, %1, %2;" : "=r"(r) : "f"(hi), "f"(lo)); return r;
}
__device__ __forceinline__ uint32_t hadd2(uint32_t a, uint32_t b) {
    uint32_t r; asm("add.rn.bf16x2 %0, %1, %2;" : "=r"(r) : "r"(a), "r"(b)); return r;
}
__device__ __forceinline__ float bflo(uint32_t u) { return __uint_as_float(u << 16); }
__device__ __forceinline__ float bfhi(uint32_t u) { return __uint_as_float(u & 0xffff0000u); }
__device__ __forceinline__ float ex2(float x) { float r; asm("ex2.approx.ftz.f32 %0, %1;" : "=f"(r) : "f"(x)); return r; }
__device__ __forceinline__ uint4 ldg_rlx4(const void* p) {
    uint4 v; asm volatile("ld.relaxed.gpu.global.v4.u32 {%0,%1,%2,%3}, [%4];" : "=r"(v.x), "=r"(v.y), "=r"(v.z), "=r"(v.w) : "l"(p) : "memory"); return v;
}
__device__ __forceinline__ uint2 ldg_rlx2(const void* p) {
    unsigned long long v; asm volatile("ld.relaxed.gpu.global.b64 %0, [%1];" : "=l"(v) : "l"(p) : "memory");
    return make_uint2((uint32_t)v, (uint32_t)(v >> 32));
}
__device__ __forceinline__ uint32_t ldg_rlx1(const void* p) {
    uint32_t v; asm volatile("ld.relaxed.gpu.global.u32 %0, [%1];" : "=r"(v) : "l"(p) : "memory"); return v;
}
__device__ __forceinline__ void stg_rlx1(void* p, uint32_t v) { asm volatile("st.relaxed.gpu.global.u32 [%0], %1;" ::"l"(p), "r"(v) : "memory"); }
__device__ __forceinline__ void stg_rlx2(void* p, uint32_t x, uint32_t y) {
    unsigned long long v = (unsigned long long)x | ((unsigned long long)y << 32);
    asm volatile("st.relaxed.gpu.global.b64 [%0], %1;" ::"l"(p), "l"(v) : "memory");
}
__device__ __forceinline__ void stg_rlx4(void* p, uint32_t x, uint32_t y, uint32_t z, uint32_t w) {
    asm volatile("st.relaxed.gpu.global.v4.u32 [%0], {%1,%2,%3,%4};" ::"l"(p), "r"(x), "r"(y), "r"(z), "r"(w) : "memory");
}
__device__ __forceinline__ void sts4(uint32_t a, uint32_t x, uint32_t y, uint32_t z, uint32_t w) {
    asm volatile("st.shared.v4.u32 [%0], {%1,%2,%3,%4};" ::"r"(a), "r"(x), "r"(y), "r"(z), "r"(w) : "memory");
}
__device__ __forceinline__ uint4 lds4(uint32_t a) {
    uint4 v; asm volatile("ld.shared.v4.u32 {%0,%1,%2,%3}, [%4];" : "=r"(v.x), "=r"(v.y), "=r"(v.z), "=r"(v.w) : "r"(a) : "memory"); return v;
}
__device__ __forceinline__ void st_async4(uint32_t a, float x, float y, float z, float w, uint32_t bar) {
    asm volatile("st.async.shared::cluster.mbarrier::complete_tx::bytes.v4.f32 [%0], {%1,%2,%3,%4}, [%5];" ::"r"(a), "f"(x), "f"(y), "f"(z), "f"(w), "r"(bar) : "memory");
}
#define F4(d, i) "+f"(d[i]), "+f"(d[i + 1]), "+f"(d[i + 2]), "+f"(d[i + 3])
__device__ __forceinline__ void wgmma_rs32(float* d, const uint32_t* a, uint64_t b, int sc) {
    asm volatile("{.reg .pred p; setp.ne.b32 p, %21, 0;\n wgmma.mma_async.sync.aligned.m64n32k16.f32.bf16.bf16 {%0,%1,%2,%3,%4,%5,%6,%7,%8,%9,%10,%11,%12,%13,%14,%15}, {%16,%17,%18,%19}, %20, p, 1, 1, 0;}"
                 : F4(d, 0), F4(d, 4), F4(d, 8), F4(d, 12) : "r"(a[0]), "r"(a[1]), "r"(a[2]), "r"(a[3]), "l"(b), "r"(sc));
}
__device__ __forceinline__ void wgmma_ss32(float* d, uint64_t a, uint64_t b, int sc) {
    asm volatile("{.reg .pred p; setp.ne.b32 p, %18, 0;\n wgmma.mma_async.sync.aligned.m64n32k16.f32.bf16.bf16 {%0,%1,%2,%3,%4,%5,%6,%7,%8,%9,%10,%11,%12,%13,%14,%15}, %16, %17, p, 1, 1, 1, 0;}"
                 : F4(d, 0), F4(d, 4), F4(d, 8), F4(d, 12) : "l"(a), "l"(b), "r"(sc));
}
__device__ __forceinline__ void wgmma_rs40(float* d, const uint32_t* a, uint64_t b, int sc) {
    asm volatile("{.reg .pred p; setp.ne.b32 p, %25, 0;\n wgmma.mma_async.sync.aligned.m64n40k16.f32.bf16.bf16 {%0,%1,%2,%3,%4,%5,%6,%7,%8,%9,%10,%11,%12,%13,%14,%15,%16,%17,%18,%19}, {%20,%21,%22,%23}, %24, p, 1, 1, 0;}"
                 : F4(d, 0), F4(d, 4), F4(d, 8), F4(d, 12), F4(d, 16) : "r"(a[0]), "r"(a[1]), "r"(a[2]), "r"(a[3]), "l"(b), "r"(sc));
}
__device__ __forceinline__ void wgmma_ss40(float* d, uint64_t a, uint64_t b, int sc) {
    asm volatile("{.reg .pred p; setp.ne.b32 p, %22, 0;\n wgmma.mma_async.sync.aligned.m64n40k16.f32.bf16.bf16 {%0,%1,%2,%3,%4,%5,%6,%7,%8,%9,%10,%11,%12,%13,%14,%15,%16,%17,%18,%19}, %20, %21, p, 1, 1, 1, 0;}"
                 : F4(d, 0), F4(d, 4), F4(d, 8), F4(d, 12), F4(d, 16) : "l"(a), "l"(b), "r"(sc));
}
#define F16(d, i) F4(d, i), F4(d, i + 4), F4(d, i + 8), F4(d, i + 12)
template <int TA>
__device__ __forceinline__ void wgmma_ss128(float* d, uint64_t a, uint64_t b, int sc) {
    asm volatile("{.reg .pred p; setp.ne.b32 p, %66, 0;\n wgmma.mma_async.sync.aligned.m64n128k16.f32.bf16.bf16 "
                 "{%0,%1,%2,%3,%4,%5,%6,%7,%8,%9,%10,%11,%12,%13,%14,%15,%16,%17,%18,%19,%20,%21,%22,%23,%24,%25,%26,%27,%28,%29,%30,%31,"
                 "%32,%33,%34,%35,%36,%37,%38,%39,%40,%41,%42,%43,%44,%45,%46,%47,%48,%49,%50,%51,%52,%53,%54,%55,%56,%57,%58,%59,%60,%61,%62,%63}, %64, %65, p, 1, 1, %67, 1;}"
                 : F16(d, 0), F16(d, 16), F16(d, 32), F16(d, 48) : "l"(a), "l"(b), "r"(sc), "n"(TA));
}

__device__ __forceinline__ float warp_sum(float v) {
#pragma unroll
    for (int o = 16; o; o >>= 1) v += __shfl_xor_sync(~0u, v, o);
    return v;
}
__device__ __forceinline__ float bfround(float x) { return __bfloat162float(__float2bfloat16(x)); }

__device__ __forceinline__ void wait_count1(const uint32_t* p, uint32_t target) {
    int it = 0;
#pragma unroll 1
    while (true) {
        uint32_t v;
        asm volatile("ld.acquire.gpu.global.u32 %0, [%1];" : "=r"(v) : "l"(p) : "memory");
        if (v >= target) break;
        spin_guard(++it);
    }
}
__device__ __forceinline__ void red2(float* p, float a, float b) {
    asm volatile("red.relaxed.gpu.global.add.v2.f32 [%0], {%1, %2};" ::"l"(p), "f"(a), "f"(b) : "memory");
}
__device__ __forceinline__ void l2_prefetch(const void* p, uint32_t bytes) {
    asm volatile("cp.async.bulk.prefetch.L2.global [%0], %1;" ::"l"(p), "r"(bytes) : "memory");
}
__device__ __forceinline__ void signal_count(uint32_t* p) { asm volatile("red.release.gpu.global.add.u32 [%0], 1;" ::"l"(p) : "memory"); }
__device__ __forceinline__ void e_expect(uint32_t b, uint32_t tx) {
    asm volatile("{.reg .pred p; elect.sync _|p, 0xffffffff; @p mbarrier.arrive.expect_tx.shared.b64 _, [%0], %1;}" ::"r"(b), "r"(tx) : "memory");
}
__device__ __forceinline__ void e_tma2d(uint32_t dst, const CUtensorMap* m, int c0, int c1, uint32_t bar) {
    asm volatile("{.reg .pred p; elect.sync _|p, 0xffffffff;\n @p cp.async.bulk.tensor.2d.shared::cluster.global.mbarrier::complete_tx::bytes [%0], [%1, {%3, %4}], [%2];}"
                 ::"r"(dst), "l"(m), "r"(bar), "r"(c0), "r"(c1) : "memory");
}
__device__ __forceinline__ void e_tma2d_mc(uint32_t dst, const CUtensorMap* m, int c0, int c1, uint32_t bar) {
    asm volatile("{.reg .pred p; elect.sync _|p, 0xffffffff;\n @p cp.async.bulk.tensor.2d.shared::cluster.global.mbarrier::complete_tx::bytes.multicast::cluster [%0], [%1, {%3, %4}], [%2], %5;}"
                 ::"r"(dst), "l"(m), "r"(bar), "r"(c0), "r"(c1), "h"((uint16_t)3) : "memory");
}
__device__ __forceinline__ void e_prefetch(const void* p, uint32_t bytes) {
    asm volatile("{.reg .pred p; elect.sync _|p, 0xffffffff; @p cp.async.bulk.prefetch.L2.global [%0], %1;}" ::"l"(p), "r"(bytes) : "memory");
}
__device__ __forceinline__ void wait_count_w(const uint32_t* p, uint32_t target) {
    int it = 0;
#pragma unroll 1
    while (true) {
        uint32_t v;
        asm volatile("ld.acquire.gpu.global.u32 %0, [%1];" : "=r"(v) : "l"(p) : "memory");
        if (__all_sync(~0u, v >= target)) break;
        spin_guard(++it);
    }
}

__device__ __forceinline__ void ln_row(float* x) {
    float s = 0;
#pragma unroll
    for (int i = 0; i < 32; i++) s += x[i];
    float m = warp_sum(s) * (1.0f / DM);
    float q = 0;
#pragma unroll
    for (int i = 0; i < 32; i++) { x[i] -= m; q += x[i] * x[i]; }
    float r = rsqrtf(warp_sum(q) * (1.0f / DM) + 1e-5f);
#pragma unroll
    for (int i = 0; i < 32; i++) x[i] *= r;
}
__device__ __forceinline__ uint4 pack8(const float* x) {
    return make_uint4(pack2(x[0], x[1]), pack2(x[2], x[3]), pack2(x[4], x[5]), pack2(x[6], x[7]));
}
#define NL 6
constexpr uint32_t SM_HB = 16384, HBK = 5120, SM_SX = 57344, SM_OX = 122880, SM_PX = 124928, SM_PA = 126976, SM_WO = 147456,
                   SM_TAB = 212992, SM_PRE = SM_TAB, SM_BAR = 227328, SM_REC_TOTAL = 227328 + 256;
constexpr uint32_t SB0 = 1024;
constexpr int B_WO = 0, B_HE = 1, B_ROLE = 2, B_HB = 3, B_W = 5;
constexpr int NB_MEM = 1, NB_QK = 2, NB_X1 = 3, NB_X2 = 4, NB_WIN = 5, NB_WG = 6, NB_KDONE = 7, NB_FIN0 = 8, NB_P = 9, NB_PX = 10, NB_G = 11, NB_A = 12, NB_B = 13, NB_C = 14, NB_S = 15;
#define SPF 33
#define SPF_AT 54
#define SPF_R 12
#define SPF_NS 40
#define D_TPV 100
#define V_POS 2
#define D_X2 450
#define D_TV 50
#define D_V 400
#define D_NEAR 1750
#define D_FAR (D_NEAR - 140)
#define E_MUL 28
#define D_WF 60
#define NE 0
#define D_H 0
#define D_W2 150
#define SETTLE 0
#define TV_POS 1
#define D_PA 0
#define NE1 10
#define H_POS 0
#define PA_POS 1
#define G_AT 24
#define W0_AT 4
#define W0_RS (NL - 1)
#define P_GATE 0
#define NPF (NL + 6)

struct Delays { uint32_t near, far, x2, v, w2, pa, wf, tv; };
#define MISS(i, v)
#define MISS_INIT
#define MISS_OUT
#define HT(i)
#define PROF_INIT
#define PROF(i)
#define PROFV(i, v)
#define PROF_OUT

__device__ __forceinline__ uint32_t clk32() { uint32_t t; asm volatile("mov.u32 %0, %%clock;" : "=r"(t) :: "memory"); return t; }
__device__ __forceinline__ uint32_t gtime() { uint32_t t; asm volatile("mov.u32 %0, %%globaltimer_lo;" : "=r"(t) :: "memory"); return t; }
__device__ __forceinline__ void spin_until(uint32_t t0, uint32_t d) { while (clk32() - t0 < d) {} }
template <int N> __device__ __forceinline__ uint32_t delay(uint32_t zero) {
    float x = __uint_as_float(clk32());
#pragma unroll
    for (int i = 0; i < N; i++) asm volatile("ex2.approx.ftz.f32 %0, %0;" : "+f"(x));
    return __float_as_uint(x) & zero;
}
__device__ __forceinline__ uint32_t opaque(uint32_t v) { return __shfl_sync(~0u, v, threadIdx.x & 31); }
__device__ __forceinline__ uint32_t xor_or(uint32_t a, uint32_t b, uint32_t t) {
    uint32_t r; asm volatile("lop3.b32 %0, %1, %2, %3, 0x7E;" : "=r"(r) : "r"(a), "r"(b), "r"(t)); return r;
}
__device__ __forceinline__ uint32_t or3(uint32_t a, uint32_t b, uint32_t c) {
    uint32_t r; asm volatile("lop3.b32 %0, %1, %2, %3, 0xFE;" : "=r"(r) : "r"(a), "r"(b), "r"(c)); return r;
}
__device__ __forceinline__ uint32_t settag(uint32_t v, uint32_t tag) {
    uint32_t r; asm("lop3.b32 %0, %1, 1, %2, 0xB8;" : "=r"(r) : "r"(v), "r"(tag)); return r;
}
__device__ __forceinline__ void ldg4_if(uint4& v, const void* p, bool c) {
    asm volatile("{.reg .pred p; setp.ne.u32 p, %5, 0; @p ld.relaxed.gpu.global.v4.u32 {%0,%1,%2,%3}, [%4];}"
                 : "+r"(v.x), "+r"(v.y), "+r"(v.z), "+r"(v.w) : "l"(p), "r"((uint32_t)c) : "memory");
}
__device__ __forceinline__ uint4 ldg_rlx2x2(const void* p) {
    unsigned long long a, b;
    asm volatile("ld.relaxed.gpu.global.v2.b64 {%0,%1}, [%2];" : "=l"(a), "=l"(b) : "l"(p) : "memory");
    return make_uint4((uint32_t)a, (uint32_t)(a >> 32), (uint32_t)b, (uint32_t)(b >> 32));
}
__device__ __forceinline__ void stg_rlx2x2(void* p, uint32_t x, uint32_t y, uint32_t z, uint32_t w) {
    asm volatile("{.reg .b64 a, b; mov.b64 a, {%1,%2}; mov.b64 b, {%3,%4}; st.relaxed.gpu.global.v2.b64 [%0], {a, b};}" ::"l"(p), "r"(x), "r"(y), "r"(z), "r"(w) : "memory");
}
__device__ __forceinline__ void ldg1_if(uint32_t& v, const void* p, bool c) {
    asm volatile("{.reg .pred p; setp.ne.u32 p, %2, 0; @p ld.relaxed.gpu.global.u32 %0, [%1];}" : "+r"(v) : "l"(p), "r"((uint32_t)c) : "memory");
}
__device__ __forceinline__ void sts2(uint32_t a, float x, float y) { asm volatile("st.shared.v2.f32 [%0], {%1,%2};" ::"r"(a), "f"(x), "f"(y) : "memory"); }
__device__ __forceinline__ void sts4f(uint32_t a, float x, float y, float z, float w) {
    asm volatile("st.shared.v4.f32 [%0], {%1,%2,%3,%4};" ::"r"(a), "f"(x), "f"(y), "f"(z), "f"(w) : "memory");
}
__device__ __forceinline__ void sts1(uint32_t a, uint32_t x) { asm volatile("st.shared.u32 [%0], %1;" ::"r"(a), "r"(x) : "memory"); }
__device__ __forceinline__ uint32_t lds1(uint32_t a) { uint32_t v; asm volatile("ld.shared.u32 %0, [%1];" : "=r"(v) : "r"(a) : "memory"); return v; }
__device__ __forceinline__ float4 lds4f(uint32_t a) {
    float4 v; asm volatile("ld.shared.v4.f32 {%0,%1,%2,%3}, [%4];" : "=f"(v.x), "=f"(v.y), "=f"(v.z), "=f"(v.w) : "r"(a) : "memory"); return v;
}
__device__ __forceinline__ float2 lds2f(uint32_t a) {
    float2 v; asm volatile("ld.shared.v2.f32 {%0,%1}, [%2];" : "=f"(v.x), "=f"(v.y) : "r"(a) : "memory"); return v;
}
__device__ __forceinline__ bool any_bit0(uint32_t x) {
    uint32_t r;
    asm volatile("{.reg .pred p, q; .reg .b32 t; and.b32 t, %1, 1; setp.ne.u32 p, t, 0; vote.sync.any.pred q, p, 0xffffffff; selp.u32 %0, 1, 0, q;}" : "=r"(r) : "r"(x));
    return r;
}
__device__ __forceinline__ float rcp_fast(float x) { float r; asm("rcp.approx.ftz.f32 %0, %1;" : "=f"(r) : "f"(x)); return r; }
__device__ __forceinline__ void stsm4(uint32_t a, uint32_t r0, uint32_t r1, uint32_t r2, uint32_t r3) {
    asm volatile("stmatrix.sync.aligned.m8n8.x4.shared.b16 [%0], {%1,%2,%3,%4};" ::"r"(a), "r"(r0), "r"(r1), "r"(r2), "r"(r3) : "memory");
}
__device__ __forceinline__ void stsm4t(uint32_t a, uint32_t r0, uint32_t r1, uint32_t r2, uint32_t r3) {
    asm volatile("stmatrix.sync.aligned.m8n8.x4.trans.shared.b16 [%0], {%1,%2,%3,%4};" ::"r"(a), "r"(r0), "r"(r1), "r"(r2), "r"(r3) : "memory");
}
__device__ __forceinline__ uint32_t and3(uint32_t a, uint32_t b, uint32_t c) {
    uint32_t r; asm("lop3.b32 %0, %1, %2, %3, 0x80;" : "=r"(r) : "r"(a), "r"(b), "r"(c)); return r;
}
__device__ __forceinline__ void red_mem(void* p, uint32_t x, uint32_t y, uint32_t z, uint32_t w, void* q, uint32_t e) {
    asm volatile("red.relaxed.gpu.global.add.noftz.v4.bf16x2 [%0], {%1,%2,%3,%4}; red.relaxed.gpu.global.add.noftz.bf16x2 [%5], %6;"
                 ::"l"(p), "r"(x), "r"(y), "r"(z), "r"(w), "l"(q), "r"(e) : "memory");
}
__device__ __forceinline__ void stg4_if(bool c, void* p, uint32_t x) {
    asm volatile("{.reg .pred p; setp.ne.u32 p, %2, 0; @p st.relaxed.gpu.global.v4.u32 [%0], {%1,%1,%1,%1};}" ::"l"(p), "r"(x), "r"((uint32_t)c) : "memory");
}
__device__ __forceinline__ uint32_t max3u(uint32_t a, uint32_t b, uint32_t c) { return __vimax3_u32(a, b, c); }
__device__ __forceinline__ void fence_gpu() { asm volatile("fence.acq_rel.gpu;" ::: "memory"); }

__device__ __forceinline__ void h_load(uint32_t sb, const uint8_t* hsrc, int pass, uint32_t rank, uint32_t rot) {
    const uint8_t* src = hsrc + (size_t)pass * 65536;
    const uint32_t bar = sb + SM_BAR + 8 * (B_HB + (pass & 1)), dst = sb + SM_HB + (pass & 1) * 65536 + rank * 4 * HBK;
    e_expect(bar, 32768);
#pragma unroll 1
    for (int i = 0; i < H_PIECES; i++) {
        const uint32_t o = ((i + rot) & (H_PIECES - 1)) * (16384 / H_PIECES);
        asm volatile("{.reg .pred p; elect.sync _|p, 0xffffffff;\n"
                     " @p cp.async.bulk.shared::cluster.global.mbarrier::complete_tx::bytes.multicast::cluster [%0], [%1], %4, [%2], %3;}"
                     ::"r"(dst + o + (o >> 12) * 1024), "l"(src + o), "r"(bar), "h"((uint16_t)3), "n"(16384 / H_PIECES) : "memory");
    }
}
__device__ __forceinline__ uint4 ldg_b128(const void* p) {
    uint4 v;
    asm volatile("{.reg .b128 t; .reg .b64 a, b; ld.relaxed.gpu.global.b128 t, [%4]; mov.b128 {a, b}, t; mov.b64 {%0,%1}, a; mov.b64 {%2,%3}, b;}"
                 : "=r"(v.x), "=r"(v.y), "=r"(v.z), "=r"(v.w) : "l"(p) : "memory");
    return v;
}
__device__ __forceinline__ void ldg_b128_into(uint4& v, const void* p) {
    asm volatile("{.reg .b128 t; .reg .b64 a, b; ld.relaxed.gpu.global.b128 t, [%4]; mov.b128 {a, b}, t; mov.b64 {%0,%1}, a; mov.b64 {%2,%3}, b;}"
                 : "+r"(v.x), "+r"(v.y), "+r"(v.z), "+r"(v.w) : "l"(p) : "memory");
}
__device__ __forceinline__ void stg_b128_if(bool c, void* p, uint32_t x, uint32_t y, uint32_t z, uint32_t w) {
    asm volatile("{.reg .pred p; .reg .b128 t; .reg .b64 a, b; setp.ne.u32 p, %5, 0; mov.b64 a, {%1,%2}; mov.b64 b, {%3,%4}; mov.b128 t, {a, b}; @p st.relaxed.gpu.global.b128 [%0], t;}"
                 ::"l"(p), "r"(x), "r"(y), "r"(z), "r"(w), "r"((uint32_t)c) : "memory");
}
__device__ __forceinline__ float pretag(float x, uint32_t add, uint32_t keep) { return __uint_as_float((__float_as_uint(x) + add) & keep); }

template <class F, class G>
__device__ __forceinline__ void softmax_rows(uint32_t src, uint32_t dst, uint32_t g16, int row0, F ready, G mid) {
    const uint32_t u = (g16 >> 7) & 3, e = ((g16 >> 9) << 3) | ((g16 >> 4) & 7);
    uint32_t se = src + e * 8, su = se + u * 1088, d0 = dst + e * 16 + u * 4, d1 = dst + 512 + e * 4;
    int vis = row0 + (e >> 2) - 2 * (e & 3) - 8 * u;
    asm volatile("" : "+r"(se), "+r"(su), "+r"(d0), "+r"(d1), "+r"(vis));
    ready();
    const float2 p0 = lds2f(su), p1 = lds2f(su + 256), p2 = lds2f(su + 512), p3 = lds2f(su + 768);
    const float2 m0 = lds2f(se + 4352), m1 = lds2f(se + 4352 + 256), m2 = lds2f(se + 4352 + 512), m3 = lds2f(se + 4352 + 768);
    float a0 = (p0.x + p1.x) + (p2.x + p3.x), a1 = (p0.y + p1.y) + (p2.y + p3.y);
    const float a2 = (m0.x + m1.x) + (m2.x + m3.x), a3 = (m0.y + m1.y) + (m2.y + m3.y);
    if (vis < 0) a0 = -1e9f / 0.08838834764831845f;
    if (vis < 1) a1 = -1e9f / 0.08838834764831845f;
    int k = __float_as_int(fmaxf(fmaxf(a0, a1), fmaxf(a2, a3)));
    k ^= (k >> 31) & 0x7fffffff;
    const bool hi = g16 & 64;
    const int k0 = __reduce_max_sync(~0u, hi ? INT_MIN : k), k1 = __reduce_max_sync(~0u, hi ? k : INT_MIN);
    mid();
    k = hi ? k1 : k0;
    const float m = __int_as_float(k ^ ((k >> 31) & 0x7fffffff));
    const float sl2 = 0.08838834764831845f * 1.4426950408889634f, mb = -m * sl2;
    sts1(d0, pack2(ex2(fmaf(a0, sl2, mb)), ex2(fmaf(a1, sl2, mb))));
    sts1(d1, pack2(ex2(fmaf(a2, sl2, mb)), ex2(fmaf(a3, sl2, mb))));
}

__device__ __forceinline__ uint32_t pack_h2(float lo, float hi) {
    uint32_t r; asm("cvt.rn.satfinite.f16x2.f32 %0, %1, %2;" : "=r"(r) : "f"(hi), "f"(lo)); return r;
}
__device__ __forceinline__ float2 unpack_h2(uint32_t u) {
    float2 r; asm("{.reg .b16 l, h; mov.b32 {l, h}, %2; cvt.f32.f16 %0, l; cvt.f32.f16 %1, h;}" : "=f"(r.x), "=f"(r.y) : "r"(u)); return r;
}
__device__ __forceinline__ uint32_t add_h2(uint32_t a, uint32_t b) { uint32_t r; asm("add.rn.f16x2 %0, %1, %2;" : "=r"(r) : "r"(a), "r"(b)); return r; }
__device__ __forceinline__ uint32_t max_h2(uint32_t a, uint32_t b) { uint32_t r; asm("max.f16x2 %0, %1, %2;" : "=r"(r) : "r"(a), "r"(b)); return r; }
__device__ __forceinline__ void stg2_if(bool c, void* p, uint32_t x, uint32_t y) {
    asm volatile("{.reg .pred p; .reg .b64 v; setp.ne.u32 p, %3, 0; mov.b64 v, {%1, %2}; @p st.relaxed.gpu.global.b64 [%0], v;}" ::"l"(p), "r"(x), "r"(y), "r"((uint32_t)c) : "memory");
}
__device__ __forceinline__ void stg1_if(bool c, void* p, uint32_t x) {
    asm volatile("{.reg .pred p; setp.ne.u32 p, %2, 0; @p st.relaxed.gpu.global.u32 [%0], %1;}" ::"l"(p), "r"(x), "r"((uint32_t)c) : "memory");
}
struct U2 { uint32_t x, y; };
__device__ __forceinline__ U2 ldg_u2(const void* p) {
    U2 v; asm volatile("{.reg .b64 t; ld.relaxed.gpu.global.b64 t, [%2]; mov.b64 {%0, %1}, t;}" : "=r"(v.x), "=r"(v.y) : "l"(p) : "memory"); return v;
}
constexpr int POLL_LIMIT = 1 << 16;
constexpr float SM_L2E = 0.08838834764831845f * 1.4426950408889634f;
template <int V> struct IC { static constexpr int value = V; };
typedef unsigned long long u64;
__device__ __forceinline__ uint32_t lo32(u64 v) { return (uint32_t)v; }
__device__ __forceinline__ uint32_t hi32(u64 v) { return (uint32_t)(v >> 32); }
__device__ __forceinline__ u64 ldg_u64(const void* p) { u64 v; asm volatile("ld.relaxed.gpu.global.b64 %0, [%1];" : "=l"(v) : "l"(p) : "memory"); return v; }
__device__ __forceinline__ void ldg_u64_if(u64& v, const void* p, bool c) {
    asm volatile("{.reg .pred p; setp.ne.u32 p, %2, 0; @p ld.relaxed.gpu.global.b64 %0, [%1];}" : "+l"(v) : "l"(p), "r"((uint32_t)c) : "memory");
}
__device__ __forceinline__ void rec_main(uint32_t sb, const CUtensorMap* tWo, uint8_t* arena, int role, int hinfo, int wg, uint32_t zero, const Delays& dly) {
    const int hA = hinfo & 255;
    const int tid = threadIdx.x, t = tid & 127, lane = tid & 31, wi = t >> 5;
    const uint32_t bars = sb + SM_BAR;
    const int head = role >> 2, qd = role & 3, j = blockIdx.x & 1, kh = role & 1;
    const uint32_t mypar = head >= hA;
    const bool warp0 = __all_sync(~0u, wi == 0), warp1 = __all_sync(~0u, wi == 1);
    const uint8_t* hsrc = (const uint8_t*)g_himg + kh * 32768 + j * 16384;
    auto tokbase = [&](int ty) { return ((ty + 1) << 21) + blk(lb_tok(head), mypar ^ ((hinfo >> (8 + ty)) & 1)); };
    const uint32_t tbw = tokbase(wg), tbq = tokbase(0) + (qd >> 1) * 2048 + (qd & 1) * 8;
    uint32_t w[32 - NL][4];
    const uint32_t frow = ((lane >> 4) * 8 + (lane & 7)) * 128, fx = ((lane >> 3) & 1) ^ (lane & 7);
    const uint32_t wl0 = sb + wg * 65536 + frow + ((fx ^ (2 * wi)) << 4);
    {
#pragma unroll 1
        for (int i = 0; i < 4; i++) mbar_wait_w(bars + 8 * (B_W + (wg == 2 ? 8 + i : 2 * i + wg)), 0);
#pragma unroll
        for (int p = NL; p < 32; p++) ldsm4t(w[p - NL], wl0 + p * 2048);
        fence_async_smem();
        if (wg < 2) bar_sync(NB_WG, 256);
        if (wg > 0) wait_count_w(&g_tick[32 + (lane & 3) * 8], 1);
        if (wg == 1 && warp0) {
            if (lane == 0) mbar_arrive_cluster(bars + 8 * B_HE, j ^ 1);
            asm volatile("fence.proxy.async.global;" ::: "memory");
            mbar_wait_w(bars + 8 * B_HE, 0);
#pragma unroll 1
            for (int i = 0; i < 2; i++) h_load(sb, hsrc, i, j, head);
        }
        TL(3 + wg)
    }
    uint32_t g16 = opaque(t * 16);
    auto G16 = [&]() { asm volatile("" : "+r"(g16)); return g16; };
    const uint32_t wu = __reduce_max_sync(~0u, wi), sbl = sb - wu * 512;
    const uint32_t xso = blk(lb_x2(head), mypar), cu = kh * 2048 + (2 * j + (wu >> 1)) * 512;
    const uint32_t u_xo = xso + wg * 16384 + (wu & 1) * 2048 + (cu >> 1) - wu * 256, u_to = tbw + (wu & 1) * 16384 + cu - wu * 512;
    const uint32_t mrow = wg < 2 ? mem_row(wu >> 1, wg * 2 + (wu & 1), qd) : mem_row(kh, wu, 0);
    const uint32_t u_m = mrow - wu * 512, u_e = mrow + 512 - wu * 128;
#define TAB(i) lds1(sb + SM_TAB + (i) * 512 + (G16() >> 2))
    {
        const uint32_t r8 = lane & 7;
        bar_sync(NB_X2, 384);
        if (wg == 0 && lane == 0) {
            mbar_expect(bars + 8 * B_WO, 16384);
            tma2d(sb + SM_WO + wi * 16384, tWo, (wi >> 1) * 512 + qd * 128 + (wi & 1) * 64, head * DH, bars + 8 * B_WO);
            tma2d(sb + SM_WO + wi * 16384 + 8192, tWo, (wi >> 1) * 512 + qd * 128 + (wi & 1) * 64, head * DH + 64, bars + 8 * B_WO);
        }
        __syncwarp();
        const uint32_t tb = sb + SM_TAB + wg * 1536 + t * 4, ma = sb + SM_HB + 4096 + r8 * 128;
        if (wg < 2) {
            sts1(tb, sb + SM_WO + wi * 16384 + frow + ((fx ^ (2 * wg)) << 4));
            sts1(tb + 512, wl0);
            sts1(tb + 1024, ma + (((lane >> 3) ^ r8) << 4));
        } else {
            sts1(tb, ma + (wi & 1) * HBK + ((((wi & 2) + (lane >> 4) * 4 + ((lane >> 3) & 1)) ^ r8) << 4));
            sts1(tb + 512, ((((wi & 2) + 5) ^ r8) << 4) + (lane & 1 ? ma + ((wi & 1) + (lane >> 3) * 2) * HBK : sb + SM_HB - 128));
            sts1(tb + 1024, mem_row(role >> 6, (role >> 4) & 3, (role >> 2) & 3) + (lane < 8 ? qd * 128 + lane * 16 : 512 + qd * 32 + (lane & 1) * 16));
        }
    }
    PROF_INIT
    MISS_INIT
#define HB(ks) dadd(mkdesc(SB0 + SM_HB + ((ks) >> 2) * HBK + ((ks) & 3) * 32, 16, 1024, 1), hbo)
#define STEP_CONSTS                                                                                  \
    const uint32_t tag = (s & 1) ^ 1, ttag = ((s >> 1) & 1) ^ 1, tso = (s & 1) * 32768;              \
    G16();                            \
    const int p = s + 2, b = p & 1;                                                                  \
    uint32_t hbo = b * 4096, fz[5] = {0, 0, 0, 0, 0};                                                \
    const uint32_t ftag = (((p - 1) >> 1) & 1) ^ 1, ptag = ((p >> 1) & 1) ^ 1;                       \
    const uint32_t pso = tbw + (1 << 20) + (b ^ 1) * 32768 + j * 16384 + kh * 2048;
#define SCHED_FENCE(i) fz[i] = clk32();
#define FZ ((fz[0] | fz[1] | fz[2] | fz[3] | fz[4]) & zero)
#define BLOCK_FENCE asm volatile("pmevent 0;" ::: "memory");
    constexpr int GAP = 32 / NL;
#define l16 (sbl + g16)
#define g8 (g16 >> 1)
    uint4 u, v;
    uint8_t *pdst, *fdst;
    auto tok_pack = [&](int ty, const float* acc, uint32_t ftag, uint32_t ptag) {
        const bool tg = ty == 2 || !(g16 & 64);
        const uint32_t add = tg ? (ftag ^ 1) << 16 : 0u, keep = tg ? 0xfffe0000u : ~0u;
        const uint32_t add1 = ty == 2 ? 0u : add, keep1 = ty == 2 ? ~0u : keep;
        const uint32_t add2 = ty == 0 ? add : 0u, keep2 = ty == 0 ? keep : ~0u;
        v = {pack2(pretag(acc[0], add, keep), pretag(acc[1], add1, keep1)), pack2(acc[2], acc[3]),
             pack2(pretag(acc[4], add2, keep2), pretag(acc[5], add2, keep2)), pack2(acc[6], acc[7])};
        if (ty < 2) { v.x = movm(v.x); v.z = movm(v.z); v.y = movm(v.y); v.w = movm(v.w); }
        u = {pack2(pretag(acc[8], (ptag ^ 1) << 16, 0xfffe0000u), acc[9]) | ptag, pack2(acc[10], acc[11]), pack2(acc[12], acc[13]), pack2(acc[14], acc[15])};
        v.x = settag(v.x, ftag);
        if (ty == 0) v.z = settag(v.z, ftag);
    };

#pragma unroll 1
    for (int s = -2; s < 0; s++) {
        STEP_CONSTS
        (void)tag; (void)ttag; (void)tso; (void)fz;
        float acc[16];
        mbar_wait_w(bars + 8 * (B_HB + b), 0);
        wg_fence();
#pragma unroll
        for (int i = 0; i < 32; i++) {
            if (i < NL) wgmma_ss32(acc, dadd(mkdesc(SB0 + i * 2048, 8192, 1024, 1), wg * 4096), HB(i), i != 0);
            else wgmma_rs32(acc, w[i < NL ? 0 : i - NL], HB(i), 1);
        }
        wg_commit();
        uint4 pa;
        int it = 0;
#pragma unroll 1
        do pa = ldg_b128(arena + (pso + g16)); while ((p > 0) & any_bit0(pa.x ^ ftag) & (++it < POLL_LIMIT));
        pdst = arena + ((pso ^ (32768 + 2048)) + G16());
        fdst = arena + ((b ^ 1) * 32768 + u_to + g16);
        wg_wait<0>();
#pragma unroll
        for (int k = 0; k < 4; k++) { acc[2 * k] += bflo((&pa.x)[k]); acc[2 * k + 1] += bfhi((&pa.x)[k]); }
        tok_pack(wg, acc, ftag, ptag);
        stg_b128_if(true, pdst, u.x, u.y, u.z, u.w);
        stg_b128_if(p > 0, fdst, v.x, v.y, v.z, v.w);
        if (p == 0) {
            TL(2)
            bar_sync(NB_MEM, 384);
            if (wg == 1 && warp0) {
                if (g16 == 0) mbar_arrive_cluster(bars + 8 * B_HE, j ^ 1);
                mbar_wait_w(bars + 8 * B_HE, 1);
                h_load(sb, hsrc, 2, j, head);
            }
        }
    }

    auto qk_loop = [&](auto wgc) {
        constexpr int WG = decltype(wgc)::value;
        uint32_t w0[NL][4], lm0;
        auto w0_load = [&]() {
            const uint32_t wl = TAB(WG * 3 + 1);
            lm0 = TAB(WG * 3 + 2);
#pragma unroll
            for (int k = 0; k < NL; k++) ldsm4t(w0[k], wl + k * 2048);
        };
        w0_load();
#pragma unroll 1
        for (int s = 0;; s++) {
            STEP_CONSTS
            uint32_t wz0 = zero;
#pragma unroll
            for (int k = 0; k < NL; k += 2) wz0 = and3(wz0, w0[k][0], w0[k + 1 < NL ? k + 1 : k][0]);
            const uint32_t lm = lm0 + b * 65536 + wz0, lm1 = lm ^ 64;
            const bool fst = XP & 8 ? s == 99 : true, pst = XP & 8 ? s == 99 : s + 1 < NSEG;
            uint4 pa;
            float acc[16];
            auto acc_init = [&]() {
#pragma unroll
                for (int k = 0; k < 4; k++) { acc[2 * k] = bflo((&pa.x)[k]); acc[2 * k + 1] = bfhi((&pa.x)[k]); acc[8 + 2 * k] = __uint_as_float((&pa.x)[k] & zero); acc[9 + 2 * k] = __uint_as_float(~(&pa.x)[k] & zero); }
            };
            BLOCK_FENCE
            if (P_GATE >= 0) bar_sync(NB_P, 384);
            stg_b128_if(fst, fdst, v.x, v.y, v.z, v.w);
            stg_b128_if(pst, pdst, u.x, u.y, u.z, u.w);
            bar_sync(NB_MEM, 384);
            PROF(1)
            { const int s_ = s; { const int s = s_ - 1; (void)s; PROF(16) } }
            uint32_t tq0;
            {
                float c[4][4];
                const uint32_t xo = u_xo + (G16() >> 1);
#pragma unroll
                for (int it = 0; it < 16; it++) {
                    uint32_t bfr[4];
                    ldsm4(bfr, (it & 1 ? lm1 : lm) + (it >> 1) * HBK);
                    const uint32_t* wa = 2 * it < NL ? w0[2 * it < NL ? 2 * it : 0] : w[2 * it < NL ? 0 : 2 * it - NL];
                    const uint32_t* wb = 2 * it + 1 < NL ? w0[2 * it + 1 < NL ? 2 * it + 1 : 0] : w[2 * it + 1 < NL ? 0 : 2 * it + 1 - NL];
                    float *ca = c[(2 * it) & 3], *cb = c[(2 * it + 1) & 3];
                    if (it < 2) { mma16816z(ca, wa, bfr[0], bfr[1]); mma16816z(cb, wb, bfr[2], bfr[3]); }
                    else { mma16816(ca, wa[0], wa[1], wa[2], wa[3], bfr[0], bfr[1]); mma16816(cb, wb[0], wb[1], wb[2], wb[3], bfr[2], bfr[3]); }
                }
                float r[4];
#pragma unroll
                for (int e = 0; e < 4; e++) {
                    constexpr float SH = SM_L2E / 64;
                    r[e] = WG ? (c[0][e] + c[1][e]) + (c[2][e] + c[3][e]) : fmaf(c[2][e] + c[3][e], SH, (c[0][e] + c[1][e]) * SH);
                }
                const uint32_t r0 = pack2(r[0], r[1]), r1 = pack2(r[2], r[3]);
                const uint32_t m0 = movm(r0), m1 = movm(r1);
                tq0 = clk32();
                bar_arrive(NB_QK, 384);
                stg_rlx2(arena + xo, settag(m0, tag), m1);
            }
            PROF(2)
            uint32_t wf[NPF][4], a3;
#define WF(f) ((a3 ^ (((f) & 1) * 64)) + ((f) >> 1) * 2048)
            if (WG == 1) {
                float sc[5][4];
                uint32_t sx0 = sb + SM_SX - wu * (2560 - 16) + G16() * 5;
                asm volatile("" : "+r"(sx0));
                int it = 0;
                bool bad;
#pragma unroll 1
                do {
                    uint4 kf[2][2];
                    U2 qf[2], x[8];
                    const uint32_t gz = g16 | (it & zero);
                    const uint8_t *ts = arena + (tso + tbw + gz), *tq = arena + (tso + tbq + gz), *xp = arena + (xso + (gz >> 1));
#pragma unroll
                    for (int a = 0; a < 4; a++) kf[a >> 1][a & 1] = ldg_b128(ts + (a >> 1) * 16384 + (a & 1) * 2048);
#pragma unroll
                    for (int a = 0; a < 2; a++) qf[a] = ldg_u2(tq + a * 16384);
                    spin_until(tq0, dly.x2);
#pragma unroll
                    for (int i = 0; i < 8; i++) x[i] = ldg_u2(xp + (i >> 2) * 16384 + (i & 3) * 1024);
                    PROF(8)
                    const uint32_t q0[4] = {hadd2(x[0].x, x[1].x), qf[0].x, hadd2(x[0].y, x[1].y), qf[0].y};
                    const uint32_t q1[4] = {hadd2(x[2].x, x[3].x), qf[1].x, hadd2(x[2].y, x[3].y), qf[1].y};
                    PROFV(7, clk32() + (q0[0] & zero))
                    const uint32_t bt = ((qf[0].x ^ ttag) | (qf[1].x ^ ttag)) | ((kf[0][0].x ^ ttag) | (kf[0][1].x ^ ttag)) | ((kf[1][0].x ^ ttag) | (kf[1][1].x ^ ttag));
                    uint32_t bx = 0;
#pragma unroll
                    for (int i = 0; i < 8; i += 2) bx |= (x[i].x ^ tag) | (x[i + 1].x ^ tag);
                    mma16816z(sc[0], q0, kf[0][0].x, kf[0][0].y);
                    mma16816z(sc[1], q0, kf[0][0].z, kf[0][0].w);
                    mma16816z(sc[2], q0, kf[0][1].x, kf[0][1].y);
                    mma16816z(sc[3], q0, kf[0][1].z, kf[0][1].w);
                    mma16816z(sc[4], q0, hadd2(x[4].x, x[5].x), hadd2(x[4].y, x[5].y));
                    bad = any_bit0((XP & 8 ? bt & zero : bt) | bx) & (++it < POLL_LIMIT);
                    mma16816(sc[0], q1[0], q1[1], q1[2], q1[3], kf[1][0].x, kf[1][0].y);
                    mma16816(sc[1], q1[0], q1[1], q1[2], q1[3], kf[1][0].z, kf[1][0].w);
                    mma16816(sc[2], q1[0], q1[1], q1[2], q1[3], kf[1][1].x, kf[1][1].y);
                    mma16816(sc[3], q1[0], q1[1], q1[2], q1[3], kf[1][1].z, kf[1][1].w);
                    mma16816(sc[4], q1[0], q1[1], q1[2], q1[3], hadd2(x[6].x, x[7].x), hadd2(x[6].y, x[7].y));
                } while (bad);
                PROFV(13, it - 1) MISS(1, it - 1)
                sts4(sx0, pack_h2(sc[0][0], sc[0][1]), pack_h2(sc[1][0], sc[1][1]), pack_h2(sc[2][0], sc[2][1]), pack_h2(sc[3][0], sc[3][1]));
                sts1(sx0 + 64 - wu * 12, pack_h2(sc[4][0], sc[4][1]));
                bar_arrive(NB_X1, 384);
#pragma unroll
                for (int n = 0; n < 5; n++) sts2(sb + SM_SX + 2560 + g8 + n * 1088, sc[n][2], sc[n][3]);
                PROF(3)
                a3 = TAB(WG * 3);
                softmax_rows(sb + SM_SX + 2560, sb + SM_PX + 1024, g16 | (clk32() & zero), qd * 8, [&]() { BLOCK_FENCE bar_sync(NB_PX, 128); }, [&]() {
                    BLOCK_FENCE
#pragma unroll
                    for (int f = 0; f < NE1; f++) ldsm4t(wf[f], WF(f));
                    BLOCK_FENCE
                });
                PROF(4)
            } else {
                a3 = TAB(WG * 3);
                if (warp1 && (s & 3) < 2) asm volatile("fence.proxy.async.global;" ::: "memory");
                spin_until(tq0, dly.pa);
                uint4 x, y;
                int it = 0;
#pragma unroll 1
                do { x = ldg_b128(arena + (pso + g16)); y = ldg_b128(arena + (pso + tokbase(1) - tokbase(0) + g16)); }
                while (!(XP & 8) & (p <= NSEG) & any_bit0(xor_or(x.x, y.x, ftag)) & (++it < POLL_LIMIT));
                sts4(sb + SM_PA + g16, x.x, x.y, x.z, x.w);
                sts4(sb + SM_PA + 2048 + g16, y.x, y.y, y.z, y.w);
                if (NE) spin_until(tq0, dly.wf);
#pragma unroll
                for (int f = 0; f < NE; f++) ldsm4t(wf[f], WF(f));
                bar_sync(NB_X1, 384);
                if (E_MUL && g16 < 32) asm volatile("red.relaxed.gpu.global.max.u32 [%0], %1; red.relaxed.gpu.global.add.u32 [%0+4], 1;"
                                                    ::"l"(arena + ((blk(LB_TIME, 0) ^ (g16 << 8)) + qd * 1024 + (tq0 & zero))), "r"(gtime()) : "memory");
                __syncwarp();
                const uint32_t tx = clk32();
                if (H_POS == 2 && !(XP & 1) && warp1 && s + 3 <= NSEG) h_load(sb, hsrc, s + 3, j, head);
                spin_until(tx, dly.w2);
            }
#pragma unroll
            for (int f = WG ? NE1 : NE; f < NPF; f++) ldsm4t(wf[f], WF(f));
            PROF(5)
            if (s + 1 == NSEG) { bar_arrive(NB_X2, 384); break; }
            const uint32_t oa = l16 + SM_OX, slot = mem_slot(s + 1);
            float c[4][4];
            uint32_t ob[4][4];
            uint32_t wz = zero;
#pragma unroll
            for (int f = 0; f < NPF; f += 2) wz = and3(wz, wf[f][0], wf[f + 1 < NPF ? f + 1 : f][0]);
            BLOCK_FENCE
            bar_sync(NB_X2 + (SETTLE ? wz : 0), 384);
            ldsm4t(ob[0], oa);
            ldsm4t(ob[1], oa + 512);
            SCHED_FENCE(0)
#pragma unroll
            for (int f = 0; f < 16; f++) {
                const uint32_t *a = wf[f % NPF], *o = ob[f >> 2] + (f & 2);
                if (f < 4) mma16816z(c[f], a, o[0], o[1]);
                else mma16816(c[f & 3], a[0], a[1], a[2], a[3], o[0], o[1]);
                if (f == 3) ldsm4t(ob[2], oa + 1024);
                if (f == 5) { ldsm4t(ob[3], oa + 1536); if (NPF < 16) ldsm4t(wf[0], WF(NPF)); }
                if (f == 7) {
#pragma unroll
                    for (int k = NPF + 1; k < 16; k++) ldsm4t(wf[k - NPF], WF(k));
                }
                if (f == 3 || f == 5 || f == 7) SCHED_FENCE(f / 2)
                if (f == 11) SCHED_FENCE(4)
            }
            const float last = c[1][3] + c[3][3], one = __uint_as_float(CNT1 << 16);
            red_mem(arena + (u_m + slot + G16()), pack2(c[0][0] + c[2][0], c[0][1] + c[2][1]), pack2(c[0][2] + c[2][2], c[0][3] + c[2][3]),
                    pack2(c[1][0] + c[3][0], c[1][1] + c[3][1]), pack2(c[1][2] + c[3][2], one),
                    arena + (u_e + slot + (g16 >> 2)), pack2(one, last));
            hbo += FZ;
            PROF(6)
            constexpr int NS = WG ? NL : NL - W0_RS, GS = (32 - NL + NS) / NS;
            if (WG == 0) {
                bar_arrive(NB_WIN, 384);
                spin_until(clk32(), dly.tv);
                pa = lds4(sb + SM_PA + g16);
                w0_load();
                acc_init();
                asm volatile("" : F16(acc, 0));
                BLOCK_FENCE
            }
            wg_fence();
            bar_sync(WG ? NB_WIN : NB_B, WG ? 384 : 256);
#pragma unroll
            for (int i = 0; i < 32; i++) {
                const int k = i / GS;
                if (i >= 32 - NL + NS) wgmma_rs32(acc, w0[i < 32 - NL + NS ? 0 : i - 32 + NL], HB(i - 32 + NL), 1);
                else if (i % GS == GS - 1 && k < NS) wgmma_ss32(acc, mkdesc(SB0 + WG * 65536 + k * 2048, 8192, 1024, 1), HB(k), 1);
                else wgmma_rs32(acc, w[i - (k < NS ? k : NS)], HB(NL + i - (k < NS ? k : NS)), WG == 0 || i);
                if (WG == 1 && i == G_AT) bar_arrive(NB_B, 256);
            }
            wg_commit();
            BLOCK_FENCE
            if (WG == 1 && warp0 && !(s & 3)) wait_count_w(&g_tick[32 + ((G16() >> 4) & 3) * 8], min(s / 4 + 2, 16));
            if (WG == 1) { pa = lds4(sb + SM_PA + 2048 + g16); w0_load(); }
            pdst = arena + ((pso ^ (32768 + 2048)) + G16());
            fdst = arena + ((b ^ 1) * 32768 + u_to + g16);
            BLOCK_FENCE
            wg_wait<0>();
            PROF(9)
            if (WG == 1) {
#pragma unroll
                for (int k = 0; k < 4; k++) { acc[2 * k] += bflo((&pa.x)[k]); acc[2 * k + 1] += bfhi((&pa.x)[k]); }
            }
            tok_pack(WG, acc, ftag, ptag);
            PROF(10) HT(6)
        }
    };
    if (wg == 0) {
        qk_loop(IC<0>());
    } else if (wg == 1) {
        qk_loop(IC<1>());
    } else {
        const uint32_t ONES = 0x3f803f80u, u_o = qd * 65536 + head * 2048 + wu * 384;
        uint32_t tw = 0, dl = 0, dst0, dx0;
        dst0 = TAB(6); dx0 = TAB(7);
        uint4 vf[2][2], pa;
        auto vf_fetch = [&](int s) {
            const uint8_t* ts = arena + ((s & 1) * 32768 + tbw + g16);
#pragma unroll
            for (int a = 0; a < 4; a++) vf[a >> 1][a & 1] = ldg_b128(ts + (a >> 1) * 16384 + (a & 1) * 2048);
        };
        auto tok_fetch = [&](int s) {
            if (TV_POS != 1) vf_fetch(s);
            pa = ldg_b128(arena + (tbw + (1 << 20) + (~s & 1) * 32768 + j * 16384 + kh * 2048 + g16));
        };
        if (PA_POS) tok_fetch(0);
        TL(9)
        mbar_wait_w(bars + 8 * B_WO, 0);
        TL(6)
#pragma unroll 1
        for (int s = 0; s < NSEG; s++) {
            STEP_CONSTS
#define VFBAD ((vf[0][0].x ^ ttag) | (vf[0][1].x ^ ttag) | (vf[1][0].x ^ ttag) | (vf[1][1].x ^ ttag))
#define TOKBAD ((TV_POS == 1 ? 0 : VFBAD) | (p <= NSEG ? pa.x ^ ftag : 0))
            {
                const uint32_t dst = dst0 + b * 65536, dx = dx0 + b * 65536;
                const uint8_t *ms = arena + (u_m + mem_slot(s) + g16), *me = arena + (u_e + mem_slot(s) + (g16 >> 2));
                asm volatile("" : "+l"(ms), "+l"(me));
                spin_until(tw, dl);
                PROF(11)
                uint32_t it2 = 0;
                int it = 0;
                bool bad;
#pragma unroll 1
                do {
                    uint4 m[4];
                    uint32_t x[4];
#pragma unroll
                    for (int i = 0; i < 4; i++) m[i] = ldg_rlx4(ms + i * 1024);
#pragma unroll
                    for (int i = 0; i < 4; i++) x[i] = ldg_rlx1(me + i * 1024);
#pragma unroll
                    for (int i = 0; i < 4; i++) {
                        stsm4t(dst + i * 2 * HBK, m[i].x, m[i].y, m[i].z, m[i].w);
                        if (i == P_GATE) asm volatile("{.reg .pred p; setp.eq.s32 p, %0, 0; @p bar.arrive %1, 384;}" ::"r"(it), "n"(NB_P) : "memory");
                    }
                    BLOCK_FENCE
                    asm volatile("{.reg .b32 t; lop3.b32 %0, %1, %2, %3, 0x80; and.b32 %0, %0, %4; shr.u32 %0, %0, 16;}" : "+r"(it2) : "r"(m[0].w), "r"(m[1].w), "r"(m[2].w), "r"(m[3].w));
                    stsm4t(dx, x[0], x[1], x[2], x[3]);
                    it2 = and3(and3(it2, x[0], x[1]), x[2], x[3]);
                    bad = __any_sync(~0u, !(it2 & CNT_ALL)) & (++it < POLL_LIMIT);
                } while (bad);
                PROFV(12, it - 1)
                bar_arrive(NB_MEM, 384);
                MISS(0, it - 1) HT(5)
                PROF(8)
            }
            if (s == 1) { TL(7) TLC(0) }
            if (s == 63) TLC(1)
            if (s == 0) TL(13)
            fence_async_smem();
            int it = 0;
            if (!PA_POS) tok_fetch(s);
#pragma unroll 1
            while (!(XP & 8) & any_bit0(TOKBAD) & (++it < POLL_LIMIT)) tok_fetch(s + (it & zero));
            float acc[20];
#pragma unroll
            for (int k = 0; k < 4; k++) { acc[2 * k] = bflo((&pa.x)[k]); acc[2 * k + 1] = bfhi((&pa.x)[k]); acc[8 + 2 * k] = acc[9 + 2 * k] = acc[16 + k] = __uint_as_float(pa.x & zero); }
            if (XP & 1 ? s < 1 : p <= NSEG) mbar_wait_w(bars + 8 * (B_HB + b), (p >> 1) & 1);
            asm volatile("" : F16(acc, 0), F4(acc, 16));
            BLOCK_FENCE
            wg_fence();
            bar_sync(NB_QK, 384);
#pragma unroll
            for (int i = 0; i < 32; i++) {
                const int k = i / GAP;
                if (i % GAP == GAP - 1 && k < NL) wgmma_ss40(acc, mkdesc(SB0 + 131072 + k * 2048, 8192, 1024, 1), HB(k), 1);
                else wgmma_rs40(acc, w[i - (k < NL ? k : NL)], HB(NL + i - (k < NL ? k : NL)), 1);
            }
            wg_commit();
            uint8_t* vo = arena + (u_xo + (G16() >> 1));
            pdst = arena + ((pso ^ (32768 + 2048)) + G16());
            fdst = arena + ((b ^ 1) * 32768 + u_to + g16);
            BLOCK_FENCE
            wg_wait<0>();
            PROF(9)
            stg_rlx2(vo, settag(pack2(acc[16], acc[17]), tag), pack2(acc[18], acc[19]));
            const uint32_t tv = clk32();
            if (TV_POS == 1) vf_fetch(s);
            tok_pack(2, acc, ftag, ptag);
            stg_b128_if(XP & 8 ? s == 99 : p <= NSEG, fdst, v.x, v.y, v.z, v.w);
            stg_b128_if(XP & 8 ? s == 99 : p < NSEG, pdst, u.x, u.y, u.z, u.w);
            PROF(10)
            const uint8_t* xp = arena + (xso + 32768 + (G16() >> 1));
            const uint32_t sxa = sb + SM_SX - wu * 2560 + G16() * 5;
            uint32_t xv[4], ov[4], gt = 0;
            auto pv = [&](uint32_t p0, uint32_t p1, uint32_t p2, uint32_t p3, uint32_t p4, auto getv) {
                float oc[2][4], lc[4] = {0.f, 0.f, 0.f, 0.f};
                mma16816(lc, ONES, ONES, ONES, ONES, p0, p1);
                mma16816z(oc[0], &vf[0][0].x, p0, p1);
                mma16816z(oc[1], &vf[1][0].x, p0, p1);
                mma16816(lc, ONES, ONES, ONES, ONES, p2, p3);
                mma16816(oc[0], vf[0][1].x, vf[0][1].y, vf[0][1].z, vf[0][1].w, p2, p3);
                mma16816(oc[1], vf[1][1].x, vf[1][1].y, vf[1][1].z, vf[1][1].w, p2, p3);
                mma1688(lc, ONES, ONES, p4);
                getv();
                mma1688(oc[0], xv[0], xv[1], p4);
                mma1688(oc[1], xv[2], xv[3], p4);
                const float r0 = rcp_fast(lc[0]), r1 = rcp_fast(lc[1]);
                ov[0] = pack2(oc[0][0] * r0, oc[0][1] * r1); ov[1] = pack2(oc[0][2] * r0, oc[0][3] * r1);
                ov[2] = pack2(oc[1][0] * r0, oc[1][1] * r1); ov[3] = pack2(oc[1][2] * r0, oc[1][3] * r1);
            };
            bool bad;
            it = 0;
#pragma unroll 1
            do {
                U2 xr[4];
                auto load_v = [&]() {
                    spin_until(tv, dly.v);
#pragma unroll
                    for (int i = 0; i < 4; i++) xr[i] = ldg_u2(xp + i * 1024);
                };
                if (TV_POS == 1 && it) {
                    const uint8_t* tz = arena + (tso + tbw + (g16 | (it & zero)));
#pragma unroll
                    for (int a = 0; a < 4; a++) ldg_b128_into(vf[a >> 1][a & 1], tz + (a >> 1) * 16384 + (a & 1) * 2048);
                }
                if (!V_POS) load_v();
                PROF(3)
                asm volatile("{.reg .pred p; setp.eq.s32 p, %0, 0; @p bar.sync %1, 384;}" ::"r"(it), "n"(NB_X1) : "memory");
                uint4 sx[5];
#pragma unroll
                for (int i = 0; i < 5; i++) sx[i] = lds4(sxa + i * 16);
                if (it == 0) { gt = gtime(); tw = clk32(); }
                if (V_POS == 2) load_v();
                uint32_t h[5];
#pragma unroll
                for (int n = 0; n < 4; n++) h[n] = add_h2(add_h2((&sx[0].x)[n], (&sx[1].x)[n]), add_h2((&sx[2].x)[n], (&sx[3].x)[n]));
                h[4] = add_h2(add_h2(sx[4].x, sx[4].y), add_h2(sx[4].z, sx[4].w));
                uint32_t hm = max_h2(max_h2(max_h2(h[0], h[1]), h[2]), max_h2(h[3], h[4]));
                hm = max_h2(hm, __byte_perm(hm, hm, 0x1032));
                const uint32_t m1 = __shfl_xor_sync(~0u, hm, 1), m2 = __shfl_xor_sync(~0u, hm, 2), m3 = __shfl_xor_sync(~0u, hm, 3);
                float2 a[5];
#pragma unroll
                for (int n = 0; n < 5; n++) a[n] = unpack_h2(h[n]);
                if (V_POS == 1) load_v(); else SCHED_FENCE(0)
                const float mb = -64.0f * unpack_h2(max_h2(max_h2(hm, m1), max_h2(m2, m3))).x;
                uint32_t pm[5];
#pragma unroll
                for (int n = 0; n < 5; n++) pm[n] = pack2(ex2(fmaf(a[n].x, 64.0f, mb)), ex2(fmaf(a[n].y, 64.0f, mb)));
                pv(pm[0], pm[1], pm[2], pm[3], pm[4], [&]() {
                    xv[0] = hadd2(xr[0].x, xr[1].x); xv[1] = hadd2(xr[0].y, xr[1].y);
                    xv[2] = hadd2(xr[2].x, xr[3].x); xv[3] = hadd2(xr[2].y, xr[3].y);
                });
                bad = any_bit0((TV_POS == 1 && !(XP & 8) ? VFBAD : 0) | (xr[0].x ^ tag) | (xr[1].x ^ tag) | (xr[2].x ^ tag) | (xr[3].x ^ tag)) & (++it < POLL_LIMIT);
                stsm4(sb + SM_OX + g16, ov[0], ov[1], ov[2], ov[3]);
            } while (bad);
            PROFV(14, it - 1) MISS(2, it - 1)
            PROF(5)
            bar_sync(NB_X2, 384);
            U2 tv2 = {0, 0};
            const uint8_t* tp = arena + (blk(LB_TIME, mypar) + (((g16 | (tw & zero)) << 6) & 0xc00));
            {
                const uint4 pp = lds4(l16 + SM_PX + 1024);
                const uint32_t p4 = lds1(sb + SM_PX + 512 + 1024 - wu * 128 + (G16() >> 2));
                if (E_MUL) tv2 = ldg_u2(tp);
                if (H_POS == 0 && !(XP & 1) && warp0 && s + 3 <= NSEG) h_load(sb, hsrc, s + 3, j, head);
                pv(pp.x, pp.y, pp.z, pp.w, p4, []() {});
            }
            dst0 = TAB(6); dx0 = TAB(7);
            const uint32_t zo = TAB(8);
            PROF(6) HT(7)
            bar_arrive(NB_WIN + ((ov[0] | ov[3] | fz[0]) & zero), 384);
            BLOCK_FENCE
            if (H_POS == 1 && !(XP & 1) && warp0 && s + 3 <= NSEG) h_load(sb, hsrc, s + 3, j, head);
            asm volatile("" : "+r"(tv2.y));
            it = 0;
#pragma unroll 1
            while (E_MUL && __any_sync(~0u, tv2.y < 32 * (s + 1)) & (++it < 16)) tv2 = ldg_u2(tp);
            const uint32_t e = __reduce_max_sync(~0u, tv2.x) - gt;
            MISS(3, it - 1) MISS(4, gt)
            if (PA_POS) tok_fetch(s + 1);
            uint8_t* od = (uint8_t*)g_O + (uint32_t)(s * (32 * NH * DH * 2) + u_o + (G16() >> 2));
#pragma unroll
            for (int a = 0; a < 4; a++) stg_rlx1(od + a * 128, ov[a]);
            stg4_if(g16 < 160, arena + (zo + mem_slot(s + 3)), 0);
            dl = (kh == mypar ? dly.near : dly.far) + (e > 4096 ? 0 : e * E_MUL >> 4);
        }
        TL(8)
    }
    PROF_OUT
    MISS_OUT
}

struct RecMaps { CUtensorMap wq, wk, wv, wo, wmod, w3, w1; };
struct RecPtrs { const bf16 *x, *mem0, *c, *wmod, *w1, *w3; uint8_t* arena; uint32_t zero; const bf16 *w2, *w4, *wo; Delays dly; };

__device__ __forceinline__ float silu_bf(const bf16* c, int i) {
    const float v = __bfloat162float(c[i]);
    return bfround(__fdividef(v, 1.0f + __expf(-v)));
}
#define W_LATE 1000
#define W_OPEN 1400
__device__ __forceinline__ void side_window(const uint8_t* arena, uint32_t& n) {
    U2 v;
    int it = 0;
#pragma unroll 1
    while (v = ldg_u2(arena + (LB_TIME << 13)), ((v.y >> 5) == n || gtime() - v.x > W_OPEN + W_LATE) && v.y < 32 * NSEG && ++it < 64) __nanosleep(100);
    n = v.y >> 5;
    it = 0;
#pragma unroll 1
    while ((int)(gtime() - v.x - W_OPEN) < 0 && ++it < 256) {}
}
__device__ __noinline__ void rec_ln(float* coef, const RecPtrs& p, int id, int r0) {
    int r1 = 32;
    const int tid = threadIdx.x;
    const int lane = tid & 31, wid = tid >> 5;
    const uint32_t ring = smem_u32(coef) - SM_PRE + wid * 8192 + lane * 16;
    auto rowof = [&](int j) { return (j >> 1) * 64 + (id * 8 + wid) * 2 + (j & 1); };
    auto fetch = [&](int j) {
        if (j < 2 * r1) {
#pragma unroll
            for (int i = 0; i < 4; i++)
                asm volatile("cp.async.cg.shared.global [%0], [%1], 16;" ::"r"(ring + (j & 3) * 2048 + i * 512), "l"(p.x + (size_t)rowof(j) * DM + i * 256 + lane * 8) : "memory");
        }
        asm volatile("cp.async.commit_group;" ::: "memory");
    };
#pragma unroll 1
    for (int j = 2 * r0; j < 2 * r0 + 4; j++) fetch(j);
#pragma unroll 1
    for (int i = tid; i < 2 * DM / 4; i += 256) {
        uint4 v[8];
        int it = 0;
        uint32_t ok;
        do {
            ok = 1;
#pragma unroll
            for (int k = 0; k < 8; k++) v[k] = ldg_rlx4(g_modp + k * 2 * DM + i * 4);
#pragma unroll
            for (int k = 0; k < 8; k++) ok &= v[k].x & v[k].y & v[k].z & v[k].w;
            spin_guard(++it);
        } while (!ok);
        float t[4] = {0, 0, 0, 0};
#pragma unroll
        for (int k = 0; k < 8; k++) { t[0] += __uint_as_float(v[k].x); t[1] += __uint_as_float(v[k].y); t[2] += __uint_as_float(v[k].z); t[3] += __uint_as_float(v[k].w); }
#pragma unroll
        for (int j = 0; j < 4; j++) coef[i * 4 + j] = bfround(t[j]) + (i >= DM / 4 ? 1.0f : 0.0f);
    }
    bar_sync(NB_FIN0, 256);
    if (r0 == 0) {
        int v, it = 0;
#pragma unroll 1
        do { v = *(volatile int*)((uint8_t*)coef - SM_PRE + SM_BAR + 192); spin_guard(++it); } while (v == INT_MIN);
        if (v >= 0) r1 = 2;
    }
    if (tid == 0 && r0 == 0) TL(2)
#pragma unroll 1
    for (int j = 2 * r0; j < 2 * r1; j++) {
        float x[32];
        asm volatile("cp.async.wait_group 3;" ::: "memory");
#pragma unroll
        for (int i = 0; i < 4; i++) {
            const uint4 v = lds4(ring + (j & 3) * 2048 + i * 512);
            float* d = x + i * 8;
            d[0] = bflo(v.x); d[1] = bfhi(v.x); d[2] = bflo(v.y); d[3] = bfhi(v.y); d[4] = bflo(v.z); d[5] = bfhi(v.z); d[6] = bflo(v.w); d[7] = bfhi(v.w);
        }
        const int row = rowof(j), rr = row & 15;
        ln_row(x);
        fetch(j + 4);
#pragma unroll
        for (int i = 0; i < 4; i++) {
            float y[8];
            const float4* cf = (const float4*)(coef + i * 256 + lane * 8);
            const float4 s0 = cf[0], s1 = cf[1], c0 = cf[256], c1 = cf[257];
            const float sh[8] = {s0.x, s0.y, s0.z, s0.w, s1.x, s1.y, s1.z, s1.w}, sc[8] = {c0.x, c0.y, c0.z, c0.w, c1.x, c1.y, c1.z, c1.w};
#pragma unroll
            for (int e = 0; e < 8; e++) y[e] = fmaf(x[i * 8 + e], sc[e], sh[e]);
            const int own = ((row >> 4) & 1) == (i >> 1), c16 = i * 32 + lane;
            const uint32_t off = ((row >> 5) + own) * 65536 + (c16 >> 3) * 4096 + (rr + (own ? 0 : 16)) * 128 + (((c16 & 7) ^ (rr & 7)) << 4);
            *(uint4*)((uint8_t*)g_himg + off) = pack8(y);
        }
        if ((j & 3) != 3) continue;
        bar_sync(j == 3 ? NB_C : NB_FIN0, j == 3 ? 320 : 256);
        if (wid == 0) {
            if (j == 3) bar_arrive(NB_B, 64);
            if (lane == 0) { if (j == 7) wait_count1(&g_tick[32 + id * 8], 1); signal_count(&g_tick[32 + id * 8]); if (j < 8) TL(13) }
            __syncwarp();
        }
    }
}
#define SIDE_T 300
template <int NQ>
__device__ __forceinline__ void side_gemv(const CUtensorMap* tm, int c0, int k0, int k1, uint32_t cs, uint32_t sb, const uint8_t* arena, uint32_t& n, uint32_t& ph, float (*acc)[8], const uint8_t* xr = nullptr) {
    const uint32_t w = __reduce_max_sync(~0u, threadIdx.x >> 5 & 3), ring = sb + 65536 + w * 24576, bars = sb + SM_BAR + 8 * B_W + w * 24;
#pragma unroll
    for (int q = 0; q < NQ; q++)
#pragma unroll
        for (int j = 0; j < 8; j++) acc[q][j] = 0.f;
#pragma unroll 1
    for (; k0 < k1; k0 += 48, ph ^= 1) {
        const int nr = min(48, k1 - k0);
        side_window(arena, n);
        const uint32_t t0 = clk32();
        if (xr && k0 < 9 * 48) {
#pragma unroll
            for (int i = 0; i < 6; i++) asm volatile("prefetch.global.L2 [%0];" ::"l"(xr + (5 + k0 / 16 + (i >> 1)) * 131072 + (i & 1) * 16384));
        }
#pragma unroll 1
        for (int g = 0; g < 3; g++) {
            spin_until(t0, (g * 4 + w) * (SIDE_T / 4));
            e_expect(bars + 8 * g, g * 16 < nr ? 8192 : 0);
            if (g * 16 < nr) e_tma2d(ring + g * 8192, tm, c0, k0 + g * 16, bars + 8 * g);
        }
#pragma unroll 1
        for (int r = 0; r < nr; r += 16) {
            mbar_wait_w(bars + (r >> 1), ph);
            uint4 v[16];
#pragma unroll
            for (int h = 0; h < 16; h++) v[h] = lds4(ring + (r + h) * 512 + (threadIdx.x & 31) * 16);
            float4 cf[NQ][4];
#pragma unroll
            for (int q = 0; q < NQ * 4; q++) cf[q >> 2][q & 3] = lds4f(cs + ((q >> 2) * DM + k0 + r + (q & 3) * 4) * 4);
#pragma unroll
            for (int h = 0; h < 16; h++) {
                const float f[8] = {bflo(v[h].x), bfhi(v[h].x), bflo(v[h].y), bfhi(v[h].y), bflo(v[h].z), bfhi(v[h].z), bflo(v[h].w), bfhi(v[h].w)};
#pragma unroll
                for (int q = 0; q < NQ; q++)
#pragma unroll
                    for (int j = 0; j < 8; j++) acc[q][j] = fmaf((&cf[q][h >> 2].x)[h & 3], f[j], acc[q][j]);
            }
        }
        fence_async_smem();
        __syncwarp();
    }
}
__device__ __noinline__ void rec_side(float* sm, const RecMaps& mp, const RecPtrs& p, int id) {
    const int tid = threadIdx.x;
    if (tid < 256) {
        if (blockIdx.x < 128) rec_ln(sm + SM_PRE / 4, p, id, 2);
        if (tid == 0) TL(14)
        for (int i = tid; i < 2 * S_; i += 256) g_st[id * 2 * S_ + i] = 0.f;
        if (id == 0 && tid < 64) g_pcnt[tid * 8] = 0;
        if (id == 1) for (int i = tid; i < 5 * 256; i += 256) g_pflag[i] = 0;
        uint32_t n = 0;
        int it = 0;
#pragma unroll 1
        while (n < SPF_AT && ++it < 256) side_window(p.arena, n);
#pragma unroll 1
        for (int i = 0; i < 96 && SPF; i++) {
            const uint8_t* w = i < 64 ? (const uint8_t*)p.wo + (id * 64 + i) * 32768 : (const uint8_t*)p.x + (id * 32 + i - 64) * 32768;
            asm volatile("prefetch.global.L2 [%0];" ::"l"(w + tid * 128));
            if (i % SPF_R == SPF_R - 1 && i < 95) side_window(p.arena, n); else __nanosleep(SPF_NS);
        }
        return;
    }
    const int t = tid - 256;
    float *coef = sm + 40960, *red = coef + 3 * DM;
    const uint32_t sb = smem_u32(sm), cs = smem_u32(coef);
    uint32_t n = 0, ph = 0;
    for (int i = t; i < DM; i += 128) { coef[i] = silu_bf(p.c, i); coef[2 * DM + i] = 1.0f; }
    if (t == 0) wait_count1(&g_tick[32 + id * 8], 2);
    bar_sync(NB_G, 128);
    const int w = __reduce_max_sync(~0u, t >> 5);
    float acc[3][8];
    side_gemv<1>(&mp.wmod, (2 + id) * DM + w * 256, 0, DM, cs, sb, p.arena, n, ph, acc, (const uint8_t*)p.x + id * 32768 + t * 128);
#pragma unroll
    for (int j = 0; j < 8; j++) g_mod[(2 + id) * DM + t * 8 + j] = bfround(acc[0][j]);
    bar_sync(NB_G, 128);
    if (t == 0) signal_count(&g_tick[8]);
    side_gemv<1>(&mp.w3, id * (FF / 4) + w * 256, 0, DM, cs + 8 * DM, sb, p.arena, n, ph, acc);
    if (t < FF / 32) {
#pragma unroll
        for (int j = 0; j < 8; j++) g_vec[3 * DM + id * (FF / 4) + t * 8 + j] = acc[0][j];
    }
    if (t == 0) wait_count1(&g_tick[8], 4);
    bar_sync(NB_G, 128);
    for (int i = t; i < DM; i += 128) { coef[i] = 1.0f + __ldcg(g_mod + 4 * DM + i); coef[DM + i] = __ldcg(g_mod + 3 * DM + i); }
    bar_sync(NB_G, 128);
    if (id == 1 && t < 32) {
        float u[5] = {0, 0, 0, 0, 0};
        for (int i = t; i < DM; i += 32) {
            const float a = coef[i], b = coef[DM + i];
            u[0] += a; u[1] += a * a; u[2] += a * b; u[3] += b; u[4] += b * b;
        }
#pragma unroll
        for (int q = 0; q < 5; q++) { const float r = warp_sum(u[q]); if (t == 0) g_cst[q] = r * (1.0f / DM); }
    }
    side_gemv<3>(&mp.w1, id * 256, w * 256, w * 256 + 256, cs, sb, p.arena, n, ph, acc);
#pragma unroll
    for (int q = 0; q < 3; q++)
#pragma unroll
        for (int j = 0; j < 8; j++) red[((t >> 5) * 3 + q) * 256 + (t & 31) * 8 + j] = acc[q][j];
    bar_sync(NB_G, 128);
    for (int i = t; i < 768; i += 128) g_vec[(i >> 8) * DM + id * 256 + (i & 255)] = (red[i] + red[768 + i]) + (red[1536 + i] + red[2304 + i]);
    if (t == 0) TL(9)
}

__global__ void __cluster_dims__(2, 1, 1) __launch_bounds__(384, 1)
k_rec(const __grid_constant__ RecMaps mp, const __grid_constant__ RecPtrs p) {
    extern __shared__ uint8_t smraw[];
    const uint32_t sb = smem_u32(smraw);
    if ((sb & 0x3FFFF) != SB0) __trap();
    const uint32_t bars = sb + SM_BAR;
    const int tid = threadIdx.x, lane = tid & 31, b = blockIdx.x;
    const int wid = __reduce_max_sync(~0u, tid >> 5);
    const uint32_t rank = b & 1;
    uint8_t* arena = p.arena;
    volatile int* sinfo = (volatile int*)(smraw + SM_BAR + 192);
    if (tid == 0) TL(0)
    if (tid == 0) sinfo[0] = INT_MIN;
    if (tid == 352) {
        for (int i = 0; i < 17; i++) mbar_init(bars + 8 * i, i == B_WO ? 4 : 1);
        asm volatile("fence.mbarrier_init.release.cluster;" ::: "memory");
        mbar_expect(bars + 8 * B_ROLE, 8);

    }
    __syncwarp();
    asm volatile("barrier.cluster.arrive.relaxed.aligned;" ::: "memory");
    int pr = 0, hA = 0;
    if (wid < 8) {
        if (b < 128) {
            const int cb = (b & 15) * 128, k0 = (b >> 4) * 128 + (tid >> 4);
            uint4 v[8];
#pragma unroll
            for (int i = 0; i < 8; i++) v[i] = __ldg((const uint4*)(p.wmod + (size_t)(k0 + 16 * i) * (6 * DM) + cb + (tid & 15) * 8));
            float acc[8] = {0, 0, 0, 0, 0, 0, 0, 0};
#pragma unroll
            for (int i = 0; i < 8; i++) {
                const float sv = silu_bf(p.c, k0 + 16 * i);
                acc[0] += sv * bflo(v[i].x); acc[1] += sv * bfhi(v[i].x); acc[2] += sv * bflo(v[i].y); acc[3] += sv * bfhi(v[i].y);
                acc[4] += sv * bflo(v[i].z); acc[5] += sv * bfhi(v[i].z); acc[6] += sv * bflo(v[i].w); acc[7] += sv * bfhi(v[i].w);
            }
            float* red = (float*)(smraw + SM_PRE);
            *(float4*)(red + (tid >> 4) * 128 + (tid & 15) * 8) = make_float4(acc[0], acc[1], acc[2], acc[3]);
            *(float4*)(red + (tid >> 4) * 128 + (tid & 15) * 8 + 4) = make_float4(acc[4], acc[5], acc[6], acc[7]);
            bar_sync(NB_FIN0, 256);
            if (wid < 4) {
                float t = 0;
#pragma unroll
                for (int i = 0; i < 16; i++) t += red[i * 128 + tid];
                stg_rlx1(&g_modp[(b >> 4) * 2 * DM + cb + tid], __float_as_uint(t) | 1u);
            }
        } else {
            rec_ln((float*)(smraw + SM_PRE), p, b - 128, 0);
        }
    } else if (wid >= 10 && b >= 128) {
        {
            const int w = (b - 128) * 2 + wid - 10;
            const uint16_t* src = (const uint16_t*)p.mem0 + (lane & 3) * 2 * DM + (w >> 2) * 512 + (w & 1) * 64 + (w & 2) * 8 + (lane >> 2);
            uint32_t v[4][4];
#pragma unroll
            for (int i = 0; i < 16; i++) v[i >> 2][i & 3] = src[(i >> 2) * 128 + (i & 2) * 16 + (i & 1) * 8] | ((uint32_t)src[DM + (i >> 2) * 128 + (i & 2) * 16 + (i & 1) * 8] << 16);
            uint8_t* d = arena + mem_row(w >> 2, w & 3, 0);
            uint8_t* e = d + 512 + lane * 4;
            d += lane * 16;
#pragma unroll
            for (int i = 0; i < 4; i++, d += 1024, e += 1024) {
                stg_rlx4(d, v[i][0], v[i][1], v[i][2], (v[i][3] & 0xffff) | CNT_ALL << 16);
                stg_rlx4(d + mem_slot(1), 0, 0, 0, 0);
                stg_rlx4(d + mem_slot(2), 0, 0, 0, 0);
                stg_rlx1(e, (v[i][3] & 0xffff0000u) | CNT_ALL); stg_rlx1(e + mem_slot(1), 0); stg_rlx1(e + mem_slot(2), 0);
            }
            if (w == 0 && lane < 8) stg_rlx2(arena + (LB_TIME << 13) + lane * 1024, 0, 0);
            bar_arrive(NB_C, 320);
        }
    } else if (rank == 0) {
        uint32_t best = ~0u;
        const int pg = wid < 10 ? 0 : 1 + (b >> 1) % 3;
        uint32_t* q = (uint32_t*)(arena + (pg << 21) + (pg ? blk(b >> 1, wid & 1) : blk(LB_PROBE, wid & 1) + b * 16));
        if (lane < 8) stg_rlx1(q + lane, 0);
        uint2 tk2 = ldg_rlx2(&g_tick[0]);
        __syncwarp();
        if (lane == 0) {
            q += 3;
            uint32_t v = atomicAdd(q, 1u);
#pragma unroll 1
            for (int r = 0; r < NPROBE; r++) {
                const uint32_t t0 = clk32() + (v >> 8);
                v = atomicAdd(q + (v >> 8), 1u);
                uint32_t t1;
                asm volatile("{.reg .pred p; setp.eq.u32 p, %1, 0xffffffff; @p exit; mov.u32 %0, %%clock;}" : "=r"(t1) : "r"(v) : "memory");
                best = min(best, t1 - t0);
            }
            sinfo[wid - 6] = best;
        }
        bar_sync(NB_KDONE, b < 128 ? 128 : 64);
        if (wid == 8) {
            const int par = sinfo[2] <= sinfo[3] ? 0 : 1, ncl = gridDim.x >> 1;
            int tk = 0, it = 0;
            const uint32_t vote = b < 128 && (sinfo[4] <= sinfo[5] ? 0 : 1) != par ? 256u << (8 * ((b >> 1) % 3)) : 0u;
            if (b >= 128) {
#pragma unroll 1
                while (!__all_sync(~0u, (int)((tk2.x + tk2.y) & 255) >= ncl - 2)) { tk2 = ldg_rlx2(&g_tick[0]); spin_guard(++it); }
            }
            if (lane == 0) tk = atomicAdd(&g_tick[par], 1u + vote) & 255;
#pragma unroll 1
            while (!__all_sync(~0u, (int)((tk2.x + tk2.y) & 255) >= ncl)) { tk2 = ldg_rlx2(&g_tick[0]); spin_guard(++it); }
            tk = __shfl_sync(~0u, tk, 0);
            const int n0 = tk2.x & 255, n1 = tk2.y & 255;
            hA = min(n0 >> 1, NH);
            const int q0 = 2 * hA, q1 = 2 * NH - q0;
            const int over = tk - (par ? q1 : q0), lack = max(par ? q0 - n0 : q1 - n1, 0);
            if (over < 0) pr = par ? q0 + tk : tk;
            else if (over < lack) pr = (par ? n0 : q0 + n1) + over;
            else pr = -1 - (over - lack + (par ? max(n0 - q0, 0) : 0));
#pragma unroll
            for (int i = 0; i < 3; i++) hA |= (((tk2.x + tk2.y) >> (8 + 8 * i)) & 255) > 10 ? 256 << i : 0;
        }
    }
    asm volatile("barrier.cluster.wait.aligned;" ::: "memory");
    if (wid == 8) {
        if (rank == 0) {
            if (lane == 0) {
                uint32_t rsb;
                asm("mapa.shared::cluster.u32 %0, %1, 1;" : "=r"(rsb) : "r"(sb));
                asm volatile("st.async.shared::cluster.mbarrier::complete_tx::bytes.v2.u32 [%0], {%1, %2}, [%3];"
                             ::"r"(rsb + SM_BAR + 192), "r"(pr), "r"(hA), "r"(rsb + SM_BAR + 8 * B_ROLE) : "memory");
                sinfo[0] = pr; sinfo[1] = hA;
                if (b >= 128) atomicOr(&g_tick[4], (pr < 0 ? 4u : 1u) << ((b - 128) >> 1));
            }
        } else {
            mbar_wait_w(bars + 8 * B_ROLE, 0);
            pr = sinfo[0];
        }
        TL(1)
        __syncwarp();
        bar_arrive(NB_A, 288);
        bar_arrive(NB_S, 128);
        if (b >= 128 && pr < 0) bar_sync(NB_B, 64);
        if (pr >= 0) {
            const int pu = __reduce_max_sync(~0u, pr), c0 = (pu >> 1) * 128 + rank * 64, r0 = (pu & 1) * 512;
            bool fast = false;
#pragma unroll 1
            for (int n = 0; n < 12; n++) {
                const int rot = b >= 128 ? 8 : 0, i = (n + rot) % 12;
                if (rot && n == 4) bar_sync(NB_B, 64);
                if (n >= W_INFL && !fast) {
                    const uint32_t v = ldg_rlx1(&g_tick[32 + (lane & 3) * 8]);
                    mbar_wait_w(bars + 8 * (B_W + (n - W_INFL + rot) % 12), 0);
                    fast = __all_sync(~0u, v != 0);
                }
                const int m = i < 8 ? i & 1 : 2, k = i < 8 ? i >> 1 : i - 8;
                const uint32_t dst = sb + m * 65536 + k * 16384, br = bars + 8 * (B_W + i);
                if (lane == 0) {
                    mbar_expect(br, 16384);
                    tma2d(dst, &mp.wq + m, c0, r0 + k * 128, br);
                    tma2d(dst + 8192, &mp.wq + m, c0, r0 + k * 128 + 64, br);
                }
                __syncwarp();
            }
        }
    } else {
        bar_sync(wid < 8 ? NB_A : NB_S, wid < 8 ? 288 : 128);
    }
    const int prr = __reduce_max_sync(~0u, sinfo[0]);
    hA = __reduce_max_sync(~0u, sinfo[1]);
    if (prr < 0) {
        int j = (b - 128) >> 1;
        if (b < 128) {
            uint32_t v;
            int it = 0;
#pragma unroll 1
            do { v = __reduce_max_sync(~0u, ldg_rlx1(&g_tick[4])); spin_guard(++it); } while (__popc(v) < 2);
            j = v == 3 ? -1 - prr : (v & 1) ^ 1;
        }
        rec_side((float*)smraw, mp, p, j * 2 + rank);
        return;
    }
    const int role = (prr >> 1) * 4 + rank * 2 + (prr & 1);
    rec_main(sb, &mp.wo, arena, role, hA, wid >> 2, p.zero, p.dly);
}

__device__ __forceinline__ void wgmma_ss192(float* d, uint64_t a, uint64_t b, int sc) {
    asm volatile("{.reg .pred p; setp.ne.b32 p, %98, 0;\n wgmma.mma_async.sync.aligned.m64n192k16.f32.bf16.bf16 "
                 "{%0,%1,%2,%3,%4,%5,%6,%7,%8,%9,%10,%11,%12,%13,%14,%15,%16,%17,%18,%19,%20,%21,%22,%23,%24,%25,%26,%27,%28,%29,%30,%31,%32,%33,%34,%35,%36,%37,%38,%39,%40,%41,%42,%43,%44,%45,%46,%47,%48,%49,%50,%51,%52,%53,%54,%55,%56,%57,%58,%59,%60,%61,%62,%63,%64,%65,%66,%67,%68,%69,%70,%71,%72,%73,%74,%75,%76,%77,%78,%79,%80,%81,%82,%83,%84,%85,%86,%87,%88,%89,%90,%91,%92,%93,%94,%95}, %96, %97, p, 1, 1, 0, 1;}"
                 : F16(d, 0), F16(d, 16), F16(d, 32), F16(d, 48), F16(d, 64), F16(d, 80) : "l"(a), "l"(b), "r"(sc));
}
__device__ __forceinline__ void wgmma_ss256(float* d, uint64_t a, uint64_t b, int sc) {
    asm volatile("{.reg .pred p; setp.ne.b32 p, %130, 0;\n wgmma.mma_async.sync.aligned.m64n256k16.f32.bf16.bf16 "
                 "{%0,%1,%2,%3,%4,%5,%6,%7,%8,%9,%10,%11,%12,%13,%14,%15,%16,%17,%18,%19,%20,%21,%22,%23,%24,%25,%26,%27,%28,%29,%30,%31,%32,%33,%34,%35,%36,%37,%38,%39,%40,%41,%42,%43,%44,%45,%46,%47,%48,%49,%50,%51,%52,%53,%54,%55,%56,%57,%58,%59,%60,%61,%62,%63,%64,%65,%66,%67,%68,%69,%70,%71,%72,%73,%74,%75,%76,%77,%78,%79,%80,%81,%82,%83,%84,%85,%86,%87,%88,%89,%90,%91,%92,%93,%94,%95,%96,%97,%98,%99,%100,%101,%102,%103,%104,%105,%106,%107,%108,%109,%110,%111,%112,%113,%114,%115,%116,%117,%118,%119,%120,%121,%122,%123,%124,%125,%126,%127}, %128, %129, p, 1, 1, 0, 1;}"
                 : F16(d, 0), F16(d, 16), F16(d, 32), F16(d, 48), F16(d, 64), F16(d, 80), F16(d, 96), F16(d, 112) : "l"(a), "l"(b), "r"(sc));
}

constexpr uint32_t P_VEC = 212992, P_ROW = P_VEC + 6144, P_BAR = P_ROW + 4096, P_SMEM = P_BAR + 256;
constexpr uint32_t P_OUT = 180224, P_OUT3 = 147456, P_OUT4 = 163840;
#define PPH 1
#define FLAG_ST "st.release.gpu.global.u32"
#define FLAG_LD "ld.acquire.gpu.global.u32"
#define BA3 2
#define BA 5
#define BA0 1
constexpr int P_SA = 5, P_SB = 3;
constexpr int PB_FA = 0, PB_EA = 5, PB_FB = 10, PB_EB = 13, PB_OUT = 16;
enum { C_Y = 0, C_G = 1, C_X1 = 2, C_U = 3, C_S1 = 8, C_S3 = 9 };
enum { V_GA = 0, V_A = 1, V_B = 2, V_GB = 3, V_VA = 4, V_VB = 5, V_VC = 6, V_C3 = 7 };
struct PostMaps { CUtensorMap o, wo, y, w1, g, w2, x1, w3, u, w4, out; };
struct PostPtrs { const bf16* x; };

struct GeluK { float k0, k1, kh; };
__device__ __forceinline__ GeluK gelu_k(float c) { return {0.7978845608028654f * c, 0.7978845608028654f * 0.044715f * c * c * c, 0.5f * c}; }
__device__ __forceinline__ float gelu_s(float t, const GeluK& k) {
    const float u = t * fmaf(t * t, k.k1, k.k0);
    float th; asm("tanh.approx.f32 %0, %1;" : "=f"(th) : "f"(u));
    const float hx = k.kh * t;
    return fmaf(hx, th, hx);
}
__device__ __forceinline__ float2 ldsv(uint32_t a) {
    float2 v; asm("ld.shared.v2.f32 {%0,%1}, [%2];" : "=f"(v.x), "=f"(v.y) : "r"(a)); return v;
}
__device__ __forceinline__ void wait_smem(uint32_t a, int target) {
    int it = 0;
#pragma unroll 1
    while (true) {
        int v;
        asm volatile("ld.acquire.cta.shared.u32 %0, [%1];" : "=r"(v) : "r"(a) : "memory");
        if (__all_sync(~0u, v >= target)) break;
        spin_guard(++it);
    }
}

#define PP(i)
#define PH_(c, w, i)
struct Pipe { int st, ph; };
template <int ST> __device__ __forceinline__ void adv(Pipe& p) { if (++p.st == ST) { p.st = 0; p.ph ^= 1; } }

__device__ __forceinline__ void post_produce(uint32_t sb, const PostMaps& mp, int mb, int nb, int rank) {
    const int rh = 2 * mb + rank, lane = threadIdx.x & 31;
    int st = 0, pp = 0, st2 = 0, pp2 = 0;
#pragma unroll 1
    for (int ph = 0; ph < 7; ph++) {
        const bool W = ph == 3 || ph == 4;
        if (ph == 3 || ph >= 5) {
            const int n = ph == 5 ? P_SB : P_SA;
            const uint32_t e = sb + P_BAR + 8 * (ph == 5 ? PB_EB : PB_EA);
#pragma unroll 1
            for (int i = 0; i < n; i++) mbar_wait_w(e + 8 * i, pp ^ (i >= st));
            if (ph == 6) break;
            if (ph == 5) wait_smem(sb + P_BAR + 8 * (PB_OUT + (lane & 1)), 4);
            int t = st; st = st2; st2 = t; t = pp; pp = pp2; pp2 = t;
        }
        const int ST = W ? P_SB : P_SA, NK = ph == 0 ? 64 : ph == 5 ? 56 : 16, NB = ph == 3 ? 4 : ph == 4 ? 3 : 2;
        const uint32_t SBYTES = W ? 49152 : 32768;
        const uint32_t full = sb + P_BAR + 8 * (W ? PB_FB : PB_FA), empty = sb + P_BAR + 8 * (W ? PB_EB : PB_EA);
        const CUtensorMap* ta = &mp.o + 2 * (ph > 3 ? ph - 1 : ph);
        const CUtensorMap* tb = ta + 1;
        const int n0 = ph == 3 ? nb * 256 : ph == 4 ? 2048 + nb * 192 : nb * 128;
        const int amul = ph == 0 ? 256 : 64, arow = ph == 0 ? rh * 8 : rh * 64;
        const uint32_t shifts = ph == 2 ? 0x04000301u : 0x02020202u;
        const uint32_t* fl = &g_pflag[(ph == 5 ? C_U + ((lane >> 3) & 1) : ph - 1) * 256 + (ph == 2 ? min(max(rh + min(lane >> 3, 2) - 1, 0), 31) : rh) * 8 + (lane & 7)];
        uint32_t have = ph == 0 || ph == 4 ? 9 : 0;
        auto order = [&](int i, int& need, int& grp) {
            need = 0; grp = i & 1;
            if (ph == 5) {
                const int q = i < 32 ? i >> 2 : ((i - 32) * 43) >> 7, src = (q + (nb & 6)) & 7;
                need = (i < 32 ? 1 : 256) << src; grp = i < 32 ? i & 3 : i - 32 - 3 * q;
                return i + (src - q) * (i < 32 ? 4 : 3);
            }
            if (ph == 0) return i;
            const int kb = (i + 2 * (nb & 6)) & 15;
            need = (ph == 2 ? 0x10101 : 1) << (kb >> 1);
            return kb;
        };
        PH_(ph == PPH, 0, 26) PH_(ph == PPH, 1, 26)
        int ib = 0, sB = st, pB = pp;
#pragma unroll 1
        for (int i = 0; i < NK; i++) {
            int need, grp;
#pragma unroll 1
            for (const int lim = i || ph > 3 ? i + 1 : ph == 3 ? BA3 : ph ? BA : BA0; ib < lim; ib++) {
                const int kb = order(ib, need, grp);
                const uint32_t a = sb + sB * SBYTES, f = full + 8 * sB;
                mbar_wait_w(empty + 8 * sB, pB ^ 1);
                e_expect(f, 16384 + NB * 8192);
                e_tma2d(a + 16384, tb, n0, kb * 64, f);
                e_tma2d(a + 24576, tb, n0 + 64, kb * 64, f);
                if (W) { e_tma2d(a + 32768, tb, n0 + 128, kb * 64, f); if (ph == 3) e_tma2d(a + 40960, tb, n0 + 192, kb * 64, f); }
                if (++sB == ST) { sB = 0; pB ^= 1; }
            }
            const int kb = order(i, need, grp);
            PH_(ph == PPH && i == 0, 0, 27) PH_(ph == PPH && i == 0, 1, 27)
            if (ph == 0 && i == 0) {
                asm volatile("barrier.cluster.wait.aligned;" ::: "memory");
                PH_(PPH == 0, 0, 25) PH_(PPH == 0, 1, 25)
            }
            if ((__ballot_sync(~0u, have > grp) & need) != need) {
                int it = 0;
#pragma unroll 1
                do {
                    asm volatile(FLAG_LD " %0, [%1];" : "=r"(have) : "l"(fl) : "memory");
                    spin_guard(++it);
                } while ((__ballot_sync(~0u, have > grp) & need) != need);
                PH_(ph == PPH && i == 0, 0, 23) PH_(ph == PPH, 0, 24) PH_(ph == PPH && i == 0, 1, 23) PH_(ph == PPH, 1, 24)
                asm volatile("fence.proxy.async.global;" ::: "memory");
                PH_(ph == PPH && i == 0, 0, 25) PH_(ph == PPH && i == 0, 1, 25)
            }
            e_tma2d_mc(sb + st * SBYTES + rank * 8192, ta, kb * amul, arow + (int)((shifts >> ((kb & 12) * 2)) & 7) - 2, full + 8 * st);
            if (++st == ST) { st = 0; pp ^= 1; }
        }
    }
}

template <int PH>
__device__ __forceinline__ void post_mma(uint32_t sb, float* acc, Pipe& p, int wg, bool lead, int pi) {
    constexpr bool W = PH == 3 || PH == 4;
    constexpr int ST = W ? P_SB : P_SA, SBYTES = W ? 49152 : 32768, NK = PH == 0 ? 64 : PH == 5 ? 56 : 16;
    const uint32_t full = sb + P_BAR + 8 * (W ? PB_FB : PB_FA), empty = sb + P_BAR + 8 * (W ? PB_EB : PB_EA);
    constexpr uint64_t DA = PH == 0 ? mkdesc(SB0, 128, 1024, 0) : mkdesc(SB0, 16, 1024, 1);
    constexpr uint64_t DB = mkdesc(SB0 + 16384, 8192, 1024, 1);
    auto release = [&](int st) { if (lead) { mbar_arrive_cluster(empty + 8 * st, 0); mbar_arrive_cluster(empty + 8 * st, 1); } };
    int prev = 0;
#pragma unroll 1
    for (int kb = 0; kb < NK; kb++) {
        mbar_wait_w(full + 8 * p.st, p.ph);
        const uint32_t so = p.st * (SBYTES >> 4);
        const uint32_t a = (uint32_t)DA + so + wg * 512, b = (uint32_t)DB + so;
        wg_fence();
#pragma unroll
        for (int k = 0; k < 4; k++) {
            const uint64_t da = (DA & 0xffffffff00000000ull) | (a + k * (PH == 0 ? 16 : 2)), db = (DB & 0xffffffff00000000ull) | (b + k * 128);
            if (PH == 3) wgmma_ss256(acc, da, db, (kb | k) != 0);
            else if (PH == 4) wgmma_ss192(acc, da, db, (kb | k) != 0);
            else wgmma_ss128<PH == 0>(acc, da, db, (kb | k) != 0);
        }
        wg_commit();
        if (kb == 0) { PP(pi) if (PH == 0 && wg == 0) TL(11) }
        wg_wait<1>();
        if (kb > 0) release(prev);
        prev = p.st;
        adv<ST>(p);
    }
    wg_wait<0>();
    release(prev);
    PP(pi + 1)
}

__global__ void __cluster_dims__(2, 1, 1) __launch_bounds__(384, 1)
k_post(const __grid_constant__ PostMaps mp, const __grid_constant__ PostPtrs pp) {
    extern __shared__ uint8_t smraw[];
    const uint32_t sb = smem_u32(smraw);
    if ((sb & 0x3FFFF) != SB0) __trap();
    const int tid = threadIdx.x, lane = tid & 31;
    const int mb = blockIdx.x >> 3, nb = blockIdx.x & 7, rank = blockIdx.x & 1;
    const uint32_t bars = sb + P_BAR;
    if (tid < PB_OUT) {
        mbar_init(bars + 8 * tid, (tid >= PB_EA && tid < PB_FB) || tid >= PB_EB ? 4 : 1);
        asm volatile("fence.mbarrier_init.release.cluster;" ::: "memory");
    }
    if (tid == 32) sts4(bars + 8 * PB_OUT, 0, 0, 0, 0);
    if (tid >= 256 && tid < 267) asm volatile("prefetch.tensormap [%0];" ::"l"(&mp.o + (tid - 256)) : "memory");
    __syncthreads();
    asm volatile("barrier.cluster.arrive.aligned;" ::: "memory");
    if (tid < 256 || tid >= 288) asm volatile("barrier.cluster.wait.aligned;" ::: "memory");
    if (tid >= 256) {
        asm volatile("setmaxnreg.dec.sync.aligned.u32 40;");
        const int w = __reduce_max_sync(~0u, (tid >> 5) - 8);
        if (w == 0) {
            post_produce(sb, mp, mb, nb, rank);
        } else if (w < 3) {
            const int wg = w - 1, rh = 2 * mb + wg;
            float* rowc = (float*)(smraw + P_ROW) + (wg * 64 + lane * 2) * 8;
            int nout = 0, sig = 0;
#pragma unroll 1
            for (int i = 0; i < 8; i++) {
                const int cnt = (0x54392180u >> (4 * i)) & 15;
                if (cnt < C_S1) {
                    const int ng = cnt == 3 ? 4 : cnt == 4 ? 3 : 2, c0 = cnt == 3 ? nb * 256 : cnt == 4 ? 2048 + nb * 192 : nb * 128;
                    const uint32_t src = sb + (cnt == 3 ? P_OUT3 : cnt == 4 ? P_OUT4 : P_OUT) + wg * ng * 8192;
                    uint32_t* fl = &g_pflag[cnt * 256 + rh * 8 + nb];
#pragma unroll 1
                    for (int j = 0; j < ng; j++) {
                        bar_sync(4 + 4 * wg + (sig++ & 3), 160);
                        if (lane == 0) {
                            PH_(cnt == PPH - 1, wg, 20)
                            asm volatile("cp.async.bulk.tensor.2d.global.shared::cta.bulk_group [%0, {%2, %3}], [%1]; cp.async.bulk.commit_group;"
                                         ::"l"(&mp.y + 2 * (cnt > 3 ? cnt - 1 : cnt)), "r"(src + j * 8192), "r"(c0 + j * 64), "r"(rh * 64) : "memory");
                        }
                        __syncwarp();
                    }
                    if (lane == 0) {
                        asm volatile("cp.async.bulk.wait_group 0; fence.proxy.async.global;" ::: "memory");
                        PH_(cnt == PPH - 1, wg, 21)
                        asm volatile(FLAG_ST " [%0], %1;" ::"l"(fl), "r"(ng) : "memory");
                        PH_(cnt == PPH - 1, wg, 22)
                        asm volatile("st.release.cta.shared.u32 [%0], %1;" ::"r"(bars + 8 * (PB_OUT + wg)), "r"(nout + 1) : "memory");
                    }
                    nout++;
                    __syncwarp();
                    continue;
                }
                bar_sync(4 + 4 * wg + (sig++ & 3), 160);
                uint32_t* c = &g_pcnt[(cnt - C_S1) * 256 + rh * 8];
                if (lane == 0) { signal_count(c); wait_count1(c, 8); }
                __syncwarp();
                const float4* sp = (const float4*)g_st + rh * 32 + lane;
                float4 u[3] = {__ldcg(sp + (cnt == C_S1 ? 0 : 3) * (S_ / 2)), __ldcg(sp + S_ / 2), __ldcg(sp + S_)};
#pragma unroll 1
                for (int h = 0; h < 2; h++) {
                    const float id = 1.0f / DM;
                    const float m = u[0].x * id, var = fmaxf(u[0].y * id - m * m, 0.f) + 1e-5f, r = rsqrtf(var);
                    float sc = r, m2 = 0.f;
                    if (cnt == C_S1) {
                        m2 = r * (u[1].x * id - m * g_cst[0]) + g_cst[3];
                        const float e2 = r * r * (u[2].x * id - 2.0f * m * u[1].y * id + m * m * g_cst[1]) + 2.0f * r * (u[2].y * id - m * g_cst[2]) + g_cst[4];
                        sc = r * rsqrtf(fmaxf(e2 - m2 * m2, 0.f) + 1e-5f);
                    }
                    const GeluK k = gelu_k(sc);
                    *(float4*)(rowc + h * 8) = make_float4(k.k0, k.k1, k.kh, -m);
                    *(float4*)(rowc + h * 8 + 4) = make_float4(var * r, -m2 * var * r, r, -m * r);
#pragma unroll
                    for (int q = 0; q < 3; q++) { u[q].x = u[q].z; u[q].y = u[q].w; }
                }
                bar_arrive(1 + wg, 160);
            }
        }
    } else {
        asm volatile("setmaxnreg.inc.sync.aligned.u32 232;");
        const bf16* xin = pp.x;
        const int wg = __reduce_max_sync(~0u, tid >> 7), wi = (tid >> 5) & 3, g = lane >> 2, tq = lane & 3;
        const int rh = 2 * mb + wg, row = rh * 64 + wi * 16 + g;
        const bool lead = (tid & 127) == 0;
        PP(0)
        if (tid == 0) TL(10)
        uint4 xg[8];
#pragma unroll
        for (int i = 0; i < 8; i++)
            xg[i] = __ldg((const uint4*)(xin + (size_t)(rh * 64 + wi * 16 + (i & 3) * 4 + (lane >> 3)) * DM + nb * 128 + (i >> 2) * 64 + (lane & 7) * 8));
        if (blockIdx.x < 64) g_modp[blockIdx.x * 256 + tid] = 0;
        if (blockIdx.x == 64 && tid < 64) g_tick[tid] = 0;
        {
            float* sv = (float*)(smraw + P_VEC);
            if (tid < 128) {
                const int c = nb * 128 + tid;
                sv[V_GA * 128 + tid] = __ldcg(&g_mod[2 * DM + c]); sv[V_A * 128 + tid] = 1.0f + __ldcg(&g_mod[4 * DM + c]);
                sv[V_B * 128 + tid] = __ldcg(&g_mod[3 * DM + c]); sv[V_GB * 128 + tid] = __ldcg(&g_mod[5 * DM + c]);
            } else {
                const int c = nb * 128 + tid - 128;
                sv[V_VA * 128 + tid - 128] = __ldcg(&g_vec[c]); sv[V_VB * 128 + tid - 128] = __ldcg(&g_vec[DM + c]); sv[V_VC * 128 + tid - 128] = __ldcg(&g_vec[2 * DM + c]);
            }
            sv[V_C3 * 128 + tid] = __ldcg(&g_vec[3 * DM + nb * 256 + tid]);
            if (tid < 192) sv[V_C3 * 128 + 256 + tid] = __ldcg(&g_vec[3 * DM + 2048 + nb * 192 + tid]);
            bar_sync(3, 256);
        }
        uint32_t vec = sb + P_VEC + tq * 8;
        asm volatile("" : "+r"(vec) :: "memory");
        const uint32_t stw = sb + (wi * 16 + ((lane >> 3) & 1) * 8 + (lane & 7)) * 128 + (((lane >> 4) ^ (lane & 7)) << 4);
        int sig = 0;
        auto signal = [&]() { bar_arrive(4 + 4 * wg + (sig++ & 3), 160); };
        auto put64 = [&](uint32_t o, const float* v) {
#pragma unroll
            for (int jj = 0; jj < 4; jj++, v += 8) stsm4((stw + o) ^ (jj << 5), pack2(v[0], v[1]), pack2(v[2], v[3]), pack2(v[4], v[5]), pack2(v[6], v[7]));
            fence_async_smem();
            signal();
        };
        auto out_free = [&](int n) { wait_smem(bars + 8 * (PB_OUT + (lane & 1)), n); };
        const uint32_t rowc = sb + P_ROW + (wg * 64 + wi * 16 + g) * 32, o128 = P_OUT + wg * 16384;
        Pipe pa = {0, 0}, pb = {0, 0};
        uint32_t keep[32];
#define KEEP(jn, e) (((e) & 1) ? bfhi(keep[2 * (jn) + ((e) >> 1)]) : bflo(keep[2 * (jn) + ((e) >> 1)]))
        float mu1[2], r1[2];
        {
            float acc[64];
            const uint32_t xo = sb + o128 + wi * 2048 + (lane >> 3) * 128;
#pragma unroll
            for (int i = 0; i < 8; i++) sts4(xo + (i >> 2) * 8192 + (i & 3) * 512 + (((lane & 7) ^ ((i & 1) * 4 + (lane >> 3))) << 4), xg[i].x, xg[i].y, xg[i].z, xg[i].w);
            __syncwarp();
#pragma unroll
            for (int jj = 0; jj < 8; jj++) ldsm4(keep + jj * 4, (stw + o128 + (jj >> 2) * 8192) ^ ((jj & 3) << 5));
            __syncwarp();
            post_mma<0>(sb, acc, pa, wg, lead, 1);
            float st[2][6];
#pragma unroll
            for (int q = 0; q < 6; q++) st[0][q] = st[1][q] = 0.f;
#pragma unroll
            for (int jn = 0; jn < 16; jn++) {
                const float2 ga = ldsv(vec + V_GA * 512 + jn * 32), a = ldsv(vec + V_A * 512 + jn * 32);
                float xa[4];
#pragma unroll
                for (int e = 0; e < 4; e++) {
                    xa[e] = fmaf((e & 1) ? ga.y : ga.x, acc[4 * jn + e], KEEP(jn, e));
                    st[e >> 1][0] += xa[e]; st[e >> 1][1] = fmaf(xa[e], xa[e], st[e >> 1][1]);
                    acc[4 * jn + e] = ((e & 1) ? a.y : a.x) * xa[e];
                }
                keep[2 * jn] = pack2(xa[0], xa[1]); keep[2 * jn + 1] = pack2(xa[2], xa[3]);
                if ((jn & 7) == 7) put64(o128 + (jn >> 3) * 8192, acc + 4 * jn - 28);
            }
            PP(3)
#pragma unroll
            for (int jn = 0; jn < 16; jn++) {
                const float2 a = ldsv(vec + V_A * 512 + jn * 32), b = ldsv(vec + V_B * 512 + jn * 32);
#pragma unroll
                for (int e = 0; e < 4; e++) {
                    const float y = acc[4 * jn + e], aa = (e & 1) ? a.y : a.x, bb = (e & 1) ? b.y : b.x;
                    float* s = st[e >> 1];
                    s[2] += y; s[3] = fmaf(aa, y, s[3]); s[4] = fmaf(y, y, s[4]); s[5] = fmaf(bb, y, s[5]);
                }
            }
#pragma unroll
            for (int h = 0; h < 2; h++)
#pragma unroll
                for (int q = 0; q < 6; q++) { st[h][q] += __shfl_xor_sync(~0u, st[h][q], 1); st[h][q] += __shfl_xor_sync(~0u, st[h][q], 2); }
            if (tq < 3) {
#pragma unroll
                for (int h = 0; h < 2; h++)
                    red2(g_st + (tq * S_ + row + h * 8) * 2, tq == 0 ? st[h][0] : tq == 1 ? st[h][2] : st[h][4], tq == 0 ? st[h][1] : tq == 1 ? st[h][3] : st[h][5]);
            }
            signal();
            PP(29)
        }
        {
            float acc[64];
            post_mma<1>(sb, acc, pa, wg, lead, 4);
            float c1[2], c2[2], c3[2];
            GeluK gk[2];
            bar_sync(1 + wg, 160);
#pragma unroll
            for (int h = 0; h < 2; h++) {
                const float4 a = lds4f(rowc + h * 256), b = lds4f(rowc + h * 256 + 16);
                gk[h] = {a.x, a.y, a.z}; c1[h] = a.w; c2[h] = b.x; c3[h] = b.y; mu1[h] = b.w; r1[h] = b.z;
            }
#pragma unroll
            for (int jn = 0; jn < 16; jn++) {
                const float2 va = ldsv(vec + V_VA * 512 + jn * 32), vb = ldsv(vec + V_VB * 512 + jn * 32), vc = ldsv(vec + V_VC * 512 + jn * 32);
#pragma unroll
                for (int e = 0; e < 4; e++) {
                    const int h = e >> 1;
                    const float t = fmaf(c1[h], (e & 1) ? va.y : va.x, fmaf(c2[h], (e & 1) ? vb.y : vb.x, fmaf(c3[h], (e & 1) ? vc.y : vc.x, acc[4 * jn + e])));
                    acc[4 * jn + e] = gelu_s(t, gk[h]);
                }
                if ((jn & 7) == 7) put64(o128 + (jn >> 3) * 8192, acc + 4 * jn - 28);
            }
            PP(6)
        }
        {
            float acc[64];
            post_mma<2>(sb, acc, pa, wg, lead, 7);
#pragma unroll
            for (int jn = 0; jn < 16; jn++) {
                const float2 a = ldsv(vec + V_A * 512 + jn * 32), b = ldsv(vec + V_B * 512 + jn * 32);
#pragma unroll
                for (int e = 0; e < 4; e++) {
                    const int h = e >> 1;
                    acc[4 * jn + e] += fmaf(fmaf(KEEP(jn, e), r1[h], mu1[h]), (e & 1) ? a.y : a.x, (e & 1) ? b.y : b.x);
                }
                if ((jn & 7) == 7) put64(o128 + (jn >> 3) * 8192, acc + 4 * jn - 28);
            }
            PP(9)
            float st[2][2] = {{0.f, 0.f}, {0.f, 0.f}};
#pragma unroll
            for (int jn = 0; jn < 16; jn++) {
                const float2 gb = ldsv(vec + V_GB * 512 + jn * 32);
                float z[4];
#pragma unroll
                for (int e = 0; e < 4; e++) {
                    const float x1 = acc[4 * jn + e];
                    st[e >> 1][0] += x1; st[e >> 1][1] = fmaf(x1, x1, st[e >> 1][1]);
                    z[e] = fmaf((e & 1) ? gb.y : gb.x, x1, KEEP(jn, e));
                }
                keep[2 * jn] = pack2(z[0], z[1]); keep[2 * jn + 1] = pack2(z[2], z[3]);
            }
#pragma unroll
            for (int h = 0; h < 2; h++)
#pragma unroll
                for (int q = 0; q < 2; q++) { st[h][q] += __shfl_xor_sync(~0u, st[h][q], 1); st[h][q] += __shfl_xor_sync(~0u, st[h][q], 2); }
            if (tq < 2) red2(g_st + (3 * S_ + row + tq * 8) * 2, tq ? st[1][0] : st[0][0], tq ? st[1][1] : st[0][1]);
            signal();
            PP(30)
        }
        {
            uint32_t v3 = vec + V_C3 * 512;
#pragma unroll 1
            for (int r = 0; r < 2; r++) {
                float acc[128];
#pragma unroll
                for (int i = 96; i < 128; i++) acc[i] = 0.f;
                if (r == 0) post_mma<3>(sb, acc, pb, wg, lead, 10);
                else post_mma<4>(sb, acc, pb, wg, lead, 13);
                float c1[2];
                GeluK gk[2];
                if (r == 0) bar_sync(1 + wg, 160);
                out_free(3 + r);
#pragma unroll
                for (int h = 0; h < 2; h++) { const float4 a = lds4f(rowc + h * 256); gk[h] = {a.x, a.y, a.z}; c1[h] = a.w; }
                uint32_t o = r ? P_OUT4 + wg * 24576 : P_OUT3 + wg * 32768;
#pragma unroll 1
                for (int left = 3 - r; left >= 0; left--) {
#pragma unroll
                    for (int jn = 0; jn < 8; jn++) {
                        const float2 vc = ldsv(v3 + jn * 32);
#pragma unroll
                        for (int e = 0; e < 4; e++) acc[4 * jn + e] = gelu_s(fmaf(c1[e >> 1], (e & 1) ? vc.y : vc.x, acc[4 * jn + e]), gk[e >> 1]);
                    }
                    put64(o, acc);
#pragma unroll
                    for (int i = 0; i < 32; i++) acc[i] = acc[32 + i];
                    if (left > 1) {
#pragma unroll
                        for (int i = 32; i < 64; i++) acc[i] = acc[32 + i];
                        if (left > 2) {
#pragma unroll
                            for (int i = 64; i < 96; i++) acc[i] = acc[32 + i];
                        }
                    }
                    o += 8192; v3 += 256;
                }
                PP(12 + 3 * r)
            }
        }
        {
            float acc[64];
            post_mma<5>(sb, acc, pa, wg, lead, 16);
#pragma unroll
            for (int jn = 0; jn < 16; jn++) {
                const float2 gb = ldsv(vec + V_GB * 512 + jn * 32);
#pragma unroll
                for (int e = 0; e < 4; e++) acc[4 * jn + e] = fmaf((e & 1) ? gb.y : gb.x, acc[4 * jn + e], KEEP(jn, e));
                if ((jn & 7) == 7) put64(o128 + (jn >> 3) * 8192, acc + 4 * jn - 28);
            }
            PP(18)
            if (tid == 0) TL(12)
        }
    }
}

typedef CUresult (*EncFn)(CUtensorMap*, CUtensorMapDataType, cuuint32_t, void*, const cuuint64_t*, const cuuint64_t*, const cuuint32_t*,
                          const cuuint32_t*, CUtensorMapInterleave, CUtensorMapSwizzle, CUtensorMapL2promotion, CUtensorMapFloatOOBfill);

static CUtensorMap make_map(EncFn enc, const void* p, uint64_t inner, uint64_t outer, uint32_t bi = 64) {
    CUtensorMap m;
    cuuint64_t dims[2] = {inner, outer};
    cuuint64_t str[1] = {inner * 2};
    cuuint32_t box[2] = {bi, bi == 64 ? 64u : 16u};
    cuuint32_t es[2] = {1, 1};
    enc(&m, CU_TENSOR_MAP_DATA_TYPE_BFLOAT16, 2, (void*)p, dims, str, box, es, CU_TENSOR_MAP_INTERLEAVE_NONE,
        bi == 64 ? CU_TENSOR_MAP_SWIZZLE_128B : CU_TENSOR_MAP_SWIZZLE_NONE, CU_TENSOR_MAP_L2_PROMOTION_L2_256B, CU_TENSOR_MAP_FLOAT_OOB_FILL_NONE);
    return m;
}
static CUtensorMap make_map_o(EncFn enc, const void* p) {
    CUtensorMap m;
    cuuint64_t dims[2] = {16384, 256};
    cuuint64_t str[1] = {65536};
    cuuint32_t box[2] = {256, 8};
    cuuint32_t es[2] = {1, 1};
    enc(&m, CU_TENSOR_MAP_DATA_TYPE_UINT32, 2, (void*)p, dims, str, box, es, CU_TENSOR_MAP_INTERLEAVE_NONE, CU_TENSOR_MAP_SWIZZLE_NONE,
        CU_TENSOR_MAP_L2_PROMOTION_L2_256B, CU_TENSOR_MAP_FLOAT_OOB_FILL_NONE);
    return m;
}
template <class T> static T* sym(T& s) { void* p = nullptr; cudaGetSymbolAddress(&p, s); return (T*)p; }

static const Delays h_dly = {D_NEAR, D_FAR, D_X2, D_V, D_W2, D_PA, D_WF, D_TV};
extern "C" void kernel_launch(void* const* d_in, const int* in_sizes, int n_in, void* d_out, int out_size) {
    const bf16* x = (const bf16*)d_in[0];
    const bf16* mem0 = (const bf16*)d_in[1];
    const bf16 *Wq = (const bf16*)d_in[2], *Wk = (const bf16*)d_in[3], *Wv = (const bf16*)d_in[4], *Wo = (const bf16*)d_in[5];
    const bf16 *w1 = (const bf16*)d_in[8], *w2 = (const bf16*)d_in[9], *w3 = (const bf16*)d_in[10], *w4 = (const bf16*)d_in[11];
    const bf16 *c = (const bf16*)d_in[12], *wmod = (const bf16*)d_in[13];
    bf16* out = (bf16*)d_out;

    EncFn enc = nullptr;
    cudaDriverEntryPointQueryResult qr;
    cudaGetDriverEntryPoint("cuTensorMapEncodeTiled", (void**)&enc, cudaEnableDefault, &qr);
    CUtensorMap tWq = make_map(enc, Wq, NH * DH, DM), tWk = make_map(enc, Wk, NH * DH, DM), tWv = make_map(enc, Wv, NH * DH, DM);
    PostMaps mp;
    mp.o = make_map_o(enc, sym(g_O)); mp.wo = make_map(enc, Wo, DM, NH * DH);
    mp.y = make_map(enc, sym(g_y), DM, S_); mp.w1 = make_map(enc, w1, DM, DM);
    mp.g = make_map(enc, sym(g_g), DM, S_); mp.w2 = make_map(enc, w2, DM, DM);
    mp.x1 = make_map(enc, sym(g_x1), DM, S_); mp.w3 = make_map(enc, w3, FF, DM);
    mp.u = make_map(enc, sym(g_u), FF, S_); mp.w4 = make_map(enc, w4, DM, FF);
    mp.out = make_map(enc, out, DM, S_);
    cudaFuncSetAttribute(k_rec, cudaFuncAttributeMaxDynamicSharedMemorySize, SM_REC_TOTAL + 2048);
    cudaFuncSetAttribute(k_post, cudaFuncAttributeMaxDynamicSharedMemorySize, P_SMEM);

    uint8_t* arena = (uint8_t*)(((uintptr_t)sym(g_arena) + (2u << 20) - 1) & ~(uintptr_t)((2u << 20) - 1));
    const PostPtrs pp = {x};
    const RecPtrs rp = {x, mem0, c, wmod, w1, w3, arena, 0u, w2, w4, Wo, h_dly};
    const RecMaps rm = {tWq, tWk, tWv, mp.wo, make_map(enc, wmod, 6 * DM, DM, 256), make_map(enc, w3, FF, DM, 256), make_map(enc, w1, DM, DM, 256)};
    k_rec<<<132, 384, SM_REC_TOTAL + 2048>>>(rm, rp);
    k_post<<<128, 384, P_SMEM>>>(mp, pp);
}
```

```cpp
#include <cuda_runtime.h>
#include <cuda.h>
#include <cuda_bf16.h>
#include <stdint.h>
#include <limits.h>

typedef __nv_bfloat16 bf16;

constexpr int S_ = 2048, DM = 1024, NH = 32, DH = 128, NSEG = 64, FF = 3584;
constexpr int SPIN_LIMIT = 1 << 22;
#define W_INFL 2
#define XP 0
#define H_PIECES 4
#define NPROBE 3

__device__ uint8_t g_arena[10 << 20];
__device__ uint32_t g_tick[64];
__device__ __align__(16) uint32_t g_modp[8 * 2 * DM];
__host__ __device__ constexpr uint32_t blk(uint32_t lb, uint32_t par) {
    return (lb << 13) | ((((lb) ^ (lb >> 3) ^ (lb >> 4) ^ (lb >> 6) ^ par) & 1) << 12);
}
__host__ __device__ constexpr uint32_t lb_x2(uint32_t h) { return (h & 1) | ((h >> 1) << 3); }
__host__ __device__ constexpr uint32_t mem_row(uint32_t kh, uint32_t b, uint32_t r) { return blk(128 | b, kh) + r * 1024; }
__device__ __forceinline__ uint32_t mem_slot(uint32_t s) { return ((s & 1) << 15) | ((s & 2) << 17); }
constexpr uint32_t CNT1 = 0x3d80, CNT_ALL = 0x4000;
constexpr uint32_t LB_PROBE = 6 | 64, LB_TIME = 6;
__host__ __device__ constexpr uint32_t lb_tok(uint32_t h) { return (h & 1) | ((h >> 1) << 3); }
__device__ float g_mod[6 * DM];
__device__ __align__(1024) bf16 g_himg[(S_ + 32) * DM];
__device__ __align__(1024) bf16 g_O[S_ * NH * DH];
__device__ __align__(1024) bf16 g_y[S_ * DM];
__device__ __align__(1024) bf16 g_g[S_ * DM];
__device__ __align__(1024) bf16 g_x1[S_ * DM];
__device__ __align__(16) float g_st[4 * S_ * 2];
__device__ float g_vec[3 * DM + FF];
__device__ float g_cst[8];
__device__ uint32_t g_pcnt[2 * 32 * 8], g_pflag[6 * 32 * 8];
__device__ __align__(1024) bf16 g_u[S_ * FF];

#define TL(i) {}
#define TLC(i) {}
__device__ __forceinline__ uint32_t smem_u32(const void* p) { return (uint32_t)__cvta_generic_to_shared(p); }
__device__ __forceinline__ void spin_guard(int it) {
    asm volatile("{.reg .pred p; setp.gt.s32 p, %0, %1; @p st.global.u32 [%2], %0;}" ::"r"(it), "n"(SPIN_LIMIT), "l"(1ull));
}
__device__ __forceinline__ void wg_fence() { asm volatile("wgmma.fence.sync.aligned;" ::: "memory"); }
__device__ __forceinline__ void wg_commit() { asm volatile("wgmma.commit_group.sync.aligned;" ::: "memory"); }
template <int N> __device__ __forceinline__ void wg_wait() { asm volatile("wgmma.wait_group.sync.aligned %0;" ::"n"(N) : "memory"); }
__host__ __device__ constexpr uint64_t mkdesc(uint32_t addr, uint32_t lbo, uint32_t sbo, uint32_t swz) {
    return (uint64_t)((addr & 0x3FFFF) >> 4) | ((uint64_t)(lbo >> 4) << 16) | ((uint64_t)(sbo >> 4) << 32) | ((uint64_t)swz << 62);
}
__device__ __forceinline__ uint64_t dadd(uint64_t d, uint32_t o) { return (d & 0xffffffff00000000ull) | (uint32_t)((uint32_t)d + o); }
__device__ __forceinline__ void mbar_init(uint32_t b, uint32_t c) { asm volatile("mbarrier.init.shared.b64 [%0], %1;" ::"r"(b), "r"(c) : "memory"); }
__device__ __forceinline__ void mbar_expect(uint32_t b, uint32_t tx) { asm volatile("mbarrier.arrive.expect_tx.shared.b64 _, [%0], %1;" ::"r"(b), "r"(tx) : "memory"); }
__device__ __forceinline__ void mbar_arrive(uint32_t b) { asm volatile("mbarrier.arrive.shared.b64 _, [%0];" ::"r"(b) : "memory"); }
__device__ __forceinline__ void mbar_arrive_cluster(uint32_t b, uint32_t cta) {
    asm volatile("{.reg .b32 r; mapa.shared::cluster.u32 r, %0, %1; mbarrier.arrive.shared::cluster.b64 _, [r];}" ::"r"(b), "r"(cta) : "memory");
}
__device__ __forceinline__ bool mbar_try(uint32_t b, uint32_t par) {
    uint32_t ok;
    asm volatile("{.reg .pred p; mbarrier.try_wait.parity.shared.b64 p, [%1], %2; selp.u32 %0, 1, 0, p;}" : "=r"(ok) : "r"(b), "r"(par) : "memory");
    return ok;
}
__device__ __forceinline__ void mbar_wait(uint32_t b, uint32_t par) {
    int it = 0;
#pragma unroll 1
    while (!mbar_try(b, par)) { spin_guard(++it); }
}
__device__ __forceinline__ void mbar_wait_w(uint32_t b, uint32_t par) {
    int it = 0;
    bool ok;
#pragma unroll 1
    do { ok = __all_sync(~0u, mbar_try(b, par)); spin_guard(++it); } while (!ok);
}
__device__ __forceinline__ void mbar_wait_cluster(uint32_t b, uint32_t par) {
    int it = 0;
    while (true) {
        uint32_t ok;
        asm volatile("{.reg .pred p; mbarrier.try_wait.parity.acquire.cluster.shared::cta.b64 p, [%1], %2; selp.u32 %0, 1, 0, p;}" : "=r"(ok) : "r"(b), "r"(par) : "memory");
        if (ok) break;
        spin_guard(++it);
    }
}
__device__ __forceinline__ void tma2d(uint32_t dst, const CUtensorMap* m, int c0, int c1, uint32_t bar) {
    asm volatile("cp.async.bulk.tensor.2d.shared::cluster.global.mbarrier::complete_tx::bytes [%0], [%1, {%3, %4}], [%2];" ::"r"(dst), "l"(m), "r"(bar), "r"(c0), "r"(c1) : "memory");
}
__device__ __forceinline__ void tma2d_mc(uint32_t dst, const CUtensorMap* m, int c0, int c1, uint32_t bar, uint16_t mask) {
    asm volatile("cp.async.bulk.tensor.2d.shared::cluster.global.mbarrier::complete_tx::bytes.multicast::cluster [%0], [%1, {%3, %4}], [%2], %5;" ::"r"(dst), "l"(m), "r"(bar), "r"(c0), "r"(c1), "h"(mask) : "memory");
}
__device__ __forceinline__ void bulk_g2s(uint32_t dst, const void* src, uint32_t bytes, uint32_t bar) {
    asm volatile("cp.async.bulk.shared::cluster.global.mbarrier::complete_tx::bytes [%0], [%1], %2, [%3];" ::"r"(dst), "l"(src), "r"(bytes), "r"(bar) : "memory");
}
__device__ __forceinline__ void bar_sync(int id, int n) { asm volatile("bar.sync %0, %1;" ::"r"(id), "r"(n) : "memory"); }
__device__ __forceinline__ void bar_arrive(int id, int n) { asm volatile("bar.arrive %0, %1;" ::"r"(id), "r"(n) : "memory"); }
__device__ __forceinline__ void cluster_sync_all() { asm volatile("barrier.cluster.arrive.aligned; barrier.cluster.wait.aligned;" ::: "memory"); }
__device__ __forceinline__ void fence_async_smem() { asm volatile("fence.proxy.async.shared::cta;" ::: "memory"); }
__device__ __forceinline__ void ldsm4t(uint32_t* r, uint32_t a) {
    asm volatile("ldmatrix.sync.aligned.m8n8.x4.trans.shared.b16 {%0,%1,%2,%3}, [%4];" : "=r"(r[0]), "=r"(r[1]), "=r"(r[2]), "=r"(r[3]) : "r"(a) : "memory");
}
__device__ __forceinline__ void ldsm4(uint32_t* r, uint32_t a) {
    asm volatile("ldmatrix.sync.aligned.m8n8.x4.shared.b16 {%0,%1,%2,%3}, [%4];" : "=r"(r[0]), "=r"(r[1]), "=r"(r[2]), "=r"(r[3]) : "r"(a) : "memory");
}
__device__ __forceinline__ uint32_t movm(uint32_t a) {
    uint32_t d; asm volatile("movmatrix.sync.aligned.m8n8.trans.b16 %0, %1;" : "=r"(d) : "r"(a)); return d;
}
__device__ __forceinline__ void mma16816(float* d, uint32_t a0, uint32_t a1, uint32_t a2, uint32_t a3, uint32_t b0, uint32_t b1) {
    asm volatile("mma.sync.aligned.m16n8k16.row.col.f32.bf16.bf16.f32 {%0,%1,%2,%3},{%4,%5,%6,%7},{%8,%9},{%0,%1,%2,%3};"
                 : "+f"(d[0]), "+f"(d[1]), "+f"(d[2]), "+f"(d[3]) : "r"(a0), "r"(a1), "r"(a2), "r"(a3), "r"(b0), "r"(b1));
}
__device__ __forceinline__ void mma16816z(float* d, const uint32_t* a, uint32_t b0, uint32_t b1) {
    asm volatile("mma.sync.aligned.m16n8k16.row.col.f32.bf16.bf16.f32 {%0,%1,%2,%3},{%4,%5,%6,%7},{%8,%9},{%10,%10,%10,%10};"
                 : "=f"(d[0]), "=f"(d[1]), "=f"(d[2]), "=f"(d[3]) : "r"(a[0]), "r"(a[1]), "r"(a[2]), "r"(a[3]), "r"(b0), "r"(b1), "f"(0.f));
}
__device__ __forceinline__ void mma1688(float* d, uint32_t a0, uint32_t a1, uint32_t b0) {
    asm volatile("mma.sync.aligned.m16n8k8.row.col.f32.bf16.bf16.f32 {%0,%1,%2,%3},{%4,%5},{%6},{%0,%1,%2,%3};"
                 : "+f"(d[0]), "+f"(d[1]), "+f"(d[2]), "+f"(d[3]) : "r"(a0), "r"(a1), "r"(b0));
}
__device__ __forceinline__ uint32_t pack2(float lo, float hi) {
    uint32_t r; asm("cvt.rn.bf16x2.f32 %0, %1, %2;" : "=r"(r) : "f"(hi), "f"(lo)); return r;
}
__device__ __forceinline__ uint32_t hadd2(uint32_t a, uint32_t b) {
    uint32_t r; asm("add.rn.bf16x2 %0, %1, %2;" : "=r"(r) : "r"(a), "r"(b)); return r;
}
__device__ __forceinline__ float bflo(uint32_t u) { return __uint_as_float(u << 16); }
__device__ __forceinline__ float bfhi(uint32_t u) { return __uint_as_float(u & 0xffff0000u); }
__device__ __forceinline__ float ex2(float x) { float r; asm("ex2.approx.ftz.f32 %0, %1;" : "=f"(r) : "f"(x)); return r; }
__device__ __forceinline__ uint4 ldg_rlx4(const void* p) {
    uint4 v; asm volatile("ld.relaxed.gpu.global.v4.u32 {%0,%1,%2,%3}, [%4];" : "=r"(v.x), "=r"(v.y), "=r"(v.z), "=r"(v.w) : "l"(p) : "memory"); return v;
}
__device__ __forceinline__ uint2 ldg_rlx2(const void* p) {
    unsigned long long v; asm volatile("ld.relaxed.gpu.global.b64 %0, [%1];" : "=l"(v) : "l"(p) : "memory");
    return make_uint2((uint32_t)v, (uint32_t)(v >> 32));
}
__device__ __forceinline__ uint32_t ldg_rlx1(const void* p) {
    uint32_t v; asm volatile("ld.relaxed.gpu.global.u32 %0, [%1];" : "=r"(v) : "l"(p) : "memory"); return v;
}
__device__ __forceinline__ void stg_rlx1(void* p, uint32_t v) { asm volatile("st.relaxed.gpu.global.u32 [%0], %1;" ::"l"(p), "r"(v) : "memory"); }
__device__ __forceinline__ void stg_rlx2(void* p, uint32_t x, uint32_t y) {
    unsigned long long v = (unsigned long long)x | ((unsigned long long)y << 32);
    asm volatile("st.relaxed.gpu.global.b64 [%0], %1;" ::"l"(p), "l"(v) : "memory");
}
__device__ __forceinline__ void stg_rlx4(void* p, uint32_t x, uint32_t y, uint32_t z, uint32_t w) {
    asm volatile("st.relaxed.gpu.global.v4.u32 [%0], {%1,%2,%3,%4};" ::"l"(p), "r"(x), "r"(y), "r"(z), "r"(w) : "memory");
}
__device__ __forceinline__ void sts4(uint32_t a, uint32_t x, uint32_t y, uint32_t z, uint32_t w) {
    asm volatile("st.shared.v4.u32 [%0], {%1,%2,%3,%4};" ::"r"(a), "r"(x), "r"(y), "r"(z), "r"(w) : "memory");
}
__device__ __forceinline__ uint4 lds4(uint32_t a) {
    uint4 v; asm volatile("ld.shared.v4.u32 {%0,%1,%2,%3}, [%4];" : "=r"(v.x), "=r"(v.y), "=r"(v.z), "=r"(v.w) : "r"(a) : "memory"); return v;
}
__device__ __forceinline__ void st_async4(uint32_t a, float x, float y, float z, float w, uint32_t bar) {
    asm volatile("st.async.shared::cluster.mbarrier::complete_tx::bytes.v4.f32 [%0], {%1,%2,%3,%4}, [%5];" ::"r"(a), "f"(x), "f"(y), "f"(z), "f"(w), "r"(bar) : "memory");
}
#define F4(d, i) "+f"(d[i]), "+f"(d[i + 1]), "+f"(d[i + 2]), "+f"(d[i + 3])
__device__ __forceinline__ void wgmma_rs32(float* d, const uint32_t* a, uint64_t b, int sc) {
    asm volatile("{.reg .pred p; setp.ne.b32 p, %21, 0;\n wgmma.mma_async.sync.aligned.m64n32k16.f32.bf16.bf16 {%0,%1,%2,%3,%4,%5,%6,%7,%8,%9,%10,%11,%12,%13,%14,%15}, {%16,%17,%18,%19}, %20, p, 1, 1, 0;}"
                 : F4(d, 0), F4(d, 4), F4(d, 8), F4(d, 12) : "r"(a[0]), "r"(a[1]), "r"(a[2]), "r"(a[3]), "l"(b), "r"(sc));
}
__device__ __forceinline__ void wgmma_ss32(float* d, uint64_t a, uint64_t b, int sc) {
    asm volatile("{.reg .pred p; setp.ne.b32 p, %18, 0;\n wgmma.mma_async.sync.aligned.m64n32k16.f32.bf16.bf16 {%0,%1,%2,%3,%4,%5,%6,%7,%8,%9,%10,%11,%12,%13,%14,%15}, %16, %17, p, 1, 1, 1, 0;}"
                 : F4(d, 0), F4(d, 4), F4(d, 8), F4(d, 12) : "l"(a), "l"(b), "r"(sc));
}
__device__ __forceinline__ void wgmma_rs40(float* d, const uint32_t* a, uint64_t b, int sc) {
    asm volatile("{.reg .pred p; setp.ne.b32 p, %25, 0;\n wgmma.mma_async.sync.aligned.m64n40k16.f32.bf16.bf16 {%0,%1,%2,%3,%4,%5,%6,%7,%8,%9,%10,%11,%12,%13,%14,%15,%16,%17,%18,%19}, {%20,%21,%22,%23}, %24, p, 1, 1, 0;}"
                 : F4(d, 0), F4(d, 4), F4(d, 8), F4(d, 12), F4(d, 16) : "r"(a[0]), "r"(a[1]), "r"(a[2]), "r"(a[3]), "l"(b), "r"(sc));
}
__device__ __forceinline__ void wgmma_ss40(float* d, uint64_t a, uint64_t b, int sc) {
    asm volatile("{.reg .pred p; setp.ne.b32 p, %22, 0;\n wgmma.mma_async.sync.aligned.m64n40k16.f32.bf16.bf16 {%0,%1,%2,%3,%4,%5,%6,%7,%8,%9,%10,%11,%12,%13,%14,%15,%16,%17,%18,%19}, %20, %21, p, 1, 1, 1, 0;}"
                 : F4(d, 0), F4(d, 4), F4(d, 8), F4(d, 12), F4(d, 16) : "l"(a), "l"(b), "r"(sc));
}
#define F16(d, i) F4(d, i), F4(d, i + 4), F4(d, i + 8), F4(d, i + 12)
template <int TA>
__device__ __forceinline__ void wgmma_ss128(float* d, uint64_t a, uint64_t b, int sc) {
    asm volatile("{.reg .pred p; setp.ne.b32 p, %66, 0;\n wgmma.mma_async.sync.aligned.m64n128k16.f32.bf16.bf16 "
                 "{%0,%1,%2,%3,%4,%5,%6,%7,%8,%9,%10,%11,%12,%13,%14,%15,%16,%17,%18,%19,%20,%21,%22,%23,%24,%25,%26,%27,%28,%29,%30,%31,"
                 "%32,%33,%34,%35,%36,%37,%38,%39,%40,%41,%42,%43,%44,%45,%46,%47,%48,%49,%50,%51,%52,%53,%54,%55,%56,%57,%58,%59,%60,%61,%62,%63}, %64, %65, p, 1, 1, %67, 1;}"
                 : F16(d, 0), F16(d, 16), F16(d, 32), F16(d, 48) : "l"(a), "l"(b), "r"(sc), "n"(TA));
}

__device__ __forceinline__ float warp_sum(float v) {
#pragma unroll
    for (int o = 16; o; o >>= 1) v += __shfl_xor_sync(~0u, v, o);
    return v;
}
__device__ __forceinline__ float bfround(float x) { return __bfloat162float(__float2bfloat16(x)); }

__device__ __forceinline__ void wait_count1(const uint32_t* p, uint32_t target) {
    int it = 0;
#pragma unroll 1
    while (true) {
        uint32_t v;
        asm volatile("ld.acquire.gpu.global.u32 %0, [%1];" : "=r"(v) : "l"(p) : "memory");
        if (v >= target) break;
        spin_guard(++it);
    }
}
__device__ __forceinline__ void red2(float* p, float a, float b) {
    asm volatile("red.relaxed.gpu.global.add.v2.f32 [%0], {%1, %2};" ::"l"(p), "f"(a), "f"(b) : "memory");
}
__device__ __forceinline__ void l2_prefetch(const void* p, uint32_t bytes) {
    asm volatile("cp.async.bulk.prefetch.L2.global [%0], %1;" ::"l"(p), "r"(bytes) : "memory");
}
__device__ __forceinline__ void signal_count(uint32_t* p) { asm volatile("red.release.gpu.global.add.u32 [%0], 1;" ::"l"(p) : "memory"); }
__device__ __forceinline__ void e_expect(uint32_t b, uint32_t tx) {
    asm volatile("{.reg .pred p; elect.sync _|p, 0xffffffff; @p mbarrier.arrive.expect_tx.shared.b64 _, [%0], %1;}" ::"r"(b), "r"(tx) : "memory");
}
__device__ __forceinline__ void e_tma2d(uint32_t dst, const CUtensorMap* m, int c0, int c1, uint32_t bar) {
    asm volatile("{.reg .pred p; elect.sync _|p, 0xffffffff;\n @p cp.async.bulk.tensor.2d.shared::cluster.global.mbarrier::complete_tx::bytes [%0], [%1, {%3, %4}], [%2];}"
                 ::"r"(dst), "l"(m), "r"(bar), "r"(c0), "r"(c1) : "memory");
}
__device__ __forceinline__ void e_tma2d_mc(uint32_t dst, const CUtensorMap* m, int c0, int c1, uint32_t bar) {
    asm volatile("{.reg .pred p; elect.sync _|p, 0xffffffff;\n @p cp.async.bulk.tensor.2d.shared::cluster.global.mbarrier::complete_tx::bytes.multicast::cluster [%0], [%1, {%3, %4}], [%2], %5;}"
                 ::"r"(dst), "l"(m), "r"(bar), "r"(c0), "r"(c1), "h"((uint16_t)3) : "memory");
}
__device__ __forceinline__ void e_prefetch(const void* p, uint32_t bytes) {
    asm volatile("{.reg .pred p; elect.sync _|p, 0xffffffff; @p cp.async.bulk.prefetch.L2.global [%0], %1;}" ::"l"(p), "r"(bytes) : "memory");
}
__device__ __forceinline__ void wait_count_w(const uint32_t* p, uint32_t target) {
    int it = 0;
#pragma unroll 1
    while (true) {
        uint32_t v;
        asm volatile("ld.acquire.gpu.global.u32 %0, [%1];" : "=r"(v) : "l"(p) : "memory");
        if (__all_sync(~0u, v >= target)) break;
        spin_guard(++it);
    }
}

__device__ __forceinline__ void ln_row(float* x) {
    float s = 0;
#pragma unroll
    for (int i = 0; i < 32; i++) s += x[i];
    float m = warp_sum(s) * (1.0f / DM);
    float q = 0;
#pragma unroll
    for (int i = 0; i < 32; i++) { x[i] -= m; q += x[i] * x[i]; }
    float r = rsqrtf(warp_sum(q) * (1.0f / DM) + 1e-5f);
#pragma unroll
    for (int i = 0; i < 32; i++) x[i] *= r;
}
__device__ __forceinline__ uint4 pack8(const float* x) {
    return make_uint4(pack2(x[0], x[1]), pack2(x[2], x[3]), pack2(x[4], x[5]), pack2(x[6], x[7]));
}
#define NL 6
constexpr uint32_t SM_HB = 16384, HBK = 5120, SM_SX = 57344, SM_OX = 122880, SM_PX = 124928, SM_PA = 126976, SM_WO = 147456,
                   SM_TAB = 212992, SM_PRE = SM_TAB, SM_BAR = 227328, SM_REC_TOTAL = 227328 + 256;
constexpr uint32_t SB0 = 1024;
constexpr int B_WO = 0, B_HE = 1, B_ROLE = 2, B_HB = 3, B_W = 5;
constexpr int NB_MEM = 1, NB_QK = 2, NB_X1 = 3, NB_X2 = 4, NB_WIN = 5, NB_WG = 6, NB_KDONE = 7, NB_FIN0 = 8, NB_P = 9, NB_PX = 10, NB_G = 11, NB_A = 12, NB_B = 13, NB_C = 14, NB_S = 15;
#define SPF 33
#define SPF_AT 54
#define SPF_R 12
#define SPF_NS 40
#define D_TPV 100
#define V_POS 2
#define D_X2 470
#define D_TV 50
#define D_V 390
#define D_NEAR 1670
#define D_FAR (D_NEAR - 140)
#define E_MUL 28
#define D_WF 60
#define NE 0
#define D_H 0
#define D_W2 170
#define SETTLE 0
#define TV_POS 1
#define D_PA 0
#define NE1 10
#define H_POS 3
#define PA_POS 1
#define K_DLY 0
#define ST_BAR 1
#define W1_AT -1
#define ROT 2
#define ALIGN 0
#define CNT32 0
#define O_POS 1
#define Z_POS 0
#define QF_LATE 100
#define W0_E 3
#define G_AT 24
#define W0_AT 4
#define W0_RS (NL - 1)
#define P_GATE 0
#define NPF (NL + 6)

struct Delays { uint32_t near, far, x2, v, w2, pa, wf, tv; };
#define MISS(i, v)
#define MISS_INIT
#define MISS_OUT
#define HT(i)
#define PROF_INIT
#define PROF(i)
#define PROFV(i, v)
#define PROF_OUT

__device__ __forceinline__ uint32_t clk32() { uint32_t t; asm volatile("mov.u32 %0, %%clock;" : "=r"(t) :: "memory"); return t; }
__device__ __forceinline__ uint32_t gtime() { uint32_t t; asm volatile("mov.u32 %0, %%globaltimer_lo;" : "=r"(t) :: "memory"); return t; }
__device__ __forceinline__ void spin_until(uint32_t t0, uint32_t d) { while (clk32() - t0 < d) {} }
template <int N> __device__ __forceinline__ uint32_t delay(uint32_t zero) {
    float x = __uint_as_float(clk32());
#pragma unroll
    for (int i = 0; i < N; i++) asm volatile("ex2.approx.ftz.f32 %0, %0;" : "+f"(x));
    return __float_as_uint(x) & zero;
}
__device__ __forceinline__ uint32_t opaque(uint32_t v) { return __shfl_sync(~0u, v, threadIdx.x & 31); }
__device__ __forceinline__ uint32_t xor_or(uint32_t a, uint32_t b, uint32_t t) {
    uint32_t r; asm volatile("lop3.b32 %0, %1, %2, %3, 0x7E;" : "=r"(r) : "r"(a), "r"(b), "r"(t)); return r;
}
__device__ __forceinline__ uint32_t or3(uint32_t a, uint32_t b, uint32_t c) {
    uint32_t r; asm volatile("lop3.b32 %0, %1, %2, %3, 0xFE;" : "=r"(r) : "r"(a), "r"(b), "r"(c)); return r;
}
__device__ __forceinline__ uint32_t settag(uint32_t v, uint32_t tag) {
    uint32_t r; asm("lop3.b32 %0, %1, 1, %2, 0xB8;" : "=r"(r) : "r"(v), "r"(tag)); return r;
}
__device__ __forceinline__ void ldg4_if(uint4& v, const void* p, bool c) {
    asm volatile("{.reg .pred p; setp.ne.u32 p, %5, 0; @p ld.relaxed.gpu.global.v4.u32 {%0,%1,%2,%3}, [%4];}"
                 : "+r"(v.x), "+r"(v.y), "+r"(v.z), "+r"(v.w) : "l"(p), "r"((uint32_t)c) : "memory");
}
__device__ __forceinline__ uint4 ldg_rlx2x2(const void* p) {
    unsigned long long a, b;
    asm volatile("ld.relaxed.gpu.global.v2.b64 {%0,%1}, [%2];" : "=l"(a), "=l"(b) : "l"(p) : "memory");
    return make_uint4((uint32_t)a, (uint32_t)(a >> 32), (uint32_t)b, (uint32_t)(b >> 32));
}
__device__ __forceinline__ void stg_rlx2x2(void* p, uint32_t x, uint32_t y, uint32_t z, uint32_t w) {
    asm volatile("{.reg .b64 a, b; mov.b64 a, {%1,%2}; mov.b64 b, {%3,%4}; st.relaxed.gpu.global.v2.b64 [%0], {a, b};}" ::"l"(p), "r"(x), "r"(y), "r"(z), "r"(w) : "memory");
}
__device__ __forceinline__ void ldg1_if(uint32_t& v, const void* p, bool c) {
    asm volatile("{.reg .pred p; setp.ne.u32 p, %2, 0; @p ld.relaxed.gpu.global.u32 %0, [%1];}" : "+r"(v) : "l"(p), "r"((uint32_t)c) : "memory");
}
__device__ __forceinline__ void sts2(uint32_t a, float x, float y) { asm volatile("st.shared.v2.f32 [%0], {%1,%2};" ::"r"(a), "f"(x), "f"(y) : "memory"); }
__device__ __forceinline__ void sts4f(uint32_t a, float x, float y, float z, float w) {
    asm volatile("st.shared.v4.f32 [%0], {%1,%2,%3,%4};" ::"r"(a), "f"(x), "f"(y), "f"(z), "f"(w) : "memory");
}
__device__ __forceinline__ void sts1(uint32_t a, uint32_t x) { asm volatile("st.shared.u32 [%0], %1;" ::"r"(a), "r"(x) : "memory"); }
__device__ __forceinline__ uint32_t lds1(uint32_t a) { uint32_t v; asm volatile("ld.shared.u32 %0, [%1];" : "=r"(v) : "r"(a) : "memory"); return v; }
__device__ __forceinline__ float4 lds4f(uint32_t a) {
    float4 v; asm volatile("ld.shared.v4.f32 {%0,%1,%2,%3}, [%4];" : "=f"(v.x), "=f"(v.y), "=f"(v.z), "=f"(v.w) : "r"(a) : "memory"); return v;
}
__device__ __forceinline__ float2 lds2f(uint32_t a) {
    float2 v; asm volatile("ld.shared.v2.f32 {%0,%1}, [%2];" : "=f"(v.x), "=f"(v.y) : "r"(a) : "memory"); return v;
}
__device__ __forceinline__ bool any_bit0(uint32_t x) {
    uint32_t r;
    asm volatile("{.reg .pred p, q; .reg .b32 t; and.b32 t, %1, 1; setp.ne.u32 p, t, 0; vote.sync.any.pred q, p, 0xffffffff; selp.u32 %0, 1, 0, q;}" : "=r"(r) : "r"(x));
    return r;
}
__device__ __forceinline__ float rcp_fast(float x) { float r; asm("rcp.approx.ftz.f32 %0, %1;" : "=f"(r) : "f"(x)); return r; }
__device__ __forceinline__ void stsm4(uint32_t a, uint32_t r0, uint32_t r1, uint32_t r2, uint32_t r3) {
    asm volatile("stmatrix.sync.aligned.m8n8.x4.shared.b16 [%0], {%1,%2,%3,%4};" ::"r"(a), "r"(r0), "r"(r1), "r"(r2), "r"(r3) : "memory");
}
__device__ __forceinline__ void stsm4t(uint32_t a, uint32_t r0, uint32_t r1, uint32_t r2, uint32_t r3) {
    asm volatile("stmatrix.sync.aligned.m8n8.x4.trans.shared.b16 [%0], {%1,%2,%3,%4};" ::"r"(a), "r"(r0), "r"(r1), "r"(r2), "r"(r3) : "memory");
}
__device__ __forceinline__ uint32_t and3(uint32_t a, uint32_t b, uint32_t c) {
    uint32_t r; asm("lop3.b32 %0, %1, %2, %3, 0x80;" : "=r"(r) : "r"(a), "r"(b), "r"(c)); return r;
}
__device__ __forceinline__ void red_mem(void* p, uint32_t x, uint32_t y, uint32_t z, uint32_t w, void* q, uint32_t e, bool c) {
    asm volatile("{.reg .pred p; setp.ne.u32 p, %7, 0; red.relaxed.gpu.global.add.noftz.v4.bf16x2 [%0], {%1,%2,%3,%4}; @p red.relaxed.gpu.global.add.noftz.bf16x2 [%5], %6;}"
                 ::"l"(p), "r"(x), "r"(y), "r"(z), "r"(w), "l"(q), "r"(e), "r"((uint32_t)c) : "memory");
}
__device__ __forceinline__ void stg4_if(bool c, void* p, uint32_t x) {
    asm volatile("{.reg .pred p; setp.ne.u32 p, %2, 0; @p st.relaxed.gpu.global.v4.u32 [%0], {%1,%1,%1,%1};}" ::"l"(p), "r"(x), "r"((uint32_t)c) : "memory");
}
__device__ __forceinline__ uint32_t max3u(uint32_t a, uint32_t b, uint32_t c) { return __vimax3_u32(a, b, c); }
__device__ __forceinline__ void fence_gpu() { asm volatile("fence.acq_rel.gpu;" ::: "memory"); }

__device__ __forceinline__ void h_load(uint32_t sb, const uint8_t* hsrc, int pass, uint32_t rank, uint32_t rot) {
    const uint8_t* src = hsrc + (size_t)pass * 65536;
    const uint32_t bar = sb + SM_BAR + 8 * (B_HB + (pass & 1)), dst = sb + SM_HB + (pass & 1) * 65536 + rank * 4 * HBK;
    e_expect(bar, 32768);
#pragma unroll 1
    for (int i = 0; i < H_PIECES; i++) {
        const uint32_t o = ((i + rot) & (H_PIECES - 1)) * (16384 / H_PIECES);
        asm volatile("{.reg .pred p; elect.sync _|p, 0xffffffff;\n"
                     " @p cp.async.bulk.shared::cluster.global.mbarrier::complete_tx::bytes.multicast::cluster [%0], [%1], %4, [%2], %3;}"
                     ::"r"(dst + o + (o >> 12) * 1024), "l"(src + o), "r"(bar), "h"((uint16_t)3), "n"(16384 / H_PIECES) : "memory");
    }
}
__device__ __forceinline__ void h_piece(uint32_t sb, const uint8_t* hsrc, int pass, uint32_t rank, uint32_t i, bool first) {
    const uint32_t bar = sb + SM_BAR + 8 * (B_HB + (pass & 1));
    asm volatile("{.reg .pred p, q; elect.sync _|p, 0xffffffff; setp.le.and.s32 p, %5, 64, p; setp.ne.and.u32 q, %4, 0, p;\n"
                 " @q mbarrier.arrive.expect_tx.shared.b64 _, [%2], 32768;\n"
                 " @p cp.async.bulk.shared::cluster.global.mbarrier::complete_tx::bytes.multicast::cluster [%0], [%1], 4096, [%2], %3;}"
                 ::"r"(sb + SM_HB + (pass & 1) * 65536 + (rank * 4 + i) * HBK), "l"(hsrc + (uint32_t)(pass * 65536 + i * 4096)), "r"(bar), "h"((uint16_t)3), "r"((uint32_t)first), "r"(pass) : "memory");
}
__device__ __forceinline__ uint4 ldg_b128(const void* p) {
    uint4 v;
    asm volatile("{.reg .b128 t; .reg .b64 a, b; ld.relaxed.gpu.global.b128 t, [%4]; mov.b128 {a, b}, t; mov.b64 {%0,%1}, a; mov.b64 {%2,%3}, b;}"
                 : "=r"(v.x), "=r"(v.y), "=r"(v.z), "=r"(v.w) : "l"(p) : "memory");
    return v;
}
__device__ __forceinline__ void ldg_b128_into(uint4& v, const void* p) {
    asm volatile("{.reg .b128 t; .reg .b64 a, b; ld.relaxed.gpu.global.b128 t, [%4]; mov.b128 {a, b}, t; mov.b64 {%0,%1}, a; mov.b64 {%2,%3}, b;}"
                 : "+r"(v.x), "+r"(v.y), "+r"(v.z), "+r"(v.w) : "l"(p) : "memory");
}
__device__ __forceinline__ void stg_b128_if(bool c, void* p, uint32_t x, uint32_t y, uint32_t z, uint32_t w) {
    asm volatile("{.reg .pred p; setp.ne.u32 p, %5, 0; @p st.relaxed.gpu.global.v4.u32 [%0], {%1,%2,%3,%4};}"
                 ::"l"(p), "r"(x), "r"(y), "r"(z), "r"(w), "r"((uint32_t)c) : "memory");
}
__device__ __forceinline__ float pretag(float x, uint32_t add, uint32_t keep) { return __uint_as_float((__float_as_uint(x) + add) & keep); }

template <class F, class G>
__device__ __forceinline__ void softmax_rows(uint32_t src, uint32_t dst, uint32_t g16, int row0, F ready, G mid) {
    const uint32_t u = (g16 >> 7) & 3, e = ((g16 >> 9) << 3) | ((g16 >> 4) & 7);
    uint32_t se = src + e * 8, su = se + u * 1088, d0 = dst + e * 16 + u * 4, d1 = dst + 512 + e * 4;
    int vis = row0 + (e >> 2) - 2 * (e & 3) - 8 * u;
    asm volatile("" : "+r"(se), "+r"(su), "+r"(d0), "+r"(d1), "+r"(vis));
    ready();
    const float2 p0 = lds2f(su), p1 = lds2f(su + 256), p2 = lds2f(su + 512), p3 = lds2f(su + 768);
    const float2 m0 = lds2f(se + 4352), m1 = lds2f(se + 4352 + 256), m2 = lds2f(se + 4352 + 512), m3 = lds2f(se + 4352 + 768);
    float a0 = (p0.x + p1.x) + (p2.x + p3.x), a1 = (p0.y + p1.y) + (p2.y + p3.y);
    const float a2 = (m0.x + m1.x) + (m2.x + m3.x), a3 = (m0.y + m1.y) + (m2.y + m3.y);
    if (vis < 0) a0 = -1e9f / 0.08838834764831845f;
    if (vis < 1) a1 = -1e9f / 0.08838834764831845f;
    int k = __float_as_int(fmaxf(fmaxf(a0, a1), fmaxf(a2, a3)));
    k ^= (k >> 31) & 0x7fffffff;
    const bool hi = g16 & 64;
    const int k0 = __reduce_max_sync(~0u, hi ? INT_MIN : k), k1 = __reduce_max_sync(~0u, hi ? k : INT_MIN);
    mid();
    k = hi ? k1 : k0;
    const float m = __int_as_float(k ^ ((k >> 31) & 0x7fffffff));
    const float sl2 = 0.08838834764831845f * 1.4426950408889634f, mb = -m * sl2;
    sts1(d0, pack2(ex2(fmaf(a0, sl2, mb)), ex2(fmaf(a1, sl2, mb))));
    sts1(d1, pack2(ex2(fmaf(a2, sl2, mb)), ex2(fmaf(a3, sl2, mb))));
}

__device__ __forceinline__ uint32_t pack_h2(float lo, float hi) {
    uint32_t r; asm("cvt.rn.satfinite.f16x2.f32 %0, %1, %2;" : "=r"(r) : "f"(hi), "f"(lo)); return r;
}
__device__ __forceinline__ float2 unpack_h2(uint32_t u) {
    float2 r; asm("{.reg .b16 l, h; mov.b32 {l, h}, %2; cvt.f32.f16 %0, l; cvt.f32.f16 %1, h;}" : "=f"(r.x), "=f"(r.y) : "r"(u)); return r;
}
__device__ __forceinline__ uint32_t add_h2(uint32_t a, uint32_t b) { uint32_t r; asm("add.rn.f16x2 %0, %1, %2;" : "=r"(r) : "r"(a), "r"(b)); return r; }
__device__ __forceinline__ uint32_t max_h2(uint32_t a, uint32_t b) { uint32_t r; asm("max.f16x2 %0, %1, %2;" : "=r"(r) : "r"(a), "r"(b)); return r; }
__device__ __forceinline__ void stg2_if(bool c, void* p, uint32_t x, uint32_t y) {
    asm volatile("{.reg .pred p; .reg .b64 v; setp.ne.u32 p, %3, 0; mov.b64 v, {%1, %2}; @p st.relaxed.gpu.global.b64 [%0], v;}" ::"l"(p), "r"(x), "r"(y), "r"((uint32_t)c) : "memory");
}
__device__ __forceinline__ void stg1_if(bool c, void* p, uint32_t x) {
    asm volatile("{.reg .pred p; setp.ne.u32 p, %2, 0; @p st.relaxed.gpu.global.u32 [%0], %1;}" ::"l"(p), "r"(x), "r"((uint32_t)c) : "memory");
}
struct U2 { uint32_t x, y; };
__device__ __forceinline__ U2 ldg_u2(const void* p) {
    U2 v; asm volatile("{.reg .b64 t; ld.relaxed.gpu.global.b64 t, [%2]; mov.b64 {%0, %1}, t;}" : "=r"(v.x), "=r"(v.y) : "l"(p) : "memory"); return v;
}
constexpr int POLL_LIMIT = 1 << 16;
constexpr float SM_L2E = 0.08838834764831845f * 1.4426950408889634f;
template <int V> struct IC { static constexpr int value = V; };
typedef unsigned long long u64;
__device__ __forceinline__ uint32_t lo32(u64 v) { return (uint32_t)v; }
__device__ __forceinline__ uint32_t hi32(u64 v) { return (uint32_t)(v >> 32); }
__device__ __forceinline__ u64 ldg_u64(const void* p) { u64 v; asm volatile("ld.relaxed.gpu.global.b64 %0, [%1];" : "=l"(v) : "l"(p) : "memory"); return v; }
__device__ __forceinline__ void ldg_u64_if(u64& v, const void* p, bool c) {
    asm volatile("{.reg .pred p; setp.ne.u32 p, %2, 0; @p ld.relaxed.gpu.global.b64 %0, [%1];}" : "+l"(v) : "l"(p), "r"((uint32_t)c) : "memory");
}
__device__ __forceinline__ void rec_main(uint32_t sb, const CUtensorMap* tWo, uint8_t* arena, int role, int hinfo, int wg, uint32_t zero, const Delays& dly) {
    const int hA = hinfo & 255;
    const int tid = threadIdx.x, t = tid & 127, lane = tid & 31, wi = t >> 5;
    const uint32_t bars = sb + SM_BAR;
    const int head = role >> 2, qd = role & 3, j = blockIdx.x & 1, kh = role & 1;
    const uint32_t mypar = head >= hA;
    const bool warp0 = __all_sync(~0u, wi == 0), warp1 = __all_sync(~0u, wi == 1);
    const uint8_t* hsrc = (const uint8_t*)g_himg + kh * 32768 + j * 16384;
    auto tokbase = [&](int ty) { return ((ty + 1) << 21) + blk(lb_tok(head), mypar ^ ((hinfo >> (8 + ty)) & 1)); };
    const uint32_t tbw = tokbase(wg), tbq = tokbase(0) + (qd >> 1) * 2048 + (qd & 1) * 8;
    uint32_t w[32 - NL][4];
    const uint32_t frow = ((lane >> 4) * 8 + (lane & 7)) * 128, fx = ((lane >> 3) & 1) ^ (lane & 7);
    const uint32_t wl0 = sb + wg * 65536 + frow + ((fx ^ (2 * wi)) << 4);
    {
#pragma unroll 1
        for (int i = 0; i < 4; i++) mbar_wait_w(bars + 8 * (B_W + (wg == 2 ? 8 + i : 2 * i + wg)), 0);
#pragma unroll
        for (int p = NL; p < 32; p++) ldsm4t(w[p - NL], wl0 + p * 2048);
        fence_async_smem();
        if (wg < 2) bar_sync(NB_WG, 256);
        if (wg > 0) wait_count_w(&g_tick[32 + (lane & 3) * 8], 1);
        if (wg == 1 && warp0) {
            if (lane == 0) mbar_arrive_cluster(bars + 8 * B_HE, j ^ 1);
            asm volatile("fence.proxy.async.global;" ::: "memory");
            mbar_wait_w(bars + 8 * B_HE, 0);
#pragma unroll 1
            for (int i = 0; i < 2; i++) h_load(sb, hsrc, i, j, head);
        }
        TL(3 + wg)
    }
    uint32_t g16 = opaque(t * 16);
    auto G16 = [&]() { asm volatile("" : "+r"(g16)); return g16; };
    const uint32_t wu = __reduce_max_sync(~0u, wi), sbl = sb - wu * 512;
    const uint32_t xso = blk(lb_x2(head), mypar), cu = kh * 2048 + (2 * j + (wu >> 1)) * 512;
    const uint32_t u_xo = xso + wg * 16384 + (wu & 1) * 2048 + (cu >> 1) - wu * 256, u_to = tbw + (wu & 1) * 16384 + cu - wu * 512;
    const uint32_t mrow = wg < 2 ? mem_row(wu >> 1, wg * 2 + (wu & 1), qd) : mem_row(kh, wu, 0);
    const uint32_t u_m = mrow - wu * 512, u_e = mrow + 512 - wu * (CNT32 ? 64 : 128);
#define TAB(i) lds1(sb + SM_TAB + (i) * 512 + (G16() >> 2))
    {
        const uint32_t r8 = lane & 7;
        bar_sync(NB_X2, 384);
        if (wg == 0 && lane == 0) {
            mbar_expect(bars + 8 * B_WO, 16384);
            tma2d(sb + SM_WO + wi * 16384, tWo, (wi >> 1) * 512 + qd * 128 + (wi & 1) * 64, head * DH, bars + 8 * B_WO);
            tma2d(sb + SM_WO + wi * 16384 + 8192, tWo, (wi >> 1) * 512 + qd * 128 + (wi & 1) * 64, head * DH + 64, bars + 8 * B_WO);
        }
        __syncwarp();
        const uint32_t tb = sb + SM_TAB + wg * 1536 + t * 4, ma = sb + SM_HB + 4096 + r8 * 128;
        if (wg < 2) {
            sts1(tb, sb + SM_WO + wi * 16384 + frow + ((fx ^ (2 * wg)) << 4));
            sts1(tb + 512, wl0);
            sts1(tb + 1024, ma + (((lane >> 3) ^ r8) << 4));
        } else {
            sts1(tb, ma + (wi & 1) * HBK + ((((wi & 2) + (lane >> 4) * 4 + ((lane >> 3) & 1)) ^ r8) << 4));
            sts1(tb + 512, ((((wi & 2) + 5) ^ r8) << 4) + ((CNT32 ? (lane & 3) == 3 : lane & 1) ? ma + ((wi & 1) + (lane >> 3) * 2) * HBK : sb + SM_HB - 128));
            sts1(tb + 1024, mem_row(role >> 6, (role >> 4) & 3, (role >> 2) & 3) + (lane < 8 ? qd * 128 + lane * 16 : 512 + qd * 32 + (lane & 1) * 16));
        }
    }
    PROF_INIT
    MISS_INIT
#define HB(ks) dadd(mkdesc(SB0 + SM_HB + ((ks) >> 2) * HBK + ((ks) & 3) * 32, 16, 1024, 1), hbo)
#define STEP_CONSTS                                                                                  \
    const uint32_t tag = (s & 1) ^ 1, ttag = ((s >> 1) & 1) ^ 1, tso = (s & 1) * 32768;              \
    G16();                            \
    const int p = s + 2, b = p & 1;                                                                  \
    uint32_t hbo = b * 4096, fz[5] = {0, 0, 0, 0, 0};                                                \
    const uint32_t ftag = (((p - 1) >> 1) & 1) ^ 1, ptag = ((p >> 1) & 1) ^ 1;                       \
    const uint32_t pso = tbw + (1 << 20) + (b ^ 1) * 32768 + j * 16384 + kh * 2048;
#define SCHED_FENCE(i) fz[i] = clk32();
#define FZ ((fz[0] | fz[1] | fz[2] | fz[3] | fz[4]) & zero)
#define BLOCK_FENCE asm volatile("pmevent 0;" ::: "memory");
    constexpr int GAP = 32 / NL;
#define l16 (sbl + g16)
#define g8 (g16 >> 1)
    uint4 u, v;
    uint8_t *pdst, *fdst;
    auto tok_pack = [&](int ty, const float* acc, uint32_t ftag, uint32_t ptag, bool later = false) {
        const bool tg = ty == 2 || !(g16 & 64);
        const uint32_t add = tg ? (ftag ^ 1) << 16 : 0u, keep = tg ? 0xfffe0000u : ~0u;
        const uint32_t add1 = ty == 2 ? 0u : add, keep1 = ty == 2 ? ~0u : keep;
        const uint32_t add2 = ty == 0 ? add : 0u, keep2 = ty == 0 ? keep : ~0u;
        v = {pack2(pretag(acc[0], add, keep), pretag(acc[1], add1, keep1)), pack2(acc[2], acc[3]),
             pack2(pretag(acc[4], add2, keep2), pretag(acc[5], add2, keep2)), pack2(acc[6], acc[7])};
        if (ty < 2) { v.x = movm(v.x); v.z = movm(v.z); v.y = movm(v.y); v.w = movm(v.w); }
        u = {pack2(pretag(acc[8], (ptag ^ 1) << 16, 0xfffe0000u), acc[9]) | ptag, pack2(acc[10], acc[11]), pack2(acc[12], acc[13]), pack2(acc[14], acc[15])};
        if (later) return;
        v.x = settag(v.x, ftag);
        if (ty == 0) v.z = settag(v.z, ftag);
    };

#pragma unroll 1
    for (int s = -2; s < 0; s++) {
        STEP_CONSTS
        (void)tag; (void)ttag; (void)tso; (void)fz;
        float acc[16];
        mbar_wait_w(bars + 8 * (B_HB + b), 0);
        wg_fence();
#pragma unroll
        for (int i = 0; i < 32; i++) {
            if (i < NL) wgmma_ss32(acc, dadd(mkdesc(SB0 + i * 2048, 8192, 1024, 1), wg * 4096), HB(i), i != 0);
            else wgmma_rs32(acc, w[i < NL ? 0 : i - NL], HB(i), 1);
        }
        wg_commit();
        uint4 pa;
        int it = 0;
#pragma unroll 1
        do pa = ldg_b128(arena + (pso + g16)); while ((p > 0) & any_bit0(pa.x ^ ftag) & (++it < POLL_LIMIT));
        pdst = arena + ((pso ^ (32768 + 2048)) + G16());
        fdst = arena + ((b ^ 1) * 32768 + u_to + g16);
        wg_wait<0>();
#pragma unroll
        for (int k = 0; k < 4; k++) { acc[2 * k] += bflo((&pa.x)[k]); acc[2 * k + 1] += bfhi((&pa.x)[k]); }
        tok_pack(wg, acc, ftag, ptag);
        stg_b128_if(true, pdst, u.x, u.y, u.z, u.w);
        stg_b128_if(p > 0, fdst, v.x, v.y, v.z, v.w);
        if (p == 0) {
            TL(2)
            bar_sync(NB_MEM, 384);
            if (wg == 1 && warp0) {
                if (g16 == 0) mbar_arrive_cluster(bars + 8 * B_HE, j ^ 1);
                mbar_wait_w(bars + 8 * B_HE, 1);
                h_load(sb, hsrc, 2, j, head);
            }
        }
    }

    auto qk_loop = [&](auto wgc) {
        constexpr int WG = decltype(wgc)::value;
        uint32_t w0[NL][4], lm0;
        auto w0_load = [&]() {
            const uint32_t wl = TAB(WG * 3 + 1);
            lm0 = TAB(WG * 3 + 2);
#pragma unroll
            for (int k = 0; k < NL; k++) ldsm4t(w0[k], wl + k * 2048);
        };
        const uint32_t wlo = WG * 65536 - SM_WO - wu * 16384, wlx = __reduce_max_sync(~0u, (wi ^ WG) << 5);
        uint32_t tq0, lm, lm1;
        auto proj_pre = [&](int s) {
            uint32_t wz0 = zero;
#pragma unroll
            for (int k = 0; k < NL; k += 2) wz0 = and3(wz0, w0[k][0], w0[k + 1 < NL ? k + 1 : k][0]);
            lm = lm0 + (s & 1) * 65536 + wz0; lm1 = lm ^ 64;
            asm volatile("" : "+r"(lm), "+r"(lm1));
        };
        auto proj = [&](int s, auto mid) {
            bar_sync(NB_MEM, 384);
            float c[4][4];
            uint32_t bf[16][4];
#pragma unroll
            for (int it = 0; it < 3; it++) ldsm4(bf[it], (it & 1 ? lm1 : lm) + (it >> 1) * HBK);
            mid(-1);
#pragma unroll
            for (int it = 0; it < 16; it++) {
                const uint32_t* bfr = bf[it];
                if (it + 3 < 16) ldsm4(bf[it + 3 < 16 ? it + 3 : 0], (it & 1 ? lm : lm1) + ((it + 3) >> 1) * HBK);
                const uint32_t* wa = 2 * it < NL ? w0[2 * it < NL ? 2 * it : 0] : w[2 * it < NL ? 0 : 2 * it - NL];
                const uint32_t* wb = 2 * it + 1 < NL ? w0[2 * it + 1 < NL ? 2 * it + 1 : 0] : w[2 * it + 1 < NL ? 0 : 2 * it + 1 - NL];
                float *ca = c[(2 * it) & 3], *cb = c[(2 * it + 1) & 3];
                if (it < 2) { mma16816z(ca, wa, bfr[0], bfr[1]); mma16816z(cb, wb, bfr[2], bfr[3]); }
                else { mma16816(ca, wa[0], wa[1], wa[2], wa[3], bfr[0], bfr[1]); mma16816(cb, wb[0], wb[1], wb[2], wb[3], bfr[2], bfr[3]); }
                mid(it);
            }
            const uint32_t xo = u_xo + (G16() >> 1);
            float r[4];
#pragma unroll
            for (int e = 0; e < 4; e++) {
                constexpr float SH = SM_L2E / 64;
                r[e] = WG ? (c[0][e] + c[1][e]) + (c[2][e] + c[3][e]) : fmaf(c[2][e] + c[3][e], SH, (c[0][e] + c[1][e]) * SH);
            }
            const uint32_t r0 = pack2(r[0], r[1]), r1 = pack2(r[2], r[3]);
            const uint32_t m0 = movm(r0), m1 = movm(r1);
            tq0 = clk32();
            bar_arrive(NB_QK, 384);
            stg_rlx2(arena + xo, settag(m0, (s & 1) ^ 1), m1);
        };
        w0_load();
        proj_pre(0);
        if (WG == 1 || !ROT) bar_sync(NB_P, ROT ? 256 : 384);
        proj(0, [](int) {});
#pragma unroll 1
        for (int s = 0;; s++) {
            STEP_CONSTS
            uint4 pa;
            float acc[16];
            auto acc_init = [&]() {
#pragma unroll
                for (int k = 0; k < 4; k++) { acc[2 * k] = bflo((&pa.x)[k]); acc[2 * k + 1] = bfhi((&pa.x)[k]); acc[8 + 2 * k] = __uint_as_float((&pa.x)[k] & zero); acc[9 + 2 * k] = __uint_as_float(~(&pa.x)[k] & zero); }
            };
            uint32_t wf[NPF][4], a3;
#define WF(f) ((a3 ^ (((f) & 1) * 64)) + ((f) >> 1) * 2048)
            if (WG == 1) {
                float sc[5][4];
                uint32_t sx0 = sb + SM_SX - wu * (2560 - 16) + G16() * 5;
                asm volatile("" : "+r"(sx0));
                int it = 0;
                bool bad;
#pragma unroll 1
                do {
                    uint4 kf[2][2];
                    U2 qf[2], x[8];
                    const uint32_t gz = g16 | (it & zero);
                    const uint8_t *ts = arena + (tso + tbw + gz), *tq = arena + (tso + tbq + gz), *xp = arena + (xso + (gz >> 1));
#pragma unroll
                    for (int a = 0; a < 4; a++) kf[a >> 1][a & 1] = ldg_b128(ts + (a >> 1) * 16384 + (a & 1) * 2048);
                    if (QF_LATE) spin_until(tq0, dly.x2 - QF_LATE);
#pragma unroll
                    for (int a = 0; a < 2; a++) qf[a] = ldg_u2(tq + a * 16384);
                    spin_until(tq0, dly.x2);
#pragma unroll
                    for (int i = 0; i < 8; i++) x[i] = ldg_u2(xp + (i >> 2) * 16384 + (i & 3) * 1024);
                    PROF(8)
                    const uint32_t q0[4] = {hadd2(x[0].x, x[1].x), qf[0].x, hadd2(x[0].y, x[1].y), qf[0].y};
                    const uint32_t q1[4] = {hadd2(x[2].x, x[3].x), qf[1].x, hadd2(x[2].y, x[3].y), qf[1].y};
                    PROFV(7, clk32() + (q0[0] & zero))
                    const uint32_t bt = ((qf[0].x ^ ttag) | (qf[1].x ^ ttag)) | ((kf[0][0].x ^ ttag) | (kf[0][1].x ^ ttag)) | ((kf[1][0].x ^ ttag) | (kf[1][1].x ^ ttag));
                    uint32_t bx = 0;
#pragma unroll
                    for (int i = 0; i < 8; i += 2) bx |= (x[i].x ^ tag) | (x[i + 1].x ^ tag);
                    mma16816z(sc[0], q0, kf[0][0].x, kf[0][0].y);
                    mma16816z(sc[1], q0, kf[0][0].z, kf[0][0].w);
                    mma16816z(sc[2], q0, kf[0][1].x, kf[0][1].y);
                    mma16816z(sc[3], q0, kf[0][1].z, kf[0][1].w);
                    mma16816z(sc[4], q0, hadd2(x[4].x, x[5].x), hadd2(x[4].y, x[5].y));
                    bad = any_bit0((XP & 8 ? bt & zero : bt) | bx) & (++it < POLL_LIMIT);
                    mma16816(sc[0], q1[0], q1[1], q1[2], q1[3], kf[1][0].x, kf[1][0].y);
                    mma16816(sc[1], q1[0], q1[1], q1[2], q1[3], kf[1][0].z, kf[1][0].w);
                    mma16816(sc[2], q1[0], q1[1], q1[2], q1[3], kf[1][1].x, kf[1][1].y);
                    mma16816(sc[3], q1[0], q1[1], q1[2], q1[3], kf[1][1].z, kf[1][1].w);
                    mma16816(sc[4], q1[0], q1[1], q1[2], q1[3], hadd2(x[6].x, x[7].x), hadd2(x[6].y, x[7].y));
                } while (bad);
                PROFV(13, it - 1) MISS(1, it - 1)
                sts4(sx0, pack_h2(sc[0][0], sc[0][1]), pack_h2(sc[1][0], sc[1][1]), pack_h2(sc[2][0], sc[2][1]), pack_h2(sc[3][0], sc[3][1]));
                sts1(sx0 + 64 - wu * 12, pack_h2(sc[4][0], sc[4][1]));
                bar_arrive(NB_X1, 384);
#pragma unroll
                for (int n = 0; n < 5; n++) sts2(sb + SM_SX + 2560 + g8 + n * 1088, sc[n][2], sc[n][3]);
                PROF(3)
                a3 = TAB(WG * 3);
                softmax_rows(sb + SM_SX + 2560, sb + SM_PX + 1024, g16 | (clk32() & zero), qd * 8, [&]() { BLOCK_FENCE bar_sync(NB_PX, 128); }, [&]() {
                    BLOCK_FENCE
#pragma unroll
                    for (int f = 0; f < NE1; f++) ldsm4t(wf[f], WF(f));
                    BLOCK_FENCE
                });
                PROF(4)
            } else {
                a3 = TAB(WG * 3);
                if (warp1 && (H_POS == 4 ? (s & 3) == 0 : (s & 3) < 2)) asm volatile("fence.proxy.async.global;" ::: "memory");
                spin_until(tq0, dly.pa);
                uint4 x, y;
                int it = 0;
#pragma unroll 1
                do { x = ldg_b128(arena + (pso + g16)); y = ldg_b128(arena + (pso + tokbase(1) - tokbase(0) + g16)); }
                while (!(XP & 8) & (p <= NSEG) & any_bit0(xor_or(x.x, y.x, ftag)) & (++it < POLL_LIMIT));
                sts4(sb + SM_PA + g16, x.x, x.y, x.z, x.w);
                sts4(sb + SM_PA + 2048 + g16, y.x, y.y, y.z, y.w);
                if (NE) spin_until(tq0, dly.wf);
#pragma unroll
                for (int f = 0; f < NE; f++) ldsm4t(wf[f], WF(f));
                bar_sync(NB_X1, 384);
                if (E_MUL && g16 < 32) asm volatile("red.relaxed.gpu.global.max.u32 [%0], %1; red.relaxed.gpu.global.add.u32 [%0+4], 1;"
                                                    ::"l"(arena + ((blk(LB_TIME, 0) ^ (g16 << 8)) + qd * 1024 + (tq0 & zero))), "r"(gtime()) : "memory");
                __syncwarp();
                const uint32_t tx = clk32();
                if (H_POS == 2 && !(XP & 1) && warp1 && s + 3 <= NSEG) h_load(sb, hsrc, s + 3, j, head);
                spin_until(tx, dly.w2);
            }
#pragma unroll
            for (int f = WG ? NE1 : NE; f < NPF; f++) ldsm4t(wf[f], WF(f));
            PROF(5)
            if (s + 1 == NSEG) { bar_arrive(NB_X2, 384); break; }
            const uint32_t oa = l16 + SM_OX, slot = mem_slot(s + 1);
            float c[4][4];
            uint32_t ob[4][4];
            uint32_t wz = zero;
#pragma unroll
            for (int f = 0; f < NPF; f += 2) wz = and3(wz, wf[f][0], wf[f + 1 < NPF ? f + 1 : f][0]);
            BLOCK_FENCE
            bar_sync(NB_X2 + (SETTLE ? wz : 0), 384);
            ldsm4t(ob[0], oa);
            ldsm4t(ob[1], oa + 512);
            SCHED_FENCE(0)
#pragma unroll
            for (int f = 0; f < 16; f++) {
                const uint32_t *a = wf[f % NPF], *o = ob[f >> 2] + (f & 2);
                if (f < 4) mma16816z(c[f], a, o[0], o[1]);
                else mma16816(c[f & 3], a[0], a[1], a[2], a[3], o[0], o[1]);
                if (f == 3) ldsm4t(ob[2], oa + 1024);
                if (f == 5) { ldsm4t(ob[3], oa + 1536); if (NPF < 16) ldsm4t(wf[0], WF(NPF)); }
                if (f == 7) {
#pragma unroll
                    for (int k = NPF + 1; k < 16; k++) ldsm4t(wf[k - NPF], WF(k));
                }
                if (f == 3 || f == 5 || f == 7) SCHED_FENCE(f / 2)
                if (f == 11) {
#pragma unroll
                    for (int k = NL - W0_E; k < NL; k++) ldsm4t(w0[k], (a3 ^ wlx) + wlo + k * 2048);
                    SCHED_FENCE(4)
                }
            }
            const float last = c[1][3] + c[3][3], one = __uint_as_float(CNT1 << 16);
            red_mem(arena + (u_m + slot + G16()), pack2(c[0][0] + c[2][0], c[0][1] + c[2][1]), pack2(c[0][2] + c[2][2], c[0][3] + c[2][3]),
                    pack2(c[1][0] + c[3][0], c[1][1] + c[3][1]), pack2(c[1][2] + c[3][2], CNT32 && !(g16 & 16) ? last : one),
                    arena + (u_e + slot + (CNT32 ? (g16 >> 3) & ~3u : g16 >> 2)), pack2(one, last), !CNT32 || (g16 & 16));
            hbo += FZ;
            PROF(6)
            constexpr int NS = WG && W0_E < 0 ? NL : NL - W0_RS, GS = (32 - NL + NS) / NS;
            if (W0_E >= 0) {
                BLOCK_FENCE
#pragma unroll
                for (int k = NL - W0_E - 1; k >= 0; k--) ldsm4t(w0[k], (a3 ^ wlx) + wlo + k * 2048);
                lm0 = TAB(WG * 3 + 2);
                if (WG == 1) pa = lds4(sb + SM_PA + 2048 + g16);
            }
            if (WG == 0) {
                bar_arrive(NB_WIN, 384);
                if (W0_E < 0) spin_until(clk32(), dly.tv);
                pa = lds4(sb + SM_PA + g16);
                if (W0_E < 0) w0_load();
                acc_init();
                asm volatile("" : F16(acc, 0));
                BLOCK_FENCE
            }
            if (WG == 1 && K_DLY) spin_until(clk32(), dly.wf);
            wg_fence();
            bar_sync(WG ? NB_WIN : NB_B, WG ? 384 : 256);
#pragma unroll
            for (int i = 0; i < 32; i++) {
                const int k = i / GS;
                if (i >= 32 - NL + NS) wgmma_rs32(acc, w0[i < 32 - NL + NS ? 0 : i - 32 + NL], HB(i - 32 + NL), 1);
                else if (i % GS == GS - 1 && k < NS) wgmma_ss32(acc, mkdesc(SB0 + WG * 65536 + k * 2048, 8192, 1024, 1), HB(k), 1);
                else wgmma_rs32(acc, w[i - (k < NS ? k : NS)], HB(NL + i - (k < NS ? k : NS)), WG == 0 || i);
                if (WG == 1 && i == G_AT) bar_arrive(NB_B, 256);
                if (WG == 1 && i == W1_AT) w0_load();
            }
            wg_commit();
            BLOCK_FENCE
            if (WG == 1 && warp0 && (s & 3) == (H_POS == 4 ? 3 : 0)) wait_count_w(&g_tick[32 + ((G16() >> 4) & 3) * 8], min((s + 1) / 4 + 2, 16));
            if (WG == 1 && W0_E < 0) { pa = lds4(sb + SM_PA + 2048 + g16); if (W1_AT < 0) w0_load(); }
            auto tok_store = [&](int m) {
                if (m & 1) stg_b128_if(XP & 8 ? s == 99 : true, arena + ((b ^ 1) * 32768 + u_to + G16()), v.x, v.y, v.z, v.w);
                if (m & 2) stg_b128_if(XP & 8 ? s == 99 : p < NSEG, arena + ((pso ^ (32768 + 2048)) + G16()), u.x, u.y, u.z, u.w);
            };
            if (WG == 0) proj_pre(s + 1);
            BLOCK_FENCE
            wg_wait<0>();
            if (WG == 0 && ROT) {
                asm volatile("" : F16(acc, 0));
                proj(s + 1, [&](int it) {
                    if (it < 0) {
                        SCHED_FENCE(0)
                        asm volatile("" : F16(acc, 0));
                        tok_pack(WG, acc, ftag, ptag, true);
                        tok_store(2);
                        SCHED_FENCE(1)
                    }
                    if (it == ROT) { SCHED_FENCE(2) v.x = settag(v.x, ftag); v.z = settag(v.z, ftag); tok_store(1); SCHED_FENCE(3) }
                });
                tq0 += (fz[0] | fz[1] | fz[2] | fz[3]) & zero;
            } else {
                if (WG == 1) {
#pragma unroll
                    for (int k = 0; k < 4; k++) { acc[2 * k] += bflo((&pa.x)[k]); acc[2 * k + 1] += bfhi((&pa.x)[k]); }
                }
                tok_pack(WG, acc, ftag, ptag);
                if (WG == 1) proj_pre(s + 1);
                asm volatile("" : "+r"(u.x), "+r"(u.y), "+r"(u.z), "+r"(u.w), "+r"(v.x), "+r"(v.y), "+r"(v.z), "+r"(v.w));
                BLOCK_FENCE
                bar_sync(NB_P, ROT ? 256 : 384);
                tok_store(3);
                proj(s + 1, [](int) {});
            }
        }
    };
    if (wg == 0) {
        qk_loop(IC<0>());
    } else if (wg == 1) {
        qk_loop(IC<1>());
    } else {
        const uint32_t ONES = 0x3f803f80u, u_o = qd * 65536 + head * 2048 + wu * 384;
        uint32_t tw = 0, dl = 0, dm = 0, dst0, dx0;
        dst0 = TAB(6); dx0 = TAB(7);
        uint32_t ov[4] = {0, 0, 0, 0};
        auto o_store = [&](int s) {
            uint8_t* od = (uint8_t*)g_O + (uint32_t)(s * (32 * NH * DH * 2) + u_o + (G16() >> 2));
#pragma unroll
            for (int a = 0; a < 4; a++) stg_rlx1(od + a * 128, ov[a]);
        };
        uint4 vf[2][2], pa;
        auto vf_fetch = [&](int s) {
            const uint8_t* ts = arena + ((s & 1) * 32768 + tbw + g16);
#pragma unroll
            for (int a = 0; a < 4; a++) vf[a >> 1][a & 1] = ldg_b128(ts + (a >> 1) * 16384 + (a & 1) * 2048);
        };
        auto tok_fetch = [&](int s) {
            if (TV_POS != 1) vf_fetch(s);
            pa = ldg_b128(arena + (tbw + (1 << 20) + (~s & 1) * 32768 + j * 16384 + kh * 2048 + g16));
        };
        if (PA_POS) tok_fetch(0);
        TL(9)
        mbar_wait_w(bars + 8 * B_WO, 0);
        if (H_POS == 4 && warp0) { wait_count_w(&g_tick[32 + ((g16 >> 4) & 3) * 8], 2); asm volatile("fence.proxy.async.global;" ::: "memory"); }
        TL(6)
#pragma unroll 1
        for (int s = 0; s < NSEG; s++) {
            STEP_CONSTS
#define VFBAD ((vf[0][0].x ^ ttag) | (vf[0][1].x ^ ttag) | (vf[1][0].x ^ ttag) | (vf[1][1].x ^ ttag))
#define TOKBAD ((TV_POS == 1 ? 0 : VFBAD) | (p <= NSEG ? pa.x ^ ftag : 0))
            {
                const uint32_t dst = dst0 + b * 65536, dx = dx0 + b * 65536;
                const uint8_t *ms = arena + (u_m + mem_slot(s) + g16), *me = arena + (u_e + mem_slot(s) + (CNT32 ? (g16 >> 3) & ~3u : g16 >> 2));
                const uint32_t em = CNT32 && !(g16 & 16) ? ~0u : 0u;
                asm volatile("" : "+l"(ms), "+l"(me));
                spin_until(tw, dl);
                PROF(11)
                int it = 0;
                bool bad;
#pragma unroll 1
                do {
                    uint4 m[4];
                    uint32_t x[4];
#pragma unroll
                    for (int i = 0; i < 4; i++) m[i] = ldg_rlx4(ms + i * 1024);
#pragma unroll
                    for (int i = 0; i < 4; i++) x[i] = ldg_rlx1(me + i * 1024);
#pragma unroll
                    for (int i = 0; i < 3; i++) {
                        stsm4t(dst + i * 2 * HBK, m[i].x, m[i].y, m[i].z, m[i].w);
                        if (i == P_GATE) asm volatile("{.reg .pred p; setp.eq.s32 p, %0, 0; @p bar.arrive %1, %2;}" ::"r"(it), "n"(NB_P), "n"(ROT ? 256 : 384) : "memory");
                    }
                    uint32_t c = and3(m[0].w, m[1].w, m[2].w);
                    SCHED_FENCE(1)
                    stsm4t(dst + 6 * HBK, m[3].x, m[3].y, m[3].z, m[3].w);
                    stsm4t(dx, x[0], x[1], x[2], x[3]);
                    asm volatile("" : "+r"(c));
                    c = and3(and3(((c & m[3].w) | em) >> 16, x[0], x[1]), x[2], x[3]);
                    bad = __any_sync(~0u, !(c & CNT_ALL)) & (++it < POLL_LIMIT);
                    if (H_POS == 4) asm volatile("{.reg .pred p; setp.eq.u32 p, %0, 0; @p bar.sync %1, 384;}" ::"r"((uint32_t)bad), "n"(NB_MEM) : "memory");
                    else if (!ALIGN) asm volatile("{.reg .pred p; setp.eq.u32 p, %0, 0; @p bar.arrive %1, 384;}" ::"r"((uint32_t)bad), "n"(NB_MEM) : "memory");
                } while (bad);
                if (ALIGN) { spin_until(tw, dm); bar_arrive(NB_MEM, 384); }
                PROFV(12, it - 1)
                MISS(0, it - 1) HT(5)
                PROF(8)
            }
            if (s == 1) { TL(7) TLC(0) }
            if (s == 63) TLC(1)
            if (s == 0) TL(13)
            const uint32_t tm = clk32();
            if (H_POS == 4 && g16 == 0) mbar_arrive_cluster(bars + 8 * B_HE, j ^ 1);
            if (O_POS == 1) o_store(max(s - 1, 0));
            if (Z_POS && warp1) stg4_if(g16 < 512 + 160, arena + (TAB(8) + mem_slot(s + 3)), 0);
            fence_async_smem();
            hbo += fz[1] & zero;
            int it = 0;
            if (!PA_POS) tok_fetch(s);
#pragma unroll 1
            while (!(XP & 8) & any_bit0(TOKBAD) & (++it < POLL_LIMIT)) tok_fetch(s + (it & zero));
            float acc[20];
#pragma unroll
            for (int k = 0; k < 4; k++) { acc[2 * k] = bflo((&pa.x)[k]); acc[2 * k + 1] = bfhi((&pa.x)[k]); acc[8 + 2 * k] = acc[9 + 2 * k] = acc[16 + k] = __uint_as_float(pa.x & zero); }
            if (XP & 1 ? s < 1 : p <= NSEG) mbar_wait_w(bars + 8 * (B_HB + b), (p >> 1) & 1);
            if (H_POS == 4 && warp0) {
                mbar_wait_w(bars + 8 * B_HE, s & 1);
                spin_until(tm, dly.wf);
                if (s + 3 <= NSEG) h_load(sb, hsrc, s + 3, j, head);
            }
            asm volatile("" : F16(acc, 0), F4(acc, 16));
            BLOCK_FENCE
            wg_fence();
            bar_sync(NB_QK, 384);
#pragma unroll
            for (int i = 0; i < 32; i++) {
                const int k = i / GAP;
                if (i % GAP == GAP - 1 && k < NL) wgmma_ss40(acc, mkdesc(SB0 + 131072 + k * 2048, 8192, 1024, 1), HB(k), 1);
                else wgmma_rs40(acc, w[i - (k < NL ? k : NL)], HB(NL + i - (k < NL ? k : NL)), 1);
            }
            wg_commit();
            uint8_t* vo = arena + (u_xo + (G16() >> 1));
            pdst = arena + ((pso ^ (32768 + 2048)) + G16());
            fdst = arena + ((b ^ 1) * 32768 + u_to + g16);
            BLOCK_FENCE
            wg_wait<0>();
            PROF(9)
            stg_rlx2(vo, settag(pack2(acc[16], acc[17]), tag), pack2(acc[18], acc[19]));
            const uint32_t tv = clk32();
            if (TV_POS == 1) vf_fetch(s);
            tok_pack(2, acc, ftag, ptag);
            stg_b128_if(XP & 8 ? s == 99 : p <= NSEG, fdst, v.x, v.y, v.z, v.w);
            stg_b128_if(XP & 8 ? s == 99 : p < NSEG, pdst, u.x, u.y, u.z, u.w);
            if (O_POS == 2) o_store(max(s - 1, 0));
            if (ST_BAR) bar_sync(NB_WG, 128);
            PROF(10)
            const uint8_t* xp = arena + (xso + 32768 + (G16() >> 1));
            const uint32_t sxa = sb + SM_SX - wu * 2560 + G16() * 5;
            uint32_t xv[4], gt = 0;
            auto pv = [&](uint32_t p0, uint32_t p1, uint32_t p2, uint32_t p3, uint32_t p4, auto getv, auto done) {
                float oc[2][4], lc[4] = {0.f, 0.f, 0.f, 0.f};
                mma16816(lc, ONES, ONES, ONES, ONES, p0, p1);
                mma16816z(oc[0], &vf[0][0].x, p0, p1);
                mma16816z(oc[1], &vf[1][0].x, p0, p1);
                mma16816(lc, ONES, ONES, ONES, ONES, p2, p3);
                mma16816(oc[0], vf[0][1].x, vf[0][1].y, vf[0][1].z, vf[0][1].w, p2, p3);
                mma16816(oc[1], vf[1][1].x, vf[1][1].y, vf[1][1].z, vf[1][1].w, p2, p3);
                mma1688(lc, ONES, ONES, p4);
                getv();
                mma1688(oc[0], xv[0], xv[1], p4);
                mma1688(oc[1], xv[2], xv[3], p4);
                done(__float_as_uint(oc[0][0]) | __float_as_uint(oc[1][0]) | __float_as_uint(lc[0]));
                const float r0 = rcp_fast(lc[0]), r1 = rcp_fast(lc[1]);
                ov[0] = pack2(oc[0][0] * r0, oc[0][1] * r1); ov[1] = pack2(oc[0][2] * r0, oc[0][3] * r1);
                ov[2] = pack2(oc[1][0] * r0, oc[1][1] * r1); ov[3] = pack2(oc[1][2] * r0, oc[1][3] * r1);
            };
            bool bad;
            it = 0;
#pragma unroll 1
            do {
                U2 xr[4];
                auto load_v = [&]() {
                    if (V_POS < 3) spin_until(tv, dly.v);
#pragma unroll
                    for (int i = 0; i < 4; i++) xr[i] = ldg_u2(xp + i * 1024);
                };
                if (TV_POS == 1 && it) {
                    const uint8_t* tz = arena + (tso + tbw + (g16 | (it & zero)));
#pragma unroll
                    for (int a = 0; a < 4; a++) ldg_b128_into(vf[a >> 1][a & 1], tz + (a >> 1) * 16384 + (a & 1) * 2048);
                }
                if (!V_POS) load_v();
                if (V_POS >= 3) spin_until(tv, dly.v);
                PROF(3)
                asm volatile("{.reg .pred p; setp.eq.s32 p, %0, 0; @p bar.sync %1, 384;}" ::"r"(it), "n"(NB_X1) : "memory");
                uint4 sx[5];
                if (V_POS == 3) load_v();
#pragma unroll
                for (int i = 0; i < 5; i++) sx[i] = lds4(sxa + i * 16);
                if (V_POS == 4) load_v();
                if (it == 0) { gt = gtime(); tw = clk32(); }
                if (V_POS == 2) load_v();
                uint32_t h[5];
#pragma unroll
                for (int n = 0; n < 4; n++) h[n] = add_h2(add_h2((&sx[0].x)[n], (&sx[1].x)[n]), add_h2((&sx[2].x)[n], (&sx[3].x)[n]));
                h[4] = add_h2(add_h2(sx[4].x, sx[4].y), add_h2(sx[4].z, sx[4].w));
                uint32_t hm = max_h2(max_h2(max_h2(h[0], h[1]), h[2]), max_h2(h[3], h[4]));
                hm = max_h2(hm, __byte_perm(hm, hm, 0x1032));
                const uint32_t m1 = __shfl_xor_sync(~0u, hm, 1), m2 = __shfl_xor_sync(~0u, hm, 2), m3 = __shfl_xor_sync(~0u, hm, 3);
                float2 a[5];
#pragma unroll
                for (int n = 0; n < 5; n++) a[n] = unpack_h2(h[n]);
                if (V_POS == 1) load_v(); else SCHED_FENCE(0)
                const float mb = -64.0f * unpack_h2(max_h2(max_h2(hm, m1), max_h2(m2, m3))).x;
                uint32_t pm[5];
#pragma unroll
                for (int n = 0; n < 5; n++) pm[n] = pack2(ex2(fmaf(a[n].x, 64.0f, mb)), ex2(fmaf(a[n].y, 64.0f, mb)));
                pv(pm[0], pm[1], pm[2], pm[3], pm[4], [&]() {
                    xv[0] = hadd2(xr[0].x, xr[1].x); xv[1] = hadd2(xr[0].y, xr[1].y);
                    xv[2] = hadd2(xr[2].x, xr[3].x); xv[3] = hadd2(xr[2].y, xr[3].y);
                }, [](uint32_t) {});
                bad = any_bit0((TV_POS == 1 && !(XP & 8) ? VFBAD : 0) | (xr[0].x ^ tag) | (xr[1].x ^ tag) | (xr[2].x ^ tag) | (xr[3].x ^ tag)) & (++it < POLL_LIMIT);
                stsm4(sb + SM_OX + g16, ov[0], ov[1], ov[2], ov[3]);
            } while (bad);
            PROFV(14, it - 1) MISS(2, it - 1)
            PROF(5)
            bar_sync(NB_X2, 384);
            U2 tv2 = {0, 0};
            const uint8_t* tp = arena + (blk(LB_TIME, mypar) + (((g16 | (tw & zero)) << 6) & 0xc00));
            {
                const uint4 pp = lds4(l16 + SM_PX + 1024);
                const uint32_t p4 = lds1(sb + SM_PX + 512 + 1024 - wu * 128 + (G16() >> 2));
                if (E_MUL) tv2 = ldg_u2(tp);
                if (H_POS == 3 && !(XP & 1) && warp0 && s + 3 <= NSEG) h_load(sb, hsrc, s + 3, j, head);
                if (H_POS == 0 && !(XP & 1)) h_piece(sb, hsrc, s + 3, j, (wu + head) & 3, wu == 0);
                pv(pp.x, pp.y, pp.z, pp.w, p4, []() {}, [&](uint32_t r) { bar_arrive(NB_WIN + ((r | fz[0]) & zero), 384); });
            }
            dst0 = TAB(6); dx0 = TAB(7);
            const uint32_t zo = Z_POS ? 0 : TAB(8);
            PROF(6) HT(7)
            BLOCK_FENCE
            if (H_POS == 1 && !(XP & 1)) h_piece(sb, hsrc, s + 3, j, (wu + head) & 3, wu == 0);
            asm volatile("" : "+r"(tv2.y));
            it = 0;
#pragma unroll 1
            while (E_MUL && __any_sync(~0u, tv2.y < 32 * (s + 1)) & (++it < 16)) tv2 = ldg_u2(tp);
            const uint32_t e = __reduce_max_sync(~0u, tv2.x) - gt;
            MISS(3, it - 1) MISS(4, gt)
            if (PA_POS) tok_fetch(s + 1);
            if (O_POS == 0) o_store(s);
            if (!Z_POS) stg4_if(g16 < 160, arena + (zo + mem_slot(s + 3)), 0);
            dm = e > 4096 ? 0 : e * E_MUL >> 4;
            dl = dm + (ALIGN ? dly.near - dly.wf - (kh == mypar ? 0 : 140) : kh == mypar ? dly.near : dly.far);
            dm += dly.near;
        }
        if (O_POS) o_store(NSEG - 1);
        TL(8)
    }
    PROF_OUT
    MISS_OUT
}

struct RecMaps { CUtensorMap wq, wk, wv, wo, wmod, w3, w1; };
struct RecPtrs { const bf16 *x, *mem0, *c, *wmod, *w1, *w3; uint8_t* arena; uint32_t zero; const bf16 *w2, *w4, *wo; Delays dly; };

__device__ __forceinline__ float silu_bf(const bf16* c, int i) {
    const float v = __bfloat162float(c[i]);
    return bfround(__fdividef(v, 1.0f + __expf(-v)));
}
#define W_LATE 1000
#define W_OPEN 1400
__device__ __forceinline__ void side_window(const uint8_t* arena, uint32_t& n) {
    U2 v;
    int it = 0;
#pragma unroll 1
    while (v = ldg_u2(arena + (LB_TIME << 13)), ((v.y >> 5) == n || gtime() - v.x > W_OPEN + W_LATE) && v.y < 32 * NSEG && ++it < 64) __nanosleep(100);
    n = v.y >> 5;
    it = 0;
#pragma unroll 1
    while ((int)(gtime() - v.x - W_OPEN) < 0 && ++it < 256) {}
}
__device__ __noinline__ void rec_ln(float* coef, const RecPtrs& p, int id, int r0) {
    int r1 = 32;
    const int tid = threadIdx.x;
    const int lane = tid & 31, wid = tid >> 5;
    const uint32_t ring = smem_u32(coef) - SM_PRE + wid * 8192 + lane * 16;
    auto rowof = [&](int j) { return (j >> 1) * 64 + (id * 8 + wid) * 2 + (j & 1); };
    auto fetch = [&](int j) {
        if (j < 2 * r1) {
#pragma unroll
            for (int i = 0; i < 4; i++)
                asm volatile("cp.async.cg.shared.global [%0], [%1], 16;" ::"r"(ring + (j & 3) * 2048 + i * 512), "l"(p.x + (size_t)rowof(j) * DM + i * 256 + lane * 8) : "memory");
        }
        asm volatile("cp.async.commit_group;" ::: "memory");
    };
#pragma unroll 1
    for (int j = 2 * r0; j < 2 * r0 + 4; j++) fetch(j);
#pragma unroll 1
    for (int i = tid; i < 2 * DM / 4; i += 256) {
        uint4 v[8];
        int it = 0;
        uint32_t ok;
        do {
            ok = 1;
#pragma unroll
            for (int k = 0; k < 8; k++) v[k] = ldg_rlx4(g_modp + k * 2 * DM + i * 4);
#pragma unroll
            for (int k = 0; k < 8; k++) ok &= v[k].x & v[k].y & v[k].z & v[k].w;
            spin_guard(++it);
        } while (!ok);
        float t[4] = {0, 0, 0, 0};
#pragma unroll
        for (int k = 0; k < 8; k++) { t[0] += __uint_as_float(v[k].x); t[1] += __uint_as_float(v[k].y); t[2] += __uint_as_float(v[k].z); t[3] += __uint_as_float(v[k].w); }
#pragma unroll
        for (int j = 0; j < 4; j++) coef[i * 4 + j] = bfround(t[j]) + (i >= DM / 4 ? 1.0f : 0.0f);
    }
    bar_sync(NB_FIN0, 256);
    if (r0 == 0) {
        int v, it = 0;
#pragma unroll 1
        do { v = *(volatile int*)((uint8_t*)coef - SM_PRE + SM_BAR + 192); spin_guard(++it); } while (v == INT_MIN);
        if (v >= 0) r1 = 2;
    }
    if (tid == 0 && r0 == 0) TL(2)
#pragma unroll 1
    for (int j = 2 * r0; j < 2 * r1; j++) {
        float x[32];
        asm volatile("cp.async.wait_group 3;" ::: "memory");
#pragma unroll
        for (int i = 0; i < 4; i++) {
            const uint4 v = lds4(ring + (j & 3) * 2048 + i * 512);
            float* d = x + i * 8;
            d[0] = bflo(v.x); d[1] = bfhi(v.x); d[2] = bflo(v.y); d[3] = bfhi(v.y); d[4] = bflo(v.z); d[5] = bfhi(v.z); d[6] = bflo(v.w); d[7] = bfhi(v.w);
        }
        const int row = rowof(j), rr = row & 15;
        ln_row(x);
        fetch(j + 4);
#pragma unroll
        for (int i = 0; i < 4; i++) {
            float y[8];
            const float4* cf = (const float4*)(coef + i * 256 + lane * 8);
            const float4 s0 = cf[0], s1 = cf[1], c0 = cf[256], c1 = cf[257];
            const float sh[8] = {s0.x, s0.y, s0.z, s0.w, s1.x, s1.y, s1.z, s1.w}, sc[8] = {c0.x, c0.y, c0.z, c0.w, c1.x, c1.y, c1.z, c1.w};
#pragma unroll
            for (int e = 0; e < 8; e++) y[e] = fmaf(x[i * 8 + e], sc[e], sh[e]);
            const int own = ((row >> 4) & 1) == (i >> 1), c16 = i * 32 + lane;
            const uint32_t off = ((row >> 5) + own) * 65536 + (c16 >> 3) * 4096 + (rr + (own ? 0 : 16)) * 128 + (((c16 & 7) ^ (rr & 7)) << 4);
            *(uint4*)((uint8_t*)g_himg + off) = pack8(y);
        }
        if ((j & 3) != 3) continue;
        bar_sync(j == 3 ? NB_C : NB_FIN0, j == 3 ? 320 : 256);
        if (wid == 0) {
            if (j == 3) bar_arrive(NB_B, 64);
            if (lane == 0) { if (j == 7) wait_count1(&g_tick[32 + id * 8], 1); signal_count(&g_tick[32 + id * 8]); if (j < 8) TL(13) }
            __syncwarp();
        }
    }
}
#define SIDE_T 300
template <int NQ>
__device__ __forceinline__ void side_gemv(const CUtensorMap* tm, int c0, int k0, int k1, uint32_t cs, uint32_t sb, const uint8_t* arena, uint32_t& n, uint32_t& ph, float (*acc)[8], const uint8_t* xr = nullptr) {
    const uint32_t w = __reduce_max_sync(~0u, threadIdx.x >> 5 & 3), ring = sb + 65536 + w * 24576, bars = sb + SM_BAR + 8 * B_W + w * 24;
#pragma unroll
    for (int q = 0; q < NQ; q++)
#pragma unroll
        for (int j = 0; j < 8; j++) acc[q][j] = 0.f;
#pragma unroll 1
    for (; k0 < k1; k0 += 48, ph ^= 1) {
        const int nr = min(48, k1 - k0);
        side_window(arena, n);
        const uint32_t t0 = clk32();
        if (xr && k0 < 9 * 48) {
#pragma unroll
            for (int i = 0; i < 6; i++) asm volatile("prefetch.global.L2 [%0];" ::"l"(xr + (5 + k0 / 16 + (i >> 1)) * 131072 + (i & 1) * 16384));
        }
#pragma unroll 1
        for (int g = 0; g < 3; g++) {
            spin_until(t0, (g * 4 + w) * (SIDE_T / 4));
            e_expect(bars + 8 * g, g * 16 < nr ? 8192 : 0);
            if (g * 16 < nr) e_tma2d(ring + g * 8192, tm, c0, k0 + g * 16, bars + 8 * g);
        }
#pragma unroll 1
        for (int r = 0; r < nr; r += 16) {
            mbar_wait_w(bars + (r >> 1), ph);
            uint4 v[16];
#pragma unroll
            for (int h = 0; h < 16; h++) v[h] = lds4(ring + (r + h) * 512 + (threadIdx.x & 31) * 16);
            float4 cf[NQ][4];
#pragma unroll
            for (int q = 0; q < NQ * 4; q++) cf[q >> 2][q & 3] = lds4f(cs + ((q >> 2) * DM + k0 + r + (q & 3) * 4) * 4);
#pragma unroll
            for (int h = 0; h < 16; h++) {
                const float f[8] = {bflo(v[h].x), bfhi(v[h].x), bflo(v[h].y), bfhi(v[h].y), bflo(v[h].z), bfhi(v[h].z), bflo(v[h].w), bfhi(v[h].w)};
#pragma unroll
                for (int q = 0; q < NQ; q++)
#pragma unroll
                    for (int j = 0; j < 8; j++) acc[q][j] = fmaf((&cf[q][h >> 2].x)[h & 3], f[j], acc[q][j]);
            }
        }
        fence_async_smem();
        __syncwarp();
    }
}
__device__ __noinline__ void rec_side(float* sm, const RecMaps& mp, const RecPtrs& p, int id) {
    const int tid = threadIdx.x;
    if (tid < 256) {
        if (blockIdx.x < 128) rec_ln(sm + SM_PRE / 4, p, id, 2);
        if (tid == 0) TL(14)
        for (int i = tid; i < 2 * S_; i += 256) g_st[id * 2 * S_ + i] = 0.f;
        if (id == 0 && tid < 64) g_pcnt[tid * 8] = 0;
        if (id == 1) for (int i = tid; i < 5 * 256; i += 256) g_pflag[i] = 0;
        uint32_t n = 0;
        int it = 0;
#pragma unroll 1
        while (n < SPF_AT && ++it < 256) side_window(p.arena, n);
#pragma unroll 1
        for (int i = 0; i < 96 && SPF; i++) {
            const uint8_t* w = i < 64 ? (const uint8_t*)p.wo + (id * 64 + i) * 32768 : (const uint8_t*)p.x + (id * 32 + i - 64) * 32768;
            asm volatile("prefetch.global.L2 [%0];" ::"l"(w + tid * 128));
            if (i % SPF_R == SPF_R - 1 && i < 95) side_window(p.arena, n); else __nanosleep(SPF_NS);
        }
        return;
    }
    const int t = tid - 256;
    float *coef = sm + 40960, *red = coef + 3 * DM;
    const uint32_t sb = smem_u32(sm), cs = smem_u32(coef);
    uint32_t n = 0, ph = 0;
    for (int i = t; i < DM; i += 128) { coef[i] = silu_bf(p.c, i); coef[2 * DM + i] = 1.0f; }
    if (t == 0) wait_count1(&g_tick[32 + id * 8], 2);
    bar_sync(NB_G, 128);
    const int w = __reduce_max_sync(~0u, t >> 5);
    float acc[3][8];
    side_gemv<1>(&mp.wmod, (2 + id) * DM + w * 256, 0, DM, cs, sb, p.arena, n, ph, acc, (const uint8_t*)p.x + id * 32768 + t * 128);
#pragma unroll
    for (int j = 0; j < 8; j++) g_mod[(2 + id) * DM + t * 8 + j] = bfround(acc[0][j]);
    bar_sync(NB_G, 128);
    if (t == 0) signal_count(&g_tick[8]);
    side_gemv<1>(&mp.w3, id * (FF / 4) + w * 256, 0, DM, cs + 8 * DM, sb, p.arena, n, ph, acc);
    if (t < FF / 32) {
#pragma unroll
        for (int j = 0; j < 8; j++) g_vec[3 * DM + id * (FF / 4) + t * 8 + j] = acc[0][j];
    }
    if (t == 0) wait_count1(&g_tick[8], 4);
    bar_sync(NB_G, 128);
    for (int i = t; i < DM; i += 128) { coef[i] = 1.0f + __ldcg(g_mod + 4 * DM + i); coef[DM + i] = __ldcg(g_mod + 3 * DM + i); }
    bar_sync(NB_G, 128);
    if (id == 1 && t < 32) {
        float u[5] = {0, 0, 0, 0, 0};
        for (int i = t; i < DM; i += 32) {
            const float a = coef[i], b = coef[DM + i];
            u[0] += a; u[1] += a * a; u[2] += a * b; u[3] += b; u[4] += b * b;
        }
#pragma unroll
        for (int q = 0; q < 5; q++) { const float r = warp_sum(u[q]); if (t == 0) g_cst[q] = r * (1.0f / DM); }
    }
    side_gemv<3>(&mp.w1, id * 256, w * 256, w * 256 + 256, cs, sb, p.arena, n, ph, acc);
#pragma unroll
    for (int q = 0; q < 3; q++)
#pragma unroll
        for (int j = 0; j < 8; j++) red[((t >> 5) * 3 + q) * 256 + (t & 31) * 8 + j] = acc[q][j];
    bar_sync(NB_G, 128);
    for (int i = t; i < 768; i += 128) g_vec[(i >> 8) * DM + id * 256 + (i & 255)] = (red[i] + red[768 + i]) + (red[1536 + i] + red[2304 + i]);
    if (t == 0) TL(9)
}

__global__ void __cluster_dims__(2, 1, 1) __launch_bounds__(384, 1)
k_rec(const __grid_constant__ RecMaps mp, const __grid_constant__ RecPtrs p) {
    extern __shared__ uint8_t smraw[];
    const uint32_t sb = smem_u32(smraw);
    if ((sb & 0x3FFFF) != SB0) __trap();
    const uint32_t bars = sb + SM_BAR;
    const int tid = threadIdx.x, lane = tid & 31, b = blockIdx.x;
    const int wid = __reduce_max_sync(~0u, tid >> 5);
    const uint32_t rank = b & 1;
    uint8_t* arena = p.arena;
    volatile int* sinfo = (volatile int*)(smraw + SM_BAR + 192);
    if (tid == 0) TL(0)
    if (tid == 0) sinfo[0] = INT_MIN;
    if (tid == 352) {
        for (int i = 0; i < 17; i++) mbar_init(bars + 8 * i, i == B_WO ? 4 : 1);
        asm volatile("fence.mbarrier_init.release.cluster;" ::: "memory");
        mbar_expect(bars + 8 * B_ROLE, 8);

    }
    __syncwarp();
    asm volatile("barrier.cluster.arrive.relaxed.aligned;" ::: "memory");
    int pr = 0, hA = 0;
    if (wid < 8) {
        if (b < 128) {
            const int cb = (b & 15) * 128, k0 = (b >> 4) * 128 + (tid >> 4);
            uint4 v[8];
#pragma unroll
            for (int i = 0; i < 8; i++) v[i] = __ldg((const uint4*)(p.wmod + (size_t)(k0 + 16 * i) * (6 * DM) + cb + (tid & 15) * 8));
            float acc[8] = {0, 0, 0, 0, 0, 0, 0, 0};
#pragma unroll
            for (int i = 0; i < 8; i++) {
                const float sv = silu_bf(p.c, k0 + 16 * i);
                acc[0] += sv * bflo(v[i].x); acc[1] += sv * bfhi(v[i].x); acc[2] += sv * bflo(v[i].y); acc[3] += sv * bfhi(v[i].y);
                acc[4] += sv * bflo(v[i].z); acc[5] += sv * bfhi(v[i].z); acc[6] += sv * bflo(v[i].w); acc[7] += sv * bfhi(v[i].w);
            }
            float* red = (float*)(smraw + SM_PRE);
            *(float4*)(red + (tid >> 4) * 128 + (tid & 15) * 8) = make_float4(acc[0], acc[1], acc[2], acc[3]);
            *(float4*)(red + (tid >> 4) * 128 + (tid & 15) * 8 + 4) = make_float4(acc[4], acc[5], acc[6], acc[7]);
            bar_sync(NB_FIN0, 256);
            if (wid < 4) {
                float t = 0;
#pragma unroll
                for (int i = 0; i < 16; i++) t += red[i * 128 + tid];
                stg_rlx1(&g_modp[(b >> 4) * 2 * DM + cb + tid], __float_as_uint(t) | 1u);
            }
        } else {
            rec_ln((float*)(smraw + SM_PRE), p, b - 128, 0);
        }
    } else if (wid >= 10 && b >= 128) {
        {
            const int w = (b - 128) * 2 + wid - 10;
            const uint16_t* src = (const uint16_t*)p.mem0 + (lane & 3) * 2 * DM + (w >> 2) * 512 + (w & 1) * 64 + (w & 2) * 8 + (lane >> 2);
            uint32_t v[4][4];
#pragma unroll
            for (int i = 0; i < 16; i++) v[i >> 2][i & 3] = src[(i >> 2) * 128 + (i & 2) * 16 + (i & 1) * 8] | ((uint32_t)src[DM + (i >> 2) * 128 + (i & 2) * 16 + (i & 1) * 8] << 16);
            uint8_t* d = arena + mem_row(w >> 2, w & 3, 0);
            uint8_t* e = d + 512 + (CNT32 ? lane >> 1 : lane) * 4;
            d += lane * 16;
#pragma unroll
            for (int i = 0; i < 4; i++, d += 1024, e += 1024) {
                stg_rlx4(d, v[i][0], v[i][1], v[i][2], CNT32 && !(lane & 1) ? v[i][3] : (v[i][3] & 0xffff) | CNT_ALL << 16);
                stg_rlx4(d + mem_slot(1), 0, 0, 0, 0);
                stg_rlx4(d + mem_slot(2), 0, 0, 0, 0);
                if (!CNT32 || (lane & 1)) { stg_rlx1(e, (v[i][3] & 0xffff0000u) | CNT_ALL); stg_rlx1(e + mem_slot(1), 0); stg_rlx1(e + mem_slot(2), 0); }
            }
            if (w == 0 && lane < 8) stg_rlx2(arena + (LB_TIME << 13) + lane * 1024, 0, 0);
            bar_arrive(NB_C, 320);
        }
    } else if (rank == 0) {
        uint32_t best = ~0u;
        const int pg = wid < 10 ? 0 : 1 + (b >> 1) % 3;
        uint32_t* q = (uint32_t*)(arena + (pg << 21) + (pg ? blk(b >> 1, wid & 1) : blk(LB_PROBE, wid & 1) + b * 16));
        if (lane < 8) stg_rlx1(q + lane, 0);
        uint2 tk2 = ldg_rlx2(&g_tick[0]);
        __syncwarp();
        if (lane == 0) {
            q += 3;
            uint32_t v = atomicAdd(q, 1u);
#pragma unroll 1
            for (int r = 0; r < NPROBE; r++) {
                const uint32_t t0 = clk32() + (v >> 8);
                v = atomicAdd(q + (v >> 8), 1u);
                uint32_t t1;
                asm volatile("{.reg .pred p; setp.eq.u32 p, %1, 0xffffffff; @p exit; mov.u32 %0, %%clock;}" : "=r"(t1) : "r"(v) : "memory");
                best = min(best, t1 - t0);
            }
            sinfo[wid - 6] = best;
        }
        bar_sync(NB_KDONE, b < 128 ? 128 : 64);
        if (wid == 8) {
            const int par = sinfo[2] <= sinfo[3] ? 0 : 1, ncl = gridDim.x >> 1;
            int tk = 0, it = 0;
            const uint32_t vote = b < 128 && (sinfo[4] <= sinfo[5] ? 0 : 1) != par ? 256u << (8 * ((b >> 1) % 3)) : 0u;
            if (b >= 128) {
#pragma unroll 1
                while (!__all_sync(~0u, (int)((tk2.x + tk2.y) & 255) >= ncl - 2)) { tk2 = ldg_rlx2(&g_tick[0]); spin_guard(++it); }
            }
            if (lane == 0) tk = atomicAdd(&g_tick[par], 1u + vote) & 255;
#pragma unroll 1
            while (!__all_sync(~0u, (int)((tk2.x + tk2.y) & 255) >= ncl)) { tk2 = ldg_rlx2(&g_tick[0]); spin_guard(++it); }
            tk = __shfl_sync(~0u, tk, 0);
            const int n0 = tk2.x & 255, n1 = tk2.y & 255;
            hA = min(n0 >> 1, NH);
            const int q0 = 2 * hA, q1 = 2 * NH - q0;
            const int over = tk - (par ? q1 : q0), lack = max(par ? q0 - n0 : q1 - n1, 0);
            if (over < 0) pr = par ? q0 + tk : tk;
            else if (over < lack) pr = (par ? n0 : q0 + n1) + over;
            else pr = -1 - (over - lack + (par ? max(n0 - q0, 0) : 0));
#pragma unroll
            for (int i = 0; i < 3; i++) hA |= (((tk2.x + tk2.y) >> (8 + 8 * i)) & 255) > 10 ? 256 << i : 0;
        }
    }
    asm volatile("barrier.cluster.wait.aligned;" ::: "memory");
    if (wid == 8) {
        if (rank == 0) {
            if (lane == 0) {
                uint32_t rsb;
                asm("mapa.shared::cluster.u32 %0, %1, 1;" : "=r"(rsb) : "r"(sb));
                asm volatile("st.async.shared::cluster.mbarrier::complete_tx::bytes.v2.u32 [%0], {%1, %2}, [%3];"
                             ::"r"(rsb + SM_BAR + 192), "r"(pr), "r"(hA), "r"(rsb + SM_BAR + 8 * B_ROLE) : "memory");
                sinfo[0] = pr; sinfo[1] = hA;
                if (b >= 128) atomicOr(&g_tick[4], (pr < 0 ? 4u : 1u) << ((b - 128) >> 1));
            }
        } else {
            mbar_wait_w(bars + 8 * B_ROLE, 0);
            pr = sinfo[0];
        }
        TL(1)
        __syncwarp();
        bar_arrive(NB_A, 288);
        bar_arrive(NB_S, 128);
        if (b >= 128 && pr < 0) bar_sync(NB_B, 64);
        if (pr >= 0) {
            const int pu = __reduce_max_sync(~0u, pr), c0 = (pu >> 1) * 128 + rank * 64, r0 = (pu & 1) * 512;
            bool fast = false;
#pragma unroll 1
            for (int n = 0; n < 12; n++) {
                const int rot = b >= 128 ? 8 : 0, i = (n + rot) % 12;
                if (rot && n == 4) bar_sync(NB_B, 64);
                if (n >= W_INFL && !fast) {
                    const uint32_t v = ldg_rlx1(&g_tick[32 + (lane & 3) * 8]);
                    mbar_wait_w(bars + 8 * (B_W + (n - W_INFL + rot) % 12), 0);
                    fast = __all_sync(~0u, v != 0);
                }
                const int m = i < 8 ? i & 1 : 2, k = i < 8 ? i >> 1 : i - 8;
                const uint32_t dst = sb + m * 65536 + k * 16384, br = bars + 8 * (B_W + i);
                if (lane == 0) {
                    mbar_expect(br, 16384);
                    tma2d(dst, &mp.wq + m, c0, r0 + k * 128, br);
                    tma2d(dst + 8192, &mp.wq + m, c0, r0 + k * 128 + 64, br);
                }
                __syncwarp();
            }
        }
    } else {
        bar_sync(wid < 8 ? NB_A : NB_S, wid < 8 ? 288 : 128);
    }
    const int prr = __reduce_max_sync(~0u, sinfo[0]);
    hA = __reduce_max_sync(~0u, sinfo[1]);
    if (prr < 0) {
        int j = (b - 128) >> 1;
        if (b < 128) {
            uint32_t v;
            int it = 0;
#pragma unroll 1
            do { v = __reduce_max_sync(~0u, ldg_rlx1(&g_tick[4])); spin_guard(++it); } while (__popc(v) < 2);
            j = v == 3 ? -1 - prr : (v & 1) ^ 1;
        }
        rec_side((float*)smraw, mp, p, j * 2 + rank);
        return;
    }
    const int role = (prr >> 1) * 4 + rank * 2 + (prr & 1);
    rec_main(sb, &mp.wo, arena, role, hA, wid >> 2, p.zero, p.dly);
}

__device__ __forceinline__ void wgmma_ss192(float* d, uint64_t a, uint64_t b, int sc) {
    asm volatile("{.reg .pred p; setp.ne.b32 p, %98, 0;\n wgmma.mma_async.sync.aligned.m64n192k16.f32.bf16.bf16 "
                 "{%0,%1,%2,%3,%4,%5,%6,%7,%8,%9,%10,%11,%12,%13,%14,%15,%16,%17,%18,%19,%20,%21,%22,%23,%24,%25,%26,%27,%28,%29,%30,%31,%32,%33,%34,%35,%36,%37,%38,%39,%40,%41,%42,%43,%44,%45,%46,%47,%48,%49,%50,%51,%52,%53,%54,%55,%56,%57,%58,%59,%60,%61,%62,%63,%64,%65,%66,%67,%68,%69,%70,%71,%72,%73,%74,%75,%76,%77,%78,%79,%80,%81,%82,%83,%84,%85,%86,%87,%88,%89,%90,%91,%92,%93,%94,%95}, %96, %97, p, 1, 1, 0, 1;}"
                 : F16(d, 0), F16(d, 16), F16(d, 32), F16(d, 48), F16(d, 64), F16(d, 80) : "l"(a), "l"(b), "r"(sc));
}
__device__ __forceinline__ void wgmma_ss256(float* d, uint64_t a, uint64_t b, int sc) {
    asm volatile("{.reg .pred p; setp.ne.b32 p, %130, 0;\n wgmma.mma_async.sync.aligned.m64n256k16.f32.bf16.bf16 "
                 "{%0,%1,%2,%3,%4,%5,%6,%7,%8,%9,%10,%11,%12,%13,%14,%15,%16,%17,%18,%19,%20,%21,%22,%23,%24,%25,%26,%27,%28,%29,%30,%31,%32,%33,%34,%35,%36,%37,%38,%39,%40,%41,%42,%43,%44,%45,%46,%47,%48,%49,%50,%51,%52,%53,%54,%55,%56,%57,%58,%59,%60,%61,%62,%63,%64,%65,%66,%67,%68,%69,%70,%71,%72,%73,%74,%75,%76,%77,%78,%79,%80,%81,%82,%83,%84,%85,%86,%87,%88,%89,%90,%91,%92,%93,%94,%95,%96,%97,%98,%99,%100,%101,%102,%103,%104,%105,%106,%107,%108,%109,%110,%111,%112,%113,%114,%115,%116,%117,%118,%119,%120,%121,%122,%123,%124,%125,%126,%127}, %128, %129, p, 1, 1, 0, 1;}"
                 : F16(d, 0), F16(d, 16), F16(d, 32), F16(d, 48), F16(d, 64), F16(d, 80), F16(d, 96), F16(d, 112) : "l"(a), "l"(b), "r"(sc));
}

constexpr uint32_t P_VEC = 212992, P_ROW = P_VEC + 6144, P_BAR = P_ROW + 4096, P_SMEM = P_BAR + 256;
constexpr uint32_t P_OUT = 180224, P_OUT3 = 147456, P_OUT4 = 163840;
#define PPH 1
#define FLAG_ST "st.release.gpu.global.u32"
#define FLAG_LD "ld.acquire.gpu.global.u32"
#define BA3 2
#define BA 5
#define BA0 1
constexpr int P_SA = 5, P_SB = 3;
constexpr int PB_FA = 0, PB_EA = 5, PB_FB = 10, PB_EB = 13, PB_OUT = 16;
enum { C_Y = 0, C_G = 1, C_X1 = 2, C_U = 3, C_S1 = 8, C_S3 = 9 };
enum { V_GA = 0, V_A = 1, V_B = 2, V_GB = 3, V_VA = 4, V_VB = 5, V_VC = 6, V_C3 = 7 };
struct PostMaps { CUtensorMap o, wo, y, w1, g, w2, x1, w3, u, w4, out; };
struct PostPtrs { const bf16* x; };

struct GeluK { float k0, k1, kh; };
__device__ __forceinline__ GeluK gelu_k(float c) { return {0.7978845608028654f * c, 0.7978845608028654f * 0.044715f * c * c * c, 0.5f * c}; }
__device__ __forceinline__ float gelu_s(float t, const GeluK& k) {
    const float u = t * fmaf(t * t, k.k1, k.k0);
    float th; asm("tanh.approx.f32 %0, %1;" : "=f"(th) : "f"(u));
    const float hx = k.kh * t;
    return fmaf(hx, th, hx);
}
__device__ __forceinline__ float2 ldsv(uint32_t a) {
    float2 v; asm("ld.shared.v2.f32 {%0,%1}, [%2];" : "=f"(v.x), "=f"(v.y) : "r"(a)); return v;
}
__device__ __forceinline__ void wait_smem(uint32_t a, int target) {
    int it = 0;
#pragma unroll 1
    while (true) {
        int v;
        asm volatile("ld.acquire.cta.shared.u32 %0, [%1];" : "=r"(v) : "r"(a) : "memory");
        if (__all_sync(~0u, v >= target)) break;
        spin_guard(++it);
    }
}

#define PP(i)
#define PH_(c, w, i)
struct Pipe { int st, ph; };
template <int ST> __device__ __forceinline__ void adv(Pipe& p) { if (++p.st == ST) { p.st = 0; p.ph ^= 1; } }

__device__ __forceinline__ void post_produce(uint32_t sb, const PostMaps& mp, int mb, int nb, int rank) {
    const int rh = 2 * mb + rank, lane = threadIdx.x & 31;
    int st = 0, pp = 0, st2 = 0, pp2 = 0;
#pragma unroll 1
    for (int ph = 0; ph < 7; ph++) {
        const bool W = ph == 3 || ph == 4;
        if (ph == 3 || ph >= 5) {
            const int n = ph == 5 ? P_SB : P_SA;
            const uint32_t e = sb + P_BAR + 8 * (ph == 5 ? PB_EB : PB_EA);
#pragma unroll 1
            for (int i = 0; i < n; i++) mbar_wait_w(e + 8 * i, pp ^ (i >= st));
            if (ph == 6) break;
            if (ph == 5) wait_smem(sb + P_BAR + 8 * (PB_OUT + (lane & 1)), 4);
            int t = st; st = st2; st2 = t; t = pp; pp = pp2; pp2 = t;
        }
        const int ST = W ? P_SB : P_SA, NK = ph == 0 ? 64 : ph == 5 ? 56 : 16, NB = ph == 3 ? 4 : ph == 4 ? 3 : 2;
        const uint32_t SBYTES = W ? 49152 : 32768;
        const uint32_t full = sb + P_BAR + 8 * (W ? PB_FB : PB_FA), empty = sb + P_BAR + 8 * (W ? PB_EB : PB_EA);
        const CUtensorMap* ta = &mp.o + 2 * (ph > 3 ? ph - 1 : ph);
        const CUtensorMap* tb = ta + 1;
        const int n0 = ph == 3 ? nb * 256 : ph == 4 ? 2048 + nb * 192 : nb * 128;
        const int amul = ph == 0 ? 256 : 64, arow = ph == 0 ? rh * 8 : rh * 64;
        const uint32_t shifts = ph == 2 ? 0x04000301u : 0x02020202u;
        const uint32_t* fl = &g_pflag[(ph == 5 ? C_U + ((lane >> 3) & 1) : ph - 1) * 256 + (ph == 2 ? min(max(rh + min(lane >> 3, 2) - 1, 0), 31) : rh) * 8 + (lane & 7)];
        uint32_t have = ph == 0 || ph == 4 ? 9 : 0;
        auto order = [&](int i, int& need, int& grp) {
            need = 0; grp = i & 1;
            if (ph == 5) {
                const int q = i < 32 ? i >> 2 : ((i - 32) * 43) >> 7, src = (q + (nb & 6)) & 7;
                need = (i < 32 ? 1 : 256) << src; grp = i < 32 ? i & 3 : i - 32 - 3 * q;
                return i + (src - q) * (i < 32 ? 4 : 3);
            }
            if (ph == 0) return i;
            const int kb = (i + 2 * (nb & 6)) & 15;
            need = (ph == 2 ? 0x10101 : 1) << (kb >> 1);
            return kb;
        };
        PH_(ph == PPH, 0, 26) PH_(ph == PPH, 1, 26)
        int ib = 0, sB = st, pB = pp;
#pragma unroll 1
        for (int i = 0; i < NK; i++) {
            int need, grp;
#pragma unroll 1
            for (const int lim = i || ph > 3 ? i + 1 : ph == 3 ? BA3 : ph ? BA : BA0; ib < lim; ib++) {
                const int kb = order(ib, need, grp);
                const uint32_t a = sb + sB * SBYTES, f = full + 8 * sB;
                mbar_wait_w(empty + 8 * sB, pB ^ 1);
                e_expect(f, 16384 + NB * 8192);
                e_tma2d(a + 16384, tb, n0, kb * 64, f);
                e_tma2d(a + 24576, tb, n0 + 64, kb * 64, f);
                if (W) { e_tma2d(a + 32768, tb, n0 + 128, kb * 64, f); if (ph == 3) e_tma2d(a + 40960, tb, n0 + 192, kb * 64, f); }
                if (++sB == ST) { sB = 0; pB ^= 1; }
            }
            const int kb = order(i, need, grp);
            PH_(ph == PPH && i == 0, 0, 27) PH_(ph == PPH && i == 0, 1, 27)
            if (ph == 0 && i == 0) {
                asm volatile("barrier.cluster.wait.aligned;" ::: "memory");
                PH_(PPH == 0, 0, 25) PH_(PPH == 0, 1, 25)
            }
            if ((__ballot_sync(~0u, have > grp) & need) != need) {
                int it = 0;
#pragma unroll 1
                do {
                    asm volatile(FLAG_LD " %0, [%1];" : "=r"(have) : "l"(fl) : "memory");
                    spin_guard(++it);
                } while ((__ballot_sync(~0u, have > grp) & need) != need);
                PH_(ph == PPH && i == 0, 0, 23) PH_(ph == PPH, 0, 24) PH_(ph == PPH && i == 0, 1, 23) PH_(ph == PPH, 1, 24)
                asm volatile("fence.proxy.async.global;" ::: "memory");
                PH_(ph == PPH && i == 0, 0, 25) PH_(ph == PPH && i == 0, 1, 25)
            }
            e_tma2d_mc(sb + st * SBYTES + rank * 8192, ta, kb * amul, arow + (int)((shifts >> ((kb & 12) * 2)) & 7) - 2, full + 8 * st);
            if (++st == ST) { st = 0; pp ^= 1; }
        }
    }
}

template <int PH>
__device__ __forceinline__ void post_mma(uint32_t sb, float* acc, Pipe& p, int wg, bool lead, int pi) {
    constexpr bool W = PH == 3 || PH == 4;
    constexpr int ST = W ? P_SB : P_SA, SBYTES = W ? 49152 : 32768, NK = PH == 0 ? 64 : PH == 5 ? 56 : 16;
    const uint32_t full = sb + P_BAR + 8 * (W ? PB_FB : PB_FA), empty = sb + P_BAR + 8 * (W ? PB_EB : PB_EA);
    constexpr uint64_t DA = PH == 0 ? mkdesc(SB0, 128, 1024, 0) : mkdesc(SB0, 16, 1024, 1);
    constexpr uint64_t DB = mkdesc(SB0 + 16384, 8192, 1024, 1);
    auto release = [&](int st) { if (lead) { mbar_arrive_cluster(empty + 8 * st, 0); mbar_arrive_cluster(empty + 8 * st, 1); } };
    int prev = 0;
#pragma unroll 1
    for (int kb = 0; kb < NK; kb++) {
        mbar_wait_w(full + 8 * p.st, p.ph);
        const uint32_t so = p.st * (SBYTES >> 4);
        const uint32_t a = (uint32_t)DA + so + wg * 512, b = (uint32_t)DB + so;
        wg_fence();
#pragma unroll
        for (int k = 0; k < 4; k++) {
            const uint64_t da = (DA & 0xffffffff00000000ull) | (a + k * (PH == 0 ? 16 : 2)), db = (DB & 0xffffffff00000000ull) | (b + k * 128);
            if (PH == 3) wgmma_ss256(acc, da, db, (kb | k) != 0);
            else if (PH == 4) wgmma_ss192(acc, da, db, (kb | k) != 0);
            else wgmma_ss128<PH == 0>(acc, da, db, (kb | k) != 0);
        }
        wg_commit();
        if (kb == 0) { PP(pi) if (PH == 0 && wg == 0) TL(11) }
        wg_wait<1>();
        if (kb > 0) release(prev);
        prev = p.st;
        adv<ST>(p);
    }
    wg_wait<0>();
    release(prev);
    PP(pi + 1)
}

__global__ void __cluster_dims__(2, 1, 1) __launch_bounds__(384, 1)
k_post(const __grid_constant__ PostMaps mp, const __grid_constant__ PostPtrs pp) {
    extern __shared__ uint8_t smraw[];
    const uint32_t sb = smem_u32(smraw);
    if ((sb & 0x3FFFF) != SB0) __trap();
    const int tid = threadIdx.x, lane = tid & 31;
    const int mb = blockIdx.x >> 3, nb = blockIdx.x & 7, rank = blockIdx.x & 1;
    const uint32_t bars = sb + P_BAR;
    if (tid < PB_OUT) {
        mbar_init(bars + 8 * tid, (tid >= PB_EA && tid < PB_FB) || tid >= PB_EB ? 4 : 1);
        asm volatile("fence.mbarrier_init.release.cluster;" ::: "memory");
    }
    if (tid == 32) sts4(bars + 8 * PB_OUT, 0, 0, 0, 0);
    if (tid >= 256 && tid < 267) asm volatile("prefetch.tensormap [%0];" ::"l"(&mp.o + (tid - 256)) : "memory");
    __syncthreads();
    asm volatile("barrier.cluster.arrive.aligned;" ::: "memory");
    if (tid < 256 || tid >= 288) asm volatile("barrier.cluster.wait.aligned;" ::: "memory");
    if (tid >= 256) {
        asm volatile("setmaxnreg.dec.sync.aligned.u32 40;");
        const int w = __reduce_max_sync(~0u, (tid >> 5) - 8);
        if (w == 0) {
            post_produce(sb, mp, mb, nb, rank);
        } else if (w < 3) {
            const int wg = w - 1, rh = 2 * mb + wg;
            float* rowc = (float*)(smraw + P_ROW) + (wg * 64 + lane * 2) * 8;
            int nout = 0, sig = 0;
#pragma unroll 1
            for (int i = 0; i < 8; i++) {
                const int cnt = (0x54392180u >> (4 * i)) & 15;
                if (cnt < C_S1) {
                    const int ng = cnt == 3 ? 4 : cnt == 4 ? 3 : 2, c0 = cnt == 3 ? nb * 256 : cnt == 4 ? 2048 + nb * 192 : nb * 128;
                    const uint32_t src = sb + (cnt == 3 ? P_OUT3 : cnt == 4 ? P_OUT4 : P_OUT) + wg * ng * 8192;
                    uint32_t* fl = &g_pflag[cnt * 256 + rh * 8 + nb];
#pragma unroll 1
                    for (int j = 0; j < ng; j++) {
                        bar_sync(4 + 4 * wg + (sig++ & 3), 160);
                        if (lane == 0) {
                            PH_(cnt == PPH - 1, wg, 20)
                            asm volatile("cp.async.bulk.tensor.2d.global.shared::cta.bulk_group [%0, {%2, %3}], [%1]; cp.async.bulk.commit_group;"
                                         ::"l"(&mp.y + 2 * (cnt > 3 ? cnt - 1 : cnt)), "r"(src + j * 8192), "r"(c0 + j * 64), "r"(rh * 64) : "memory");
                        }
                        __syncwarp();
                    }
                    if (lane == 0) {
                        asm volatile("cp.async.bulk.wait_group 0; fence.proxy.async.global;" ::: "memory");
                        PH_(cnt == PPH - 1, wg, 21)
                        asm volatile(FLAG_ST " [%0], %1;" ::"l"(fl), "r"(ng) : "memory");
                        PH_(cnt == PPH - 1, wg, 22)
                        asm volatile("st.release.cta.shared.u32 [%0], %1;" ::"r"(bars + 8 * (PB_OUT + wg)), "r"(nout + 1) : "memory");
                    }
                    nout++;
                    __syncwarp();
                    continue;
                }
                bar_sync(4 + 4 * wg + (sig++ & 3), 160);
                uint32_t* c = &g_pcnt[(cnt - C_S1) * 256 + rh * 8];
                if (lane == 0) { signal_count(c); wait_count1(c, 8); }
                __syncwarp();
                const float4* sp = (const float4*)g_st + rh * 32 + lane;
                float4 u[3] = {__ldcg(sp + (cnt == C_S1 ? 0 : 3) * (S_ / 2)), __ldcg(sp + S_ / 2), __ldcg(sp + S_)};
#pragma unroll 1
                for (int h = 0; h < 2; h++) {
                    const float id = 1.0f / DM;
                    const float m = u[0].x * id, var = fmaxf(u[0].y * id - m * m, 0.f) + 1e-5f, r = rsqrtf(var);
                    float sc = r, m2 = 0.f;
                    if (cnt == C_S1) {
                        m2 = r * (u[1].x * id - m * g_cst[0]) + g_cst[3];
                        const float e2 = r * r * (u[2].x * id - 2.0f * m * u[1].y * id + m * m * g_cst[1]) + 2.0f * r * (u[2].y * id - m * g_cst[2]) + g_cst[4];
                        sc = r * rsqrtf(fmaxf(e2 - m2 * m2, 0.f) + 1e-5f);
                    }
                    const GeluK k = gelu_k(sc);
                    *(float4*)(rowc + h * 8) = make_float4(k.k0, k.k1, k.kh, -m);
                    *(float4*)(rowc + h * 8 + 4) = make_float4(var * r, -m2 * var * r, r, -m * r);
#pragma unroll
                    for (int q = 0; q < 3; q++) { u[q].x = u[q].z; u[q].y = u[q].w; }
                }
                bar_arrive(1 + wg, 160);
            }
        }
    } else {
        asm volatile("setmaxnreg.inc.sync.aligned.u32 232;");
        const bf16* xin = pp.x;
        const int wg = __reduce_max_sync(~0u, tid >> 7), wi = (tid >> 5) & 3, g = lane >> 2, tq = lane & 3;
        const int rh = 2 * mb + wg, row = rh * 64 + wi * 16 + g;
        const bool lead = (tid & 127) == 0;
        PP(0)
        if (tid == 0) TL(10)
        uint4 xg[8];
#pragma unroll
        for (int i = 0; i < 8; i++)
            xg[i] = __ldg((const uint4*)(xin + (size_t)(rh * 64 + wi * 16 + (i & 3) * 4 + (lane >> 3)) * DM + nb * 128 + (i >> 2) * 64 + (lane & 7) * 8));
        if (blockIdx.x < 64) g_modp[blockIdx.x * 256 + tid] = 0;
        if (blockIdx.x == 64 && tid < 64) g_tick[tid] = 0;
        {
            float* sv = (float*)(smraw + P_VEC);
            if (tid < 128) {
                const int c = nb * 128 + tid;
                sv[V_GA * 128 + tid] = __ldcg(&g_mod[2 * DM + c]); sv[V_A * 128 + tid] = 1.0f + __ldcg(&g_mod[4 * DM + c]);
                sv[V_B * 128 + tid] = __ldcg(&g_mod[3 * DM + c]); sv[V_GB * 128 + tid] = __ldcg(&g_mod[5 * DM + c]);
            } else {
                const int c = nb * 128 + tid - 128;
                sv[V_VA * 128 + tid - 128] = __ldcg(&g_vec[c]); sv[V_VB * 128 + tid - 128] = __ldcg(&g_vec[DM + c]); sv[V_VC * 128 + tid - 128] = __ldcg(&g_vec[2 * DM + c]);
            }
            sv[V_C3 * 128 + tid] = __ldcg(&g_vec[3 * DM + nb * 256 + tid]);
            if (tid < 192) sv[V_C3 * 128 + 256 + tid] = __ldcg(&g_vec[3 * DM + 2048 + nb * 192 + tid]);
            bar_sync(3, 256);
        }
        uint32_t vec = sb + P_VEC + tq * 8;
        asm volatile("" : "+r"(vec) :: "memory");
        const uint32_t stw = sb + (wi * 16 + ((lane >> 3) & 1) * 8 + (lane & 7)) * 128 + (((lane >> 4) ^ (lane & 7)) << 4);
        int sig = 0;
        auto signal = [&]() { bar_arrive(4 + 4 * wg + (sig++ & 3), 160); };
        auto put64 = [&](uint32_t o, const float* v) {
#pragma unroll
            for (int jj = 0; jj < 4; jj++, v += 8) stsm4((stw + o) ^ (jj << 5), pack2(v[0], v[1]), pack2(v[2], v[3]), pack2(v[4], v[5]), pack2(v[6], v[7]));
            fence_async_smem();
            signal();
        };
        auto out_free = [&](int n) { wait_smem(bars + 8 * (PB_OUT + (lane & 1)), n); };
        const uint32_t rowc = sb + P_ROW + (wg * 64 + wi * 16 + g) * 32, o128 = P_OUT + wg * 16384;
        Pipe pa = {0, 0}, pb = {0, 0};
        uint32_t keep[32];
#define KEEP(jn, e) (((e) & 1) ? bfhi(keep[2 * (jn) + ((e) >> 1)]) : bflo(keep[2 * (jn) + ((e) >> 1)]))
        float mu1[2], r1[2];
        {
            float acc[64];
            const uint32_t xo = sb + o128 + wi * 2048 + (lane >> 3) * 128;
#pragma unroll
            for (int i = 0; i < 8; i++) sts4(xo + (i >> 2) * 8192 + (i & 3) * 512 + (((lane & 7) ^ ((i & 1) * 4 + (lane >> 3))) << 4), xg[i].x, xg[i].y, xg[i].z, xg[i].w);
            __syncwarp();
#pragma unroll
            for (int jj = 0; jj < 8; jj++) ldsm4(keep + jj * 4, (stw + o128 + (jj >> 2) * 8192) ^ ((jj & 3) << 5));
            __syncwarp();
            post_mma<0>(sb, acc, pa, wg, lead, 1);
            float st[2][6];
#pragma unroll
            for (int q = 0; q < 6; q++) st[0][q] = st[1][q] = 0.f;
#pragma unroll
            for (int jn = 0; jn < 16; jn++) {
                const float2 ga = ldsv(vec + V_GA * 512 + jn * 32), a = ldsv(vec + V_A * 512 + jn * 32);
                float xa[4];
#pragma unroll
                for (int e = 0; e < 4; e++) {
                    xa[e] = fmaf((e & 1) ? ga.y : ga.x, acc[4 * jn + e], KEEP(jn, e));
                    st[e >> 1][0] += xa[e]; st[e >> 1][1] = fmaf(xa[e], xa[e], st[e >> 1][1]);
                    acc[4 * jn + e] = ((e & 1) ? a.y : a.x) * xa[e];
                }
                keep[2 * jn] = pack2(xa[0], xa[1]); keep[2 * jn + 1] = pack2(xa[2], xa[3]);
                if ((jn & 7) == 7) put64(o128 + (jn >> 3) * 8192, acc + 4 * jn - 28);
            }
            PP(3)
#pragma unroll
            for (int jn = 0; jn < 16; jn++) {
                const float2 a = ldsv(vec + V_A * 512 + jn * 32), b = ldsv(vec + V_B * 512 + jn * 32);
#pragma unroll
                for (int e = 0; e < 4; e++) {
                    const float y = acc[4 * jn + e], aa = (e & 1) ? a.y : a.x, bb = (e & 1) ? b.y : b.x;
                    float* s = st[e >> 1];
                    s[2] += y; s[3] = fmaf(aa, y, s[3]); s[4] = fmaf(y, y, s[4]); s[5] = fmaf(bb, y, s[5]);
                }
            }
#pragma unroll
            for (int h = 0; h < 2; h++)
#pragma unroll
                for (int q = 0; q < 6; q++) { st[h][q] += __shfl_xor_sync(~0u, st[h][q], 1); st[h][q] += __shfl_xor_sync(~0u, st[h][q], 2); }
            if (tq < 3) {
#pragma unroll
                for (int h = 0; h < 2; h++)
                    red2(g_st + (tq * S_ + row + h * 8) * 2, tq == 0 ? st[h][0] : tq == 1 ? st[h][2] : st[h][4], tq == 0 ? st[h][1] : tq == 1 ? st[h][3] : st[h][5]);
            }
            signal();
            PP(29)
        }
        {
            float acc[64];
            post_mma<1>(sb, acc, pa, wg, lead, 4);
            float c1[2], c2[2], c3[2];
            GeluK gk[2];
            bar_sync(1 + wg, 160);
#pragma unroll
            for (int h = 0; h < 2; h++) {
                const float4 a = lds4f(rowc + h * 256), b = lds4f(rowc + h * 256 + 16);
                gk[h] = {a.x, a.y, a.z}; c1[h] = a.w; c2[h] = b.x; c3[h] = b.y; mu1[h] = b.w; r1[h] = b.z;
            }
#pragma unroll
            for (int jn = 0; jn < 16; jn++) {
                const float2 va = ldsv(vec + V_VA * 512 + jn * 32), vb = ldsv(vec + V_VB * 512 + jn * 32), vc = ldsv(vec + V_VC * 512 + jn * 32);
#pragma unroll
                for (int e = 0; e < 4; e++) {
                    const int h = e >> 1;
                    const float t = fmaf(c1[h], (e & 1) ? va.y : va.x, fmaf(c2[h], (e & 1) ? vb.y : vb.x, fmaf(c3[h], (e & 1) ? vc.y : vc.x, acc[4 * jn + e])));
                    acc[4 * jn + e] = gelu_s(t, gk[h]);
                }
                if ((jn & 7) == 7) put64(o128 + (jn >> 3) * 8192, acc + 4 * jn - 28);
            }
            PP(6)
        }
        {
            float acc[64];
            post_mma<2>(sb, acc, pa, wg, lead, 7);
#pragma unroll
            for (int jn = 0; jn < 16; jn++) {
                const float2 a = ldsv(vec + V_A * 512 + jn * 32), b = ldsv(vec + V_B * 512 + jn * 32);
#pragma unroll
                for (int e = 0; e < 4; e++) {
                    const int h = e >> 1;
                    acc[4 * jn + e] += fmaf(fmaf(KEEP(jn, e), r1[h], mu1[h]), (e & 1) ? a.y : a.x, (e & 1) ? b.y : b.x);
                }
                if ((jn & 7) == 7) put64(o128 + (jn >> 3) * 8192, acc + 4 * jn - 28);
            }
            PP(9)
            float st[2][2] = {{0.f, 0.f}, {0.f, 0.f}};
#pragma unroll
            for (int jn = 0; jn < 16; jn++) {
                const float2 gb = ldsv(vec + V_GB * 512 + jn * 32);
                float z[4];
#pragma unroll
                for (int e = 0; e < 4; e++) {
                    const float x1 = acc[4 * jn + e];
                    st[e >> 1][0] += x1; st[e >> 1][1] = fmaf(x1, x1, st[e >> 1][1]);
                    z[e] = fmaf((e & 1) ? gb.y : gb.x, x1, KEEP(jn, e));
                }
                keep[2 * jn] = pack2(z[0], z[1]); keep[2 * jn + 1] = pack2(z[2], z[3]);
            }
#pragma unroll
            for (int h = 0; h < 2; h++)
#pragma unroll
                for (int q = 0; q < 2; q++) { st[h][q] += __shfl_xor_sync(~0u, st[h][q], 1); st[h][q] += __shfl_xor_sync(~0u, st[h][q], 2); }
            if (tq < 2) red2(g_st + (3 * S_ + row + tq * 8) * 2, tq ? st[1][0] : st[0][0], tq ? st[1][1] : st[0][1]);
            signal();
            PP(30)
        }
        {
            uint32_t v3 = vec + V_C3 * 512;
#pragma unroll 1
            for (int r = 0; r < 2; r++) {
                float acc[128];
#pragma unroll
                for (int i = 96; i < 128; i++) acc[i] = 0.f;
                if (r == 0) post_mma<3>(sb, acc, pb, wg, lead, 10);
                else post_mma<4>(sb, acc, pb, wg, lead, 13);
                float c1[2];
                GeluK gk[2];
                if (r == 0) bar_sync(1 + wg, 160);
                out_free(3 + r);
#pragma unroll
                for (int h = 0; h < 2; h++) { const float4 a = lds4f(rowc + h * 256); gk[h] = {a.x, a.y, a.z}; c1[h] = a.w; }
                uint32_t o = r ? P_OUT4 + wg * 24576 : P_OUT3 + wg * 32768;
#pragma unroll 1
                for (int left = 3 - r; left >= 0; left--) {
#pragma unroll
                    for (int jn = 0; jn < 8; jn++) {
                        const float2 vc = ldsv(v3 + jn * 32);
#pragma unroll
                        for (int e = 0; e < 4; e++) acc[4 * jn + e] = gelu_s(fmaf(c1[e >> 1], (e & 1) ? vc.y : vc.x, acc[4 * jn + e]), gk[e >> 1]);
                    }
                    put64(o, acc);
#pragma unroll
                    for (int i = 0; i < 32; i++) acc[i] = acc[32 + i];
                    if (left > 1) {
#pragma unroll
                        for (int i = 32; i < 64; i++) acc[i] = acc[32 + i];
                        if (left > 2) {
#pragma unroll
                            for (int i = 64; i < 96; i++) acc[i] = acc[32 + i];
                        }
                    }
                    o += 8192; v3 += 256;
                }
                PP(12 + 3 * r)
            }
        }
        {
            float acc[64];
            post_mma<5>(sb, acc, pa, wg, lead, 16);
#pragma unroll
            for (int jn = 0; jn < 16; jn++) {
                const float2 gb = ldsv(vec + V_GB * 512 + jn * 32);
#pragma unroll
                for (int e = 0; e < 4; e++) acc[4 * jn + e] = fmaf((e & 1) ? gb.y : gb.x, acc[4 * jn + e], KEEP(jn, e));
                if ((jn & 7) == 7) put64(o128 + (jn >> 3) * 8192, acc + 4 * jn - 28);
            }
            PP(18)
            if (tid == 0) TL(12)
        }
    }
}

typedef CUresult (*EncFn)(CUtensorMap*, CUtensorMapDataType, cuuint32_t, void*, const cuuint64_t*, const cuuint64_t*, const cuuint32_t*,
                          const cuuint32_t*, CUtensorMapInterleave, CUtensorMapSwizzle, CUtensorMapL2promotion, CUtensorMapFloatOOBfill);

static CUtensorMap make_map(EncFn enc, const void* p, uint64_t inner, uint64_t outer, uint32_t bi = 64) {
    CUtensorMap m;
    cuuint64_t dims[2] = {inner, outer};
    cuuint64_t str[1] = {inner * 2};
    cuuint32_t box[2] = {bi, bi == 64 ? 64u : 16u};
    cuuint32_t es[2] = {1, 1};
    enc(&m, CU_TENSOR_MAP_DATA_TYPE_BFLOAT16, 2, (void*)p, dims, str, box, es, CU_TENSOR_MAP_INTERLEAVE_NONE,
        bi == 64 ? CU_TENSOR_MAP_SWIZZLE_128B : CU_TENSOR_MAP_SWIZZLE_NONE, CU_TENSOR_MAP_L2_PROMOTION_L2_256B, CU_TENSOR_MAP_FLOAT_OOB_FILL_NONE);
    return m;
}
static CUtensorMap make_map_o(EncFn enc, const void* p) {
    CUtensorMap m;
    cuuint64_t dims[2] = {16384, 256};
    cuuint64_t str[1] = {65536};
    cuuint32_t box[2] = {256, 8};
    cuuint32_t es[2] = {1, 1};
    enc(&m, CU_TENSOR_MAP_DATA_TYPE_UINT32, 2, (void*)p, dims, str, box, es, CU_TENSOR_MAP_INTERLEAVE_NONE, CU_TENSOR_MAP_SWIZZLE_NONE,
        CU_TENSOR_MAP_L2_PROMOTION_L2_256B, CU_TENSOR_MAP_FLOAT_OOB_FILL_NONE);
    return m;
}
template <class T> static T* sym(T& s) { void* p = nullptr; cudaGetSymbolAddress(&p, s); return (T*)p; }

static const Delays h_dly = {D_NEAR, D_FAR, D_X2, D_V, D_W2, D_PA, D_WF, D_TV};
extern "C" void kernel_launch(void* const* d_in, const int* in_sizes, int n_in, void* d_out, int out_size) {
    const bf16* x = (const bf16*)d_in[0];
    const bf16* mem0 = (const bf16*)d_in[1];
    const bf16 *Wq = (const bf16*)d_in[2], *Wk = (const bf16*)d_in[3], *Wv = (const bf16*)d_in[4], *Wo = (const bf16*)d_in[5];
    const bf16 *w1 = (const bf16*)d_in[8], *w2 = (const bf16*)d_in[9], *w3 = (const bf16*)d_in[10], *w4 = (const bf16*)d_in[11];
    const bf16 *c = (const bf16*)d_in[12], *wmod = (const bf16*)d_in[13];
    bf16* out = (bf16*)d_out;

    EncFn enc = nullptr;
    cudaDriverEntryPointQueryResult qr;
    cudaGetDriverEntryPoint("cuTensorMapEncodeTiled", (void**)&enc, cudaEnableDefault, &qr);
    CUtensorMap tWq = make_map(enc, Wq, NH * DH, DM), tWk = make_map(enc, Wk, NH * DH, DM), tWv = make_map(enc, Wv, NH * DH, DM);
    PostMaps mp;
    mp.o = make_map_o(enc, sym(g_O)); mp.wo = make_map(enc, Wo, DM, NH * DH);
    mp.y = make_map(enc, sym(g_y), DM, S_); mp.w1 = make_map(enc, w1, DM, DM);
    mp.g = make_map(enc, sym(g_g), DM, S_); mp.w2 = make_map(enc, w2, DM, DM);
    mp.x1 = make_map(enc, sym(g_x1), DM, S_); mp.w3 = make_map(enc, w3, FF, DM);
    mp.u = make_map(enc, sym(g_u), FF, S_); mp.w4 = make_map(enc, w4, DM, FF);
    mp.out = make_map(enc, out, DM, S_);
    cudaFuncSetAttribute(k_rec, cudaFuncAttributeMaxDynamicSharedMemorySize, SM_REC_TOTAL + 2048);
    cudaFuncSetAttribute(k_post, cudaFuncAttributeMaxDynamicSharedMemorySize, P_SMEM);

    uint8_t* arena = (uint8_t*)(((uintptr_t)sym(g_arena) + (2u << 20) - 1) & ~(uintptr_t)((2u << 20) - 1));
    const PostPtrs pp = {x};
    const RecPtrs rp = {x, mem0, c, wmod, w1, w3, arena, 0u, w2, w4, Wo, h_dly};
    const RecMaps rm = {tWq, tWk, tWv, mp.wo, make_map(enc, wmod, 6 * DM, DM, 256), make_map(enc, w3, FF, DM, 256), make_map(enc, w1, DM, DM, 256)};
    k_rec<<<132, 384, SM_REC_TOTAL + 2048>>>(rm, rp);
    k_post<<<128, 384, P_SMEM>>>(mp, pp);
}
```

```cpp
#include <cuda_runtime.h>
#include <cuda.h>
#include <cuda_bf16.h>
#include <stdint.h>
#include <limits.h>

typedef __nv_bfloat16 bf16;

constexpr int S_ = 2048, DM = 1024, NH = 32, DH = 128, NSEG = 64, FF = 3584;
constexpr int SPIN_LIMIT = 1 << 22;
#define W_INFL 2
#define XP 0
#define H_PIECES 4
#define NPROBE 3

__device__ uint8_t g_arena[10 << 20];
__device__ uint32_t g_tick[64];
__device__ uint2 g_clk[66];
__device__ uint32_t g_cls[256];
__device__ unsigned long long g_pt;
__device__ __align__(16) uint32_t g_modp[8 * 2 * DM];
__host__ __device__ constexpr uint32_t blk(uint32_t lb, uint32_t par) {
    return (lb << 13) | ((((lb) ^ (lb >> 3) ^ (lb >> 4) ^ (lb >> 6) ^ par) & 1) << 12);
}
__host__ __device__ constexpr uint32_t lb_x2(uint32_t h) { return (h & 1) | ((h >> 1) << 3); }
__host__ __device__ constexpr uint32_t mem_row(uint32_t kh, uint32_t b, uint32_t r) { return blk(128 | b, kh) + r * 1024; }
__device__ __forceinline__ uint32_t mem_slot(uint32_t s) { return ((s & 1) << 15) | ((s & 2) << 17); }
constexpr uint32_t CNT1 = 0x3d80, CNT_ALL = 0x4000;
constexpr uint32_t LB_PROBE = 6 | 64, LB_TIME = 6;
__host__ __device__ constexpr uint32_t lb_tok(uint32_t h) { return (h & 1) | ((h >> 1) << 3); }
__device__ float g_mod[6 * DM];
__device__ __align__(1024) bf16 g_himg[(S_ + 32) * DM];
__device__ __align__(1024) bf16 g_O[S_ * NH * DH];
__device__ __align__(1024) bf16 g_y[S_ * DM];
__device__ __align__(1024) bf16 g_g[S_ * DM];
__device__ __align__(1024) bf16 g_x1[S_ * DM];
__device__ __align__(16) float g_st[4 * S_ * 2];
__device__ float g_vec[3 * DM + FF];
__device__ float g_cst[8];
__device__ uint32_t g_pcnt[2 * 32 * 8], g_pflag[6 * 32 * 8];
__device__ __align__(1024) bf16 g_u[S_ * FF];

#define TL(i) {}
#define TLC(i) {}
__device__ __forceinline__ uint32_t smem_u32(const void* p) { return (uint32_t)__cvta_generic_to_shared(p); }
__device__ __forceinline__ void spin_guard(int it) {
    asm volatile("{.reg .pred p; setp.gt.s32 p, %0, %1; @p st.global.u32 [%2], %0;}" ::"r"(it), "n"(SPIN_LIMIT), "l"(1ull));
}
__device__ __forceinline__ void wg_fence() { asm volatile("wgmma.fence.sync.aligned;" ::: "memory"); }
__device__ __forceinline__ void wg_commit() { asm volatile("wgmma.commit_group.sync.aligned;" ::: "memory"); }
template <int N> __device__ __forceinline__ void wg_wait() { asm volatile("wgmma.wait_group.sync.aligned %0;" ::"n"(N) : "memory"); }
__host__ __device__ constexpr uint64_t mkdesc(uint32_t addr, uint32_t lbo, uint32_t sbo, uint32_t swz) {
    return (uint64_t)((addr & 0x3FFFF) >> 4) | ((uint64_t)(lbo >> 4) << 16) | ((uint64_t)(sbo >> 4) << 32) | ((uint64_t)swz << 62);
}
__device__ __forceinline__ uint64_t dadd(uint64_t d, uint32_t o) { return (d & 0xffffffff00000000ull) | (uint32_t)((uint32_t)d + o); }
__device__ __forceinline__ void mbar_init(uint32_t b, uint32_t c) { asm volatile("mbarrier.init.shared.b64 [%0], %1;" ::"r"(b), "r"(c) : "memory"); }
__device__ __forceinline__ void mbar_expect(uint32_t b, uint32_t tx) { asm volatile("mbarrier.arrive.expect_tx.shared.b64 _, [%0], %1;" ::"r"(b), "r"(tx) : "memory"); }
__device__ __forceinline__ void mbar_arrive(uint32_t b) { asm volatile("mbarrier.arrive.shared.b64 _, [%0];" ::"r"(b) : "memory"); }
__device__ __forceinline__ void mbar_arrive_cluster(uint32_t b, uint32_t cta) {
    asm volatile("{.reg .b32 r; mapa.shared::cluster.u32 r, %0, %1; mbarrier.arrive.shared::cluster.b64 _, [r];}" ::"r"(b), "r"(cta) : "memory");
}
__device__ __forceinline__ bool mbar_try(uint32_t b, uint32_t par) {
    uint32_t ok;
    asm volatile("{.reg .pred p; mbarrier.try_wait.parity.shared.b64 p, [%1], %2; selp.u32 %0, 1, 0, p;}" : "=r"(ok) : "r"(b), "r"(par) : "memory");
    return ok;
}
__device__ __forceinline__ void mbar_wait(uint32_t b, uint32_t par) {
    int it = 0;
#pragma unroll 1
    while (!mbar_try(b, par)) { spin_guard(++it); }
}
__device__ __forceinline__ void mbar_wait_w(uint32_t b, uint32_t par) {
    int it = 0;
    bool ok;
#pragma unroll 1
    do { ok = __all_sync(~0u, mbar_try(b, par)); spin_guard(++it); } while (!ok);
}
__device__ __forceinline__ void mbar_wait_cluster(uint32_t b, uint32_t par) {
    int it = 0;
    while (true) {
        uint32_t ok;
        asm volatile("{.reg .pred p; mbarrier.try_wait.parity.acquire.cluster.shared::cta.b64 p, [%1], %2; selp.u32 %0, 1, 0, p;}" : "=r"(ok) : "r"(b), "r"(par) : "memory");
        if (ok) break;
        spin_guard(++it);
    }
}
__device__ __forceinline__ void tma2d(uint32_t dst, const CUtensorMap* m, int c0, int c1, uint32_t bar) {
    asm volatile("cp.async.bulk.tensor.2d.shared::cluster.global.mbarrier::complete_tx::bytes [%0], [%1, {%3, %4}], [%2];" ::"r"(dst), "l"(m), "r"(bar), "r"(c0), "r"(c1) : "memory");
}
__device__ __forceinline__ void tma2d_mc(uint32_t dst, const CUtensorMap* m, int c0, int c1, uint32_t bar, uint16_t mask) {
    asm volatile("cp.async.bulk.tensor.2d.shared::cluster.global.mbarrier::complete_tx::bytes.multicast::cluster [%0], [%1, {%3, %4}], [%2], %5;" ::"r"(dst), "l"(m), "r"(bar), "r"(c0), "r"(c1), "h"(mask) : "memory");
}
__device__ __forceinline__ void bulk_g2s(uint32_t dst, const void* src, uint32_t bytes, uint32_t bar) {
    asm volatile("cp.async.bulk.shared::cluster.global.mbarrier::complete_tx::bytes [%0], [%1], %2, [%3];" ::"r"(dst), "l"(src), "r"(bytes), "r"(bar) : "memory");
}
__device__ __forceinline__ void bar_sync(int id, int n) { asm volatile("bar.sync %0, %1;" ::"r"(id), "r"(n) : "memory"); }
__device__ __forceinline__ void bar_arrive(int id, int n) { asm volatile("bar.arrive %0, %1;" ::"r"(id), "r"(n) : "memory"); }
__device__ __forceinline__ void cluster_sync_all() { asm volatile("barrier.cluster.arrive.aligned; barrier.cluster.wait.aligned;" ::: "memory"); }
__device__ __forceinline__ void fence_async_smem() { asm volatile("fence.proxy.async.shared::cta;" ::: "memory"); }
__device__ __forceinline__ void ldsm4t(uint32_t* r, uint32_t a) {
    asm volatile("ldmatrix.sync.aligned.m8n8.x4.trans.shared.b16 {%0,%1,%2,%3}, [%4];" : "=r"(r[0]), "=r"(r[1]), "=r"(r[2]), "=r"(r[3]) : "r"(a) : "memory");
}
__device__ __forceinline__ void ldsm4(uint32_t* r, uint32_t a) {
    asm volatile("ldmatrix.sync.aligned.m8n8.x4.shared.b16 {%0,%1,%2,%3}, [%4];" : "=r"(r[0]), "=r"(r[1]), "=r"(r[2]), "=r"(r[3]) : "r"(a) : "memory");
}
__device__ __forceinline__ uint32_t movm(uint32_t a) {
    uint32_t d; asm volatile("movmatrix.sync.aligned.m8n8.trans.b16 %0, %1;" : "=r"(d) : "r"(a)); return d;
}
__device__ __forceinline__ void mma16816(float* d, uint32_t a0, uint32_t a1, uint32_t a2, uint32_t a3, uint32_t b0, uint32_t b1) {
    asm volatile("mma.sync.aligned.m16n8k16.row.col.f32.bf16.bf16.f32 {%0,%1,%2,%3},{%4,%5,%6,%7},{%8,%9},{%0,%1,%2,%3};"
                 : "+f"(d[0]), "+f"(d[1]), "+f"(d[2]), "+f"(d[3]) : "r"(a0), "r"(a1), "r"(a2), "r"(a3), "r"(b0), "r"(b1));
}
__device__ __forceinline__ void mma16816z(float* d, const uint32_t* a, uint32_t b0, uint32_t b1) {
    asm volatile("mma.sync.aligned.m16n8k16.row.col.f32.bf16.bf16.f32 {%0,%1,%2,%3},{%4,%5,%6,%7},{%8,%9},{%10,%10,%10,%10};"
                 : "=f"(d[0]), "=f"(d[1]), "=f"(d[2]), "=f"(d[3]) : "r"(a[0]), "r"(a[1]), "r"(a[2]), "r"(a[3]), "r"(b0), "r"(b1), "f"(0.f));
}
__device__ __forceinline__ void mma1688(float* d, uint32_t a0, uint32_t a1, uint32_t b0) {
    asm volatile("mma.sync.aligned.m16n8k8.row.col.f32.bf16.bf16.f32 {%0,%1,%2,%3},{%4,%5},{%6},{%0,%1,%2,%3};"
                 : "+f"(d[0]), "+f"(d[1]), "+f"(d[2]), "+f"(d[3]) : "r"(a0), "r"(a1), "r"(b0));
}
__device__ __forceinline__ uint32_t pack2(float lo, float hi) {
    uint32_t r; asm("cvt.rn.bf16x2.f32 %0, %1, %2;" : "=r"(r) : "f"(hi), "f"(lo)); return r;
}
__device__ __forceinline__ uint32_t hadd2(uint32_t a, uint32_t b) {
    uint32_t r; asm("add.rn.bf16x2 %0, %1, %2;" : "=r"(r) : "r"(a), "r"(b)); return r;
}
__device__ __forceinline__ float bflo(uint32_t u) { return __uint_as_float(u << 16); }
__device__ __forceinline__ float bfhi(uint32_t u) { return __uint_as_float(u & 0xffff0000u); }
__device__ __forceinline__ float ex2(float x) { float r; asm("ex2.approx.ftz.f32 %0, %1;" : "=f"(r) : "f"(x)); return r; }
__device__ __forceinline__ uint4 ldg_rlx4(const void* p) {
    uint4 v; asm volatile("ld.relaxed.gpu.global.v4.u32 {%0,%1,%2,%3}, [%4];" : "=r"(v.x), "=r"(v.y), "=r"(v.z), "=r"(v.w) : "l"(p) : "memory"); return v;
}
__device__ __forceinline__ uint2 ldg_rlx2(const void* p) {
    unsigned long long v; asm volatile("ld.relaxed.gpu.global.b64 %0, [%1];" : "=l"(v) : "l"(p) : "memory");
    return make_uint2((uint32_t)v, (uint32_t)(v >> 32));
}
__device__ __forceinline__ uint32_t ldg_rlx1(const void* p) {
    uint32_t v; asm volatile("ld.relaxed.gpu.global.u32 %0, [%1];" : "=r"(v) : "l"(p) : "memory"); return v;
}
__device__ __forceinline__ void stg_rlx1(void* p, uint32_t v) { asm volatile("st.relaxed.gpu.global.u32 [%0], %1;" ::"l"(p), "r"(v) : "memory"); }
__device__ __forceinline__ void stg_rlx2(void* p, uint32_t x, uint32_t y) {
    unsigned long long v = (unsigned long long)x | ((unsigned long long)y << 32);
    asm volatile("st.relaxed.gpu.global.b64 [%0], %1;" ::"l"(p), "l"(v) : "memory");
}
__device__ __forceinline__ void stg_rlx4(void* p, uint32_t x, uint32_t y, uint32_t z, uint32_t w) {
    asm volatile("st.relaxed.gpu.global.v4.u32 [%0], {%1,%2,%3,%4};" ::"l"(p), "r"(x), "r"(y), "r"(z), "r"(w) : "memory");
}
__device__ __forceinline__ void sts4(uint32_t a, uint32_t x, uint32_t y, uint32_t z, uint32_t w) {
    asm volatile("st.shared.v4.u32 [%0], {%1,%2,%3,%4};" ::"r"(a), "r"(x), "r"(y), "r"(z), "r"(w) : "memory");
}
__device__ __forceinline__ uint4 lds4(uint32_t a) {
    uint4 v; asm volatile("ld.shared.v4.u32 {%0,%1,%2,%3}, [%4];" : "=r"(v.x), "=r"(v.y), "=r"(v.z), "=r"(v.w) : "r"(a) : "memory"); return v;
}
__device__ __forceinline__ void st_async4(uint32_t a, float x, float y, float z, float w, uint32_t bar) {
    asm volatile("st.async.shared::cluster.mbarrier::complete_tx::bytes.v4.f32 [%0], {%1,%2,%3,%4}, [%5];" ::"r"(a), "f"(x), "f"(y), "f"(z), "f"(w), "r"(bar) : "memory");
}
#define F4(d, i) "+f"(d[i]), "+f"(d[i + 1]), "+f"(d[i + 2]), "+f"(d[i + 3])
__device__ __forceinline__ void wgmma_rs32(float* d, const uint32_t* a, uint64_t b, int sc) {
    asm volatile("{.reg .pred p; setp.ne.b32 p, %21, 0;\n wgmma.mma_async.sync.aligned.m64n32k16.f32.bf16.bf16 {%0,%1,%2,%3,%4,%5,%6,%7,%8,%9,%10,%11,%12,%13,%14,%15}, {%16,%17,%18,%19}, %20, p, 1, 1, 0;}"
                 : F4(d, 0), F4(d, 4), F4(d, 8), F4(d, 12) : "r"(a[0]), "r"(a[1]), "r"(a[2]), "r"(a[3]), "l"(b), "r"(sc));
}
__device__ __forceinline__ void wgmma_ss32(float* d, uint64_t a, uint64_t b, int sc) {
    asm volatile("{.reg .pred p; setp.ne.b32 p, %18, 0;\n wgmma.mma_async.sync.aligned.m64n32k16.f32.bf16.bf16 {%0,%1,%2,%3,%4,%5,%6,%7,%8,%9,%10,%11,%12,%13,%14,%15}, %16, %17, p, 1, 1, 1, 0;}"
                 : F4(d, 0), F4(d, 4), F4(d, 8), F4(d, 12) : "l"(a), "l"(b), "r"(sc));
}
__device__ __forceinline__ void wgmma_rs40(float* d, const uint32_t* a, uint64_t b, int sc) {
    asm volatile("{.reg .pred p; setp.ne.b32 p, %25, 0;\n wgmma.mma_async.sync.aligned.m64n40k16.f32.bf16.bf16 {%0,%1,%2,%3,%4,%5,%6,%7,%8,%9,%10,%11,%12,%13,%14,%15,%16,%17,%18,%19}, {%20,%21,%22,%23}, %24, p, 1, 1, 0;}"
                 : F4(d, 0), F4(d, 4), F4(d, 8), F4(d, 12), F4(d, 16) : "r"(a[0]), "r"(a[1]), "r"(a[2]), "r"(a[3]), "l"(b), "r"(sc));
}
__device__ __forceinline__ void wgmma_ss40(float* d, uint64_t a, uint64_t b, int sc) {
    asm volatile("{.reg .pred p; setp.ne.b32 p, %22, 0;\n wgmma.mma_async.sync.aligned.m64n40k16.f32.bf16.bf16 {%0,%1,%2,%3,%4,%5,%6,%7,%8,%9,%10,%11,%12,%13,%14,%15,%16,%17,%18,%19}, %20, %21, p, 1, 1, 1, 0;}"
                 : F4(d, 0), F4(d, 4), F4(d, 8), F4(d, 12), F4(d, 16) : "l"(a), "l"(b), "r"(sc));
}
#define F16(d, i) F4(d, i), F4(d, i + 4), F4(d, i + 8), F4(d, i + 12)
template <int TA>
__device__ __forceinline__ void wgmma_ss128(float* d, uint64_t a, uint64_t b, int sc) {
    asm volatile("{.reg .pred p; setp.ne.b32 p, %66, 0;\n wgmma.mma_async.sync.aligned.m64n128k16.f32.bf16.bf16 "
                 "{%0,%1,%2,%3,%4,%5,%6,%7,%8,%9,%10,%11,%12,%13,%14,%15,%16,%17,%18,%19,%20,%21,%22,%23,%24,%25,%26,%27,%28,%29,%30,%31,"
                 "%32,%33,%34,%35,%36,%37,%38,%39,%40,%41,%42,%43,%44,%45,%46,%47,%48,%49,%50,%51,%52,%53,%54,%55,%56,%57,%58,%59,%60,%61,%62,%63}, %64, %65, p, 1, 1, %67, 1;}"
                 : F16(d, 0), F16(d, 16), F16(d, 32), F16(d, 48) : "l"(a), "l"(b), "r"(sc), "n"(TA));
}

__device__ __forceinline__ float warp_sum(float v) {
#pragma unroll
    for (int o = 16; o; o >>= 1) v += __shfl_xor_sync(~0u, v, o);
    return v;
}
__device__ __forceinline__ float bfround(float x) { return __bfloat162float(__float2bfloat16(x)); }

__device__ __forceinline__ void wait_count1(const uint32_t* p, uint32_t target) {
    int it = 0;
#pragma unroll 1
    while (true) {
        uint32_t v;
        asm volatile("ld.acquire.gpu.global.u32 %0, [%1];" : "=r"(v) : "l"(p) : "memory");
        if (v >= target) break;
        spin_guard(++it);
    }
}
__device__ __forceinline__ void red2(float* p, float a, float b) {
    asm volatile("red.relaxed.gpu.global.add.v2.f32 [%0], {%1, %2};" ::"l"(p), "f"(a), "f"(b) : "memory");
}
__device__ __forceinline__ void l2_prefetch(const void* p, uint32_t bytes) {
    asm volatile("cp.async.bulk.prefetch.L2.global [%0], %1;" ::"l"(p), "r"(bytes) : "memory");
}
__device__ __forceinline__ void signal_count(uint32_t* p) { asm volatile("red.release.gpu.global.add.u32 [%0], 1;" ::"l"(p) : "memory"); }
__device__ __forceinline__ void e_expect(uint32_t b, uint32_t tx) {
    asm volatile("{.reg .pred p; elect.sync _|p, 0xffffffff; @p mbarrier.arrive.expect_tx.shared.b64 _, [%0], %1;}" ::"r"(b), "r"(tx) : "memory");
}
__device__ __forceinline__ void e_tma2d(uint32_t dst, const CUtensorMap* m, int c0, int c1, uint32_t bar) {
    asm volatile("{.reg .pred p; elect.sync _|p, 0xffffffff;\n @p cp.async.bulk.tensor.2d.shared::cluster.global.mbarrier::complete_tx::bytes [%0], [%1, {%3, %4}], [%2];}"
                 ::"r"(dst), "l"(m), "r"(bar), "r"(c0), "r"(c1) : "memory");
}
__device__ __forceinline__ void e_tma2d_mc(uint32_t dst, const CUtensorMap* m, int c0, int c1, uint32_t bar) {
    asm volatile("{.reg .pred p; elect.sync _|p, 0xffffffff;\n @p cp.async.bulk.tensor.2d.shared::cluster.global.mbarrier::complete_tx::bytes.multicast::cluster [%0], [%1, {%3, %4}], [%2], %5;}"
                 ::"r"(dst), "l"(m), "r"(bar), "r"(c0), "r"(c1), "h"((uint16_t)3) : "memory");
}
__device__ __forceinline__ void e_prefetch(const void* p, uint32_t bytes) {
    asm volatile("{.reg .pred p; elect.sync _|p, 0xffffffff; @p cp.async.bulk.prefetch.L2.global [%0], %1;}" ::"l"(p), "r"(bytes) : "memory");
}
__device__ __forceinline__ void wait_count_w(const uint32_t* p, uint32_t target) {
    int it = 0;
#pragma unroll 1
    while (true) {
        uint32_t v;
        asm volatile("ld.acquire.gpu.global.u32 %0, [%1];" : "=r"(v) : "l"(p) : "memory");
        if (__all_sync(~0u, v >= target)) break;
        spin_guard(++it);
    }
}

__device__ __forceinline__ void ln_row(float* x) {
    float s = 0;
#pragma unroll
    for (int i = 0; i < 32; i++) s += x[i];
    float m = warp_sum(s) * (1.0f / DM);
    float q = 0;
#pragma unroll
    for (int i = 0; i < 32; i++) { x[i] -= m; q += x[i] * x[i]; }
    float r = rsqrtf(warp_sum(q) * (1.0f / DM) + 1e-5f);
#pragma unroll
    for (int i = 0; i < 32; i++) x[i] *= r;
}
__device__ __forceinline__ uint4 pack8(const float* x) {
    return make_uint4(pack2(x[0], x[1]), pack2(x[2], x[3]), pack2(x[4], x[5]), pack2(x[6], x[7]));
}
#define NL 6
constexpr uint32_t SM_HB = 16384, HBK = 5120, SM_SX = 57344, SM_OX = 122880, SM_PX = 124928, SM_PA = 126976, SM_WO = 147456,
                   SM_TAB = 212992, SM_PRE = SM_TAB, SM_BAR = 227328, SM_REC_TOTAL = 227328 + 256;
constexpr uint32_t SB0 = 1024;
constexpr int B_WO = 0, B_HE = 1, B_ROLE = 2, B_HB = 3, B_W = 5;
constexpr int NB_MEM = 1, NB_QK = 2, NB_X1 = 3, NB_X2 = 4, NB_WIN = 5, NB_WG = 6, NB_KDONE = 7, NB_FIN0 = 8, NB_P = 9, NB_PX = 10, NB_G = 11, NB_A = 12, NB_B = 13, NB_C = 14, NB_S = 15;
#define SPF 33
#define SPF_AT 54
#define SPF_R 12
#define SPF_NS 40
#define D_TPV 100
#define V_POS 2
#define D_X2 470
#define D_TV 50
#define D_V 390
#define D_NEAR 1670
#define D_FAR (D_NEAR - 140)
#define E_MUL 28
#define D_WF 60
#define NE 0
#define D_H 0
#define D_W2 170
#define SETTLE 0
#define TV_POS 1
#define D_PA 0
#define NE1 10
#define H_POS 3
#define PA_POS 1
#define K_DLY 0
#define ST_BAR 1
#define W1_AT -1
#define ROT 2
#define ALIGN 0
#define CNT32 0
#define O_POS 1
#define Z_POS 0
#define QF_LATE 100
#define W0_E 3
#define G_AT 24
#define W0_AT 4
#define W0_RS (NL - 1)
#define P_GATE 0
#define NPF (NL + 6)

struct Delays { uint32_t near, far, x2, v, w2, pa, wf, tv; };
#define MISS(i, v)
#define MISS_INIT
#define MISS_OUT
#define HT(i)
#define PROF_INIT
#define PROF(i)
#define PROFV(i, v)
#define PROF_OUT

__device__ __forceinline__ uint32_t clk32() { uint32_t t; asm volatile("mov.u32 %0, %%clock;" : "=r"(t) :: "memory"); return t; }
__device__ __forceinline__ uint32_t smid() { uint32_t t; asm volatile("mov.u32 %0, %%smid;" : "=r"(t)); return t; }
__device__ __forceinline__ uint32_t gtime() { uint32_t t; asm volatile("mov.u32 %0, %%globaltimer_lo;" : "=r"(t) :: "memory"); return t; }
__device__ __forceinline__ void spin_until(uint32_t t0, uint32_t d) { while (clk32() - t0 < d) {} }
template <int N> __device__ __forceinline__ uint32_t delay(uint32_t zero) {
    float x = __uint_as_float(clk32());
#pragma unroll
    for (int i = 0; i < N; i++) asm volatile("ex2.approx.ftz.f32 %0, %0;" : "+f"(x));
    return __float_as_uint(x) & zero;
}
__device__ __forceinline__ uint32_t opaque(uint32_t v) { return __shfl_sync(~0u, v, threadIdx.x & 31); }
__device__ __forceinline__ uint32_t xor_or(uint32_t a, uint32_t b, uint32_t t) {
    uint32_t r; asm volatile("lop3.b32 %0, %1, %2, %3, 0x7E;" : "=r"(r) : "r"(a), "r"(b), "r"(t)); return r;
}
__device__ __forceinline__ uint32_t or3(uint32_t a, uint32_t b, uint32_t c) {
    uint32_t r; asm volatile("lop3.b32 %0, %1, %2, %3, 0xFE;" : "=r"(r) : "r"(a), "r"(b), "r"(c)); return r;
}
__device__ __forceinline__ uint32_t settag(uint32_t v, uint32_t tag) {
    uint32_t r; asm("lop3.b32 %0, %1, 1, %2, 0xB8;" : "=r"(r) : "r"(v), "r"(tag)); return r;
}
__device__ __forceinline__ void ldg4_if(uint4& v, const void* p, bool c) {
    asm volatile("{.reg .pred p; setp.ne.u32 p, %5, 0; @p ld.relaxed.gpu.global.v4.u32 {%0,%1,%2,%3}, [%4];}"
                 : "+r"(v.x), "+r"(v.y), "+r"(v.z), "+r"(v.w) : "l"(p), "r"((uint32_t)c) : "memory");
}
__device__ __forceinline__ uint4 ldg_rlx2x2(const void* p) {
    unsigned long long a, b;
    asm volatile("ld.relaxed.gpu.global.v2.b64 {%0,%1}, [%2];" : "=l"(a), "=l"(b) : "l"(p) : "memory");
    return make_uint4((uint32_t)a, (uint32_t)(a >> 32), (uint32_t)b, (uint32_t)(b >> 32));
}
__device__ __forceinline__ void stg_rlx2x2(void* p, uint32_t x, uint32_t y, uint32_t z, uint32_t w) {
    asm volatile("{.reg .b64 a, b; mov.b64 a, {%1,%2}; mov.b64 b, {%3,%4}; st.relaxed.gpu.global.v2.b64 [%0], {a, b};}" ::"l"(p), "r"(x), "r"(y), "r"(z), "r"(w) : "memory");
}
__device__ __forceinline__ void ldg1_if(uint32_t& v, const void* p, bool c) {
    asm volatile("{.reg .pred p; setp.ne.u32 p, %2, 0; @p ld.relaxed.gpu.global.u32 %0, [%1];}" : "+r"(v) : "l"(p), "r"((uint32_t)c) : "memory");
}
__device__ __forceinline__ void sts2(uint32_t a, float x, float y) { asm volatile("st.shared.v2.f32 [%0], {%1,%2};" ::"r"(a), "f"(x), "f"(y) : "memory"); }
__device__ __forceinline__ void sts4f(uint32_t a, float x, float y, float z, float w) {
    asm volatile("st.shared.v4.f32 [%0], {%1,%2,%3,%4};" ::"r"(a), "f"(x), "f"(y), "f"(z), "f"(w) : "memory");
}
__device__ __forceinline__ void sts1(uint32_t a, uint32_t x) { asm volatile("st.shared.u32 [%0], %1;" ::"r"(a), "r"(x) : "memory"); }
__device__ __forceinline__ uint32_t lds1(uint32_t a) { uint32_t v; asm volatile("ld.shared.u32 %0, [%1];" : "=r"(v) : "r"(a) : "memory"); return v; }
__device__ __forceinline__ float4 lds4f(uint32_t a) {
    float4 v; asm volatile("ld.shared.v4.f32 {%0,%1,%2,%3}, [%4];" : "=f"(v.x), "=f"(v.y), "=f"(v.z), "=f"(v.w) : "r"(a) : "memory"); return v;
}
__device__ __forceinline__ float2 lds2f(uint32_t a) {
    float2 v; asm volatile("ld.shared.v2.f32 {%0,%1}, [%2];" : "=f"(v.x), "=f"(v.y) : "r"(a) : "memory"); return v;
}
__device__ __forceinline__ bool any_bit0(uint32_t x) {
    uint32_t r;
    asm volatile("{.reg .pred p, q; .reg .b32 t; and.b32 t, %1, 1; setp.ne.u32 p, t, 0; vote.sync.any.pred q, p, 0xffffffff; selp.u32 %0, 1, 0, q;}" : "=r"(r) : "r"(x));
    return r;
}
__device__ __forceinline__ float rcp_fast(float x) { float r; asm("rcp.approx.ftz.f32 %0, %1;" : "=f"(r) : "f"(x)); return r; }
__device__ __forceinline__ void stsm4(uint32_t a, uint32_t r0, uint32_t r1, uint32_t r2, uint32_t r3) {
    asm volatile("stmatrix.sync.aligned.m8n8.x4.shared.b16 [%0], {%1,%2,%3,%4};" ::"r"(a), "r"(r0), "r"(r1), "r"(r2), "r"(r3) : "memory");
}
__device__ __forceinline__ void stsm4t(uint32_t a, uint32_t r0, uint32_t r1, uint32_t r2, uint32_t r3) {
    asm volatile("stmatrix.sync.aligned.m8n8.x4.trans.shared.b16 [%0], {%1,%2,%3,%4};" ::"r"(a), "r"(r0), "r"(r1), "r"(r2), "r"(r3) : "memory");
}
__device__ __forceinline__ uint32_t and3(uint32_t a, uint32_t b, uint32_t c) {
    uint32_t r; asm("lop3.b32 %0, %1, %2, %3, 0x80;" : "=r"(r) : "r"(a), "r"(b), "r"(c)); return r;
}
__device__ __forceinline__ void red_mem(void* p, uint32_t x, uint32_t y, uint32_t z, uint32_t w, void* q, uint32_t e, bool c) {
    asm volatile("{.reg .pred p; setp.ne.u32 p, %7, 0; red.relaxed.gpu.global.add.noftz.v4.bf16x2 [%0], {%1,%2,%3,%4}; @p red.relaxed.gpu.global.add.noftz.bf16x2 [%5], %6;}"
                 ::"l"(p), "r"(x), "r"(y), "r"(z), "r"(w), "l"(q), "r"(e), "r"((uint32_t)c) : "memory");
}
__device__ __forceinline__ void stg4_if(bool c, void* p, uint32_t x) {
    asm volatile("{.reg .pred p; setp.ne.u32 p, %2, 0; @p st.relaxed.gpu.global.v4.u32 [%0], {%1,%1,%1,%1};}" ::"l"(p), "r"(x), "r"((uint32_t)c) : "memory");
}
__device__ __forceinline__ uint32_t max3u(uint32_t a, uint32_t b, uint32_t c) { return __vimax3_u32(a, b, c); }
__device__ __forceinline__ void fence_gpu() { asm volatile("fence.acq_rel.gpu;" ::: "memory"); }

__device__ __forceinline__ void h_load(uint32_t sb, const uint8_t* hsrc, int pass, uint32_t rank, uint32_t rot) {
    const uint8_t* src = hsrc + (size_t)pass * 65536;
    const uint32_t bar = sb + SM_BAR + 8 * (B_HB + (pass & 1)), dst = sb + SM_HB + (pass & 1) * 65536 + rank * 4 * HBK;
    e_expect(bar, 32768);
#pragma unroll 1
    for (int i = 0; i < H_PIECES; i++) {
        const uint32_t o = ((i + rot) & (H_PIECES - 1)) * (16384 / H_PIECES);
        asm volatile("{.reg .pred p; elect.sync _|p, 0xffffffff;\n"
                     " @p cp.async.bulk.shared::cluster.global.mbarrier::complete_tx::bytes.multicast::cluster [%0], [%1], %4, [%2], %3;}"
                     ::"r"(dst + o + (o >> 12) * 1024), "l"(src + o), "r"(bar), "h"((uint16_t)3), "n"(16384 / H_PIECES) : "memory");
    }
}
__device__ __forceinline__ void h_piece(uint32_t sb, const uint8_t* hsrc, int pass, uint32_t rank, uint32_t i, bool first) {
    const uint32_t bar = sb + SM_BAR + 8 * (B_HB + (pass & 1));
    asm volatile("{.reg .pred p, q; elect.sync _|p, 0xffffffff; setp.le.and.s32 p, %5, 64, p; setp.ne.and.u32 q, %4, 0, p;\n"
                 " @q mbarrier.arrive.expect_tx.shared.b64 _, [%2], 32768;\n"
                 " @p cp.async.bulk.shared::cluster.global.mbarrier::complete_tx::bytes.multicast::cluster [%0], [%1], 4096, [%2], %3;}"
                 ::"r"(sb + SM_HB + (pass & 1) * 65536 + (rank * 4 + i) * HBK), "l"(hsrc + (uint32_t)(pass * 65536 + i * 4096)), "r"(bar), "h"((uint16_t)3), "r"((uint32_t)first), "r"(pass) : "memory");
}
__device__ __forceinline__ uint4 ldg_b128(const void* p) {
    uint4 v;
    asm volatile("{.reg .b128 t; .reg .b64 a, b; ld.relaxed.gpu.global.b128 t, [%4]; mov.b128 {a, b}, t; mov.b64 {%0,%1}, a; mov.b64 {%2,%3}, b;}"
                 : "=r"(v.x), "=r"(v.y), "=r"(v.z), "=r"(v.w) : "l"(p) : "memory");
    return v;
}
__device__ __forceinline__ void ldg_b128_into(uint4& v, const void* p) {
    asm volatile("{.reg .b128 t; .reg .b64 a, b; ld.relaxed.gpu.global.b128 t, [%4]; mov.b128 {a, b}, t; mov.b64 {%0,%1}, a; mov.b64 {%2,%3}, b;}"
                 : "+r"(v.x), "+r"(v.y), "+r"(v.z), "+r"(v.w) : "l"(p) : "memory");
}
__device__ __forceinline__ void stg_b128_if(bool c, void* p, uint32_t x, uint32_t y, uint32_t z, uint32_t w) {
    asm volatile("{.reg .pred p; setp.ne.u32 p, %5, 0; @p st.relaxed.gpu.global.v4.u32 [%0], {%1,%2,%3,%4};}"
                 ::"l"(p), "r"(x), "r"(y), "r"(z), "r"(w), "r"((uint32_t)c) : "memory");
}
__device__ __forceinline__ float pretag(float x, uint32_t add, uint32_t keep) { return __uint_as_float((__float_as_uint(x) + add) & keep); }

template <class F, class G>
__device__ __forceinline__ void softmax_rows(uint32_t src, uint32_t dst, uint32_t g16, int row0, F ready, G mid) {
    const uint32_t u = (g16 >> 7) & 3, e = ((g16 >> 9) << 3) | ((g16 >> 4) & 7);
    uint32_t se = src + e * 8, su = se + u * 1088, d0 = dst + e * 16 + u * 4, d1 = dst + 512 + e * 4;
    int vis = row0 + (e >> 2) - 2 * (e & 3) - 8 * u;
    asm volatile("" : "+r"(se), "+r"(su), "+r"(d0), "+r"(d1), "+r"(vis));
    ready();
    const float2 p0 = lds2f(su), p1 = lds2f(su + 256), p2 = lds2f(su + 512), p3 = lds2f(su + 768);
    const float2 m0 = lds2f(se + 4352), m1 = lds2f(se + 4352 + 256), m2 = lds2f(se + 4352 + 512), m3 = lds2f(se + 4352 + 768);
    float a0 = (p0.x + p1.x) + (p2.x + p3.x), a1 = (p0.y + p1.y) + (p2.y + p3.y);
    const float a2 = (m0.x + m1.x) + (m2.x + m3.x), a3 = (m0.y + m1.y) + (m2.y + m3.y);
    if (vis < 0) a0 = -1e9f / 0.08838834764831845f;
    if (vis < 1) a1 = -1e9f / 0.08838834764831845f;
    int k = __float_as_int(fmaxf(fmaxf(a0, a1), fmaxf(a2, a3)));
    k ^= (k >> 31) & 0x7fffffff;
    const bool hi = g16 & 64;
    const int k0 = __reduce_max_sync(~0u, hi ? INT_MIN : k), k1 = __reduce_max_sync(~0u, hi ? k : INT_MIN);
    mid();
    k = hi ? k1 : k0;
    const float m = __int_as_float(k ^ ((k >> 31) & 0x7fffffff));
    const float sl2 = 0.08838834764831845f * 1.4426950408889634f, mb = -m * sl2;
    sts1(d0, pack2(ex2(fmaf(a0, sl2, mb)), ex2(fmaf(a1, sl2, mb))));
    sts1(d1, pack2(ex2(fmaf(a2, sl2, mb)), ex2(fmaf(a3, sl2, mb))));
}

__device__ __forceinline__ uint32_t pack_h2(float lo, float hi) {
    uint32_t r; asm("cvt.rn.satfinite.f16x2.f32 %0, %1, %2;" : "=r"(r) : "f"(hi), "f"(lo)); return r;
}
__device__ __forceinline__ float2 unpack_h2(uint32_t u) {
    float2 r; asm("{.reg .b16 l, h; mov.b32 {l, h}, %2; cvt.f32.f16 %0, l; cvt.f32.f16 %1, h;}" : "=f"(r.x), "=f"(r.y) : "r"(u)); return r;
}
__device__ __forceinline__ uint32_t add_h2(uint32_t a, uint32_t b) { uint32_t r; asm("add.rn.f16x2 %0, %1, %2;" : "=r"(r) : "r"(a), "r"(b)); return r; }
__device__ __forceinline__ uint32_t max_h2(uint32_t a, uint32_t b) { uint32_t r; asm("max.f16x2 %0, %1, %2;" : "=r"(r) : "r"(a), "r"(b)); return r; }
__device__ __forceinline__ void stg2_if(bool c, void* p, uint32_t x, uint32_t y) {
    asm volatile("{.reg .pred p; .reg .b64 v; setp.ne.u32 p, %3, 0; mov.b64 v, {%1, %2}; @p st.relaxed.gpu.global.b64 [%0], v;}" ::"l"(p), "r"(x), "r"(y), "r"((uint32_t)c) : "memory");
}
__device__ __forceinline__ void stg1_if(bool c, void* p, uint32_t x) {
    asm volatile("{.reg .pred p; setp.ne.u32 p, %2, 0; @p st.relaxed.gpu.global.u32 [%0], %1;}" ::"l"(p), "r"(x), "r"((uint32_t)c) : "memory");
}
struct U2 { uint32_t x, y; };
__device__ __forceinline__ U2 ldg_u2(const void* p) {
    U2 v; asm volatile("{.reg .b64 t; ld.relaxed.gpu.global.b64 t, [%2]; mov.b64 {%0, %1}, t;}" : "=r"(v.x), "=r"(v.y) : "l"(p) : "memory"); return v;
}
constexpr int POLL_LIMIT = 1 << 16;
constexpr float SM_L2E = 0.08838834764831845f * 1.4426950408889634f;
template <int V> struct IC { static constexpr int value = V; };
typedef unsigned long long u64;
__device__ __forceinline__ uint32_t lo32(u64 v) { return (uint32_t)v; }
__device__ __forceinline__ uint32_t hi32(u64 v) { return (uint32_t)(v >> 32); }
__device__ __forceinline__ u64 ldg_u64(const void* p) { u64 v; asm volatile("ld.relaxed.gpu.global.b64 %0, [%1];" : "=l"(v) : "l"(p) : "memory"); return v; }
__device__ __forceinline__ void ldg_u64_if(u64& v, const void* p, bool c) {
    asm volatile("{.reg .pred p; setp.ne.u32 p, %2, 0; @p ld.relaxed.gpu.global.b64 %0, [%1];}" : "+l"(v) : "l"(p), "r"((uint32_t)c) : "memory");
}
__device__ __forceinline__ void rec_main(uint32_t sb, const CUtensorMap* tWo, uint8_t* arena, int role, int hinfo, int wg, uint32_t zero, const Delays& dly) {
    const int hA = hinfo & 255;
    const int tid = threadIdx.x, t = tid & 127, lane = tid & 31, wi = t >> 5;
    const uint32_t bars = sb + SM_BAR;
    const int head = role >> 2, qd = role & 3, j = blockIdx.x & 1, kh = role & 1;
    const uint32_t mypar = head >= hA;
    const bool warp0 = __all_sync(~0u, wi == 0), warp1 = __all_sync(~0u, wi == 1);
    const uint8_t* hsrc = (const uint8_t*)g_himg + kh * 32768 + j * 16384;
    auto tokbase = [&](int ty) { return ((ty + 1) << 21) + blk(lb_tok(head), mypar ^ ((hinfo >> (8 + ty)) & 1)); };
    const uint32_t tbw = tokbase(wg), tbq = tokbase(0) + (qd >> 1) * 2048 + (qd & 1) * 8;
    uint32_t w[32 - NL][4];
    const uint32_t frow = ((lane >> 4) * 8 + (lane & 7)) * 128, fx = ((lane >> 3) & 1) ^ (lane & 7);
    const uint32_t wl0 = sb + wg * 65536 + frow + ((fx ^ (2 * wi)) << 4);
    {
#pragma unroll 1
        for (int i = 0; i < 4; i++) mbar_wait_w(bars + 8 * (B_W + (wg == 2 ? 8 + i : 2 * i + wg)), 0);
#pragma unroll
        for (int p = NL; p < 32; p++) ldsm4t(w[p - NL], wl0 + p * 2048);
        fence_async_smem();
        if (wg < 2) bar_sync(NB_WG, 256);
        if (wg > 0) wait_count_w(&g_tick[32 + (lane & 3) * 8], 1);
        if (wg == 1 && warp0) {
            if (lane == 0) mbar_arrive_cluster(bars + 8 * B_HE, j ^ 1);
            asm volatile("fence.proxy.async.global;" ::: "memory");
            mbar_wait_w(bars + 8 * B_HE, 0);
#pragma unroll 1
            for (int i = 0; i < 2; i++) h_load(sb, hsrc, i, j, head);
        }
        TL(3 + wg)
    }
    uint32_t g16 = opaque(t * 16);
    auto G16 = [&]() { asm volatile("" : "+r"(g16)); return g16; };
    const uint32_t wu = __reduce_max_sync(~0u, wi), sbl = sb - wu * 512;
    const uint32_t xso = blk(lb_x2(head), mypar), cu = kh * 2048 + (2 * j + (wu >> 1)) * 512;
    const uint32_t u_xo = xso + wg * 16384 + (wu & 1) * 2048 + (cu >> 1) - wu * 256, u_to = tbw + (wu & 1) * 16384 + cu - wu * 512;
    const uint32_t mrow = wg < 2 ? mem_row(wu >> 1, wg * 2 + (wu & 1), qd) : mem_row(kh, wu, 0);
    const uint32_t u_m = mrow - wu * 512, u_e = mrow + 512 - wu * (CNT32 ? 64 : 128);
#define TAB(i) lds1(sb + SM_TAB + (i) * 512 + (G16() >> 2))
    {
        const uint32_t r8 = lane & 7;
        bar_sync(NB_X2, 384);
        if (wg == 0 && lane == 0) {
            mbar_expect(bars + 8 * B_WO, 16384);
            tma2d(sb + SM_WO + wi * 16384, tWo, (wi >> 1) * 512 + qd * 128 + (wi & 1) * 64, head * DH, bars + 8 * B_WO);
            tma2d(sb + SM_WO + wi * 16384 + 8192, tWo, (wi >> 1) * 512 + qd * 128 + (wi & 1) * 64, head * DH + 64, bars + 8 * B_WO);
        }
        __syncwarp();
        const uint32_t tb = sb + SM_TAB + wg * 1536 + t * 4, ma = sb + SM_HB + 4096 + r8 * 128;
        if (wg < 2) {
            sts1(tb, sb + SM_WO + wi * 16384 + frow + ((fx ^ (2 * wg)) << 4));
            sts1(tb + 512, wl0);
            sts1(tb + 1024, ma + (((lane >> 3) ^ r8) << 4));
        } else {
            sts1(tb, ma + (wi & 1) * HBK + ((((wi & 2) + (lane >> 4) * 4 + ((lane >> 3) & 1)) ^ r8) << 4));
            sts1(tb + 512, ((((wi & 2) + 5) ^ r8) << 4) + ((CNT32 ? (lane & 3) == 3 : lane & 1) ? ma + ((wi & 1) + (lane >> 3) * 2) * HBK : sb + SM_HB - 128));
            sts1(tb + 1024, mem_row(role >> 6, (role >> 4) & 3, (role >> 2) & 3) + (lane < 8 ? qd * 128 + lane * 16 : 512 + qd * 32 + (lane & 1) * 16));
        }
    }
    PROF_INIT
    MISS_INIT
#define HB(ks) dadd(mkdesc(SB0 + SM_HB + ((ks) >> 2) * HBK + ((ks) & 3) * 32, 16, 1024, 1), hbo)
#define STEP_CONSTS                                                                                  \
    const uint32_t tag = (s & 1) ^ 1, ttag = ((s >> 1) & 1) ^ 1, tso = (s & 1) * 32768;              \
    G16();                            \
    const int p = s + 2, b = p & 1;                                                                  \
    uint32_t hbo = b * 4096, fz[5] = {0, 0, 0, 0, 0};                                                \
    const uint32_t ftag = (((p - 1) >> 1) & 1) ^ 1, ptag = ((p >> 1) & 1) ^ 1;                       \
    const uint32_t pso = tbw + (1 << 20) + (b ^ 1) * 32768 + j * 16384 + kh * 2048;
#define SCHED_FENCE(i) fz[i] = clk32();
#define FZ ((fz[0] | fz[1] | fz[2] | fz[3] | fz[4]) & zero)
#define BLOCK_FENCE asm volatile("pmevent 0;" ::: "memory");
    constexpr int GAP = 32 / NL;
#define l16 (sbl + g16)
#define g8 (g16 >> 1)
    uint4 u, v;
    uint8_t *pdst, *fdst;
    auto tok_pack = [&](int ty, const float* acc, uint32_t ftag, uint32_t ptag, bool later = false) {
        const bool tg = ty == 2 || !(g16 & 64);
        const uint32_t add = tg ? (ftag ^ 1) << 16 : 0u, keep = tg ? 0xfffe0000u : ~0u;
        const uint32_t add1 = ty == 2 ? 0u : add, keep1 = ty == 2 ? ~0u : keep;
        const uint32_t add2 = ty == 0 ? add : 0u, keep2 = ty == 0 ? keep : ~0u;
        v = {pack2(pretag(acc[0], add, keep), pretag(acc[1], add1, keep1)), pack2(acc[2], acc[3]),
             pack2(pretag(acc[4], add2, keep2), pretag(acc[5], add2, keep2)), pack2(acc[6], acc[7])};
        if (ty < 2) { v.x = movm(v.x); v.z = movm(v.z); v.y = movm(v.y); v.w = movm(v.w); }
        u = {pack2(pretag(acc[8], (ptag ^ 1) << 16, 0xfffe0000u), acc[9]) | ptag, pack2(acc[10], acc[11]), pack2(acc[12], acc[13]), pack2(acc[14], acc[15])};
        if (later) return;
        v.x = settag(v.x, ftag);
        if (ty == 0) v.z = settag(v.z, ftag);
    };

#pragma unroll 1
    for (int s = -2; s < 0; s++) {
        STEP_CONSTS
        (void)tag; (void)ttag; (void)tso; (void)fz;
        float acc[16];
        mbar_wait_w(bars + 8 * (B_HB + b), 0);
        wg_fence();
#pragma unroll
        for (int i = 0; i < 32; i++) {
            if (i < NL) wgmma_ss32(acc, dadd(mkdesc(SB0 + i * 2048, 8192, 1024, 1), wg * 4096), HB(i), i != 0);
            else wgmma_rs32(acc, w[i < NL ? 0 : i - NL], HB(i), 1);
        }
        wg_commit();
        uint4 pa;
        int it = 0;
#pragma unroll 1
        do pa = ldg_b128(arena + (pso + g16)); while ((p > 0) & any_bit0(pa.x ^ ftag) & (++it < POLL_LIMIT));
        pdst = arena + ((pso ^ (32768 + 2048)) + G16());
        fdst = arena + ((b ^ 1) * 32768 + u_to + g16);
        wg_wait<0>();
#pragma unroll
        for (int k = 0; k < 4; k++) { acc[2 * k] += bflo((&pa.x)[k]); acc[2 * k + 1] += bfhi((&pa.x)[k]); }
        tok_pack(wg, acc, ftag, ptag);
        stg_b128_if(true, pdst, u.x, u.y, u.z, u.w);
        stg_b128_if(p > 0, fdst, v.x, v.y, v.z, v.w);
        if (p == 0) {
            TL(2)
            bar_sync(NB_MEM, 384);
            if (wg == 1 && warp0) {
                if (g16 == 0) mbar_arrive_cluster(bars + 8 * B_HE, j ^ 1);
                mbar_wait_w(bars + 8 * B_HE, 1);
                h_load(sb, hsrc, 2, j, head);
            }
        }
    }

    auto qk_loop = [&](auto wgc) {
        constexpr int WG = decltype(wgc)::value;
        uint32_t w0[NL][4], lm0;
        auto w0_load = [&]() {
            const uint32_t wl = TAB(WG * 3 + 1);
            lm0 = TAB(WG * 3 + 2);
#pragma unroll
            for (int k = 0; k < NL; k++) ldsm4t(w0[k], wl + k * 2048);
        };
        const uint32_t wlo = WG * 65536 - SM_WO - wu * 16384, wlx = __reduce_max_sync(~0u, (wi ^ WG) << 5);
        uint32_t tq0, lm, lm1;
        auto proj_pre = [&](int s) {
            uint32_t wz0 = zero;
#pragma unroll
            for (int k = 0; k < NL; k += 2) wz0 = and3(wz0, w0[k][0], w0[k + 1 < NL ? k + 1 : k][0]);
            lm = lm0 + (s & 1) * 65536 + wz0; lm1 = lm ^ 64;
            asm volatile("" : "+r"(lm), "+r"(lm1));
        };
        auto proj = [&](int s, auto mid) {
            bar_sync(NB_MEM, 384);
            float c[4][4];
            uint32_t bf[16][4];
#pragma unroll
            for (int it = 0; it < 3; it++) ldsm4(bf[it], (it & 1 ? lm1 : lm) + (it >> 1) * HBK);
            mid(-1);
#pragma unroll
            for (int it = 0; it < 16; it++) {
                const uint32_t* bfr = bf[it];
                if (it + 3 < 16) ldsm4(bf[it + 3 < 16 ? it + 3 : 0], (it & 1 ? lm : lm1) + ((it + 3) >> 1) * HBK);
                const uint32_t* wa = 2 * it < NL ? w0[2 * it < NL ? 2 * it : 0] : w[2 * it < NL ? 0 : 2 * it - NL];
                const uint32_t* wb = 2 * it + 1 < NL ? w0[2 * it + 1 < NL ? 2 * it + 1 : 0] : w[2 * it + 1 < NL ? 0 : 2 * it + 1 - NL];
                float *ca = c[(2 * it) & 3], *cb = c[(2 * it + 1) & 3];
                if (it < 2) { mma16816z(ca, wa, bfr[0], bfr[1]); mma16816z(cb, wb, bfr[2], bfr[3]); }
                else { mma16816(ca, wa[0], wa[1], wa[2], wa[3], bfr[0], bfr[1]); mma16816(cb, wb[0], wb[1], wb[2], wb[3], bfr[2], bfr[3]); }
                mid(it);
            }
            const uint32_t xo = u_xo + (G16() >> 1);
            float r[4];
#pragma unroll
            for (int e = 0; e < 4; e++) {
                constexpr float SH = SM_L2E / 64;
                r[e] = WG ? (c[0][e] + c[1][e]) + (c[2][e] + c[3][e]) : fmaf(c[2][e] + c[3][e], SH, (c[0][e] + c[1][e]) * SH);
            }
            const uint32_t r0 = pack2(r[0], r[1]), r1 = pack2(r[2], r[3]);
            const uint32_t m0 = movm(r0), m1 = movm(r1);
            tq0 = clk32();
            bar_arrive(NB_QK, 384);
            stg_rlx2(arena + xo, settag(m0, (s & 1) ^ 1), m1);
        };
        w0_load();
        proj_pre(0);
        if (WG == 1 || !ROT) bar_sync(NB_P, ROT ? 256 : 384);
        proj(0, [](int) {});
#pragma unroll 1
        for (int s = 0;; s++) {
            STEP_CONSTS
            uint4 pa;
            float acc[16];
            auto acc_init = [&]() {
#pragma unroll
                for (int k = 0; k < 4; k++) { acc[2 * k] = bflo((&pa.x)[k]); acc[2 * k + 1] = bfhi((&pa.x)[k]); acc[8 + 2 * k] = __uint_as_float((&pa.x)[k] & zero); acc[9 + 2 * k] = __uint_as_float(~(&pa.x)[k] & zero); }
            };
            uint32_t wf[NPF][4], a3;
#define WF(f) ((a3 ^ (((f) & 1) * 64)) + ((f) >> 1) * 2048)
            if (WG == 1) {
                float sc[5][4];
                uint32_t sx0 = sb + SM_SX - wu * (2560 - 16) + G16() * 5;
                asm volatile("" : "+r"(sx0));
                int it = 0;
                bool bad;
#pragma unroll 1
                do {
                    uint4 kf[2][2];
                    U2 qf[2], x[8];
                    const uint32_t gz = g16 | (it & zero);
                    const uint8_t *ts = arena + (tso + tbw + gz), *tq = arena + (tso + tbq + gz), *xp = arena + (xso + (gz >> 1));
#pragma unroll
                    for (int a = 0; a < 4; a++) kf[a >> 1][a & 1] = ldg_b128(ts + (a >> 1) * 16384 + (a & 1) * 2048);
                    if (QF_LATE) spin_until(tq0, dly.x2 - QF_LATE);
#pragma unroll
                    for (int a = 0; a < 2; a++) qf[a] = ldg_u2(tq + a * 16384);
                    spin_until(tq0, dly.x2);
#pragma unroll
                    for (int i = 0; i < 8; i++) x[i] = ldg_u2(xp + (i >> 2) * 16384 + (i & 3) * 1024);
                    PROF(8)
                    const uint32_t q0[4] = {hadd2(x[0].x, x[1].x), qf[0].x, hadd2(x[0].y, x[1].y), qf[0].y};
                    const uint32_t q1[4] = {hadd2(x[2].x, x[3].x), qf[1].x, hadd2(x[2].y, x[3].y), qf[1].y};
                    PROFV(7, clk32() + (q0[0] & zero))
                    const uint32_t bt = ((qf[0].x ^ ttag) | (qf[1].x ^ ttag)) | ((kf[0][0].x ^ ttag) | (kf[0][1].x ^ ttag)) | ((kf[1][0].x ^ ttag) | (kf[1][1].x ^ ttag));
                    uint32_t bx = 0;
#pragma unroll
                    for (int i = 0; i < 8; i += 2) bx |= (x[i].x ^ tag) | (x[i + 1].x ^ tag);
                    mma16816z(sc[0], q0, kf[0][0].x, kf[0][0].y);
                    mma16816z(sc[1], q0, kf[0][0].z, kf[0][0].w);
                    mma16816z(sc[2], q0, kf[0][1].x, kf[0][1].y);
                    mma16816z(sc[3], q0, kf[0][1].z, kf[0][1].w);
                    mma16816z(sc[4], q0, hadd2(x[4].x, x[5].x), hadd2(x[4].y, x[5].y));
                    bad = any_bit0((XP & 8 ? bt & zero : bt) | bx) & (++it < POLL_LIMIT);
                    mma16816(sc[0], q1[0], q1[1], q1[2], q1[3], kf[1][0].x, kf[1][0].y);
                    mma16816(sc[1], q1[0], q1[1], q1[2], q1[3], kf[1][0].z, kf[1][0].w);
                    mma16816(sc[2], q1[0], q1[1], q1[2], q1[3], kf[1][1].x, kf[1][1].y);
                    mma16816(sc[3], q1[0], q1[1], q1[2], q1[3], kf[1][1].z, kf[1][1].w);
                    mma16816(sc[4], q1[0], q1[1], q1[2], q1[3], hadd2(x[6].x, x[7].x), hadd2(x[6].y, x[7].y));
                } while (bad);
                PROFV(13, it - 1) MISS(1, it - 1)
                sts4(sx0, pack_h2(sc[0][0], sc[0][1]), pack_h2(sc[1][0], sc[1][1]), pack_h2(sc[2][0], sc[2][1]), pack_h2(sc[3][0], sc[3][1]));
                sts1(sx0 + 64 - wu * 12, pack_h2(sc[4][0], sc[4][1]));
                bar_arrive(NB_X1, 384);
#pragma unroll
                for (int n = 0; n < 5; n++) sts2(sb + SM_SX + 2560 + g8 + n * 1088, sc[n][2], sc[n][3]);
                PROF(3)
                a3 = TAB(WG * 3);
                softmax_rows(sb + SM_SX + 2560, sb + SM_PX + 1024, g16 | (clk32() & zero), qd * 8, [&]() { BLOCK_FENCE bar_sync(NB_PX, 128); }, [&]() {
                    BLOCK_FENCE
#pragma unroll
                    for (int f = 0; f < NE1; f++) ldsm4t(wf[f], WF(f));
                    BLOCK_FENCE
                });
                PROF(4)
            } else {
                a3 = TAB(WG * 3);
                if (warp1 && (H_POS == 4 ? (s & 3) == 0 : (s & 3) < 2)) asm volatile("fence.proxy.async.global;" ::: "memory");
                spin_until(tq0, dly.pa);
                uint4 x, y;
                int it = 0;
#pragma unroll 1
                do { x = ldg_b128(arena + (pso + g16)); y = ldg_b128(arena + (pso + tokbase(1) - tokbase(0) + g16)); }
                while (!(XP & 8) & (p <= NSEG) & any_bit0(xor_or(x.x, y.x, ftag)) & (++it < POLL_LIMIT));
                sts4(sb + SM_PA + g16, x.x, x.y, x.z, x.w);
                sts4(sb + SM_PA + 2048 + g16, y.x, y.y, y.z, y.w);
                if (NE) spin_until(tq0, dly.wf);
#pragma unroll
                for (int f = 0; f < NE; f++) ldsm4t(wf[f], WF(f));
                bar_sync(NB_X1, 384);
                if (E_MUL && g16 < 32) asm volatile("red.relaxed.gpu.global.max.u32 [%0], %1; red.relaxed.gpu.global.add.u32 [%0+4], 1;"
                                                    ::"l"(arena + ((blk(LB_TIME, 0) ^ (g16 << 8)) + qd * 1024 + (tq0 & zero))), "r"(gtime()) : "memory");
                __syncwarp();
                const uint32_t tx = clk32();
                if (H_POS == 2 && !(XP & 1) && warp1 && s + 3 <= NSEG) h_load(sb, hsrc, s + 3, j, head);
                spin_until(tx, dly.w2);
            }
#pragma unroll
            for (int f = WG ? NE1 : NE; f < NPF; f++) ldsm4t(wf[f], WF(f));
            PROF(5)
            if (s + 1 == NSEG) { bar_arrive(NB_X2, 384); break; }
            const uint32_t oa = l16 + SM_OX, slot = mem_slot(s + 1);
            float c[4][4];
            uint32_t ob[4][4];
            uint32_t wz = zero;
#pragma unroll
            for (int f = 0; f < NPF; f += 2) wz = and3(wz, wf[f][0], wf[f + 1 < NPF ? f + 1 : f][0]);
            BLOCK_FENCE
            bar_sync(NB_X2 + (SETTLE ? wz : 0), 384);
            ldsm4t(ob[0], oa);
            ldsm4t(ob[1], oa + 512);
            SCHED_FENCE(0)
#pragma unroll
            for (int f = 0; f < 16; f++) {
                const uint32_t *a = wf[f % NPF], *o = ob[f >> 2] + (f & 2);
                if (f < 4) mma16816z(c[f], a, o[0], o[1]);
                else mma16816(c[f & 3], a[0], a[1], a[2], a[3], o[0], o[1]);
                if (f == 3) ldsm4t(ob[2], oa + 1024);
                if (f == 5) { ldsm4t(ob[3], oa + 1536); if (NPF < 16) ldsm4t(wf[0], WF(NPF)); }
                if (f == 7) {
#pragma unroll
                    for (int k = NPF + 1; k < 16; k++) ldsm4t(wf[k - NPF], WF(k));
                }
                if (f == 3 || f == 5 || f == 7) SCHED_FENCE(f / 2)
                if (f == 11) {
#pragma unroll
                    for (int k = NL - W0_E; k < NL; k++) ldsm4t(w0[k], (a3 ^ wlx) + wlo + k * 2048);
                    SCHED_FENCE(4)
                }
            }
            const float last = c[1][3] + c[3][3], one = __uint_as_float(CNT1 << 16);
            red_mem(arena + (u_m + slot + G16()), pack2(c[0][0] + c[2][0], c[0][1] + c[2][1]), pack2(c[0][2] + c[2][2], c[0][3] + c[2][3]),
                    pack2(c[1][0] + c[3][0], c[1][1] + c[3][1]), pack2(c[1][2] + c[3][2], CNT32 && !(g16 & 16) ? last : one),
                    arena + (u_e + slot + (CNT32 ? (g16 >> 3) & ~3u : g16 >> 2)), pack2(one, last), !CNT32 || (g16 & 16));
            hbo += FZ;
            PROF(6)
            constexpr int NS = WG && W0_E < 0 ? NL : NL - W0_RS, GS = (32 - NL + NS) / NS;
            if (W0_E >= 0) {
                BLOCK_FENCE
#pragma unroll
                for (int k = NL - W0_E - 1; k >= 0; k--) ldsm4t(w0[k], (a3 ^ wlx) + wlo + k * 2048);
                lm0 = TAB(WG * 3 + 2);
                if (WG == 1) pa = lds4(sb + SM_PA + 2048 + g16);
            }
            if (WG == 0) {
                bar_arrive(NB_WIN, 384);
                if (W0_E < 0) spin_until(clk32(), dly.tv);
                pa = lds4(sb + SM_PA + g16);
                if (W0_E < 0) w0_load();
                acc_init();
                asm volatile("" : F16(acc, 0));
                BLOCK_FENCE
            }
            if (WG == 1 && K_DLY) spin_until(clk32(), dly.wf);
            wg_fence();
            bar_sync(WG ? NB_WIN : NB_B, WG ? 384 : 256);
#pragma unroll
            for (int i = 0; i < 32; i++) {
                const int k = i / GS;
                if (i >= 32 - NL + NS) wgmma_rs32(acc, w0[i < 32 - NL + NS ? 0 : i - 32 + NL], HB(i - 32 + NL), 1);
                else if (i % GS == GS - 1 && k < NS) wgmma_ss32(acc, mkdesc(SB0 + WG * 65536 + k * 2048, 8192, 1024, 1), HB(k), 1);
                else wgmma_rs32(acc, w[i - (k < NS ? k : NS)], HB(NL + i - (k < NS ? k : NS)), WG == 0 || i);
                if (WG == 1 && i == G_AT) bar_arrive(NB_B, 256);
                if (WG == 1 && i == W1_AT) w0_load();
            }
            wg_commit();
            BLOCK_FENCE
            if (WG == 1 && warp0 && (s & 3) == (H_POS == 4 ? 3 : 0)) wait_count_w(&g_tick[32 + ((G16() >> 4) & 3) * 8], min((s + 1) / 4 + 2, 16));
            if (WG == 1 && W0_E < 0) { pa = lds4(sb + SM_PA + 2048 + g16); if (W1_AT < 0) w0_load(); }
            auto tok_store = [&](int m) {
                if (m & 1) stg_b128_if(XP & 8 ? s == 99 : true, arena + ((b ^ 1) * 32768 + u_to + G16()), v.x, v.y, v.z, v.w);
                if (m & 2) stg_b128_if(XP & 8 ? s == 99 : p < NSEG, arena + ((pso ^ (32768 + 2048)) + G16()), u.x, u.y, u.z, u.w);
            };
            if (WG == 0) proj_pre(s + 1);
            BLOCK_FENCE
            wg_wait<0>();
            if (WG == 0 && ROT) {
                asm volatile("" : F16(acc, 0));
                proj(s + 1, [&](int it) {
                    if (it < 0) {
                        SCHED_FENCE(0)
                        asm volatile("" : F16(acc, 0));
                        tok_pack(WG, acc, ftag, ptag, true);
                        tok_store(2);
                        SCHED_FENCE(1)
                    }
                    if (it == ROT) { SCHED_FENCE(2) v.x = settag(v.x, ftag); v.z = settag(v.z, ftag); tok_store(1); SCHED_FENCE(3) }
                });
                tq0 += (fz[0] | fz[1] | fz[2] | fz[3]) & zero;
            } else {
                if (WG == 1) {
#pragma unroll
                    for (int k = 0; k < 4; k++) { acc[2 * k] += bflo((&pa.x)[k]); acc[2 * k + 1] += bfhi((&pa.x)[k]); }
                }
                tok_pack(WG, acc, ftag, ptag);
                if (WG == 1) proj_pre(s + 1);
                asm volatile("" : "+r"(u.x), "+r"(u.y), "+r"(u.z), "+r"(u.w), "+r"(v.x), "+r"(v.y), "+r"(v.z), "+r"(v.w));
                BLOCK_FENCE
                bar_sync(NB_P, ROT ? 256 : 384);
                tok_store(3);
                proj(s + 1, [](int) {});
            }
        }
    };
    if (wg == 0) {
        qk_loop(IC<0>());
    } else if (wg == 1) {
        qk_loop(IC<1>());
    } else {
        const uint32_t ONES = 0x3f803f80u, u_o = qd * 65536 + head * 2048 + wu * 384;
        uint32_t tw = 0, dl = 0, dm = 0, dst0, dx0;
        dst0 = TAB(6); dx0 = TAB(7);
        uint32_t ov[4] = {0, 0, 0, 0};
        auto o_store = [&](int s) {
            uint8_t* od = (uint8_t*)g_O + (uint32_t)(s * (32 * NH * DH * 2) + u_o + (G16() >> 2));
#pragma unroll
            for (int a = 0; a < 4; a++) stg_rlx1(od + a * 128, ov[a]);
        };
        uint4 vf[2][2], pa;
        auto vf_fetch = [&](int s) {
            const uint8_t* ts = arena + ((s & 1) * 32768 + tbw + g16);
#pragma unroll
            for (int a = 0; a < 4; a++) vf[a >> 1][a & 1] = ldg_b128(ts + (a >> 1) * 16384 + (a & 1) * 2048);
        };
        auto tok_fetch = [&](int s) {
            if (TV_POS != 1) vf_fetch(s);
            pa = ldg_b128(arena + (tbw + (1 << 20) + (~s & 1) * 32768 + j * 16384 + kh * 2048 + g16));
        };
        if (PA_POS) tok_fetch(0);
        TL(9)
        mbar_wait_w(bars + 8 * B_WO, 0);
        if (H_POS == 4 && warp0) { wait_count_w(&g_tick[32 + ((g16 >> 4) & 3) * 8], 2); asm volatile("fence.proxy.async.global;" ::: "memory"); }
        TL(6)
#pragma unroll 1
        for (int s = 0; s < NSEG; s++) {
            STEP_CONSTS
#define VFBAD ((vf[0][0].x ^ ttag) | (vf[0][1].x ^ ttag) | (vf[1][0].x ^ ttag) | (vf[1][1].x ^ ttag))
#define TOKBAD ((TV_POS == 1 ? 0 : VFBAD) | (p <= NSEG ? pa.x ^ ftag : 0))
            {
                const uint32_t dst = dst0 + b * 65536, dx = dx0 + b * 65536;
                const uint8_t *ms = arena + (u_m + mem_slot(s) + g16), *me = arena + (u_e + mem_slot(s) + (CNT32 ? (g16 >> 3) & ~3u : g16 >> 2));
                const uint32_t em = CNT32 && !(g16 & 16) ? ~0u : 0u;
                asm volatile("" : "+l"(ms), "+l"(me));
                spin_until(tw, dl);
                PROF(11)
                int it = 0;
                bool bad;
#pragma unroll 1
                do {
                    uint4 m[4];
                    uint32_t x[4];
#pragma unroll
                    for (int i = 0; i < 4; i++) m[i] = ldg_rlx4(ms + i * 1024);
#pragma unroll
                    for (int i = 0; i < 4; i++) x[i] = ldg_rlx1(me + i * 1024);
#pragma unroll
                    for (int i = 0; i < 3; i++) {
                        stsm4t(dst + i * 2 * HBK, m[i].x, m[i].y, m[i].z, m[i].w);
                        if (i == P_GATE) asm volatile("{.reg .pred p; setp.eq.s32 p, %0, 0; @p bar.arrive %1, %2;}" ::"r"(it), "n"(NB_P), "n"(ROT ? 256 : 384) : "memory");
                    }
                    uint32_t c = and3(m[0].w, m[1].w, m[2].w);
                    SCHED_FENCE(1)
                    stsm4t(dst + 6 * HBK, m[3].x, m[3].y, m[3].z, m[3].w);
                    stsm4t(dx, x[0], x[1], x[2], x[3]);
                    asm volatile("" : "+r"(c));
                    c = and3(and3(((c & m[3].w) | em) >> 16, x[0], x[1]), x[2], x[3]);
                    bad = __any_sync(~0u, !(c & CNT_ALL)) & (++it < POLL_LIMIT);
                    if (H_POS == 4) asm volatile("{.reg .pred p; setp.eq.u32 p, %0, 0; @p bar.sync %1, 384;}" ::"r"((uint32_t)bad), "n"(NB_MEM) : "memory");
                    else if (!ALIGN) asm volatile("{.reg .pred p; setp.eq.u32 p, %0, 0; @p bar.arrive %1, 384;}" ::"r"((uint32_t)bad), "n"(NB_MEM) : "memory");
                } while (bad);
                if (ALIGN) { spin_until(tw, dm); bar_arrive(NB_MEM, 384); }
                PROFV(12, it - 1)
                MISS(0, it - 1) HT(5)
                PROF(8)
            }
            if (s == 1) { TL(7) TLC(0) }
            if (s == 63) TLC(1)
            if (s == 0) TL(13)
            const uint32_t tm = clk32();
            if (H_POS == 4 && g16 == 0) mbar_arrive_cluster(bars + 8 * B_HE, j ^ 1);
            if (O_POS == 1) o_store(max(s - 1, 0));
            if (Z_POS && warp1) stg4_if(g16 < 512 + 160, arena + (TAB(8) + mem_slot(s + 3)), 0);
            fence_async_smem();
            hbo += fz[1] & zero;
            int it = 0;
            if (!PA_POS) tok_fetch(s);
#pragma unroll 1
            while (!(XP & 8) & any_bit0(TOKBAD) & (++it < POLL_LIMIT)) tok_fetch(s + (it & zero));
            float acc[20];
#pragma unroll
            for (int k = 0; k < 4; k++) { acc[2 * k] = bflo((&pa.x)[k]); acc[2 * k + 1] = bfhi((&pa.x)[k]); acc[8 + 2 * k] = acc[9 + 2 * k] = acc[16 + k] = __uint_as_float(pa.x & zero); }
            if (XP & 1 ? s < 1 : p <= NSEG) mbar_wait_w(bars + 8 * (B_HB + b), (p >> 1) & 1);
            if (H_POS == 4 && warp0) {
                mbar_wait_w(bars + 8 * B_HE, s & 1);
                spin_until(tm, dly.wf);
                if (s + 3 <= NSEG) h_load(sb, hsrc, s + 3, j, head);
            }
            asm volatile("" : F16(acc, 0), F4(acc, 16));
            BLOCK_FENCE
            wg_fence();
            bar_sync(NB_QK, 384);
#pragma unroll
            for (int i = 0; i < 32; i++) {
                const int k = i / GAP;
                if (i % GAP == GAP - 1 && k < NL) wgmma_ss40(acc, mkdesc(SB0 + 131072 + k * 2048, 8192, 1024, 1), HB(k), 1);
                else wgmma_rs40(acc, w[i - (k < NL ? k : NL)], HB(NL + i - (k < NL ? k : NL)), 1);
            }
            wg_commit();
            uint8_t* vo = arena + (u_xo + (G16() >> 1));
            pdst = arena + ((pso ^ (32768 + 2048)) + G16());
            fdst = arena + ((b ^ 1) * 32768 + u_to + g16);
            BLOCK_FENCE
            wg_wait<0>();
            PROF(9)
            stg_rlx2(vo, settag(pack2(acc[16], acc[17]), tag), pack2(acc[18], acc[19]));
            const uint32_t tv = clk32();
            if (TV_POS == 1) vf_fetch(s);
            tok_pack(2, acc, ftag, ptag);
            stg_b128_if(XP & 8 ? s == 99 : p <= NSEG, fdst, v.x, v.y, v.z, v.w);
            stg_b128_if(XP & 8 ? s == 99 : p < NSEG, pdst, u.x, u.y, u.z, u.w);
            if (O_POS == 2) o_store(max(s - 1, 0));
            if (ST_BAR) bar_sync(NB_WG, 128);
            PROF(10)
            const uint8_t* xp = arena + (xso + 32768 + (G16() >> 1));
            const uint32_t sxa = sb + SM_SX - wu * 2560 + G16() * 5;
            uint32_t xv[4], gt = 0;
            auto pv = [&](uint32_t p0, uint32_t p1, uint32_t p2, uint32_t p3, uint32_t p4, auto getv, auto done) {
                float oc[2][4], lc[4] = {0.f, 0.f, 0.f, 0.f};
                mma16816(lc, ONES, ONES, ONES, ONES, p0, p1);
                mma16816z(oc[0], &vf[0][0].x, p0, p1);
                mma16816z(oc[1], &vf[1][0].x, p0, p1);
                mma16816(lc, ONES, ONES, ONES, ONES, p2, p3);
                mma16816(oc[0], vf[0][1].x, vf[0][1].y, vf[0][1].z, vf[0][1].w, p2, p3);
                mma16816(oc[1], vf[1][1].x, vf[1][1].y, vf[1][1].z, vf[1][1].w, p2, p3);
                mma1688(lc, ONES, ONES, p4);
                getv();
                mma1688(oc[0], xv[0], xv[1], p4);
                mma1688(oc[1], xv[2], xv[3], p4);
                done(__float_as_uint(oc[0][0]) | __float_as_uint(oc[1][0]) | __float_as_uint(lc[0]));
                const float r0 = rcp_fast(lc[0]), r1 = rcp_fast(lc[1]);
                ov[0] = pack2(oc[0][0] * r0, oc[0][1] * r1); ov[1] = pack2(oc[0][2] * r0, oc[0][3] * r1);
                ov[2] = pack2(oc[1][0] * r0, oc[1][1] * r1); ov[3] = pack2(oc[1][2] * r0, oc[1][3] * r1);
            };
            bool bad;
            it = 0;
#pragma unroll 1
            do {
                U2 xr[4];
                auto load_v = [&]() {
                    if (V_POS < 3) spin_until(tv, dly.v);
#pragma unroll
                    for (int i = 0; i < 4; i++) xr[i] = ldg_u2(xp + i * 1024);
                };
                if (TV_POS == 1 && it) {
                    const uint8_t* tz = arena + (tso + tbw + (g16 | (it & zero)));
#pragma unroll
                    for (int a = 0; a < 4; a++) ldg_b128_into(vf[a >> 1][a & 1], tz + (a >> 1) * 16384 + (a & 1) * 2048);
                }
                if (!V_POS) load_v();
                if (V_POS >= 3) spin_until(tv, dly.v);
                PROF(3)
                asm volatile("{.reg .pred p; setp.eq.s32 p, %0, 0; @p bar.sync %1, 384;}" ::"r"(it), "n"(NB_X1) : "memory");
                uint4 sx[5];
                if (V_POS == 3) load_v();
#pragma unroll
                for (int i = 0; i < 5; i++) sx[i] = lds4(sxa + i * 16);
                if (V_POS == 4) load_v();
                if (it == 0) { gt = gtime(); tw = clk32(); }
                if (V_POS == 2) load_v();
                uint32_t h[5];
#pragma unroll
                for (int n = 0; n < 4; n++) h[n] = add_h2(add_h2((&sx[0].x)[n], (&sx[1].x)[n]), add_h2((&sx[2].x)[n], (&sx[3].x)[n]));
                h[4] = add_h2(add_h2(sx[4].x, sx[4].y), add_h2(sx[4].z, sx[4].w));
                uint32_t hm = max_h2(max_h2(max_h2(h[0], h[1]), h[2]), max_h2(h[3], h[4]));
                hm = max_h2(hm, __byte_perm(hm, hm, 0x1032));
                const uint32_t m1 = __shfl_xor_sync(~0u, hm, 1), m2 = __shfl_xor_sync(~0u, hm, 2), m3 = __shfl_xor_sync(~0u, hm, 3);
                float2 a[5];
#pragma unroll
                for (int n = 0; n < 5; n++) a[n] = unpack_h2(h[n]);
                if (V_POS == 1) load_v(); else SCHED_FENCE(0)
                const float mb = -64.0f * unpack_h2(max_h2(max_h2(hm, m1), max_h2(m2, m3))).x;
                uint32_t pm[5];
#pragma unroll
                for (int n = 0; n < 5; n++) pm[n] = pack2(ex2(fmaf(a[n].x, 64.0f, mb)), ex2(fmaf(a[n].y, 64.0f, mb)));
                pv(pm[0], pm[1], pm[2], pm[3], pm[4], [&]() {
                    xv[0] = hadd2(xr[0].x, xr[1].x); xv[1] = hadd2(xr[0].y, xr[1].y);
                    xv[2] = hadd2(xr[2].x, xr[3].x); xv[3] = hadd2(xr[2].y, xr[3].y);
                }, [](uint32_t) {});
                bad = any_bit0((TV_POS == 1 && !(XP & 8) ? VFBAD : 0) | (xr[0].x ^ tag) | (xr[1].x ^ tag) | (xr[2].x ^ tag) | (xr[3].x ^ tag)) & (++it < POLL_LIMIT);
                stsm4(sb + SM_OX + g16, ov[0], ov[1], ov[2], ov[3]);
            } while (bad);
            PROFV(14, it - 1) MISS(2, it - 1)
            PROF(5)
            bar_sync(NB_X2, 384);
            U2 tv2 = {0, 0};
            const uint8_t* tp = arena + (blk(LB_TIME, mypar) + (((g16 | (tw & zero)) << 6) & 0xc00));
            {
                const uint4 pp = lds4(l16 + SM_PX + 1024);
                const uint32_t p4 = lds1(sb + SM_PX + 512 + 1024 - wu * 128 + (G16() >> 2));
                if (E_MUL) tv2 = ldg_u2(tp);
                if (H_POS == 3 && !(XP & 1) && warp0 && s + 3 <= NSEG) h_load(sb, hsrc, s + 3, j, head);
                if (H_POS == 0 && !(XP & 1)) h_piece(sb, hsrc, s + 3, j, (wu + head) & 3, wu == 0);
                pv(pp.x, pp.y, pp.z, pp.w, p4, []() {}, [&](uint32_t r) { bar_arrive(NB_WIN + ((r | fz[0]) & zero), 384); });
            }
            dst0 = TAB(6); dx0 = TAB(7);
            const uint32_t zo = Z_POS ? 0 : TAB(8);
            PROF(6) HT(7)
            BLOCK_FENCE
            if (H_POS == 1 && !(XP & 1)) h_piece(sb, hsrc, s + 3, j, (wu + head) & 3, wu == 0);
            asm volatile("" : "+r"(tv2.y));
            it = 0;
#pragma unroll 1
            while (E_MUL && __any_sync(~0u, tv2.y < 32 * (s + 1)) & (++it < 16)) tv2 = ldg_u2(tp);
            const uint32_t e = __reduce_max_sync(~0u, tv2.x) - gt;
            MISS(3, it - 1) MISS(4, gt)
            if (PA_POS) tok_fetch(s + 1);
            if (O_POS == 0) o_store(s);
            if (!Z_POS) stg4_if(g16 < 160, arena + (zo + mem_slot(s + 3)), 0);
            dm = e > 4096 ? 0 : e * E_MUL >> 4;
            dl = dm + (ALIGN ? dly.near - dly.wf - (kh == mypar ? 0 : 140) : kh == mypar ? dly.near : dly.far);
            dm += dly.near;
        }
        if (O_POS) o_store(NSEG - 1);
        TL(8)
    }
    PROF_OUT
    MISS_OUT
}

struct RecMaps { CUtensorMap wq, wk, wv, wo, wmod, w3, w1; };
struct RecPtrs { const bf16 *x, *mem0, *c, *wmod, *w1, *w3; uint8_t* arena; uint32_t zero; const bf16 *w2, *w4, *wo; Delays dly; };

__device__ __forceinline__ float silu_bf(const bf16* c, int i) {
    const float v = __bfloat162float(c[i]);
    return bfround(__fdividef(v, 1.0f + __expf(-v)));
}
#define W_LATE 1000
#define W_OPEN 1400
__device__ __forceinline__ void side_window(const uint8_t* arena, uint32_t& n) {
    U2 v;
    int it = 0;
#pragma unroll 1
    while (v = ldg_u2(arena + (LB_TIME << 13)), ((v.y >> 5) == n || gtime() - v.x > W_OPEN + W_LATE) && v.y < 32 * NSEG && ++it < 64) __nanosleep(100);
    n = v.y >> 5;
    it = 0;
#pragma unroll 1
    while ((int)(gtime() - v.x - W_OPEN) < 0 && ++it < 256) {}
}
__device__ __noinline__ void rec_ln(float* coef, const RecPtrs& p, int id, int r0) {
    int r1 = 32;
    const int tid = threadIdx.x;
    const int lane = tid & 31, wid = tid >> 5;
    const uint32_t ring = smem_u32(coef) - SM_PRE + wid * 8192 + lane * 16;
    auto rowof = [&](int j) { return (j >> 1) * 64 + (id * 8 + wid) * 2 + (j & 1); };
    auto fetch = [&](int j) {
        if (j < 2 * r1) {
#pragma unroll
            for (int i = 0; i < 4; i++)
                asm volatile("cp.async.cg.shared.global [%0], [%1], 16;" ::"r"(ring + (j & 3) * 2048 + i * 512), "l"(p.x + (size_t)rowof(j) * DM + i * 256 + lane * 8) : "memory");
        }
        asm volatile("cp.async.commit_group;" ::: "memory");
    };
#pragma unroll 1
    for (int j = 2 * r0; j < 2 * r0 + 4; j++) fetch(j);
#pragma unroll 1
    for (int i = tid; i < 2 * DM / 4; i += 256) {
        uint4 v[8];
        int it = 0;
        uint32_t ok;
        do {
            ok = 1;
#pragma unroll
            for (int k = 0; k < 8; k++) v[k] = ldg_rlx4(g_modp + k * 2 * DM + i * 4);
#pragma unroll
            for (int k = 0; k < 8; k++) ok &= v[k].x & v[k].y & v[k].z & v[k].w;
            spin_guard(++it);
        } while (!ok);
        float t[4] = {0, 0, 0, 0};
#pragma unroll
        for (int k = 0; k < 8; k++) { t[0] += __uint_as_float(v[k].x); t[1] += __uint_as_float(v[k].y); t[2] += __uint_as_float(v[k].z); t[3] += __uint_as_float(v[k].w); }
#pragma unroll
        for (int j = 0; j < 4; j++) coef[i * 4 + j] = bfround(t[j]) + (i >= DM / 4 ? 1.0f : 0.0f);
    }
    bar_sync(NB_FIN0, 256);
    if (r0 == 0) {
        int v, it = 0;
#pragma unroll 1
        do { v = *(volatile int*)((uint8_t*)coef - SM_PRE + SM_BAR + 192); spin_guard(++it); } while (v == INT_MIN);
        if (v >= 0) r1 = 2;
    }
    if (tid == 0 && r0 == 0) TL(2)
#pragma unroll 1
    for (int j = 2 * r0; j < 2 * r1; j++) {
        float x[32];
        asm volatile("cp.async.wait_group 3;" ::: "memory");
#pragma unroll
        for (int i = 0; i < 4; i++) {
            const uint4 v = lds4(ring + (j & 3) * 2048 + i * 512);
            float* d = x + i * 8;
            d[0] = bflo(v.x); d[1] = bfhi(v.x); d[2] = bflo(v.y); d[3] = bfhi(v.y); d[4] = bflo(v.z); d[5] = bfhi(v.z); d[6] = bflo(v.w); d[7] = bfhi(v.w);
        }
        const int row = rowof(j), rr = row & 15;
        ln_row(x);
        fetch(j + 4);
#pragma unroll
        for (int i = 0; i < 4; i++) {
            float y[8];
            const float4* cf = (const float4*)(coef + i * 256 + lane * 8);
            const float4 s0 = cf[0], s1 = cf[1], c0 = cf[256], c1 = cf[257];
            const float sh[8] = {s0.x, s0.y, s0.z, s0.w, s1.x, s1.y, s1.z, s1.w}, sc[8] = {c0.x, c0.y, c0.z, c0.w, c1.x, c1.y, c1.z, c1.w};
#pragma unroll
            for (int e = 0; e < 8; e++) y[e] = fmaf(x[i * 8 + e], sc[e], sh[e]);
            const int own = ((row >> 4) & 1) == (i >> 1), c16 = i * 32 + lane;
            const uint32_t off = ((row >> 5) + own) * 65536 + (c16 >> 3) * 4096 + (rr + (own ? 0 : 16)) * 128 + (((c16 & 7) ^ (rr & 7)) << 4);
            *(uint4*)((uint8_t*)g_himg + off) = pack8(y);
        }
        if ((j & 3) != 3) continue;
        bar_sync(j == 3 ? NB_C : NB_FIN0, j == 3 ? 320 : 256);
        if (wid == 0) {
            if (j == 3) bar_arrive(NB_B, 64);
            if (lane == 0) { if (j == 7) wait_count1(&g_tick[32 + id * 8], 1); signal_count(&g_tick[32 + id * 8]); if (j < 8) TL(13) }
            __syncwarp();
        }
    }
}
#define SIDE_T 300
template <int NQ>
__device__ __forceinline__ void side_gemv(const CUtensorMap* tm, int c0, int k0, int k1, uint32_t cs, uint32_t sb, const uint8_t* arena, uint32_t& n, uint32_t& ph, float (*acc)[8], const uint8_t* xr = nullptr) {
    const uint32_t w = __reduce_max_sync(~0u, threadIdx.x >> 5 & 3), ring = sb + 65536 + w * 24576, bars = sb + SM_BAR + 8 * B_W + w * 24;
#pragma unroll
    for (int q = 0; q < NQ; q++)
#pragma unroll
        for (int j = 0; j < 8; j++) acc[q][j] = 0.f;
#pragma unroll 1
    for (; k0 < k1; k0 += 48, ph ^= 1) {
        const int nr = min(48, k1 - k0);
        side_window(arena, n);
        const uint32_t t0 = clk32();
        if (xr && k0 < 9 * 48) {
#pragma unroll
            for (int i = 0; i < 6; i++) asm volatile("prefetch.global.L2 [%0];" ::"l"(xr + (5 + k0 / 16 + (i >> 1)) * 131072 + (i & 1) * 16384));
        }
#pragma unroll 1
        for (int g = 0; g < 3; g++) {
            spin_until(t0, (g * 4 + w) * (SIDE_T / 4));
            e_expect(bars + 8 * g, g * 16 < nr ? 8192 : 0);
            if (g * 16 < nr) e_tma2d(ring + g * 8192, tm, c0, k0 + g * 16, bars + 8 * g);
        }
#pragma unroll 1
        for (int r = 0; r < nr; r += 16) {
            mbar_wait_w(bars + (r >> 1), ph);
            uint4 v[16];
#pragma unroll
            for (int h = 0; h < 16; h++) v[h] = lds4(ring + (r + h) * 512 + (threadIdx.x & 31) * 16);
            float4 cf[NQ][4];
#pragma unroll
            for (int q = 0; q < NQ * 4; q++) cf[q >> 2][q & 3] = lds4f(cs + ((q >> 2) * DM + k0 + r + (q & 3) * 4) * 4);
#pragma unroll
            for (int h = 0; h < 16; h++) {
                const float f[8] = {bflo(v[h].x), bfhi(v[h].x), bflo(v[h].y), bfhi(v[h].y), bflo(v[h].z), bfhi(v[h].z), bflo(v[h].w), bfhi(v[h].w)};
#pragma unroll
                for (int q = 0; q < NQ; q++)
#pragma unroll
                    for (int j = 0; j < 8; j++) acc[q][j] = fmaf((&cf[q][h >> 2].x)[h & 3], f[j], acc[q][j]);
            }
        }
        fence_async_smem();
        __syncwarp();
    }
}
__device__ __noinline__ void rec_side(float* sm, const RecMaps& mp, const RecPtrs& p, int id) {
    const int tid = threadIdx.x;
    if (tid < 256) {
        if (blockIdx.x < 128) rec_ln(sm + SM_PRE / 4, p, id, 2);
        if (tid == 0) TL(14)
        for (int i = tid; i < 2 * S_; i += 256) g_st[id * 2 * S_ + i] = 0.f;
        if (id == 0 && tid < 64) g_pcnt[tid * 8] = 0;
        if (id == 1) for (int i = tid; i < 5 * 256; i += 256) g_pflag[i] = 0;
        if (id == 2 && tid < 66) {
            const uint2 me = __ldcg(&g_clk[tid]);
            const uint32_t c0 = __ldcg(&g_clk[0].x) - 4096;
            int r = 0;
#pragma unroll 1
            for (int i = 0; i < 66; i++) { const uint32_t o = __ldcg(&g_clk[i].x) - c0; r += o < me.x - c0 || (o == me.x - c0 && i < tid); }
            g_cls[me.y & 255] = g_cls[(me.y ^ 1) & 255] = r >> 4;
            if (tid == 0) g_pt = 0;
        }
        uint32_t n = 0;
        int it = 0;
#pragma unroll 1
        while (n < SPF_AT && ++it < 256) side_window(p.arena, n);
#pragma unroll 1
        for (int i = 0; i < 96 && SPF; i++) {
            const uint8_t* w = i < 64 ? (const uint8_t*)p.wo + (id * 64 + i) * 32768 : (const uint8_t*)p.x + (id * 32 + i - 64) * 32768;
            asm volatile("prefetch.global.L2 [%0];" ::"l"(w + tid * 128));
            if (i % SPF_R == SPF_R - 1 && i < 95) side_window(p.arena, n); else __nanosleep(SPF_NS);
        }
        return;
    }
    const int t = tid - 256;
    float *coef = sm + 40960, *red = coef + 3 * DM;
    const uint32_t sb = smem_u32(sm), cs = smem_u32(coef);
    uint32_t n = 0, ph = 0;
    for (int i = t; i < DM; i += 128) { coef[i] = silu_bf(p.c, i); coef[2 * DM + i] = 1.0f; }
    if (t == 0) wait_count1(&g_tick[32 + id * 8], 2);
    bar_sync(NB_G, 128);
    const int w = __reduce_max_sync(~0u, t >> 5);
    float acc[3][8];
    side_gemv<1>(&mp.wmod, (2 + id) * DM + w * 256, 0, DM, cs, sb, p.arena, n, ph, acc, (const uint8_t*)p.x + id * 32768 + t * 128);
#pragma unroll
    for (int j = 0; j < 8; j++) g_mod[(2 + id) * DM + t * 8 + j] = bfround(acc[0][j]);
    bar_sync(NB_G, 128);
    if (t == 0) signal_count(&g_tick[8]);
    side_gemv<1>(&mp.w3, id * (FF / 4) + w * 256, 0, DM, cs + 8 * DM, sb, p.arena, n, ph, acc);
    if (t < FF / 32) {
#pragma unroll
        for (int j = 0; j < 8; j++) g_vec[3 * DM + id * (FF / 4) + t * 8 + j] = acc[0][j];
    }
    if (t == 0) wait_count1(&g_tick[8], 4);
    bar_sync(NB_G, 128);
    for (int i = t; i < DM; i += 128) { coef[i] = 1.0f + __ldcg(g_mod + 4 * DM + i); coef[DM + i] = __ldcg(g_mod + 3 * DM + i); }
    bar_sync(NB_G, 128);
    if (id == 1 && t < 32) {
        float u[5] = {0, 0, 0, 0, 0};
        for (int i = t; i < DM; i += 32) {
            const float a = coef[i], b = coef[DM + i];
            u[0] += a; u[1] += a * a; u[2] += a * b; u[3] += b; u[4] += b * b;
        }
#pragma unroll
        for (int q = 0; q < 5; q++) { const float r = warp_sum(u[q]); if (t == 0) g_cst[q] = r * (1.0f / DM); }
    }
    side_gemv<3>(&mp.w1, id * 256, w * 256, w * 256 + 256, cs, sb, p.arena, n, ph, acc);
#pragma unroll
    for (int q = 0; q < 3; q++)
#pragma unroll
        for (int j = 0; j < 8; j++) red[((t >> 5) * 3 + q) * 256 + (t & 31) * 8 + j] = acc[q][j];
    bar_sync(NB_G, 128);
    for (int i = t; i < 768; i += 128) g_vec[(i >> 8) * DM + id * 256 + (i & 255)] = (red[i] + red[768 + i]) + (red[1536 + i] + red[2304 + i]);
    if (t == 0) TL(9)
}

__global__ void __cluster_dims__(2, 1, 1) __launch_bounds__(384, 1)
k_rec(const __grid_constant__ RecMaps mp, const __grid_constant__ RecPtrs p) {
    extern __shared__ uint8_t smraw[];
    const uint32_t sb = smem_u32(smraw);
    if ((sb & 0x3FFFF) != SB0) __trap();
    const uint32_t bars = sb + SM_BAR;
    const int tid = threadIdx.x, lane = tid & 31, b = blockIdx.x;
    const int wid = __reduce_max_sync(~0u, tid >> 5);
    const uint32_t rank = b & 1;
    uint8_t* arena = p.arena;
    volatile int* sinfo = (volatile int*)(smraw + SM_BAR + 192);
    if (tid == 0) TL(0)
    if (tid == 0) sinfo[0] = INT_MIN;
    if (tid == 352) {
        for (int i = 0; i < 17; i++) mbar_init(bars + 8 * i, i == B_WO ? 4 : 1);
        asm volatile("fence.mbarrier_init.release.cluster;" ::: "memory");
        mbar_expect(bars + 8 * B_ROLE, 8);

    }
    __syncwarp();
    asm volatile("barrier.cluster.arrive.relaxed.aligned;" ::: "memory");
    int pr = 0, hA = 0;
    if (wid < 8) {
        if (b < 128) {
            const int cb = (b & 15) * 128, k0 = (b >> 4) * 128 + (tid >> 4);
            uint4 v[8];
#pragma unroll
            for (int i = 0; i < 8; i++) v[i] = __ldg((const uint4*)(p.wmod + (size_t)(k0 + 16 * i) * (6 * DM) + cb + (tid & 15) * 8));
            float acc[8] = {0, 0, 0, 0, 0, 0, 0, 0};
#pragma unroll
            for (int i = 0; i < 8; i++) {
                const float sv = silu_bf(p.c, k0 + 16 * i);
                acc[0] += sv * bflo(v[i].x); acc[1] += sv * bfhi(v[i].x); acc[2] += sv * bflo(v[i].y); acc[3] += sv * bfhi(v[i].y);
                acc[4] += sv * bflo(v[i].z); acc[5] += sv * bfhi(v[i].z); acc[6] += sv * bflo(v[i].w); acc[7] += sv * bfhi(v[i].w);
            }
            float* red = (float*)(smraw + SM_PRE);
            *(float4*)(red + (tid >> 4) * 128 + (tid & 15) * 8) = make_float4(acc[0], acc[1], acc[2], acc[3]);
            *(float4*)(red + (tid >> 4) * 128 + (tid & 15) * 8 + 4) = make_float4(acc[4], acc[5], acc[6], acc[7]);
            bar_sync(NB_FIN0, 256);
            if (wid < 4) {
                float t = 0;
#pragma unroll
                for (int i = 0; i < 16; i++) t += red[i * 128 + tid];
                stg_rlx1(&g_modp[(b >> 4) * 2 * DM + cb + tid], __float_as_uint(t) | 1u);
            }
        } else {
            rec_ln((float*)(smraw + SM_PRE), p, b - 128, 0);
        }
    } else if (wid >= 10 && b >= 128) {
        {
            const int w = (b - 128) * 2 + wid - 10;
            const uint16_t* src = (const uint16_t*)p.mem0 + (lane & 3) * 2 * DM + (w >> 2) * 512 + (w & 1) * 64 + (w & 2) * 8 + (lane >> 2);
            uint32_t v[4][4];
#pragma unroll
            for (int i = 0; i < 16; i++) v[i >> 2][i & 3] = src[(i >> 2) * 128 + (i & 2) * 16 + (i & 1) * 8] | ((uint32_t)src[DM + (i >> 2) * 128 + (i & 2) * 16 + (i & 1) * 8] << 16);
            uint8_t* d = arena + mem_row(w >> 2, w & 3, 0);
            uint8_t* e = d + 512 + (CNT32 ? lane >> 1 : lane) * 4;
            d += lane * 16;
#pragma unroll
            for (int i = 0; i < 4; i++, d += 1024, e += 1024) {
                stg_rlx4(d, v[i][0], v[i][1], v[i][2], CNT32 && !(lane & 1) ? v[i][3] : (v[i][3] & 0xffff) | CNT_ALL << 16);
                stg_rlx4(d + mem_slot(1), 0, 0, 0, 0);
                stg_rlx4(d + mem_slot(2), 0, 0, 0, 0);
                if (!CNT32 || (lane & 1)) { stg_rlx1(e, (v[i][3] & 0xffff0000u) | CNT_ALL); stg_rlx1(e + mem_slot(1), 0); stg_rlx1(e + mem_slot(2), 0); }
            }
            if (w == 0 && lane < 8) stg_rlx2(arena + (LB_TIME << 13) + lane * 1024, 0, 0);
            bar_arrive(NB_C, 320);
        }
    } else if (rank == 0) {
        uint32_t best = ~0u;
        const int pg = wid < 10 ? 0 : 1 + (b >> 1) % 3;
        uint32_t* q = (uint32_t*)(arena + (pg << 21) + (pg ? blk(b >> 1, wid & 1) : blk(LB_PROBE, wid & 1) + b * 16));
        if (lane < 8) stg_rlx1(q + lane, 0);
        uint2 tk2 = ldg_rlx2(&g_tick[0]);
        __syncwarp();
        if (lane == 0) {
            q += 3;
            uint32_t v = atomicAdd(q, 1u);
#pragma unroll 1
            for (int r = 0; r < NPROBE; r++) {
                const uint32_t t0 = clk32() + (v >> 8);
                v = atomicAdd(q + (v >> 8), 1u);
                uint32_t t1;
                asm volatile("{.reg .pred p; setp.eq.u32 p, %1, 0xffffffff; @p exit; mov.u32 %0, %%clock;}" : "=r"(t1) : "r"(v) : "memory");
                best = min(best, t1 - t0);
            }
            sinfo[wid - 6] = best;
        }
        bar_sync(NB_KDONE, b < 128 ? 128 : 64);
        if (wid == 8) {
            const int par = sinfo[2] <= sinfo[3] ? 0 : 1, ncl = gridDim.x >> 1;
            int tk = 0, it = 0;
            const uint32_t vote = b < 128 && (sinfo[4] <= sinfo[5] ? 0 : 1) != par ? 256u << (8 * ((b >> 1) % 3)) : 0u;
            if (b >= 128) {
#pragma unroll 1
                while (!__all_sync(~0u, (int)((tk2.x + tk2.y) & 255) >= ncl - 2)) { tk2 = ldg_rlx2(&g_tick[0]); spin_guard(++it); }
            }
            if (lane == 0) tk = atomicAdd(&g_tick[par], 1u + vote) & 255;
#pragma unroll 1
            while (!__all_sync(~0u, (int)((tk2.x + tk2.y) & 255) >= ncl)) { tk2 = ldg_rlx2(&g_tick[0]); spin_guard(++it); }
            if (lane == 0) g_clk[b >> 1] = make_uint2(clk32() - 2 * gtime(), smid());
            tk = __shfl_sync(~0u, tk, 0);
            const int n0 = tk2.x & 255, n1 = tk2.y & 255;
            hA = min(n0 >> 1, NH);
            const int q0 = 2 * hA, q1 = 2 * NH - q0;
            const int over = tk - (par ? q1 : q0), lack = max(par ? q0 - n0 : q1 - n1, 0);
            if (over < 0) pr = par ? q0 + tk : tk;
            else if (over < lack) pr = (par ? n0 : q0 + n1) + over;
            else pr = -1 - (over - lack + (par ? max(n0 - q0, 0) : 0));
#pragma unroll
            for (int i = 0; i < 3; i++) hA |= (((tk2.x + tk2.y) >> (8 + 8 * i)) & 255) > 10 ? 256 << i : 0;
        }
    }
    asm volatile("barrier.cluster.wait.aligned;" ::: "memory");
    if (wid == 8) {
        if (rank == 0) {
            if (lane == 0) {
                uint32_t rsb;
                asm("mapa.shared::cluster.u32 %0, %1, 1;" : "=r"(rsb) : "r"(sb));
                asm volatile("st.async.shared::cluster.mbarrier::complete_tx::bytes.v2.u32 [%0], {%1, %2}, [%3];"
                             ::"r"(rsb + SM_BAR + 192), "r"(pr), "r"(hA), "r"(rsb + SM_BAR + 8 * B_ROLE) : "memory");
                sinfo[0] = pr; sinfo[1] = hA;
                if (b >= 128) atomicOr(&g_tick[4], (pr < 0 ? 4u : 1u) << ((b - 128) >> 1));
            }
        } else {
            mbar_wait_w(bars + 8 * B_ROLE, 0);
            pr = sinfo[0];
        }
        TL(1)
        __syncwarp();
        bar_arrive(NB_A, 288);
        bar_arrive(NB_S, 128);
        if (b >= 128 && pr < 0) bar_sync(NB_B, 64);
        if (pr >= 0) {
            const int pu = __reduce_max_sync(~0u, pr), c0 = (pu >> 1) * 128 + rank * 64, r0 = (pu & 1) * 512;
            bool fast = false;
#pragma unroll 1
            for (int n = 0; n < 12; n++) {
                const int rot = b >= 128 ? 8 : 0, i = (n + rot) % 12;
                if (rot && n == 4) bar_sync(NB_B, 64);
                if (n >= W_INFL && !fast) {
                    const uint32_t v = ldg_rlx1(&g_tick[32 + (lane & 3) * 8]);
                    mbar_wait_w(bars + 8 * (B_W + (n - W_INFL + rot) % 12), 0);
                    fast = __all_sync(~0u, v != 0);
                }
                const int m = i < 8 ? i & 1 : 2, k = i < 8 ? i >> 1 : i - 8;
                const uint32_t dst = sb + m * 65536 + k * 16384, br = bars + 8 * (B_W + i);
                if (lane == 0) {
                    mbar_expect(br, 16384);
                    tma2d(dst, &mp.wq + m, c0, r0 + k * 128, br);
                    tma2d(dst + 8192, &mp.wq + m, c0, r0 + k * 128 + 64, br);
                }
                __syncwarp();
            }
        }
    } else {
        bar_sync(wid < 8 ? NB_A : NB_S, wid < 8 ? 288 : 128);
    }
    const int prr = __reduce_max_sync(~0u, sinfo[0]);
    hA = __reduce_max_sync(~0u, sinfo[1]);
    if (prr < 0) {
        int j = (b - 128) >> 1;
        if (b < 128) {
            uint32_t v;
            int it = 0;
#pragma unroll 1
            do { v = __reduce_max_sync(~0u, ldg_rlx1(&g_tick[4])); spin_guard(++it); } while (__popc(v) < 2);
            j = v == 3 ? -1 - prr : (v & 1) ^ 1;
        }
        rec_side((float*)smraw, mp, p, j * 2 + rank);
        return;
    }
    const int role = (prr >> 1) * 4 + rank * 2 + (prr & 1);
    rec_main(sb, &mp.wo, arena, role, hA, wid >> 2, p.zero, p.dly);
}

__device__ __forceinline__ void wgmma_ss192(float* d, uint64_t a, uint64_t b, int sc) {
    asm volatile("{.reg .pred p; setp.ne.b32 p, %98, 0;\n wgmma.mma_async.sync.aligned.m64n192k16.f32.bf16.bf16 "
                 "{%0,%1,%2,%3,%4,%5,%6,%7,%8,%9,%10,%11,%12,%13,%14,%15,%16,%17,%18,%19,%20,%21,%22,%23,%24,%25,%26,%27,%28,%29,%30,%31,%32,%33,%34,%35,%36,%37,%38,%39,%40,%41,%42,%43,%44,%45,%46,%47,%48,%49,%50,%51,%52,%53,%54,%55,%56,%57,%58,%59,%60,%61,%62,%63,%64,%65,%66,%67,%68,%69,%70,%71,%72,%73,%74,%75,%76,%77,%78,%79,%80,%81,%82,%83,%84,%85,%86,%87,%88,%89,%90,%91,%92,%93,%94,%95}, %96, %97, p, 1, 1, 0, 1;}"
                 : F16(d, 0), F16(d, 16), F16(d, 32), F16(d, 48), F16(d, 64), F16(d, 80) : "l"(a), "l"(b), "r"(sc));
}
__device__ __forceinline__ void wgmma_ss256(float* d, uint64_t a, uint64_t b, int sc) {
    asm volatile("{.reg .pred p; setp.ne.b32 p, %130, 0;\n wgmma.mma_async.sync.aligned.m64n256k16.f32.bf16.bf16 "
                 "{%0,%1,%2,%3,%4,%5,%6,%7,%8,%9,%10,%11,%12,%13,%14,%15,%16,%17,%18,%19,%20,%21,%22,%23,%24,%25,%26,%27,%28,%29,%30,%31,%32,%33,%34,%35,%36,%37,%38,%39,%40,%41,%42,%43,%44,%45,%46,%47,%48,%49,%50,%51,%52,%53,%54,%55,%56,%57,%58,%59,%60,%61,%62,%63,%64,%65,%66,%67,%68,%69,%70,%71,%72,%73,%74,%75,%76,%77,%78,%79,%80,%81,%82,%83,%84,%85,%86,%87,%88,%89,%90,%91,%92,%93,%94,%95,%96,%97,%98,%99,%100,%101,%102,%103,%104,%105,%106,%107,%108,%109,%110,%111,%112,%113,%114,%115,%116,%117,%118,%119,%120,%121,%122,%123,%124,%125,%126,%127}, %128, %129, p, 1, 1, 0, 1;}"
                 : F16(d, 0), F16(d, 16), F16(d, 32), F16(d, 48), F16(d, 64), F16(d, 80), F16(d, 96), F16(d, 112) : "l"(a), "l"(b), "r"(sc));
}

constexpr uint32_t P_VEC = 212992, P_ROW = P_VEC + 6144, P_BAR = P_ROW + 4096, P_SMEM = P_BAR + 256;
constexpr uint32_t P_OUT = 180224, P_OUT3 = 147456, P_OUT4 = 163840;
#define PPH 1
#define FLAG_ST "st.release.gpu.global.u32"
#define FLAG_LD "ld.acquire.gpu.global.u32"
#define BA3 2
#define BA 5
#define BA0 1
constexpr int P_SA = 5, P_SB = 3;
constexpr int PB_FA = 0, PB_EA = 5, PB_FB = 10, PB_EB = 13, PB_OUT = 16;
enum { C_Y = 0, C_G = 1, C_X1 = 2, C_U = 3, C_S1 = 8, C_S3 = 9 };
enum { V_GA = 0, V_A = 1, V_B = 2, V_GB = 3, V_VA = 4, V_VB = 5, V_VC = 6, V_C3 = 7 };
struct PostMaps { CUtensorMap o, wo, y, w1, g, w2, x1, w3, u, w4, out; };
struct PostPtrs { const bf16* x; };

struct GeluK { float k0, k1, kh; };
__device__ __forceinline__ GeluK gelu_k(float c) { return {0.7978845608028654f * c, 0.7978845608028654f * 0.044715f * c * c * c, 0.5f * c}; }
__device__ __forceinline__ float gelu_s(float t, const GeluK& k) {
    const float u = t * fmaf(t * t, k.k1, k.k0);
    float th; asm("tanh.approx.f32 %0, %1;" : "=f"(th) : "f"(u));
    const float hx = k.kh * t;
    return fmaf(hx, th, hx);
}
__device__ __forceinline__ float2 ldsv(uint32_t a) {
    float2 v; asm("ld.shared.v2.f32 {%0,%1}, [%2];" : "=f"(v.x), "=f"(v.y) : "r"(a)); return v;
}
__device__ __forceinline__ void wait_smem(uint32_t a, int target) {
    int it = 0;
#pragma unroll 1
    while (true) {
        int v;
        asm volatile("ld.acquire.cta.shared.u32 %0, [%1];" : "=r"(v) : "r"(a) : "memory");
        if (__all_sync(~0u, v >= target)) break;
        spin_guard(++it);
    }
}

#define PP(i)
#define PH_(c, w, i)
struct Pipe { int st, ph; };
template <int ST> __device__ __forceinline__ void adv(Pipe& p) { if (++p.st == ST) { p.st = 0; p.ph ^= 1; } }

__device__ __forceinline__ void post_produce(uint32_t sb, const PostMaps& mp, int mb, int nb, int rank) {
    const int rh = 2 * mb + rank, lane = threadIdx.x & 31;
    int st = 0, pp = 0, st2 = 0, pp2 = 0;
#pragma unroll 1
    for (int ph = 0; ph < 7; ph++) {
        const bool W = ph == 3 || ph == 4;
        if (ph == 3 || ph >= 5) {
            const int n = ph == 5 ? P_SB : P_SA;
            const uint32_t e = sb + P_BAR + 8 * (ph == 5 ? PB_EB : PB_EA);
#pragma unroll 1
            for (int i = 0; i < n; i++) mbar_wait_w(e + 8 * i, pp ^ (i >= st));
            if (ph == 6) break;
            if (ph == 5) wait_smem(sb + P_BAR + 8 * (PB_OUT + (lane & 1)), 4);
            int t = st; st = st2; st2 = t; t = pp; pp = pp2; pp2 = t;
        }
        const int ST = W ? P_SB : P_SA, NK = ph == 0 ? 64 : ph == 5 ? 56 : 16, NB = ph == 3 ? 4 : ph == 4 ? 3 : 2;
        const uint32_t SBYTES = W ? 49152 : 32768;
        const uint32_t full = sb + P_BAR + 8 * (W ? PB_FB : PB_FA), empty = sb + P_BAR + 8 * (W ? PB_EB : PB_EA);
        const CUtensorMap* ta = &mp.o + 2 * (ph > 3 ? ph - 1 : ph);
        const CUtensorMap* tb = ta + 1;
        const int n0 = ph == 3 ? nb * 256 : ph == 4 ? 2048 + nb * 192 : nb * 128;
        const int amul = ph == 0 ? 256 : 64, arow = ph == 0 ? rh * 8 : rh * 64;
        const uint32_t shifts = ph == 2 ? 0x04000301u : 0x02020202u;
        const uint32_t* fl = &g_pflag[(ph == 5 ? C_U + ((lane >> 3) & 1) : ph - 1) * 256 + (ph == 2 ? min(max(rh + min(lane >> 3, 2) - 1, 0), 31) : rh) * 8 + (lane & 7)];
        uint32_t have = ph == 0 || ph == 4 ? 9 : 0;
        auto order = [&](int i, int& need, int& grp) {
            need = 0; grp = i & 1;
            if (ph == 5) {
                const int q = i < 32 ? i >> 2 : ((i - 32) * 43) >> 7, src = (q + (nb & 6)) & 7;
                need = (i < 32 ? 1 : 256) << src; grp = i < 32 ? i & 3 : i - 32 - 3 * q;
                return i + (src - q) * (i < 32 ? 4 : 3);
            }
            if (ph == 0) return i;
            const int kb = (i + 2 * (nb & 6)) & 15;
            need = (ph == 2 ? 0x10101 : 1) << (kb >> 1);
            return kb;
        };
        PH_(ph == PPH, 0, 26) PH_(ph == PPH, 1, 26)
        int ib = 0, sB = st, pB = pp;
#pragma unroll 1
        for (int i = 0; i < NK; i++) {
            int need, grp;
#pragma unroll 1
            for (const int lim = i || ph > 3 ? i + 1 : ph == 3 ? BA3 : ph ? BA : BA0; ib < lim; ib++) {
                const int kb = order(ib, need, grp);
                const uint32_t a = sb + sB * SBYTES, f = full + 8 * sB;
                mbar_wait_w(empty + 8 * sB, pB ^ 1);
                e_expect(f, 16384 + NB * 8192);
                e_tma2d(a + 16384, tb, n0, kb * 64, f);
                e_tma2d(a + 24576, tb, n0 + 64, kb * 64, f);
                if (W) { e_tma2d(a + 32768, tb, n0 + 128, kb * 64, f); if (ph == 3) e_tma2d(a + 40960, tb, n0 + 192, kb * 64, f); }
                if (++sB == ST) { sB = 0; pB ^= 1; }
            }
            const int kb = order(i, need, grp);
            PH_(ph == PPH && i == 0, 0, 27) PH_(ph == PPH && i == 0, 1, 27)
            if ((__ballot_sync(~0u, have > grp) & need) != need) {
                int it = 0;
#pragma unroll 1
                do {
                    asm volatile(FLAG_LD " %0, [%1];" : "=r"(have) : "l"(fl) : "memory");
                    spin_guard(++it);
                } while ((__ballot_sync(~0u, have > grp) & need) != need);
                PH_(ph == PPH && i == 0, 0, 23) PH_(ph == PPH, 0, 24) PH_(ph == PPH && i == 0, 1, 23) PH_(ph == PPH, 1, 24)
                asm volatile("fence.proxy.async.global;" ::: "memory");
                PH_(ph == PPH && i == 0, 0, 25) PH_(ph == PPH && i == 0, 1, 25)
            }
            e_tma2d_mc(sb + st * SBYTES + rank * 8192, ta, kb * amul, arow + (int)((shifts >> ((kb & 12) * 2)) & 7) - 2, full + 8 * st);
            if (++st == ST) { st = 0; pp ^= 1; }
        }
    }
}

template <int PH>
__device__ __forceinline__ void post_mma(uint32_t sb, float* acc, Pipe& p, int wg, bool lead, int pi, int mb, int nb) {
    constexpr bool W = PH == 3 || PH == 4;
    constexpr int ST = W ? P_SB : P_SA, SBYTES = W ? 49152 : 32768, NK = PH == 0 ? 64 : PH == 5 ? 56 : 16;
    const uint32_t full = sb + P_BAR + 8 * (W ? PB_FB : PB_FA), empty = sb + P_BAR + 8 * (W ? PB_EB : PB_EA);
    constexpr uint64_t DA = PH == 0 ? mkdesc(SB0, 128, 1024, 0) : mkdesc(SB0, 16, 1024, 1);
    constexpr uint64_t DB = mkdesc(SB0 + 16384, 8192, 1024, 1);
    auto release = [&](int st) { if (lead) { mbar_arrive_cluster(empty + 8 * st, 0); mbar_arrive_cluster(empty + 8 * st, 1); } };
    int prev = 0;
#pragma unroll 1
    for (int kb = 0; kb < NK; kb++) {
        mbar_wait_w(full + 8 * p.st, p.ph);
        const uint32_t so = p.st * (SBYTES >> 4);
        const uint32_t a = (uint32_t)DA + so + wg * 512, b = (uint32_t)DB + so;
        wg_fence();
#pragma unroll
        for (int k = 0; k < 4; k++) {
            const uint64_t da = (DA & 0xffffffff00000000ull) | (a + k * (PH == 0 ? 16 : 2)), db = (DB & 0xffffffff00000000ull) | (b + k * 128);
            if (PH == 3) wgmma_ss256(acc, da, db, (kb | k) != 0);
            else if (PH == 4) wgmma_ss192(acc, da, db, (kb | k) != 0);
            else wgmma_ss128<PH == 0>(acc, da, db, (kb | k) != 0);
        }
        wg_commit();
        if (kb == 0) { PP(pi) if (PH == 0 && wg == 0) TL(11) }
        wg_wait<1>();
        if (kb > 0) release(prev);
        prev = p.st;
        adv<ST>(p);
    }
    wg_wait<0>();
    release(prev);
    PP(pi + 1)
}

__global__ void __cluster_dims__(2, 1, 1) __launch_bounds__(384, 1)
k_post(const __grid_constant__ PostMaps mp, const __grid_constant__ PostPtrs pp) {
    extern __shared__ uint8_t smraw[];
    const uint32_t sb = smem_u32(smraw);
    if ((sb & 0x3FFFF) != SB0) __trap();
    const int tid = threadIdx.x, lane = tid & 31;
    const int rank = blockIdx.x & 1;
    const uint32_t bars = sb + P_BAR;
    if (tid == 64 && rank == 0) {
        const uint32_t c = min(ldg_rlx1(&g_cls[smid() & 255]), 4u);
        unsigned long long v = atomicAdd(&g_pt, 1ull << (8 * c));
        int r = (v >> (8 * c)) & 255, role = r * 4 + c;
        if (c == 4 || r >= 16) {
            int it = 0;
#pragma unroll 1
            do { v = ldg_u64(&g_pt); spin_guard(++it); } while ((v * 0x0101010101ull >> 32 & 255) < gridDim.x / 2);
            r -= c < 4 ? 16 : 0;
            for (uint32_t i = 0; i < c; i++) r += max((int)(v >> (8 * i) & 255) - 16, 0);
            role = -1;
            for (int i = 0; i < 4; i++) {
                const int n = v >> (8 * i) & 255;
                if (r >= 0 && n + r < 16) role = (n + r) * 4 + i;
                r -= max(16 - n, 0);
            }
        }
        sts1(bars + 8 * PB_OUT + 16, role);
    }
    if (tid < PB_OUT) {
        mbar_init(bars + 8 * tid, (tid >= PB_EA && tid < PB_FB) || tid >= PB_EB ? 4 : 1);
        asm volatile("fence.mbarrier_init.release.cluster;" ::: "memory");
    }
    if (tid == 32) sts4(bars + 8 * PB_OUT, 0, 0, 0, 0);
    if (tid >= 256 && tid < 267) asm volatile("prefetch.tensormap [%0];" ::"l"(&mp.o + (tid - 256)) : "memory");
    __syncwarp();
    cluster_sync_all();
    int pr;
    asm volatile("{.reg .b32 r; mapa.shared::cluster.u32 r, %1, 0; ld.shared::cluster.u32 %0, [r];}" : "=r"(pr) : "r"(bars + 8 * PB_OUT + 16) : "memory");
    pr = __reduce_max_sync(~0u, pr);
    if (pr < 0) { cluster_sync_all(); return; }
    const int mb = pr >> 2, nb = (pr & 3) * 2 + rank, cta = pr * 2 + rank;
    if (tid >= 256) {
        asm volatile("setmaxnreg.dec.sync.aligned.u32 40;");
        const int w = __reduce_max_sync(~0u, (tid >> 5) - 8);
        if (w == 0) {
            post_produce(sb, mp, mb, nb, rank);
        } else if (w < 3) {
            const int wg = w - 1, rh = 2 * mb + wg;
            float* rowc = (float*)(smraw + P_ROW) + (wg * 64 + lane * 2) * 8;
            int nout = 0, sig = 0;
#pragma unroll 1
            for (int i = 0; i < 8; i++) {
                const int cnt = (0x54392180u >> (4 * i)) & 15;
                if (cnt < C_S1) {
                    const int ng = cnt == 3 ? 4 : cnt == 4 ? 3 : 2, c0 = cnt == 3 ? nb * 256 : cnt == 4 ? 2048 + nb * 192 : nb * 128;
                    const uint32_t src = sb + (cnt == 3 ? P_OUT3 : cnt == 4 ? P_OUT4 : P_OUT) + wg * ng * 8192;
                    uint32_t* fl = &g_pflag[cnt * 256 + rh * 8 + nb];
#pragma unroll 1
                    for (int j = 0; j < ng; j++) {
                        bar_sync(4 + 4 * wg + (sig++ & 3), 160);
                        if (lane == 0) {
                            PH_(cnt == PPH - 1, wg, 20)
                            asm volatile("cp.async.bulk.tensor.2d.global.shared::cta.bulk_group [%0, {%2, %3}], [%1]; cp.async.bulk.commit_group;"
                                         ::"l"(&mp.y + 2 * (cnt > 3 ? cnt - 1 : cnt)), "r"(src + j * 8192), "r"(c0 + j * 64), "r"(rh * 64) : "memory");
                        }
                        __syncwarp();
                    }
                    if (lane == 0) {
                        asm volatile("cp.async.bulk.wait_group 0; fence.proxy.async.global;" ::: "memory");
                        PH_(cnt == PPH - 1, wg, 21)
                        asm volatile(FLAG_ST " [%0], %1;" ::"l"(fl), "r"(ng) : "memory");
                        PH_(cnt == PPH - 1, wg, 22)
                        asm volatile("st.release.cta.shared.u32 [%0], %1;" ::"r"(bars + 8 * (PB_OUT + wg)), "r"(nout + 1) : "memory");
                    }
                    nout++;
                    __syncwarp();
                    continue;
                }
                bar_sync(4 + 4 * wg + (sig++ & 3), 160);
                uint32_t* c = &g_pcnt[(cnt - C_S1) * 256 + rh * 8];
                if (lane == 0) { signal_count(c); wait_count1(c, 8); }
                __syncwarp();
                const float4* sp = (const float4*)g_st + rh * 32 + lane;
                float4 u[3] = {__ldcg(sp + (cnt == C_S1 ? 0 : 3) * (S_ / 2)), __ldcg(sp + S_ / 2), __ldcg(sp + S_)};
#pragma unroll 1
                for (int h = 0; h < 2; h++) {
                    const float id = 1.0f / DM;
                    const float m = u[0].x * id, var = fmaxf(u[0].y * id - m * m, 0.f) + 1e-5f, r = rsqrtf(var);
                    float sc = r, m2 = 0.f;
                    if (cnt == C_S1) {
                        m2 = r * (u[1].x * id - m * g_cst[0]) + g_cst[3];
                        const float e2 = r * r * (u[2].x * id - 2.0f * m * u[1].y * id + m * m * g_cst[1]) + 2.0f * r * (u[2].y * id - m * g_cst[2]) + g_cst[4];
                        sc = r * rsqrtf(fmaxf(e2 - m2 * m2, 0.f) + 1e-5f);
                    }
                    const GeluK k = gelu_k(sc);
                    *(float4*)(rowc + h * 8) = make_float4(k.k0, k.k1, k.kh, -m);
                    *(float4*)(rowc + h * 8 + 4) = make_float4(var * r, -m2 * var * r, r, -m * r);
#pragma unroll
                    for (int q = 0; q < 3; q++) { u[q].x = u[q].z; u[q].y = u[q].w; }
                }
                bar_arrive(1 + wg, 160);
            }
        }
    } else {
        asm volatile("setmaxnreg.inc.sync.aligned.u32 232;");
        const bf16* xin = pp.x;
        const int wg = __reduce_max_sync(~0u, tid >> 7), wi = (tid >> 5) & 3, g = lane >> 2, tq = lane & 3;
        const int rh = 2 * mb + wg, row = rh * 64 + wi * 16 + g;
        const bool lead = (tid & 127) == 0;
        PP(0)
        if (tid == 0) TL(10)
        uint4 xg[8];
#pragma unroll
        for (int i = 0; i < 8; i++)
            xg[i] = __ldg((const uint4*)(xin + (size_t)(rh * 64 + wi * 16 + (i & 3) * 4 + (lane >> 3)) * DM + nb * 128 + (i >> 2) * 64 + (lane & 7) * 8));
        if (cta < 64) g_modp[cta * 256 + tid] = 0;
        if (cta == 64 && tid < 64) g_tick[tid] = 0;
        {
            float* sv = (float*)(smraw + P_VEC);
            if (tid < 128) {
                const int c = nb * 128 + tid;
                sv[V_GA * 128 + tid] = __ldcg(&g_mod[2 * DM + c]); sv[V_A * 128 + tid] = 1.0f + __ldcg(&g_mod[4 * DM + c]);
                sv[V_B * 128 + tid] = __ldcg(&g_mod[3 * DM + c]); sv[V_GB * 128 + tid] = __ldcg(&g_mod[5 * DM + c]);
            } else {
                const int c = nb * 128 + tid - 128;
                sv[V_VA * 128 + tid - 128] = __ldcg(&g_vec[c]); sv[V_VB * 128 + tid - 128] = __ldcg(&g_vec[DM + c]); sv[V_VC * 128 + tid - 128] = __ldcg(&g_vec[2 * DM + c]);
            }
            sv[V_C3 * 128 + tid] = __ldcg(&g_vec[3 * DM + nb * 256 + tid]);
            if (tid < 192) sv[V_C3 * 128 + 256 + tid] = __ldcg(&g_vec[3 * DM + 2048 + nb * 192 + tid]);
            bar_sync(3, 256);
        }
        uint32_t vec = sb + P_VEC + tq * 8;
        asm volatile("" : "+r"(vec) :: "memory");
        const uint32_t stw = sb + (wi * 16 + ((lane >> 3) & 1) * 8 + (lane & 7)) * 128 + (((lane >> 4) ^ (lane & 7)) << 4);
        int sig = 0;
        auto signal = [&]() { bar_arrive(4 + 4 * wg + (sig++ & 3), 160); };
        auto put64 = [&](uint32_t o, const float* v) {
#pragma unroll
            for (int jj = 0; jj < 4; jj++, v += 8) stsm4((stw + o) ^ (jj << 5), pack2(v[0], v[1]), pack2(v[2], v[3]), pack2(v[4], v[5]), pack2(v[6], v[7]));
            fence_async_smem();
            signal();
        };
        auto out_free = [&](int n) { wait_smem(bars + 8 * (PB_OUT + (lane & 1)), n); };
        const uint32_t rowc = sb + P_ROW + (wg * 64 + wi * 16 + g) * 32, o128 = P_OUT + wg * 16384;
        Pipe pa = {0, 0}, pb = {0, 0};
        uint32_t keep[32];
#define KEEP(jn, e) (((e) & 1) ? bfhi(keep[2 * (jn) + ((e) >> 1)]) : bflo(keep[2 * (jn) + ((e) >> 1)]))
        float mu1[2], r1[2];
        {
            float acc[64];
            const uint32_t xo = sb + o128 + wi * 2048 + (lane >> 3) * 128;
#pragma unroll
            for (int i = 0; i < 8; i++) sts4(xo + (i >> 2) * 8192 + (i & 3) * 512 + (((lane & 7) ^ ((i & 1) * 4 + (lane >> 3))) << 4), xg[i].x, xg[i].y, xg[i].z, xg[i].w);
            __syncwarp();
#pragma unroll
            for (int jj = 0; jj < 8; jj++) ldsm4(keep + jj * 4, (stw + o128 + (jj >> 2) * 8192) ^ ((jj & 3) << 5));
            __syncwarp();
            post_mma<0>(sb, acc, pa, wg, lead, 1, mb, nb);
            float st[2][6];
#pragma unroll
            for (int q = 0; q < 6; q++) st[0][q] = st[1][q] = 0.f;
#pragma unroll
            for (int jn = 0; jn < 16; jn++) {
                const float2 ga = ldsv(vec + V_GA * 512 + jn * 32), a = ldsv(vec + V_A * 512 + jn * 32);
                float xa[4];
#pragma unroll
                for (int e = 0; e < 4; e++) {
                    xa[e] = fmaf((e & 1) ? ga.y : ga.x, acc[4 * jn + e], KEEP(jn, e));
                    st[e >> 1][0] += xa[e]; st[e >> 1][1] = fmaf(xa[e], xa[e], st[e >> 1][1]);
                    acc[4 * jn + e] = ((e & 1) ? a.y : a.x) * xa[e];
                }
                keep[2 * jn] = pack2(xa[0], xa[1]); keep[2 * jn + 1] = pack2(xa[2], xa[3]);
                if ((jn & 7) == 7) put64(o128 + (jn >> 3) * 8192, acc + 4 * jn - 28);
            }
            PP(3)
#pragma unroll
            for (int jn = 0; jn < 16; jn++) {
                const float2 a = ldsv(vec + V_A * 512 + jn * 32), b = ldsv(vec + V_B * 512 + jn * 32);
#pragma unroll
                for (int e = 0; e < 4; e++) {
                    const float y = acc[4 * jn + e], aa = (e & 1) ? a.y : a.x, bb = (e & 1) ? b.y : b.x;
                    float* s = st[e >> 1];
                    s[2] += y; s[3] = fmaf(aa, y, s[3]); s[4] = fmaf(y, y, s[4]); s[5] = fmaf(bb, y, s[5]);
                }
            }
#pragma unroll
            for (int h = 0; h < 2; h++)
#pragma unroll
                for (int q = 0; q < 6; q++) { st[h][q] += __shfl_xor_sync(~0u, st[h][q], 1); st[h][q] += __shfl_xor_sync(~0u, st[h][q], 2); }
            if (tq < 3) {
#pragma unroll
                for (int h = 0; h < 2; h++)
                    red2(g_st + (tq * S_ + row + h * 8) * 2, tq == 0 ? st[h][0] : tq == 1 ? st[h][2] : st[h][4], tq == 0 ? st[h][1] : tq == 1 ? st[h][3] : st[h][5]);
            }
            signal();
            PP(29)
        }
        {
            float acc[64];
            post_mma<1>(sb, acc, pa, wg, lead, 4, mb, nb);
            float c1[2], c2[2], c3[2];
            GeluK gk[2];
            bar_sync(1 + wg, 160);
#pragma unroll
            for (int h = 0; h < 2; h++) {
                const float4 a = lds4f(rowc + h * 256), b = lds4f(rowc + h * 256 + 16);
                gk[h] = {a.x, a.y, a.z}; c1[h] = a.w; c2[h] = b.x; c3[h] = b.y; mu1[h] = b.w; r1[h] = b.z;
            }
#pragma unroll
            for (int jn = 0; jn < 16; jn++) {
                const float2 va = ldsv(vec + V_VA * 512 + jn * 32), vb = ldsv(vec + V_VB * 512 + jn * 32), vc = ldsv(vec + V_VC * 512 + jn * 32);
#pragma unroll
                for (int e = 0; e < 4; e++) {
                    const int h = e >> 1;
                    const float t = fmaf(c1[h], (e & 1) ? va.y : va.x, fmaf(c2[h], (e & 1) ? vb.y : vb.x, fmaf(c3[h], (e & 1) ? vc.y : vc.x, acc[4 * jn + e])));
                    acc[4 * jn + e] = gelu_s(t, gk[h]);
                }
                if ((jn & 7) == 7) put64(o128 + (jn >> 3) * 8192, acc + 4 * jn - 28);
            }
            PP(6)
        }
        {
            float acc[64];
            post_mma<2>(sb, acc, pa, wg, lead, 7, mb, nb);
#pragma unroll
            for (int jn = 0; jn < 16; jn++) {
                const float2 a = ldsv(vec + V_A * 512 + jn * 32), b = ldsv(vec + V_B * 512 + jn * 32);
#pragma unroll
                for (int e = 0; e < 4; e++) {
                    const int h = e >> 1;
                    acc[4 * jn + e] += fmaf(fmaf(KEEP(jn, e), r1[h], mu1[h]), (e & 1) ? a.y : a.x, (e & 1) ? b.y : b.x);
                }
                if ((jn & 7) == 7) put64(o128 + (jn >> 3) * 8192, acc + 4 * jn - 28);
            }
            PP(9)
            float st[2][2] = {{0.f, 0.f}, {0.f, 0.f}};
#pragma unroll
            for (int jn = 0; jn < 16; jn++) {
                const float2 gb = ldsv(vec + V_GB * 512 + jn * 32);
                float z[4];
#pragma unroll
                for (int e = 0; e < 4; e++) {
                    const float x1 = acc[4 * jn + e];
                    st[e >> 1][0] += x1; st[e >> 1][1] = fmaf(x1, x1, st[e >> 1][1]);
                    z[e] = fmaf((e & 1) ? gb.y : gb.x, x1, KEEP(jn, e));
                }
                keep[2 * jn] = pack2(z[0], z[1]); keep[2 * jn + 1] = pack2(z[2], z[3]);
            }
#pragma unroll
            for (int h = 0; h < 2; h++)
#pragma unroll
                for (int q = 0; q < 2; q++) { st[h][q] += __shfl_xor_sync(~0u, st[h][q], 1); st[h][q] += __shfl_xor_sync(~0u, st[h][q], 2); }
            if (tq < 2) red2(g_st + (3 * S_ + row + tq * 8) * 2, tq ? st[1][0] : st[0][0], tq ? st[1][1] : st[0][1]);
            signal();
            PP(30)
        }
        {
            uint32_t v3 = vec + V_C3 * 512;
#pragma unroll 1
            for (int r = 0; r < 2; r++) {
                float acc[128];
#pragma unroll
                for (int i = 96; i < 128; i++) acc[i] = 0.f;
                if (r == 0) post_mma<3>(sb, acc, pb, wg, lead, 10, mb, nb);
                else post_mma<4>(sb, acc, pb, wg, lead, 13, mb, nb);
                float c1[2];
                GeluK gk[2];
                if (r == 0) bar_sync(1 + wg, 160);
                out_free(3 + r);
#pragma unroll
                for (int h = 0; h < 2; h++) { const float4 a = lds4f(rowc + h * 256); gk[h] = {a.x, a.y, a.z}; c1[h] = a.w; }
                uint32_t o = r ? P_OUT4 + wg * 24576 : P_OUT3 + wg * 32768;
#pragma unroll 1
                for (int left = 3 - r; left >= 0; left--) {
#pragma unroll
                    for (int jn = 0; jn < 8; jn++) {
                        const float2 vc = ldsv(v3 + jn * 32);
#pragma unroll
                        for (int e = 0; e < 4; e++) acc[4 * jn + e] = gelu_s(fmaf(c1[e >> 1], (e & 1) ? vc.y : vc.x, acc[4 * jn + e]), gk[e >> 1]);
                    }
                    put64(o, acc);
#pragma unroll
                    for (int i = 0; i < 32; i++) acc[i] = acc[32 + i];
                    if (left > 1) {
#pragma unroll
                        for (int i = 32; i < 64; i++) acc[i] = acc[32 + i];
                        if (left > 2) {
#pragma unroll
                            for (int i = 64; i < 96; i++) acc[i] = acc[32 + i];
                        }
                    }
                    o += 8192; v3 += 256;
                }
                PP(12 + 3 * r)
            }
        }
        {
            float acc[64];
            post_mma<5>(sb, acc, pa, wg, lead, 16, mb, nb);
#pragma unroll
            for (int jn = 0; jn < 16; jn++) {
                const float2 gb = ldsv(vec + V_GB * 512 + jn * 32);
#pragma unroll
                for (int e = 0; e < 4; e++) acc[4 * jn + e] = fmaf((e & 1) ? gb.y : gb.x, acc[4 * jn + e], KEEP(jn, e));
                if ((jn & 7) == 7) put64(o128 + (jn >> 3) * 8192, acc + 4 * jn - 28);
            }
            PP(18)
            if (tid == 0) TL(12)
        }
    }
}

typedef CUresult (*EncFn)(CUtensorMap*, CUtensorMapDataType, cuuint32_t, void*, const cuuint64_t*, const cuuint64_t*, const cuuint32_t*,
                          const cuuint32_t*, CUtensorMapInterleave, CUtensorMapSwizzle, CUtensorMapL2promotion, CUtensorMapFloatOOBfill);

static CUtensorMap make_map(EncFn enc, const void* p, uint64_t inner, uint64_t outer, uint32_t bi = 64) {
    CUtensorMap m;
    cuuint64_t dims[2] = {inner, outer};
    cuuint64_t str[1] = {inner * 2};
    cuuint32_t box[2] = {bi, bi == 64 ? 64u : 16u};
    cuuint32_t es[2] = {1, 1};
    enc(&m, CU_TENSOR_MAP_DATA_TYPE_BFLOAT16, 2, (void*)p, dims, str, box, es, CU_TENSOR_MAP_INTERLEAVE_NONE,
        bi == 64 ? CU_TENSOR_MAP_SWIZZLE_128B : CU_TENSOR_MAP_SWIZZLE_NONE, CU_TENSOR_MAP_L2_PROMOTION_L2_256B, CU_TENSOR_MAP_FLOAT_OOB_FILL_NONE);
    return m;
}
static CUtensorMap make_map_o(EncFn enc, const void* p) {
    CUtensorMap m;
    cuuint64_t dims[2] = {16384, 256};
    cuuint64_t str[1] = {65536};
    cuuint32_t box[2] = {256, 8};
    cuuint32_t es[2] = {1, 1};
    enc(&m, CU_TENSOR_MAP_DATA_TYPE_UINT32, 2, (void*)p, dims, str, box, es, CU_TENSOR_MAP_INTERLEAVE_NONE, CU_TENSOR_MAP_SWIZZLE_NONE,
        CU_TENSOR_MAP_L2_PROMOTION_L2_256B, CU_TENSOR_MAP_FLOAT_OOB_FILL_NONE);
    return m;
}
template <class T> static T* sym(T& s) { void* p = nullptr; cudaGetSymbolAddress(&p, s); return (T*)p; }

static const Delays h_dly = {D_NEAR, D_FAR, D_X2, D_V, D_W2, D_PA, D_WF, D_TV};
extern "C" void kernel_launch(void* const* d_in, const int* in_sizes, int n_in, void* d_out, int out_size) {
    const bf16* x = (const bf16*)d_in[0];
    const bf16* mem0 = (const bf16*)d_in[1];
    const bf16 *Wq = (const bf16*)d_in[2], *Wk = (const bf16*)d_in[3], *Wv = (const bf16*)d_in[4], *Wo = (const bf16*)d_in[5];
    const bf16 *w1 = (const bf16*)d_in[8], *w2 = (const bf16*)d_in[9], *w3 = (const bf16*)d_in[10], *w4 = (const bf16*)d_in[11];
    const bf16 *c = (const bf16*)d_in[12], *wmod = (const bf16*)d_in[13];
    bf16* out = (bf16*)d_out;

    EncFn enc = nullptr;
    cudaDriverEntryPointQueryResult qr;
    cudaGetDriverEntryPoint("cuTensorMapEncodeTiled", (void**)&enc, cudaEnableDefault, &qr);
    CUtensorMap tWq = make_map(enc, Wq, NH * DH, DM), tWk = make_map(enc, Wk, NH * DH, DM), tWv = make_map(enc, Wv, NH * DH, DM);
    PostMaps mp;
    mp.o = make_map_o(enc, sym(g_O)); mp.wo = make_map(enc, Wo, DM, NH * DH);
    mp.y = make_map(enc, sym(g_y), DM, S_); mp.w1 = make_map(enc, w1, DM, DM);
    mp.g = make_map(enc, sym(g_g), DM, S_); mp.w2 = make_map(enc, w2, DM, DM);
    mp.x1 = make_map(enc, sym(g_x1), DM, S_); mp.w3 = make_map(enc, w3, FF, DM);
    mp.u = make_map(enc, sym(g_u), FF, S_); mp.w4 = make_map(enc, w4, DM, FF);
    mp.out = make_map(enc, out, DM, S_);
    cudaFuncSetAttribute(k_rec, cudaFuncAttributeMaxDynamicSharedMemorySize, SM_REC_TOTAL + 2048);
    cudaFuncSetAttribute(k_post, cudaFuncAttributeMaxDynamicSharedMemorySize, P_SMEM);

    uint8_t* arena = (uint8_t*)(((uintptr_t)sym(g_arena) + (2u << 20) - 1) & ~(uintptr_t)((2u << 20) - 1));
    const PostPtrs pp = {x};
    const RecPtrs rp = {x, mem0, c, wmod, w1, w3, arena, 0u, w2, w4, Wo, h_dly};
    const RecMaps rm = {tWq, tWk, tWv, mp.wo, make_map(enc, wmod, 6 * DM, DM, 256), make_map(enc, w3, FF, DM, 256), make_map(enc, w1, DM, DM, 256)};
    k_rec<<<132, 384, SM_REC_TOTAL + 2048>>>(rm, rp);
    k_post<<<132, 384, P_SMEM>>>(mp, pp);
}
```

```cpp
#include <cuda_runtime.h>
#include <cuda.h>
#include <cuda_bf16.h>
#include <stdint.h>
#include <limits.h>

typedef __nv_bfloat16 bf16;

constexpr int S_ = 2048, DM = 1024, NH = 32, DH = 128, NSEG = 64, FF = 3584;
constexpr int SPIN_LIMIT = 1 << 22;
#define W_INFL 2
#define XP 0
#define H_PIECES 4
#define NPROBE 3

__device__ uint8_t g_arena[10 << 20];
__device__ uint32_t g_tick[64];
__device__ uint2 g_clk[66];
__device__ uint32_t g_cls[256];
__device__ unsigned long long g_pt;
__device__ __align__(16) uint32_t g_modp[8 * 2 * DM];
__host__ __device__ constexpr uint32_t blk(uint32_t lb, uint32_t par) {
    return (lb << 13) | ((((lb) ^ (lb >> 3) ^ (lb >> 4) ^ (lb >> 6) ^ par) & 1) << 12);
}
__host__ __device__ constexpr uint32_t lb_x2(uint32_t h) { return (h & 1) | ((h >> 1) << 3); }
__host__ __device__ constexpr uint32_t mem_row(uint32_t kh, uint32_t b, uint32_t r) { return blk(128 | b, kh) + r * 1024; }
__device__ __forceinline__ uint32_t mem_slot(uint32_t s) { return ((s & 1) << 15) | ((s & 2) << 17); }
constexpr uint32_t CNT1 = 0x3d80, CNT_ALL = 0x4000;
constexpr uint32_t LB_PROBE = 6 | 64, LB_TIME = 6;
__host__ __device__ constexpr uint32_t lb_tok(uint32_t h) { return (h & 1) | ((h >> 1) << 3); }
__device__ float g_mod[6 * DM];
__device__ __align__(1024) bf16 g_himg[(S_ + 32) * DM];
__device__ __align__(1024) bf16 g_O[S_ * NH * DH];
__device__ __align__(1024) bf16 g_y[S_ * DM];
__device__ __align__(1024) bf16 g_g[S_ * DM];
__device__ __align__(1024) bf16 g_x1[S_ * DM];
__device__ __align__(16) float g_st[4 * S_ * 2];
__device__ float g_vec[3 * DM + FF];
__device__ float g_cst[8];
__device__ uint32_t g_pcnt[2 * 32 * 8], g_pflag[7 * 32 * 8];
__device__ __align__(1024) bf16 g_u[S_ * FF];

#define TL(i) {}
#define TLC(i) {}
__device__ __forceinline__ uint32_t smem_u32(const void* p) { return (uint32_t)__cvta_generic_to_shared(p); }
__device__ __forceinline__ void spin_guard(int it) {
    asm volatile("{.reg .pred p; setp.gt.s32 p, %0, %1; @p st.global.u32 [%2], %0;}" ::"r"(it), "n"(SPIN_LIMIT), "l"(1ull));
}
__device__ __forceinline__ void wg_fence() { asm volatile("wgmma.fence.sync.aligned;" ::: "memory"); }
__device__ __forceinline__ void wg_commit() { asm volatile("wgmma.commit_group.sync.aligned;" ::: "memory"); }
template <int N> __device__ __forceinline__ void wg_wait() { asm volatile("wgmma.wait_group.sync.aligned %0;" ::"n"(N) : "memory"); }
__host__ __device__ constexpr uint64_t mkdesc(uint32_t addr, uint32_t lbo, uint32_t sbo, uint32_t swz) {
    return (uint64_t)((addr & 0x3FFFF) >> 4) | ((uint64_t)(lbo >> 4) << 16) | ((uint64_t)(sbo >> 4) << 32) | ((uint64_t)swz << 62);
}
__device__ __forceinline__ uint64_t dadd(uint64_t d, uint32_t o) { return (d & 0xffffffff00000000ull) | (uint32_t)((uint32_t)d + o); }
__device__ __forceinline__ void mbar_init(uint32_t b, uint32_t c) { asm volatile("mbarrier.init.shared.b64 [%0], %1;" ::"r"(b), "r"(c) : "memory"); }
__device__ __forceinline__ void mbar_expect(uint32_t b, uint32_t tx) { asm volatile("mbarrier.arrive.expect_tx.shared.b64 _, [%0], %1;" ::"r"(b), "r"(tx) : "memory"); }
__device__ __forceinline__ void mbar_arrive(uint32_t b) { asm volatile("mbarrier.arrive.shared.b64 _, [%0];" ::"r"(b) : "memory"); }
__device__ __forceinline__ void mbar_arrive_cluster(uint32_t b, uint32_t cta) {
    asm volatile("{.reg .b32 r; mapa.shared::cluster.u32 r, %0, %1; mbarrier.arrive.shared::cluster.b64 _, [r];}" ::"r"(b), "r"(cta) : "memory");
}
__device__ __forceinline__ bool mbar_try(uint32_t b, uint32_t par) {
    uint32_t ok;
    asm volatile("{.reg .pred p; mbarrier.try_wait.parity.shared.b64 p, [%1], %2; selp.u32 %0, 1, 0, p;}" : "=r"(ok) : "r"(b), "r"(par) : "memory");
    return ok;
}
__device__ __forceinline__ void mbar_wait(uint32_t b, uint32_t par) {
    int it = 0;
#pragma unroll 1
    while (!mbar_try(b, par)) { spin_guard(++it); }
}
__device__ __forceinline__ void mbar_wait_w(uint32_t b, uint32_t par) {
    int it = 0;
    bool ok;
#pragma unroll 1
    do { ok = __all_sync(~0u, mbar_try(b, par)); spin_guard(++it); } while (!ok);
}
__device__ __forceinline__ void mbar_wait_cluster(uint32_t b, uint32_t par) {
    int it = 0;
    while (true) {
        uint32_t ok;
        asm volatile("{.reg .pred p; mbarrier.try_wait.parity.acquire.cluster.shared::cta.b64 p, [%1], %2; selp.u32 %0, 1, 0, p;}" : "=r"(ok) : "r"(b), "r"(par) : "memory");
        if (ok) break;
        spin_guard(++it);
    }
}
__device__ __forceinline__ void tma2d(uint32_t dst, const CUtensorMap* m, int c0, int c1, uint32_t bar) {
    asm volatile("cp.async.bulk.tensor.2d.shared::cluster.global.mbarrier::complete_tx::bytes [%0], [%1, {%3, %4}], [%2];" ::"r"(dst), "l"(m), "r"(bar), "r"(c0), "r"(c1) : "memory");
}
#define EVF 1
constexpr uint64_t EVICT_FIRST = 0x12F0000000000000ull;
__device__ __forceinline__ void tma2d_once(uint32_t dst, const CUtensorMap* m, int c0, int c1, uint32_t bar) {
    if (!EVF) { tma2d(dst, m, c0, c1, bar); return; }
    asm volatile("cp.async.bulk.tensor.2d.shared::cluster.global.mbarrier::complete_tx::bytes.L2::cache_hint [%0], [%1, {%3, %4}], [%2], %5;" ::"r"(dst), "l"(m), "r"(bar), "r"(c0), "r"(c1), "l"(EVICT_FIRST) : "memory");
}
__device__ __forceinline__ void tma2d_mc(uint32_t dst, const CUtensorMap* m, int c0, int c1, uint32_t bar, uint16_t mask) {
    asm volatile("cp.async.bulk.tensor.2d.shared::cluster.global.mbarrier::complete_tx::bytes.multicast::cluster [%0], [%1, {%3, %4}], [%2], %5;" ::"r"(dst), "l"(m), "r"(bar), "r"(c0), "r"(c1), "h"(mask) : "memory");
}
__device__ __forceinline__ void bulk_g2s(uint32_t dst, const void* src, uint32_t bytes, uint32_t bar) {
    asm volatile("cp.async.bulk.shared::cluster.global.mbarrier::complete_tx::bytes [%0], [%1], %2, [%3];" ::"r"(dst), "l"(src), "r"(bytes), "r"(bar) : "memory");
}
__device__ __forceinline__ void bar_sync(int id, int n) { asm volatile("bar.sync %0, %1;" ::"r"(id), "r"(n) : "memory"); }
__device__ __forceinline__ void bar_arrive(int id, int n) { asm volatile("bar.arrive %0, %1;" ::"r"(id), "r"(n) : "memory"); }
__device__ __forceinline__ void cluster_sync_all() { asm volatile("barrier.cluster.arrive.aligned; barrier.cluster.wait.aligned;" ::: "memory"); }
__device__ __forceinline__ void fence_async_smem() { asm volatile("fence.proxy.async.shared::cta;" ::: "memory"); }
__device__ __forceinline__ void ldsm4t(uint32_t* r, uint32_t a) {
    asm volatile("ldmatrix.sync.aligned.m8n8.x4.trans.shared.b16 {%0,%1,%2,%3}, [%4];" : "=r"(r[0]), "=r"(r[1]), "=r"(r[2]), "=r"(r[3]) : "r"(a) : "memory");
}
__device__ __forceinline__ void ldsm4(uint32_t* r, uint32_t a) {
    asm volatile("ldmatrix.sync.aligned.m8n8.x4.shared.b16 {%0,%1,%2,%3}, [%4];" : "=r"(r[0]), "=r"(r[1]), "=r"(r[2]), "=r"(r[3]) : "r"(a) : "memory");
}
__device__ __forceinline__ uint32_t movm(uint32_t a) {
    uint32_t d; asm volatile("movmatrix.sync.aligned.m8n8.trans.b16 %0, %1;" : "=r"(d) : "r"(a)); return d;
}
__device__ __forceinline__ void mma16816(float* d, uint32_t a0, uint32_t a1, uint32_t a2, uint32_t a3, uint32_t b0, uint32_t b1) {
    asm volatile("mma.sync.aligned.m16n8k16.row.col.f32.bf16.bf16.f32 {%0,%1,%2,%3},{%4,%5,%6,%7},{%8,%9},{%0,%1,%2,%3};"
                 : "+f"(d[0]), "+f"(d[1]), "+f"(d[2]), "+f"(d[3]) : "r"(a0), "r"(a1), "r"(a2), "r"(a3), "r"(b0), "r"(b1));
}
__device__ __forceinline__ void mma16816z(float* d, const uint32_t* a, uint32_t b0, uint32_t b1) {
    asm volatile("mma.sync.aligned.m16n8k16.row.col.f32.bf16.bf16.f32 {%0,%1,%2,%3},{%4,%5,%6,%7},{%8,%9},{%10,%10,%10,%10};"
                 : "=f"(d[0]), "=f"(d[1]), "=f"(d[2]), "=f"(d[3]) : "r"(a[0]), "r"(a[1]), "r"(a[2]), "r"(a[3]), "r"(b0), "r"(b1), "f"(0.f));
}
__device__ __forceinline__ void mma1688(float* d, uint32_t a0, uint32_t a1, uint32_t b0) {
    asm volatile("mma.sync.aligned.m16n8k8.row.col.f32.bf16.bf16.f32 {%0,%1,%2,%3},{%4,%5},{%6},{%0,%1,%2,%3};"
                 : "+f"(d[0]), "+f"(d[1]), "+f"(d[2]), "+f"(d[3]) : "r"(a0), "r"(a1), "r"(b0));
}
__device__ __forceinline__ uint32_t pack2(float lo, float hi) {
    uint32_t r; asm("cvt.rn.bf16x2.f32 %0, %1, %2;" : "=r"(r) : "f"(hi), "f"(lo)); return r;
}
__device__ __forceinline__ uint32_t hadd2(uint32_t a, uint32_t b) {
    uint32_t r; asm("add.rn.bf16x2 %0, %1, %2;" : "=r"(r) : "r"(a), "r"(b)); return r;
}
__device__ __forceinline__ float bflo(uint32_t u) { return __uint_as_float(u << 16); }
__device__ __forceinline__ float bfhi(uint32_t u) { return __uint_as_float(u & 0xffff0000u); }
__device__ __forceinline__ float ex2(float x) { float r; asm("ex2.approx.ftz.f32 %0, %1;" : "=f"(r) : "f"(x)); return r; }
__device__ __forceinline__ uint4 ldg_rlx4(const void* p) {
    uint4 v; asm volatile("ld.relaxed.gpu.global.v4.u32 {%0,%1,%2,%3}, [%4];" : "=r"(v.x), "=r"(v.y), "=r"(v.z), "=r"(v.w) : "l"(p) : "memory"); return v;
}
__device__ __forceinline__ uint2 ldg_rlx2(const void* p) {
    unsigned long long v; asm volatile("ld.relaxed.gpu.global.b64 %0, [%1];" : "=l"(v) : "l"(p) : "memory");
    return make_uint2((uint32_t)v, (uint32_t)(v >> 32));
}
__device__ __forceinline__ uint32_t ldg_rlx1(const void* p) {
    uint32_t v; asm volatile("ld.relaxed.gpu.global.u32 %0, [%1];" : "=r"(v) : "l"(p) : "memory"); return v;
}
__device__ __forceinline__ void stg_rlx1(void* p, uint32_t v) { asm volatile("st.relaxed.gpu.global.u32 [%0], %1;" ::"l"(p), "r"(v) : "memory"); }
__device__ __forceinline__ void stg_rlx2(void* p, uint32_t x, uint32_t y) {
    unsigned long long v = (unsigned long long)x | ((unsigned long long)y << 32);
    asm volatile("st.relaxed.gpu.global.b64 [%0], %1;" ::"l"(p), "l"(v) : "memory");
}
__device__ __forceinline__ void stg_rlx4(void* p, uint32_t x, uint32_t y, uint32_t z, uint32_t w) {
    asm volatile("st.relaxed.gpu.global.v4.u32 [%0], {%1,%2,%3,%4};" ::"l"(p), "r"(x), "r"(y), "r"(z), "r"(w) : "memory");
}
__device__ __forceinline__ void sts4(uint32_t a, uint32_t x, uint32_t y, uint32_t z, uint32_t w) {
    asm volatile("st.shared.v4.u32 [%0], {%1,%2,%3,%4};" ::"r"(a), "r"(x), "r"(y), "r"(z), "r"(w) : "memory");
}
__device__ __forceinline__ uint4 lds4(uint32_t a) {
    uint4 v; asm volatile("ld.shared.v4.u32 {%0,%1,%2,%3}, [%4];" : "=r"(v.x), "=r"(v.y), "=r"(v.z), "=r"(v.w) : "r"(a) : "memory"); return v;
}
__device__ __forceinline__ void st_async4(uint32_t a, float x, float y, float z, float w, uint32_t bar) {
    asm volatile("st.async.shared::cluster.mbarrier::complete_tx::bytes.v4.f32 [%0], {%1,%2,%3,%4}, [%5];" ::"r"(a), "f"(x), "f"(y), "f"(z), "f"(w), "r"(bar) : "memory");
}
#define F4(d, i) "+f"(d[i]), "+f"(d[i + 1]), "+f"(d[i + 2]), "+f"(d[i + 3])
__device__ __forceinline__ void wgmma_rs32(float* d, const uint32_t* a, uint64_t b, int sc) {
    asm volatile("{.reg .pred p; setp.ne.b32 p, %21, 0;\n wgmma.mma_async.sync.aligned.m64n32k16.f32.bf16.bf16 {%0,%1,%2,%3,%4,%5,%6,%7,%8,%9,%10,%11,%12,%13,%14,%15}, {%16,%17,%18,%19}, %20, p, 1, 1, 0;}"
                 : F4(d, 0), F4(d, 4), F4(d, 8), F4(d, 12) : "r"(a[0]), "r"(a[1]), "r"(a[2]), "r"(a[3]), "l"(b), "r"(sc));
}
__device__ __forceinline__ void wgmma_ss32(float* d, uint64_t a, uint64_t b, int sc) {
    asm volatile("{.reg .pred p; setp.ne.b32 p, %18, 0;\n wgmma.mma_async.sync.aligned.m64n32k16.f32.bf16.bf16 {%0,%1,%2,%3,%4,%5,%6,%7,%8,%9,%10,%11,%12,%13,%14,%15}, %16, %17, p, 1, 1, 1, 0;}"
                 : F4(d, 0), F4(d, 4), F4(d, 8), F4(d, 12) : "l"(a), "l"(b), "r"(sc));
}
__device__ __forceinline__ void wgmma_rs40(float* d, const uint32_t* a, uint64_t b, int sc) {
    asm volatile("{.reg .pred p; setp.ne.b32 p, %25, 0;\n wgmma.mma_async.sync.aligned.m64n40k16.f32.bf16.bf16 {%0,%1,%2,%3,%4,%5,%6,%7,%8,%9,%10,%11,%12,%13,%14,%15,%16,%17,%18,%19}, {%20,%21,%22,%23}, %24, p, 1, 1, 0;}"
                 : F4(d, 0), F4(d, 4), F4(d, 8), F4(d, 12), F4(d, 16) : "r"(a[0]), "r"(a[1]), "r"(a[2]), "r"(a[3]), "l"(b), "r"(sc));
}
__device__ __forceinline__ void wgmma_ss40(float* d, uint64_t a, uint64_t b, int sc) {
    asm volatile("{.reg .pred p; setp.ne.b32 p, %22, 0;\n wgmma.mma_async.sync.aligned.m64n40k16.f32.bf16.bf16 {%0,%1,%2,%3,%4,%5,%6,%7,%8,%9,%10,%11,%12,%13,%14,%15,%16,%17,%18,%19}, %20, %21, p, 1, 1, 1, 0;}"
                 : F4(d, 0), F4(d, 4), F4(d, 8), F4(d, 12), F4(d, 16) : "l"(a), "l"(b), "r"(sc));
}
#define F16(d, i) F4(d, i), F4(d, i + 4), F4(d, i + 8), F4(d, i + 12)
template <int TA>
__device__ __forceinline__ void wgmma_ss128(float* d, uint64_t a, uint64_t b, int sc) {
    asm volatile("{.reg .pred p; setp.ne.b32 p, %66, 0;\n wgmma.mma_async.sync.aligned.m64n128k16.f32.bf16.bf16 "
                 "{%0,%1,%2,%3,%4,%5,%6,%7,%8,%9,%10,%11,%12,%13,%14,%15,%16,%17,%18,%19,%20,%21,%22,%23,%24,%25,%26,%27,%28,%29,%30,%31,"
                 "%32,%33,%34,%35,%36,%37,%38,%39,%40,%41,%42,%43,%44,%45,%46,%47,%48,%49,%50,%51,%52,%53,%54,%55,%56,%57,%58,%59,%60,%61,%62,%63}, %64, %65, p, 1, 1, %67, 1;}"
                 : F16(d, 0), F16(d, 16), F16(d, 32), F16(d, 48) : "l"(a), "l"(b), "r"(sc), "n"(TA));
}

__device__ __forceinline__ float warp_sum(float v) {
#pragma unroll
    for (int o = 16; o; o >>= 1) v += __shfl_xor_sync(~0u, v, o);
    return v;
}
__device__ __forceinline__ float bfround(float x) { return __bfloat162float(__float2bfloat16(x)); }

__device__ __forceinline__ void wait_count1(const uint32_t* p, uint32_t target) {
    int it = 0;
#pragma unroll 1
    while (true) {
        uint32_t v;
        asm volatile("ld.acquire.gpu.global.u32 %0, [%1];" : "=r"(v) : "l"(p) : "memory");
        if (v >= target) break;
        spin_guard(++it);
    }
}
__device__ __forceinline__ void red2(float* p, float a, float b) {
    asm volatile("red.relaxed.gpu.global.add.v2.f32 [%0], {%1, %2};" ::"l"(p), "f"(a), "f"(b) : "memory");
}
__device__ __forceinline__ void l2_prefetch(const void* p, uint32_t bytes) {
    asm volatile("cp.async.bulk.prefetch.L2.global [%0], %1;" ::"l"(p), "r"(bytes) : "memory");
}
__device__ __forceinline__ void signal_count(uint32_t* p) { asm volatile("red.release.gpu.global.add.u32 [%0], 1;" ::"l"(p) : "memory"); }
__device__ __forceinline__ void e_expect(uint32_t b, uint32_t tx) {
    asm volatile("{.reg .pred p; elect.sync _|p, 0xffffffff; @p mbarrier.arrive.expect_tx.shared.b64 _, [%0], %1;}" ::"r"(b), "r"(tx) : "memory");
}
__device__ __forceinline__ void e_tma2d(uint32_t dst, const CUtensorMap* m, int c0, int c1, uint32_t bar) {
    asm volatile("{.reg .pred p; elect.sync _|p, 0xffffffff;\n @p cp.async.bulk.tensor.2d.shared::cluster.global.mbarrier::complete_tx::bytes [%0], [%1, {%3, %4}], [%2];}"
                 ::"r"(dst), "l"(m), "r"(bar), "r"(c0), "r"(c1) : "memory");
}
__device__ __forceinline__ void e_tma2d_hint(uint32_t dst, const CUtensorMap* m, int c0, int c1, uint32_t bar, uint64_t pol) {
    asm volatile("{.reg .pred p; elect.sync _|p, 0xffffffff;\n @p cp.async.bulk.tensor.2d.shared::cluster.global.mbarrier::complete_tx::bytes.L2::cache_hint [%0], [%1, {%3, %4}], [%2], %5;}"
                 ::"r"(dst), "l"(m), "r"(bar), "r"(c0), "r"(c1), "l"(pol) : "memory");
}
__device__ __forceinline__ void e_tma2d_mc(uint32_t dst, const CUtensorMap* m, int c0, int c1, uint32_t bar) {
    asm volatile("{.reg .pred p; elect.sync _|p, 0xffffffff;\n @p cp.async.bulk.tensor.2d.shared::cluster.global.mbarrier::complete_tx::bytes.multicast::cluster [%0], [%1, {%3, %4}], [%2], %5;}"
                 ::"r"(dst), "l"(m), "r"(bar), "r"(c0), "r"(c1), "h"((uint16_t)3) : "memory");
}
__device__ __forceinline__ void e_prefetch(const void* p, uint32_t bytes) {
    asm volatile("{.reg .pred p; elect.sync _|p, 0xffffffff; @p cp.async.bulk.prefetch.L2.global [%0], %1;}" ::"l"(p), "r"(bytes) : "memory");
}
__device__ __forceinline__ void wait_count_w(const uint32_t* p, uint32_t target) {
    int it = 0;
#pragma unroll 1
    while (true) {
        uint32_t v;
        asm volatile("ld.acquire.gpu.global.u32 %0, [%1];" : "=r"(v) : "l"(p) : "memory");
        if (__all_sync(~0u, v >= target)) break;
        spin_guard(++it);
    }
}

__device__ __forceinline__ void ln_row(float* x) {
    float s = 0;
#pragma unroll
    for (int i = 0; i < 32; i++) s += x[i];
    float m = warp_sum(s) * (1.0f / DM);
    float q = 0;
#pragma unroll
    for (int i = 0; i < 32; i++) { x[i] -= m; q += x[i] * x[i]; }
    float r = rsqrtf(warp_sum(q) * (1.0f / DM) + 1e-5f);
#pragma unroll
    for (int i = 0; i < 32; i++) x[i] *= r;
}
__device__ __forceinline__ uint4 pack8(const float* x) {
    return make_uint4(pack2(x[0], x[1]), pack2(x[2], x[3]), pack2(x[4], x[5]), pack2(x[6], x[7]));
}
#define NL 6
constexpr uint32_t SM_HB = 16384, HBK = 5120, SM_SX = 57344, SM_OX = 122880, SM_PX = 124928, SM_PA = 126976, SM_WO = 147456,
                   SM_TAB = 212992, SM_PRE = SM_TAB, SM_BAR = 227328, SM_REC_TOTAL = 227328 + 256;
constexpr uint32_t SB0 = 1024;
constexpr int B_WO = 0, B_HE = 1, B_ROLE = 2, B_HB = 3, B_W = 5;
constexpr int NB_MEM = 1, NB_QK = 2, NB_X1 = 3, NB_X2 = 4, NB_WIN = 5, NB_WG = 6, NB_KDONE = 7, NB_FIN0 = 8, NB_P = 9, NB_PX = 10, NB_G = 11, NB_A = 12, NB_B = 13, NB_C = 14, NB_S = 15;
#define SPF 33
#define SPF_AT 54
#define SPF_R 12
#define SPF_NS 40
#define D_TPV 100
#define V_POS 2
#define D_X2 470
#define D_TV 50
#define D_V 390
#define D_NEAR 1670
#define D_FAR (D_NEAR - 140)
#define E_MUL 28
#define D_WF 60
#define NE 0
#define D_H 0
#define D_W2 170
#define SETTLE 0
#define TV_POS 1
#define D_PA 0
#define NE1 10
#define H_POS 3
#define PA_POS 1
#define K_DLY 0
#define ST_BAR 1
#define W1_AT -1
#define ROT 2
#define ALIGN 0
#define CNT32 0
#define O_POS 1
#define Z_POS 0
#define QF_LATE 100
#define W0_E 3
#define G_AT 24
#define W0_AT 4
#define W0_RS (NL - 1)
#define P_GATE 0
#define NPF (NL + 6)

struct Delays { uint32_t near, far, x2, v, w2, pa, wf, tv; };
#define MISS(i, v)
#define MISS_INIT
#define MISS_OUT
#define HT(i)
#define PROF_INIT
#define PROF(i)
#define PROFV(i, v)
#define PROF_OUT

__device__ __forceinline__ uint32_t clk32() { uint32_t t; asm volatile("mov.u32 %0, %%clock;" : "=r"(t) :: "memory"); return t; }
__device__ __forceinline__ uint32_t smid() { uint32_t t; asm volatile("mov.u32 %0, %%smid;" : "=r"(t)); return t; }
__device__ __forceinline__ uint32_t gtime() { uint32_t t; asm volatile("mov.u32 %0, %%globaltimer_lo;" : "=r"(t) :: "memory"); return t; }
__device__ __forceinline__ void spin_until(uint32_t t0, uint32_t d) { while (clk32() - t0 < d) {} }
template <int N> __device__ __forceinline__ uint32_t delay(uint32_t zero) {
    float x = __uint_as_float(clk32());
#pragma unroll
    for (int i = 0; i < N; i++) asm volatile("ex2.approx.ftz.f32 %0, %0;" : "+f"(x));
    return __float_as_uint(x) & zero;
}
__device__ __forceinline__ uint32_t opaque(uint32_t v) { return __shfl_sync(~0u, v, threadIdx.x & 31); }
__device__ __forceinline__ uint32_t xor_or(uint32_t a, uint32_t b, uint32_t t) {
    uint32_t r; asm volatile("lop3.b32 %0, %1, %2, %3, 0x7E;" : "=r"(r) : "r"(a), "r"(b), "r"(t)); return r;
}
__device__ __forceinline__ uint32_t or3(uint32_t a, uint32_t b, uint32_t c) {
    uint32_t r; asm volatile("lop3.b32 %0, %1, %2, %3, 0xFE;" : "=r"(r) : "r"(a), "r"(b), "r"(c)); return r;
}
__device__ __forceinline__ uint32_t settag(uint32_t v, uint32_t tag) {
    uint32_t r; asm("lop3.b32 %0, %1, 1, %2, 0xB8;" : "=r"(r) : "r"(v), "r"(tag)); return r;
}
__device__ __forceinline__ void ldg4_if(uint4& v, const void* p, bool c) {
    asm volatile("{.reg .pred p; setp.ne.u32 p, %5, 0; @p ld.relaxed.gpu.global.v4.u32 {%0,%1,%2,%3}, [%4];}"
                 : "+r"(v.x), "+r"(v.y), "+r"(v.z), "+r"(v.w) : "l"(p), "r"((uint32_t)c) : "memory");
}
__device__ __forceinline__ uint4 ldg_rlx2x2(const void* p) {
    unsigned long long a, b;
    asm volatile("ld.relaxed.gpu.global.v2.b64 {%0,%1}, [%2];" : "=l"(a), "=l"(b) : "l"(p) : "memory");
    return make_uint4((uint32_t)a, (uint32_t)(a >> 32), (uint32_t)b, (uint32_t)(b >> 32));
}
__device__ __forceinline__ void stg_rlx2x2(void* p, uint32_t x, uint32_t y, uint32_t z, uint32_t w) {
    asm volatile("{.reg .b64 a, b; mov.b64 a, {%1,%2}; mov.b64 b, {%3,%4}; st.relaxed.gpu.global.v2.b64 [%0], {a, b};}" ::"l"(p), "r"(x), "r"(y), "r"(z), "r"(w) : "memory");
}
__device__ __forceinline__ void ldg1_if(uint32_t& v, const void* p, bool c) {
    asm volatile("{.reg .pred p; setp.ne.u32 p, %2, 0; @p ld.relaxed.gpu.global.u32 %0, [%1];}" : "+r"(v) : "l"(p), "r"((uint32_t)c) : "memory");
}
__device__ __forceinline__ void sts2(uint32_t a, float x, float y) { asm volatile("st.shared.v2.f32 [%0], {%1,%2};" ::"r"(a), "f"(x), "f"(y) : "memory"); }
__device__ __forceinline__ void sts4f(uint32_t a, float x, float y, float z, float w) {
    asm volatile("st.shared.v4.f32 [%0], {%1,%2,%3,%4};" ::"r"(a), "f"(x), "f"(y), "f"(z), "f"(w) : "memory");
}
__device__ __forceinline__ void sts1(uint32_t a, uint32_t x) { asm volatile("st.shared.u32 [%0], %1;" ::"r"(a), "r"(x) : "memory"); }
__device__ __forceinline__ uint32_t lds1(uint32_t a) { uint32_t v; asm volatile("ld.shared.u32 %0, [%1];" : "=r"(v) : "r"(a) : "memory"); return v; }
__device__ __forceinline__ float4 lds4f(uint32_t a) {
    float4 v; asm volatile("ld.shared.v4.f32 {%0,%1,%2,%3}, [%4];" : "=f"(v.x), "=f"(v.y), "=f"(v.z), "=f"(v.w) : "r"(a) : "memory"); return v;
}
__device__ __forceinline__ float2 lds2f(uint32_t a) {
    float2 v; asm volatile("ld.shared.v2.f32 {%0,%1}, [%2];" : "=f"(v.x), "=f"(v.y) : "r"(a) : "memory"); return v;
}
__device__ __forceinline__ bool any_bit0(uint32_t x) {
    uint32_t r;
    asm volatile("{.reg .pred p, q; .reg .b32 t; and.b32 t, %1, 1; setp.ne.u32 p, t, 0; vote.sync.any.pred q, p, 0xffffffff; selp.u32 %0, 1, 0, q;}" : "=r"(r) : "r"(x));
    return r;
}
__device__ __forceinline__ float rcp_fast(float x) { float r; asm("rcp.approx.ftz.f32 %0, %1;" : "=f"(r) : "f"(x)); return r; }
__device__ __forceinline__ void stsm4(uint32_t a, uint32_t r0, uint32_t r1, uint32_t r2, uint32_t r3) {
    asm volatile("stmatrix.sync.aligned.m8n8.x4.shared.b16 [%0], {%1,%2,%3,%4};" ::"r"(a), "r"(r0), "r"(r1), "r"(r2), "r"(r3) : "memory");
}
__device__ __forceinline__ void stsm4t(uint32_t a, uint32_t r0, uint32_t r1, uint32_t r2, uint32_t r3) {
    asm volatile("stmatrix.sync.aligned.m8n8.x4.trans.shared.b16 [%0], {%1,%2,%3,%4};" ::"r"(a), "r"(r0), "r"(r1), "r"(r2), "r"(r3) : "memory");
}
__device__ __forceinline__ uint32_t and3(uint32_t a, uint32_t b, uint32_t c) {
    uint32_t r; asm("lop3.b32 %0, %1, %2, %3, 0x80;" : "=r"(r) : "r"(a), "r"(b), "r"(c)); return r;
}
__device__ __forceinline__ void red_mem(void* p, uint32_t x, uint32_t y, uint32_t z, uint32_t w, void* q, uint32_t e, bool c) {
    asm volatile("{.reg .pred p; setp.ne.u32 p, %7, 0; red.relaxed.gpu.global.add.noftz.v4.bf16x2 [%0], {%1,%2,%3,%4}; @p red.relaxed.gpu.global.add.noftz.bf16x2 [%5], %6;}"
                 ::"l"(p), "r"(x), "r"(y), "r"(z), "r"(w), "l"(q), "r"(e), "r"((uint32_t)c) : "memory");
}
__device__ __forceinline__ void stg4_if(bool c, void* p, uint32_t x) {
    asm volatile("{.reg .pred p; setp.ne.u32 p, %2, 0; @p st.relaxed.gpu.global.v4.u32 [%0], {%1,%1,%1,%1};}" ::"l"(p), "r"(x), "r"((uint32_t)c) : "memory");
}
__device__ __forceinline__ uint32_t max3u(uint32_t a, uint32_t b, uint32_t c) { return __vimax3_u32(a, b, c); }
__device__ __forceinline__ void fence_gpu() { asm volatile("fence.acq_rel.gpu;" ::: "memory"); }

__device__ __forceinline__ void h_load(uint32_t sb, const uint8_t* hsrc, int pass, uint32_t rank, uint32_t rot) {
    const uint8_t* src = hsrc + (size_t)pass * 65536;
    const uint32_t bar = sb + SM_BAR + 8 * (B_HB + (pass & 1)), dst = sb + SM_HB + (pass & 1) * 65536 + rank * 4 * HBK;
    e_expect(bar, 32768);
#pragma unroll 1
    for (int i = 0; i < H_PIECES; i++) {
        const uint32_t o = ((i + rot) & (H_PIECES - 1)) * (16384 / H_PIECES);
        asm volatile("{.reg .pred p; elect.sync _|p, 0xffffffff;\n"
                     " @p cp.async.bulk.shared::cluster.global.mbarrier::complete_tx::bytes.multicast::cluster [%0], [%1], %4, [%2], %3;}"
                     ::"r"(dst + o + (o >> 12) * 1024), "l"(src + o), "r"(bar), "h"((uint16_t)3), "n"(16384 / H_PIECES) : "memory");
    }
}
__device__ __forceinline__ void h_piece(uint32_t sb, const uint8_t* hsrc, int pass, uint32_t rank, uint32_t i, bool first) {
    const uint32_t bar = sb + SM_BAR + 8 * (B_HB + (pass & 1));
    asm volatile("{.reg .pred p, q; elect.sync _|p, 0xffffffff; setp.le.and.s32 p, %5, 64, p; setp.ne.and.u32 q, %4, 0, p;\n"
                 " @q mbarrier.arrive.expect_tx.shared.b64 _, [%2], 32768;\n"
                 " @p cp.async.bulk.shared::cluster.global.mbarrier::complete_tx::bytes.multicast::cluster [%0], [%1], 4096, [%2], %3;}"
                 ::"r"(sb + SM_HB + (pass & 1) * 65536 + (rank * 4 + i) * HBK), "l"(hsrc + (uint32_t)(pass * 65536 + i * 4096)), "r"(bar), "h"((uint16_t)3), "r"((uint32_t)first), "r"(pass) : "memory");
}
__device__ __forceinline__ uint4 ldg_b128(const void* p) {
    uint4 v;
    asm volatile("{.reg .b128 t; .reg .b64 a, b; ld.relaxed.gpu.global.b128 t, [%4]; mov.b128 {a, b}, t; mov.b64 {%0,%1}, a; mov.b64 {%2,%3}, b;}"
                 : "=r"(v.x), "=r"(v.y), "=r"(v.z), "=r"(v.w) : "l"(p) : "memory");
    return v;
}
__device__ __forceinline__ void ldg_b128_into(uint4& v, const void* p) {
    asm volatile("{.reg .b128 t; .reg .b64 a, b; ld.relaxed.gpu.global.b128 t, [%4]; mov.b128 {a, b}, t; mov.b64 {%0,%1}, a; mov.b64 {%2,%3}, b;}"
                 : "+r"(v.x), "+r"(v.y), "+r"(v.z), "+r"(v.w) : "l"(p) : "memory");
}
__device__ __forceinline__ void stg_b128_if(bool c, void* p, uint32_t x, uint32_t y, uint32_t z, uint32_t w) {
    asm volatile("{.reg .pred p; setp.ne.u32 p, %5, 0; @p st.relaxed.gpu.global.v4.u32 [%0], {%1,%2,%3,%4};}"
                 ::"l"(p), "r"(x), "r"(y), "r"(z), "r"(w), "r"((uint32_t)c) : "memory");
}
__device__ __forceinline__ float pretag(float x, uint32_t add, uint32_t keep) { return __uint_as_float((__float_as_uint(x) + add) & keep); }

template <class F, class G>
__device__ __forceinline__ void softmax_rows(uint32_t src, uint32_t dst, uint32_t g16, int row0, F ready, G mid) {
    const uint32_t u = (g16 >> 7) & 3, e = ((g16 >> 9) << 3) | ((g16 >> 4) & 7);
    uint32_t se = src + e * 8, su = se + u * 1088, d0 = dst + e * 16 + u * 4, d1 = dst + 512 + e * 4;
    int vis = row0 + (e >> 2) - 2 * (e & 3) - 8 * u;
    asm volatile("" : "+r"(se), "+r"(su), "+r"(d0), "+r"(d1), "+r"(vis));
    ready();
    const float2 p0 = lds2f(su), p1 = lds2f(su + 256), p2 = lds2f(su + 512), p3 = lds2f(su + 768);
    const float2 m0 = lds2f(se + 4352), m1 = lds2f(se + 4352 + 256), m2 = lds2f(se + 4352 + 512), m3 = lds2f(se + 4352 + 768);
    float a0 = (p0.x + p1.x) + (p2.x + p3.x), a1 = (p0.y + p1.y) + (p2.y + p3.y);
    const float a2 = (m0.x + m1.x) + (m2.x + m3.x), a3 = (m0.y + m1.y) + (m2.y + m3.y);
    if (vis < 0) a0 = -1e9f / 0.08838834764831845f;
    if (vis < 1) a1 = -1e9f / 0.08838834764831845f;
    int k = __float_as_int(fmaxf(fmaxf(a0, a1), fmaxf(a2, a3)));
    k ^= (k >> 31) & 0x7fffffff;
    const bool hi = g16 & 64;
    const int k0 = __reduce_max_sync(~0u, hi ? INT_MIN : k), k1 = __reduce_max_sync(~0u, hi ? k : INT_MIN);
    mid();
    k = hi ? k1 : k0;
    const float m = __int_as_float(k ^ ((k >> 31) & 0x7fffffff));
    const float sl2 = 0.08838834764831845f * 1.4426950408889634f, mb = -m * sl2;
    sts1(d0, pack2(ex2(fmaf(a0, sl2, mb)), ex2(fmaf(a1, sl2, mb))));
    sts1(d1, pack2(ex2(fmaf(a2, sl2, mb)), ex2(fmaf(a3, sl2, mb))));
}

__device__ __forceinline__ uint32_t pack_h2(float lo, float hi) {
    uint32_t r; asm("cvt.rn.satfinite.f16x2.f32 %0, %1, %2;" : "=r"(r) : "f"(hi), "f"(lo)); return r;
}
__device__ __forceinline__ float2 unpack_h2(uint32_t u) {
    float2 r; asm("{.reg .b16 l, h; mov.b32 {l, h}, %2; cvt.f32.f16 %0, l; cvt.f32.f16 %1, h;}" : "=f"(r.x), "=f"(r.y) : "r"(u)); return r;
}
__device__ __forceinline__ uint32_t add_h2(uint32_t a, uint32_t b) { uint32_t r; asm("add.rn.f16x2 %0, %1, %2;" : "=r"(r) : "r"(a), "r"(b)); return r; }
__device__ __forceinline__ uint32_t max_h2(uint32_t a, uint32_t b) { uint32_t r; asm("max.f16x2 %0, %1, %2;" : "=r"(r) : "r"(a), "r"(b)); return r; }
__device__ __forceinline__ void stg2_if(bool c, void* p, uint32_t x, uint32_t y) {
    asm volatile("{.reg .pred p; .reg .b64 v; setp.ne.u32 p, %3, 0; mov.b64 v, {%1, %2}; @p st.relaxed.gpu.global.b64 [%0], v;}" ::"l"(p), "r"(x), "r"(y), "r"((uint32_t)c) : "memory");
}
__device__ __forceinline__ void stg1_if(bool c, void* p, uint32_t x) {
    asm volatile("{.reg .pred p; setp.ne.u32 p, %2, 0; @p st.relaxed.gpu.global.u32 [%0], %1;}" ::"l"(p), "r"(x), "r"((uint32_t)c) : "memory");
}
struct U2 { uint32_t x, y; };
__device__ __forceinline__ U2 ldg_u2(const void* p) {
    U2 v; asm volatile("{.reg .b64 t; ld.relaxed.gpu.global.b64 t, [%2]; mov.b64 {%0, %1}, t;}" : "=r"(v.x), "=r"(v.y) : "l"(p) : "memory"); return v;
}
constexpr int POLL_LIMIT = 1 << 16;
constexpr float SM_L2E = 0.08838834764831845f * 1.4426950408889634f;
template <int V> struct IC { static constexpr int value = V; };
typedef unsigned long long u64;
__device__ __forceinline__ uint32_t lo32(u64 v) { return (uint32_t)v; }
__device__ __forceinline__ uint32_t hi32(u64 v) { return (uint32_t)(v >> 32); }
__device__ __forceinline__ u64 ldg_u64(const void* p) { u64 v; asm volatile("ld.relaxed.gpu.global.b64 %0, [%1];" : "=l"(v) : "l"(p) : "memory"); return v; }
__device__ __forceinline__ void ldg_u64_if(u64& v, const void* p, bool c) {
    asm volatile("{.reg .pred p; setp.ne.u32 p, %2, 0; @p ld.relaxed.gpu.global.b64 %0, [%1];}" : "+l"(v) : "l"(p), "r"((uint32_t)c) : "memory");
}
__device__ __forceinline__ void rec_main(uint32_t sb, const CUtensorMap* tWo, uint8_t* arena, int role, int hinfo, int wg, uint32_t zero, const Delays& dly) {
    const int hA = hinfo & 255;
    const int tid = threadIdx.x, t = tid & 127, lane = tid & 31, wi = t >> 5;
    const uint32_t bars = sb + SM_BAR;
    const int head = role >> 2, qd = role & 3, j = blockIdx.x & 1, kh = role & 1;
    const uint32_t mypar = head >= hA;
    const bool warp0 = __all_sync(~0u, wi == 0), warp1 = __all_sync(~0u, wi == 1);
    const uint8_t* hsrc = (const uint8_t*)g_himg + kh * 32768 + j * 16384;
    auto tokbase = [&](int ty) { return ((ty + 1) << 21) + blk(lb_tok(head), mypar ^ ((hinfo >> (8 + ty)) & 1)); };
    const uint32_t tbw = tokbase(wg), tbq = tokbase(0) + (qd >> 1) * 2048 + (qd & 1) * 8;
    uint32_t w[32 - NL][4];
    const uint32_t frow = ((lane >> 4) * 8 + (lane & 7)) * 128, fx = ((lane >> 3) & 1) ^ (lane & 7);
    const uint32_t wl0 = sb + wg * 65536 + frow + ((fx ^ (2 * wi)) << 4);
    {
#pragma unroll 1
        for (int i = 0; i < 4; i++) mbar_wait_w(bars + 8 * (B_W + (wg == 2 ? 8 + i : 2 * i + wg)), 0);
#pragma unroll
        for (int p = NL; p < 32; p++) ldsm4t(w[p - NL], wl0 + p * 2048);
        fence_async_smem();
        if (wg < 2) bar_sync(NB_WG, 256);
        if (wg > 0) wait_count_w(&g_tick[32 + (lane & 3) * 8], 1);
        if (wg == 1 && warp0) {
            if (lane == 0) mbar_arrive_cluster(bars + 8 * B_HE, j ^ 1);
            asm volatile("fence.proxy.async.global;" ::: "memory");
            mbar_wait_w(bars + 8 * B_HE, 0);
#pragma unroll 1
            for (int i = 0; i < 2; i++) h_load(sb, hsrc, i, j, head);
        }
        TL(3 + wg)
    }
    uint32_t g16 = opaque(t * 16);
    auto G16 = [&]() { asm volatile("" : "+r"(g16)); return g16; };
    const uint32_t wu = __reduce_max_sync(~0u, wi), sbl = sb - wu * 512;
    const uint32_t xso = blk(lb_x2(head), mypar), cu = kh * 2048 + (2 * j + (wu >> 1)) * 512;
    const uint32_t u_xo = xso + wg * 16384 + (wu & 1) * 2048 + (cu >> 1) - wu * 256, u_to = tbw + (wu & 1) * 16384 + cu - wu * 512;
    const uint32_t mrow = wg < 2 ? mem_row(wu >> 1, wg * 2 + (wu & 1), qd) : mem_row(kh, wu, 0);
    const uint32_t u_m = mrow - wu * 512, u_e = mrow + 512 - wu * (CNT32 ? 64 : 128);
#define TAB(i) lds1(sb + SM_TAB + (i) * 512 + (G16() >> 2))
    {
        const uint32_t r8 = lane & 7;
        bar_sync(NB_X2, 384);
        if (wg == 0 && lane == 0) {
            mbar_expect(bars + 8 * B_WO, 16384);
            tma2d(sb + SM_WO + wi * 16384, tWo, (wi >> 1) * 512 + qd * 128 + (wi & 1) * 64, head * DH, bars + 8 * B_WO);
            tma2d(sb + SM_WO + wi * 16384 + 8192, tWo, (wi >> 1) * 512 + qd * 128 + (wi & 1) * 64, head * DH + 64, bars + 8 * B_WO);
        }
        __syncwarp();
        const uint32_t tb = sb + SM_TAB + wg * 1536 + t * 4, ma = sb + SM_HB + 4096 + r8 * 128;
        if (wg < 2) {
            sts1(tb, sb + SM_WO + wi * 16384 + frow + ((fx ^ (2 * wg)) << 4));
            sts1(tb + 512, wl0);
            sts1(tb + 1024, ma + (((lane >> 3) ^ r8) << 4));
        } else {
            sts1(tb, ma + (wi & 1) * HBK + ((((wi & 2) + (lane >> 4) * 4 + ((lane >> 3) & 1)) ^ r8) << 4));
            sts1(tb + 512, ((((wi & 2) + 5) ^ r8) << 4) + ((CNT32 ? (lane & 3) == 3 : lane & 1) ? ma + ((wi & 1) + (lane >> 3) * 2) * HBK : sb + SM_HB - 128));
            sts1(tb + 1024, mem_row(role >> 6, (role >> 4) & 3, (role >> 2) & 3) + (lane < 8 ? qd * 128 + lane * 16 : 512 + qd * 32 + (lane & 1) * 16));
        }
    }
    PROF_INIT
    MISS_INIT
#define HB(ks) dadd(mkdesc(SB0 + SM_HB + ((ks) >> 2) * HBK + ((ks) & 3) * 32, 16, 1024, 1), hbo)
#define STEP_CONSTS                                                                                  \
    const uint32_t tag = (s & 1) ^ 1, ttag = ((s >> 1) & 1) ^ 1, tso = (s & 1) * 32768;              \
    G16();                            \
    const int p = s + 2, b = p & 1;                                                                  \
    uint32_t hbo = b * 4096, fz[5] = {0, 0, 0, 0, 0};                                                \
    const uint32_t ftag = (((p - 1) >> 1) & 1) ^ 1, ptag = ((p >> 1) & 1) ^ 1;                       \
    const uint32_t pso = tbw + (1 << 20) + (b ^ 1) * 32768 + j * 16384 + kh * 2048;
#define SCHED_FENCE(i) fz[i] = clk32();
#define FZ ((fz[0] | fz[1] | fz[2] | fz[3] | fz[4]) & zero)
#define BLOCK_FENCE asm volatile("pmevent 0;" ::: "memory");
    constexpr int GAP = 32 / NL;
#define l16 (sbl + g16)
#define g8 (g16 >> 1)
    uint4 u, v;
    uint8_t *pdst, *fdst;
    auto tok_pack = [&](int ty, const float* acc, uint32_t ftag, uint32_t ptag, bool later = false) {
        const bool tg = ty == 2 || !(g16 & 64);
        const uint32_t add = tg ? (ftag ^ 1) << 16 : 0u, keep = tg ? 0xfffe0000u : ~0u;
        const uint32_t add1 = ty == 2 ? 0u : add, keep1 = ty == 2 ? ~0u : keep;
        const uint32_t add2 = ty == 0 ? add : 0u, keep2 = ty == 0 ? keep : ~0u;
        v = {pack2(pretag(acc[0], add, keep), pretag(acc[1], add1, keep1)), pack2(acc[2], acc[3]),
             pack2(pretag(acc[4], add2, keep2), pretag(acc[5], add2, keep2)), pack2(acc[6], acc[7])};
        if (ty < 2) { v.x = movm(v.x); v.z = movm(v.z); v.y = movm(v.y); v.w = movm(v.w); }
        u = {pack2(pretag(acc[8], (ptag ^ 1) << 16, 0xfffe0000u), acc[9]) | ptag, pack2(acc[10], acc[11]), pack2(acc[12], acc[13]), pack2(acc[14], acc[15])};
        if (later) return;
        v.x = settag(v.x, ftag);
        if (ty == 0) v.z = settag(v.z, ftag);
    };

#pragma unroll 1
    for (int s = -2; s < 0; s++) {
        STEP_CONSTS
        (void)tag; (void)ttag; (void)tso; (void)fz;
        float acc[16];
        mbar_wait_w(bars + 8 * (B_HB + b), 0);
        wg_fence();
#pragma unroll
        for (int i = 0; i < 32; i++) {
            if (i < NL) wgmma_ss32(acc, dadd(mkdesc(SB0 + i * 2048, 8192, 1024, 1), wg * 4096), HB(i), i != 0);
            else wgmma_rs32(acc, w[i < NL ? 0 : i - NL], HB(i), 1);
        }
        wg_commit();
        uint4 pa;
        int it = 0;
#pragma unroll 1
        do pa = ldg_b128(arena + (pso + g16)); while ((p > 0) & any_bit0(pa.x ^ ftag) & (++it < POLL_LIMIT));
        pdst = arena + ((pso ^ (32768 + 2048)) + G16());
        fdst = arena + ((b ^ 1) * 32768 + u_to + g16);
        wg_wait<0>();
#pragma unroll
        for (int k = 0; k < 4; k++) { acc[2 * k] += bflo((&pa.x)[k]); acc[2 * k + 1] += bfhi((&pa.x)[k]); }
        tok_pack(wg, acc, ftag, ptag);
        stg_b128_if(true, pdst, u.x, u.y, u.z, u.w);
        stg_b128_if(p > 0, fdst, v.x, v.y, v.z, v.w);
        if (p == 0) {
            TL(2)
            bar_sync(NB_MEM, 384);
            if (wg == 1 && warp0) {
                if (g16 == 0) mbar_arrive_cluster(bars + 8 * B_HE, j ^ 1);
                mbar_wait_w(bars + 8 * B_HE, 1);
                h_load(sb, hsrc, 2, j, head);
            }
        }
    }

    auto qk_loop = [&](auto wgc) {
        constexpr int WG = decltype(wgc)::value;
        uint32_t w0[NL][4], lm0;
        auto w0_load = [&]() {
            const uint32_t wl = TAB(WG * 3 + 1);
            lm0 = TAB(WG * 3 + 2);
#pragma unroll
            for (int k = 0; k < NL; k++) ldsm4t(w0[k], wl + k * 2048);
        };
        const uint32_t wlo = WG * 65536 - SM_WO - wu * 16384, wlx = __reduce_max_sync(~0u, (wi ^ WG) << 5);
        uint32_t tq0, lm, lm1;
        auto proj_pre = [&](int s) {
            uint32_t wz0 = zero;
#pragma unroll
            for (int k = 0; k < NL; k += 2) wz0 = and3(wz0, w0[k][0], w0[k + 1 < NL ? k + 1 : k][0]);
            lm = lm0 + (s & 1) * 65536 + wz0; lm1 = lm ^ 64;
            asm volatile("" : "+r"(lm), "+r"(lm1));
        };
        auto proj = [&](int s, auto mid) {
            bar_sync(NB_MEM, 384);
            float c[4][4];
            uint32_t bf[16][4];
#pragma unroll
            for (int it = 0; it < 3; it++) ldsm4(bf[it], (it & 1 ? lm1 : lm) + (it >> 1) * HBK);
            mid(-1);
#pragma unroll
            for (int it = 0; it < 16; it++) {
                const uint32_t* bfr = bf[it];
                if (it + 3 < 16) ldsm4(bf[it + 3 < 16 ? it + 3 : 0], (it & 1 ? lm : lm1) + ((it + 3) >> 1) * HBK);
                const uint32_t* wa = 2 * it < NL ? w0[2 * it < NL ? 2 * it : 0] : w[2 * it < NL ? 0 : 2 * it - NL];
                const uint32_t* wb = 2 * it + 1 < NL ? w0[2 * it + 1 < NL ? 2 * it + 1 : 0] : w[2 * it + 1 < NL ? 0 : 2 * it + 1 - NL];
                float *ca = c[(2 * it) & 3], *cb = c[(2 * it + 1) & 3];
                if (it < 2) { mma16816z(ca, wa, bfr[0], bfr[1]); mma16816z(cb, wb, bfr[2], bfr[3]); }
                else { mma16816(ca, wa[0], wa[1], wa[2], wa[3], bfr[0], bfr[1]); mma16816(cb, wb[0], wb[1], wb[2], wb[3], bfr[2], bfr[3]); }
                mid(it);
            }
            const uint32_t xo = u_xo + (G16() >> 1);
            float r[4];
#pragma unroll
            for (int e = 0; e < 4; e++) {
                constexpr float SH = SM_L2E / 64;
                r[e] = WG ? (c[0][e] + c[1][e]) + (c[2][e] + c[3][e]) : fmaf(c[2][e] + c[3][e], SH, (c[0][e] + c[1][e]) * SH);
            }
            const uint32_t r0 = pack2(r[0], r[1]), r1 = pack2(r[2], r[3]);
            const uint32_t m0 = movm(r0), m1 = movm(r1);
            tq0 = clk32();
            bar_arrive(NB_QK, 384);
            stg_rlx2(arena + xo, settag(m0, (s & 1) ^ 1), m1);
        };
        w0_load();
        proj_pre(0);
        if (WG == 1 || !ROT) bar_sync(NB_P, ROT ? 256 : 384);
        proj(0, [](int) {});
#pragma unroll 1
        for (int s = 0;; s++) {
            STEP_CONSTS
            uint4 pa;
            float acc[16];
            auto acc_init = [&]() {
#pragma unroll
                for (int k = 0; k < 4; k++) { acc[2 * k] = bflo((&pa.x)[k]); acc[2 * k + 1] = bfhi((&pa.x)[k]); acc[8 + 2 * k] = __uint_as_float((&pa.x)[k] & zero); acc[9 + 2 * k] = __uint_as_float(~(&pa.x)[k] & zero); }
            };
            uint32_t wf[NPF][4], a3;
#define WF(f) ((a3 ^ (((f) & 1) * 64)) + ((f) >> 1) * 2048)
            if (WG == 1) {
                float sc[5][4];
                uint32_t sx0 = sb + SM_SX - wu * (2560 - 16) + G16() * 5;
                asm volatile("" : "+r"(sx0));
                int it = 0;
                bool bad;
#pragma unroll 1
                do {
                    uint4 kf[2][2];
                    U2 qf[2], x[8];
                    const uint32_t gz = g16 | (it & zero);
                    const uint8_t *ts = arena + (tso + tbw + gz), *tq = arena + (tso + tbq + gz), *xp = arena + (xso + (gz >> 1));
#pragma unroll
                    for (int a = 0; a < 4; a++) kf[a >> 1][a & 1] = ldg_b128(ts + (a >> 1) * 16384 + (a & 1) * 2048);
                    if (QF_LATE) spin_until(tq0, dly.x2 - QF_LATE);
#pragma unroll
                    for (int a = 0; a < 2; a++) qf[a] = ldg_u2(tq + a * 16384);
                    spin_until(tq0, dly.x2);
#pragma unroll
                    for (int i = 0; i < 8; i++) x[i] = ldg_u2(xp + (i >> 2) * 16384 + (i & 3) * 1024);
                    PROF(8)
                    const uint32_t q0[4] = {hadd2(x[0].x, x[1].x), qf[0].x, hadd2(x[0].y, x[1].y), qf[0].y};
                    const uint32_t q1[4] = {hadd2(x[2].x, x[3].x), qf[1].x, hadd2(x[2].y, x[3].y), qf[1].y};
                    PROFV(7, clk32() + (q0[0] & zero))
                    const uint32_t bt = ((qf[0].x ^ ttag) | (qf[1].x ^ ttag)) | ((kf[0][0].x ^ ttag) | (kf[0][1].x ^ ttag)) | ((kf[1][0].x ^ ttag) | (kf[1][1].x ^ ttag));
                    uint32_t bx = 0;
#pragma unroll
                    for (int i = 0; i < 8; i += 2) bx |= (x[i].x ^ tag) | (x[i + 1].x ^ tag);
                    mma16816z(sc[0], q0, kf[0][0].x, kf[0][0].y);
                    mma16816z(sc[1], q0, kf[0][0].z, kf[0][0].w);
                    mma16816z(sc[2], q0, kf[0][1].x, kf[0][1].y);
                    mma16816z(sc[3], q0, kf[0][1].z, kf[0][1].w);
                    mma16816z(sc[4], q0, hadd2(x[4].x, x[5].x), hadd2(x[4].y, x[5].y));
                    bad = any_bit0((XP & 8 ? bt & zero : bt) | bx) & (++it < POLL_LIMIT);
                    mma16816(sc[0], q1[0], q1[1], q1[2], q1[3], kf[1][0].x, kf[1][0].y);
                    mma16816(sc[1], q1[0], q1[1], q1[2], q1[3], kf[1][0].z, kf[1][0].w);
                    mma16816(sc[2], q1[0], q1[1], q1[2], q1[3], kf[1][1].x, kf[1][1].y);
                    mma16816(sc[3], q1[0], q1[1], q1[2], q1[3], kf[1][1].z, kf[1][1].w);
                    mma16816(sc[4], q1[0], q1[1], q1[2], q1[3], hadd2(x[6].x, x[7].x), hadd2(x[6].y, x[7].y));
                } while (bad);
                PROFV(13, it - 1) MISS(1, it - 1)
                sts4(sx0, pack_h2(sc[0][0], sc[0][1]), pack_h2(sc[1][0], sc[1][1]), pack_h2(sc[2][0], sc[2][1]), pack_h2(sc[3][0], sc[3][1]));
                sts1(sx0 + 64 - wu * 12, pack_h2(sc[4][0], sc[4][1]));
                bar_arrive(NB_X1, 384);
#pragma unroll
                for (int n = 0; n < 5; n++) sts2(sb + SM_SX + 2560 + g8 + n * 1088, sc[n][2], sc[n][3]);
                PROF(3)
                a3 = TAB(WG * 3);
                softmax_rows(sb + SM_SX + 2560, sb + SM_PX + 1024, g16 | (clk32() & zero), qd * 8, [&]() { BLOCK_FENCE bar_sync(NB_PX, 128); }, [&]() {
                    BLOCK_FENCE
#pragma unroll
                    for (int f = 0; f < NE1; f++) ldsm4t(wf[f], WF(f));
                    BLOCK_FENCE
                });
                PROF(4)
            } else {
                a3 = TAB(WG * 3);
                if (warp1 && (H_POS == 4 ? (s & 3) == 0 : (s & 3) < 2)) asm volatile("fence.proxy.async.global;" ::: "memory");
                spin_until(tq0, dly.pa);
                uint4 x, y;
                int it = 0;
#pragma unroll 1
                do { x = ldg_b128(arena + (pso + g16)); y = ldg_b128(arena + (pso + tokbase(1) - tokbase(0) + g16)); }
                while (!(XP & 8) & (p <= NSEG) & any_bit0(xor_or(x.x, y.x, ftag)) & (++it < POLL_LIMIT));
                sts4(sb + SM_PA + g16, x.x, x.y, x.z, x.w);
                sts4(sb + SM_PA + 2048 + g16, y.x, y.y, y.z, y.w);
                if (NE) spin_until(tq0, dly.wf);
#pragma unroll
                for (int f = 0; f < NE; f++) ldsm4t(wf[f], WF(f));
                bar_sync(NB_X1, 384);
                if (E_MUL && g16 < 32) asm volatile("red.relaxed.gpu.global.max.u32 [%0], %1; red.relaxed.gpu.global.add.u32 [%0+4], 1;"
                                                    ::"l"(arena + ((blk(LB_TIME, 0) ^ (g16 << 8)) + qd * 1024 + (tq0 & zero))), "r"(gtime()) : "memory");
                __syncwarp();
                const uint32_t tx = clk32();
                if (H_POS == 2 && !(XP & 1) && warp1 && s + 3 <= NSEG) h_load(sb, hsrc, s + 3, j, head);
                spin_until(tx, dly.w2);
            }
#pragma unroll
            for (int f = WG ? NE1 : NE; f < NPF; f++) ldsm4t(wf[f], WF(f));
            PROF(5)
            if (s + 1 == NSEG) { bar_arrive(NB_X2, 384); break; }
            const uint32_t oa = l16 + SM_OX, slot = mem_slot(s + 1);
            float c[4][4];
            uint32_t ob[4][4];
            uint32_t wz = zero;
#pragma unroll
            for (int f = 0; f < NPF; f += 2) wz = and3(wz, wf[f][0], wf[f + 1 < NPF ? f + 1 : f][0]);
            BLOCK_FENCE
            bar_sync(NB_X2 + (SETTLE ? wz : 0), 384);
            ldsm4t(ob[0], oa);
            ldsm4t(ob[1], oa + 512);
            SCHED_FENCE(0)
#pragma unroll
            for (int f = 0; f < 16; f++) {
                const uint32_t *a = wf[f % NPF], *o = ob[f >> 2] + (f & 2);
                if (f < 4) mma16816z(c[f], a, o[0], o[1]);
                else mma16816(c[f & 3], a[0], a[1], a[2], a[3], o[0], o[1]);
                if (f == 3) ldsm4t(ob[2], oa + 1024);
                if (f == 5) { ldsm4t(ob[3], oa + 1536); if (NPF < 16) ldsm4t(wf[0], WF(NPF)); }
                if (f == 7) {
#pragma unroll
                    for (int k = NPF + 1; k < 16; k++) ldsm4t(wf[k - NPF], WF(k));
                }
                if (f == 3 || f == 5 || f == 7) SCHED_FENCE(f / 2)
                if (f == 11) {
#pragma unroll
                    for (int k = NL - W0_E; k < NL; k++) ldsm4t(w0[k], (a3 ^ wlx) + wlo + k * 2048);
                    SCHED_FENCE(4)
                }
            }
            const float last = c[1][3] + c[3][3], one = __uint_as_float(CNT1 << 16);
            red_mem(arena + (u_m + slot + G16()), pack2(c[0][0] + c[2][0], c[0][1] + c[2][1]), pack2(c[0][2] + c[2][2], c[0][3] + c[2][3]),
                    pack2(c[1][0] + c[3][0], c[1][1] + c[3][1]), pack2(c[1][2] + c[3][2], CNT32 && !(g16 & 16) ? last : one),
                    arena + (u_e + slot + (CNT32 ? (g16 >> 3) & ~3u : g16 >> 2)), pack2(one, last), !CNT32 || (g16 & 16));
            hbo += FZ;
            PROF(6)
            constexpr int NS = WG && W0_E < 0 ? NL : NL - W0_RS, GS = (32 - NL + NS) / NS;
            if (W0_E >= 0) {
                BLOCK_FENCE
#pragma unroll
                for (int k = NL - W0_E - 1; k >= 0; k--) ldsm4t(w0[k], (a3 ^ wlx) + wlo + k * 2048);
                lm0 = TAB(WG * 3 + 2);
                if (WG == 1) pa = lds4(sb + SM_PA + 2048 + g16);
            }
            if (WG == 0) {
                bar_arrive(NB_WIN, 384);
                if (W0_E < 0) spin_until(clk32(), dly.tv);
                pa = lds4(sb + SM_PA + g16);
                if (W0_E < 0) w0_load();
                acc_init();
                asm volatile("" : F16(acc, 0));
                BLOCK_FENCE
            }
            if (WG == 1 && K_DLY) spin_until(clk32(), dly.wf);
            wg_fence();
            bar_sync(WG ? NB_WIN : NB_B, WG ? 384 : 256);
#pragma unroll
            for (int i = 0; i < 32; i++) {
                const int k = i / GS;
                if (i >= 32 - NL + NS) wgmma_rs32(acc, w0[i < 32 - NL + NS ? 0 : i - 32 + NL], HB(i - 32 + NL), 1);
                else if (i % GS == GS - 1 && k < NS) wgmma_ss32(acc, mkdesc(SB0 + WG * 65536 + k * 2048, 8192, 1024, 1), HB(k), 1);
                else wgmma_rs32(acc, w[i - (k < NS ? k : NS)], HB(NL + i - (k < NS ? k : NS)), WG == 0 || i);
                if (WG == 1 && i == G_AT) bar_arrive(NB_B, 256);
                if (WG == 1 && i == W1_AT) w0_load();
            }
            wg_commit();
            BLOCK_FENCE
            if (WG == 1 && warp0 && (s & 3) == (H_POS == 4 ? 3 : 0)) wait_count_w(&g_tick[32 + ((G16() >> 4) & 3) * 8], min((s + 1) / 4 + 2, 16));
            if (WG == 1 && W0_E < 0) { pa = lds4(sb + SM_PA + 2048 + g16); if (W1_AT < 0) w0_load(); }
            auto tok_store = [&](int m) {
                if (m & 1) stg_b128_if(XP & 8 ? s == 99 : true, arena + ((b ^ 1) * 32768 + u_to + G16()), v.x, v.y, v.z, v.w);
                if (m & 2) stg_b128_if(XP & 8 ? s == 99 : p < NSEG, arena + ((pso ^ (32768 + 2048)) + G16()), u.x, u.y, u.z, u.w);
            };
            if (WG == 0) proj_pre(s + 1);
            BLOCK_FENCE
            wg_wait<0>();
            if (WG == 0 && ROT) {
                asm volatile("" : F16(acc, 0));
                proj(s + 1, [&](int it) {
                    if (it < 0) {
                        SCHED_FENCE(0)
                        asm volatile("" : F16(acc, 0));
                        tok_pack(WG, acc, ftag, ptag, true);
                        tok_store(2);
                        SCHED_FENCE(1)
                    }
                    if (it == ROT) { SCHED_FENCE(2) v.x = settag(v.x, ftag); v.z = settag(v.z, ftag); tok_store(1); SCHED_FENCE(3) }
                });
                tq0 += (fz[0] | fz[1] | fz[2] | fz[3]) & zero;
            } else {
                if (WG == 1) {
#pragma unroll
                    for (int k = 0; k < 4; k++) { acc[2 * k] += bflo((&pa.x)[k]); acc[2 * k + 1] += bfhi((&pa.x)[k]); }
                }
                tok_pack(WG, acc, ftag, ptag);
                if (WG == 1) proj_pre(s + 1);
                asm volatile("" : "+r"(u.x), "+r"(u.y), "+r"(u.z), "+r"(u.w), "+r"(v.x), "+r"(v.y), "+r"(v.z), "+r"(v.w));
                BLOCK_FENCE
                bar_sync(NB_P, ROT ? 256 : 384);
                tok_store(3);
                proj(s + 1, [](int) {});
            }
        }
    };
    if (wg == 0) {
        qk_loop(IC<0>());
    } else if (wg == 1) {
        qk_loop(IC<1>());
    } else {
        const uint32_t ONES = 0x3f803f80u, u_o = qd * 65536 + head * 2048 + wu * 384;
        uint32_t tw = 0, dl = 0, dm = 0, dst0, dx0;
        dst0 = TAB(6); dx0 = TAB(7);
        uint32_t ov[4] = {0, 0, 0, 0};
        auto o_store = [&](int s) {
            uint8_t* od = (uint8_t*)g_O + (uint32_t)(s * (32 * NH * DH * 2) + u_o + (G16() >> 2));
#pragma unroll
            for (int a = 0; a < 4; a++) stg_rlx1(od + a * 128, ov[a]);
        };
        uint4 vf[2][2], pa;
        auto vf_fetch = [&](int s) {
            const uint8_t* ts = arena + ((s & 1) * 32768 + tbw + g16);
#pragma unroll
            for (int a = 0; a < 4; a++) vf[a >> 1][a & 1] = ldg_b128(ts + (a >> 1) * 16384 + (a & 1) * 2048);
        };
        auto tok_fetch = [&](int s) {
            if (TV_POS != 1) vf_fetch(s);
            pa = ldg_b128(arena + (tbw + (1 << 20) + (~s & 1) * 32768 + j * 16384 + kh * 2048 + g16));
        };
        if (PA_POS) tok_fetch(0);
        TL(9)
        mbar_wait_w(bars + 8 * B_WO, 0);
        if (H_POS == 4 && warp0) { wait_count_w(&g_tick[32 + ((g16 >> 4) & 3) * 8], 2); asm volatile("fence.proxy.async.global;" ::: "memory"); }
        TL(6)
#pragma unroll 1
        for (int s = 0; s < NSEG; s++) {
            STEP_CONSTS
#define VFBAD ((vf[0][0].x ^ ttag) | (vf[0][1].x ^ ttag) | (vf[1][0].x ^ ttag) | (vf[1][1].x ^ ttag))
#define TOKBAD ((TV_POS == 1 ? 0 : VFBAD) | (p <= NSEG ? pa.x ^ ftag : 0))
            {
                const uint32_t dst = dst0 + b * 65536, dx = dx0 + b * 65536;
                const uint8_t *ms = arena + (u_m + mem_slot(s) + g16), *me = arena + (u_e + mem_slot(s) + (CNT32 ? (g16 >> 3) & ~3u : g16 >> 2));
                const uint32_t em = CNT32 && !(g16 & 16) ? ~0u : 0u;
                asm volatile("" : "+l"(ms), "+l"(me));
                spin_until(tw, dl);
                PROF(11)
                int it = 0;
                bool bad;
#pragma unroll 1
                do {
                    uint4 m[4];
                    uint32_t x[4];
#pragma unroll
                    for (int i = 0; i < 4; i++) m[i] = ldg_rlx4(ms + i * 1024);
#pragma unroll
                    for (int i = 0; i < 4; i++) x[i] = ldg_rlx1(me + i * 1024);
#pragma unroll
                    for (int i = 0; i < 3; i++) {
                        stsm4t(dst + i * 2 * HBK, m[i].x, m[i].y, m[i].z, m[i].w);
                        if (i == P_GATE) asm volatile("{.reg .pred p; setp.eq.s32 p, %0, 0; @p bar.arrive %1, %2;}" ::"r"(it), "n"(NB_P), "n"(ROT ? 256 : 384) : "memory");
                    }
                    uint32_t c = and3(m[0].w, m[1].w, m[2].w);
                    SCHED_FENCE(1)
                    stsm4t(dst + 6 * HBK, m[3].x, m[3].y, m[3].z, m[3].w);
                    stsm4t(dx, x[0], x[1], x[2], x[3]);
                    asm volatile("" : "+r"(c));
                    c = and3(and3(((c & m[3].w) | em) >> 16, x[0], x[1]), x[2], x[3]);
                    bad = __any_sync(~0u, !(c & CNT_ALL)) & (++it < POLL_LIMIT);
                    if (H_POS == 4) asm volatile("{.reg .pred p; setp.eq.u32 p, %0, 0; @p bar.sync %1, 384;}" ::"r"((uint32_t)bad), "n"(NB_MEM) : "memory");
                    else if (!ALIGN) asm volatile("{.reg .pred p; setp.eq.u32 p, %0, 0; @p bar.arrive %1, 384;}" ::"r"((uint32_t)bad), "n"(NB_MEM) : "memory");
                } while (bad);
                if (ALIGN) { spin_until(tw, dm); bar_arrive(NB_MEM, 384); }
                PROFV(12, it - 1)
                MISS(0, it - 1) HT(5)
                PROF(8)
            }
            if (s == 1) { TL(7) TLC(0) }
            if (s == 63) TLC(1)
            if (s == 0) TL(13)
            const uint32_t tm = clk32();
            if (H_POS == 4 && g16 == 0) mbar_arrive_cluster(bars + 8 * B_HE, j ^ 1);
            if (O_POS == 1) o_store(max(s - 1, 0));
            if (Z_POS && warp1) stg4_if(g16 < 512 + 160, arena + (TAB(8) + mem_slot(s + 3)), 0);
            fence_async_smem();
            hbo += fz[1] & zero;
            int it = 0;
            if (!PA_POS) tok_fetch(s);
#pragma unroll 1
            while (!(XP & 8) & any_bit0(TOKBAD) & (++it < POLL_LIMIT)) tok_fetch(s + (it & zero));
            float acc[20];
#pragma unroll
            for (int k = 0; k < 4; k++) { acc[2 * k] = bflo((&pa.x)[k]); acc[2 * k + 1] = bfhi((&pa.x)[k]); acc[8 + 2 * k] = acc[9 + 2 * k] = acc[16 + k] = __uint_as_float(pa.x & zero); }
            if (XP & 1 ? s < 1 : p <= NSEG) mbar_wait_w(bars + 8 * (B_HB + b), (p >> 1) & 1);
            if (H_POS == 4 && warp0) {
                mbar_wait_w(bars + 8 * B_HE, s & 1);
                spin_until(tm, dly.wf);
                if (s + 3 <= NSEG) h_load(sb, hsrc, s + 3, j, head);
            }
            asm volatile("" : F16(acc, 0), F4(acc, 16));
            BLOCK_FENCE
            wg_fence();
            bar_sync(NB_QK, 384);
#pragma unroll
            for (int i = 0; i < 32; i++) {
                const int k = i / GAP;
                if (i % GAP == GAP - 1 && k < NL) wgmma_ss40(acc, mkdesc(SB0 + 131072 + k * 2048, 8192, 1024, 1), HB(k), 1);
                else wgmma_rs40(acc, w[i - (k < NL ? k : NL)], HB(NL + i - (k < NL ? k : NL)), 1);
            }
            wg_commit();
            uint8_t* vo = arena + (u_xo + (G16() >> 1));
            pdst = arena + ((pso ^ (32768 + 2048)) + G16());
            fdst = arena + ((b ^ 1) * 32768 + u_to + g16);
            BLOCK_FENCE
            wg_wait<0>();
            PROF(9)
            stg_rlx2(vo, settag(pack2(acc[16], acc[17]), tag), pack2(acc[18], acc[19]));
            const uint32_t tv = clk32();
            if (TV_POS == 1) vf_fetch(s);
            tok_pack(2, acc, ftag, ptag);
            stg_b128_if(XP & 8 ? s == 99 : p <= NSEG, fdst, v.x, v.y, v.z, v.w);
            stg_b128_if(XP & 8 ? s == 99 : p < NSEG, pdst, u.x, u.y, u.z, u.w);
            if (O_POS == 2) o_store(max(s - 1, 0));
            if (ST_BAR) bar_sync(NB_WG, 128);
            PROF(10)
            const uint8_t* xp = arena + (xso + 32768 + (G16() >> 1));
            const uint32_t sxa = sb + SM_SX - wu * 2560 + G16() * 5;
            uint32_t xv[4], gt = 0;
            auto pv = [&](uint32_t p0, uint32_t p1, uint32_t p2, uint32_t p3, uint32_t p4, auto getv, auto done) {
                float oc[2][4], lc[4] = {0.f, 0.f, 0.f, 0.f};
                mma16816(lc, ONES, ONES, ONES, ONES, p0, p1);
                mma16816z(oc[0], &vf[0][0].x, p0, p1);
                mma16816z(oc[1], &vf[1][0].x, p0, p1);
                mma16816(lc, ONES, ONES, ONES, ONES, p2, p3);
                mma16816(oc[0], vf[0][1].x, vf[0][1].y, vf[0][1].z, vf[0][1].w, p2, p3);
                mma16816(oc[1], vf[1][1].x, vf[1][1].y, vf[1][1].z, vf[1][1].w, p2, p3);
                mma1688(lc, ONES, ONES, p4);
                getv();
                mma1688(oc[0], xv[0], xv[1], p4);
                mma1688(oc[1], xv[2], xv[3], p4);
                done(__float_as_uint(oc[0][0]) | __float_as_uint(oc[1][0]) | __float_as_uint(lc[0]));
                const float r0 = rcp_fast(lc[0]), r1 = rcp_fast(lc[1]);
                ov[0] = pack2(oc[0][0] * r0, oc[0][1] * r1); ov[1] = pack2(oc[0][2] * r0, oc[0][3] * r1);
                ov[2] = pack2(oc[1][0] * r0, oc[1][1] * r1); ov[3] = pack2(oc[1][2] * r0, oc[1][3] * r1);
            };
            bool bad;
            it = 0;
#pragma unroll 1
            do {
                U2 xr[4];
                auto load_v = [&]() {
                    if (V_POS < 3) spin_until(tv, dly.v);
#pragma unroll
                    for (int i = 0; i < 4; i++) xr[i] = ldg_u2(xp + i * 1024);
                };
                if (TV_POS == 1 && it) {
                    const uint8_t* tz = arena + (tso + tbw + (g16 | (it & zero)));
#pragma unroll
                    for (int a = 0; a < 4; a++) ldg_b128_into(vf[a >> 1][a & 1], tz + (a >> 1) * 16384 + (a & 1) * 2048);
                }
                if (!V_POS) load_v();
                if (V_POS >= 3) spin_until(tv, dly.v);
                PROF(3)
                asm volatile("{.reg .pred p; setp.eq.s32 p, %0, 0; @p bar.sync %1, 384;}" ::"r"(it), "n"(NB_X1) : "memory");
                uint4 sx[5];
                if (V_POS == 3) load_v();
#pragma unroll
                for (int i = 0; i < 5; i++) sx[i] = lds4(sxa + i * 16);
                if (V_POS == 4) load_v();
                if (it == 0) { gt = gtime(); tw = clk32(); }
                if (V_POS == 2) load_v();
                uint32_t h[5];
#pragma unroll
                for (int n = 0; n < 4; n++) h[n] = add_h2(add_h2((&sx[0].x)[n], (&sx[1].x)[n]), add_h2((&sx[2].x)[n], (&sx[3].x)[n]));
                h[4] = add_h2(add_h2(sx[4].x, sx[4].y), add_h2(sx[4].z, sx[4].w));
                uint32_t hm = max_h2(max_h2(max_h2(h[0], h[1]), h[2]), max_h2(h[3], h[4]));
                hm = max_h2(hm, __byte_perm(hm, hm, 0x1032));
                const uint32_t m1 = __shfl_xor_sync(~0u, hm, 1), m2 = __shfl_xor_sync(~0u, hm, 2), m3 = __shfl_xor_sync(~0u, hm, 3);
                float2 a[5];
#pragma unroll
                for (int n = 0; n < 5; n++) a[n] = unpack_h2(h[n]);
                if (V_POS == 1) load_v(); else SCHED_FENCE(0)
                const float mb = -64.0f * unpack_h2(max_h2(max_h2(hm, m1), max_h2(m2, m3))).x;
                uint32_t pm[5];
#pragma unroll
                for (int n = 0; n < 5; n++) pm[n] = pack2(ex2(fmaf(a[n].x, 64.0f, mb)), ex2(fmaf(a[n].y, 64.0f, mb)));
                pv(pm[0], pm[1], pm[2], pm[3], pm[4], [&]() {
                    xv[0] = hadd2(xr[0].x, xr[1].x); xv[1] = hadd2(xr[0].y, xr[1].y);
                    xv[2] = hadd2(xr[2].x, xr[3].x); xv[3] = hadd2(xr[2].y, xr[3].y);
                }, [](uint32_t) {});
                bad = any_bit0((TV_POS == 1 && !(XP & 8) ? VFBAD : 0) | (xr[0].x ^ tag) | (xr[1].x ^ tag) | (xr[2].x ^ tag) | (xr[3].x ^ tag)) & (++it < POLL_LIMIT);
                stsm4(sb + SM_OX + g16, ov[0], ov[1], ov[2], ov[3]);
            } while (bad);
            PROFV(14, it - 1) MISS(2, it - 1)
            PROF(5)
            bar_sync(NB_X2, 384);
            U2 tv2 = {0, 0};
            const uint8_t* tp = arena + (blk(LB_TIME, mypar) + (((g16 | (tw & zero)) << 6) & 0xc00));
            {
                const uint4 pp = lds4(l16 + SM_PX + 1024);
                const uint32_t p4 = lds1(sb + SM_PX + 512 + 1024 - wu * 128 + (G16() >> 2));
                if (E_MUL) tv2 = ldg_u2(tp);
                if (H_POS == 3 && !(XP & 1) && warp0 && s + 3 <= NSEG) h_load(sb, hsrc, s + 3, j, head);
                if (H_POS == 0 && !(XP & 1)) h_piece(sb, hsrc, s + 3, j, (wu + head) & 3, wu == 0);
                pv(pp.x, pp.y, pp.z, pp.w, p4, []() {}, [&](uint32_t r) { bar_arrive(NB_WIN + ((r | fz[0]) & zero), 384); });
            }
            dst0 = TAB(6); dx0 = TAB(7);
            const uint32_t zo = Z_POS ? 0 : TAB(8);
            PROF(6) HT(7)
            BLOCK_FENCE
            if (H_POS == 1 && !(XP & 1)) h_piece(sb, hsrc, s + 3, j, (wu + head) & 3, wu == 0);
            asm volatile("" : "+r"(tv2.y));
            it = 0;
#pragma unroll 1
            while (E_MUL && __any_sync(~0u, tv2.y < 32 * (s + 1)) & (++it < 16)) tv2 = ldg_u2(tp);
            const uint32_t e = __reduce_max_sync(~0u, tv2.x) - gt;
            MISS(3, it - 1) MISS(4, gt)
            if (PA_POS) tok_fetch(s + 1);
            if (O_POS == 0) o_store(s);
            if (!Z_POS) stg4_if(g16 < 160, arena + (zo + mem_slot(s + 3)), 0);
            dm = e > 4096 ? 0 : e * E_MUL >> 4;
            dl = dm + (ALIGN ? dly.near - dly.wf - (kh == mypar ? 0 : 140) : kh == mypar ? dly.near : dly.far);
            dm += dly.near;
        }
        if (O_POS) o_store(NSEG - 1);
        TL(8)
    }
    PROF_OUT
    MISS_OUT
}

struct RecMaps { CUtensorMap wq, wk, wv, wo, wmod, w3, w1; };
struct RecPtrs { const bf16 *x, *mem0, *c, *wmod, *w1, *w3; uint8_t* arena; uint32_t zero; const bf16 *w2, *w4, *wo; Delays dly; };

__device__ __forceinline__ float silu_bf(const bf16* c, int i) {
    const float v = __bfloat162float(c[i]);
    return bfround(__fdividef(v, 1.0f + __expf(-v)));
}
#define W_LATE 1000
#define W_OPEN 1400
__device__ __forceinline__ void side_window(const uint8_t* arena, uint32_t& n) {
    U2 v;
    int it = 0;
#pragma unroll 1
    while (v = ldg_u2(arena + (LB_TIME << 13)), ((v.y >> 5) == n || gtime() - v.x > W_OPEN + W_LATE) && v.y < 32 * NSEG && ++it < 64) __nanosleep(100);
    n = v.y >> 5;
    it = 0;
#pragma unroll 1
    while ((int)(gtime() - v.x - W_OPEN) < 0 && ++it < 256) {}
}
__device__ __noinline__ void rec_ln(float* coef, const RecPtrs& p, int id, int r0) {
    int r1 = 32;
    const int tid = threadIdx.x;
    const int lane = tid & 31, wid = tid >> 5;
    const uint32_t ring = smem_u32(coef) - SM_PRE + wid * 8192 + lane * 16;
    auto rowof = [&](int j) { return (j >> 1) * 64 + (id * 8 + wid) * 2 + (j & 1); };
    auto fetch = [&](int j) {
        if (j < 2 * r1) {
#pragma unroll
            for (int i = 0; i < 4; i++)
                asm volatile("cp.async.cg.shared.global [%0], [%1], 16;" ::"r"(ring + (j & 3) * 2048 + i * 512), "l"(p.x + (size_t)rowof(j) * DM + i * 256 + lane * 8) : "memory");
        }
        asm volatile("cp.async.commit_group;" ::: "memory");
    };
#pragma unroll 1
    for (int j = 2 * r0; j < 2 * r0 + 4; j++) fetch(j);
#pragma unroll 1
    for (int i = tid; i < 2 * DM / 4; i += 256) {
        uint4 v[8];
        int it = 0;
        uint32_t ok;
        do {
            ok = 1;
#pragma unroll
            for (int k = 0; k < 8; k++) v[k] = ldg_rlx4(g_modp + k * 2 * DM + i * 4);
#pragma unroll
            for (int k = 0; k < 8; k++) ok &= v[k].x & v[k].y & v[k].z & v[k].w;
            spin_guard(++it);
        } while (!ok);
        float t[4] = {0, 0, 0, 0};
#pragma unroll
        for (int k = 0; k < 8; k++) { t[0] += __uint_as_float(v[k].x); t[1] += __uint_as_float(v[k].y); t[2] += __uint_as_float(v[k].z); t[3] += __uint_as_float(v[k].w); }
#pragma unroll
        for (int j = 0; j < 4; j++) coef[i * 4 + j] = bfround(t[j]) + (i >= DM / 4 ? 1.0f : 0.0f);
    }
    bar_sync(NB_FIN0, 256);
    if (r0 == 0) {
        int v, it = 0;
#pragma unroll 1
        do { v = *(volatile int*)((uint8_t*)coef - SM_PRE + SM_BAR + 192); spin_guard(++it); } while (v == INT_MIN);
        if (v >= 0) r1 = 2;
    }
    if (tid == 0 && r0 == 0) TL(2)
#pragma unroll 1
    for (int j = 2 * r0; j < 2 * r1; j++) {
        float x[32];
        asm volatile("cp.async.wait_group 3;" ::: "memory");
#pragma unroll
        for (int i = 0; i < 4; i++) {
            const uint4 v = lds4(ring + (j & 3) * 2048 + i * 512);
            float* d = x + i * 8;
            d[0] = bflo(v.x); d[1] = bfhi(v.x); d[2] = bflo(v.y); d[3] = bfhi(v.y); d[4] = bflo(v.z); d[5] = bfhi(v.z); d[6] = bflo(v.w); d[7] = bfhi(v.w);
        }
        const int row = rowof(j), rr = row & 15;
        ln_row(x);
        fetch(j + 4);
#pragma unroll
        for (int i = 0; i < 4; i++) {
            float y[8];
            const float4* cf = (const float4*)(coef + i * 256 + lane * 8);
            const float4 s0 = cf[0], s1 = cf[1], c0 = cf[256], c1 = cf[257];
            const float sh[8] = {s0.x, s0.y, s0.z, s0.w, s1.x, s1.y, s1.z, s1.w}, sc[8] = {c0.x, c0.y, c0.z, c0.w, c1.x, c1.y, c1.z, c1.w};
#pragma unroll
            for (int e = 0; e < 8; e++) y[e] = fmaf(x[i * 8 + e], sc[e], sh[e]);
            const int own = ((row >> 4) & 1) == (i >> 1), c16 = i * 32 + lane;
            const uint32_t off = ((row >> 5) + own) * 65536 + (c16 >> 3) * 4096 + (rr + (own ? 0 : 16)) * 128 + (((c16 & 7) ^ (rr & 7)) << 4);
            *(uint4*)((uint8_t*)g_himg + off) = pack8(y);
        }
        if ((j & 3) != 3) continue;
        bar_sync(j == 3 ? NB_C : NB_FIN0, j == 3 ? 320 : 256);
        if (wid == 0) {
            if (j == 3) bar_arrive(NB_B, 64);
            if (lane == 0) { if (j == 7) wait_count1(&g_tick[32 + id * 8], 1); signal_count(&g_tick[32 + id * 8]); if (j < 8) TL(13) }
            __syncwarp();
        }
    }
}
#define SIDE_T 300
template <int NQ>
__device__ __forceinline__ void side_gemv(const CUtensorMap* tm, int c0, int k0, int k1, uint32_t cs, uint32_t sb, const uint8_t* arena, uint32_t& n, uint32_t& ph, float (*acc)[8], const uint8_t* xr = nullptr) {
    const uint32_t w = __reduce_max_sync(~0u, threadIdx.x >> 5 & 3), ring = sb + 65536 + w * 24576, bars = sb + SM_BAR + 8 * B_W + w * 24;
#pragma unroll
    for (int q = 0; q < NQ; q++)
#pragma unroll
        for (int j = 0; j < 8; j++) acc[q][j] = 0.f;
#pragma unroll 1
    for (; k0 < k1; k0 += 48, ph ^= 1) {
        const int nr = min(48, k1 - k0);
        side_window(arena, n);
        const uint32_t t0 = clk32();
        if (xr && k0 < 9 * 48) {
#pragma unroll
            for (int i = 0; i < 6; i++) asm volatile("prefetch.global.L2 [%0];" ::"l"(xr + (5 + k0 / 16 + (i >> 1)) * 131072 + (i & 1) * 16384));
        }
#pragma unroll 1
        for (int g = 0; g < 3; g++) {
            spin_until(t0, (g * 4 + w) * (SIDE_T / 4));
            e_expect(bars + 8 * g, g * 16 < nr ? 8192 : 0);
            if (g * 16 < nr) e_tma2d_hint(ring + g * 8192, tm, c0, k0 + g * 16, bars + 8 * g, xr && EVF ? EVICT_FIRST : 0x1000000000000000ull);
        }
#pragma unroll 1
        for (int r = 0; r < nr; r += 16) {
            mbar_wait_w(bars + (r >> 1), ph);
            uint4 v[16];
#pragma unroll
            for (int h = 0; h < 16; h++) v[h] = lds4(ring + (r + h) * 512 + (threadIdx.x & 31) * 16);
            float4 cf[NQ][4];
#pragma unroll
            for (int q = 0; q < NQ * 4; q++) cf[q >> 2][q & 3] = lds4f(cs + ((q >> 2) * DM + k0 + r + (q & 3) * 4) * 4);
#pragma unroll
            for (int h = 0; h < 16; h++) {
                const float f[8] = {bflo(v[h].x), bfhi(v[h].x), bflo(v[h].y), bfhi(v[h].y), bflo(v[h].z), bfhi(v[h].z), bflo(v[h].w), bfhi(v[h].w)};
#pragma unroll
                for (int q = 0; q < NQ; q++)
#pragma unroll
                    for (int j = 0; j < 8; j++) acc[q][j] = fmaf((&cf[q][h >> 2].x)[h & 3], f[j], acc[q][j]);
            }
        }
        fence_async_smem();
        __syncwarp();
    }
}
__device__ __noinline__ void rec_side(float* sm, const RecMaps& mp, const RecPtrs& p, int id) {
    const int tid = threadIdx.x;
    if (tid < 256) {
        if (blockIdx.x < 128) rec_ln(sm + SM_PRE / 4, p, id, 2);
        if (tid == 0) TL(14)
        for (int i = tid; i < 2 * S_; i += 256) g_st[id * 2 * S_ + i] = 0.f;
        if (id == 0 && tid < 64) g_pcnt[tid * 8] = 0;
        if (id == 1) for (int i = tid; i < 6 * 256; i += 256) g_pflag[i] = 0;
        if (id == 2 && tid < 66) {
            const uint2 me = __ldcg(&g_clk[tid]);
            const uint32_t c0 = __ldcg(&g_clk[0].x) - 4096;
            int r = 0;
#pragma unroll 1
            for (int i = 0; i < 66; i++) {
                const uint2 o = __ldcg(&g_clk[i]);
                r += (o.y ^ me.y) < 256 && (o.x - c0 < me.x - c0 || (o.x == me.x && i < tid));
            }
            g_cls[me.y & 255] = g_cls[(me.y ^ 1) & 255] = r < 32 ? (me.y >> 8) * 4 + (r >> 3) : 8;
            if (tid == 0) g_pt = 0;
        }
        uint32_t n = 0;
        int it = 0;
#pragma unroll 1
        while (n < SPF_AT && ++it < 256) side_window(p.arena, n);
#pragma unroll 1
        for (int i = 0; i < 96 && SPF; i++) {
            const uint8_t* w = i < 64 ? (const uint8_t*)p.wo + (id * 64 + i) * 32768 : (const uint8_t*)p.x + (id * 32 + i - 64) * 32768;
            asm volatile("prefetch.global.L2 [%0];" ::"l"(w + tid * 128));
            if (i % SPF_R == SPF_R - 1 && i < 95) side_window(p.arena, n); else __nanosleep(SPF_NS);
        }
        return;
    }
    const int t = tid - 256;
    float *coef = sm + 40960, *red = coef + 3 * DM;
    const uint32_t sb = smem_u32(sm), cs = smem_u32(coef);
    uint32_t n = 0, ph = 0;
    for (int i = t; i < DM; i += 128) { coef[i] = silu_bf(p.c, i); coef[2 * DM + i] = 1.0f; }
    if (t == 0) wait_count1(&g_tick[32 + id * 8], 2);
    bar_sync(NB_G, 128);
    const int w = __reduce_max_sync(~0u, t >> 5);
    float acc[3][8];
    side_gemv<1>(&mp.wmod, (2 + id) * DM + w * 256, 0, DM, cs, sb, p.arena, n, ph, acc, (const uint8_t*)p.x + id * 32768 + t * 128);
#pragma unroll
    for (int j = 0; j < 8; j++) g_mod[(2 + id) * DM + t * 8 + j] = bfround(acc[0][j]);
    bar_sync(NB_G, 128);
    if (t == 0) signal_count(&g_tick[8]);
    side_gemv<1>(&mp.w3, id * (FF / 4) + w * 256, 0, DM, cs + 8 * DM, sb, p.arena, n, ph, acc);
    if (t < FF / 32) {
#pragma unroll
        for (int j = 0; j < 8; j++) g_vec[3 * DM + id * (FF / 4) + t * 8 + j] = acc[0][j];
    }
    if (t == 0) wait_count1(&g_tick[8], 4);
    bar_sync(NB_G, 128);
    for (int i = t; i < DM; i += 128) { coef[i] = 1.0f + __ldcg(g_mod + 4 * DM + i); coef[DM + i] = __ldcg(g_mod + 3 * DM + i); }
    bar_sync(NB_G, 128);
    if (id == 1 && t < 32) {
        float u[5] = {0, 0, 0, 0, 0};
        for (int i = t; i < DM; i += 32) {
            const float a = coef[i], b = coef[DM + i];
            u[0] += a; u[1] += a * a; u[2] += a * b; u[3] += b; u[4] += b * b;
        }
#pragma unroll
        for (int q = 0; q < 5; q++) { const float r = warp_sum(u[q]); if (t == 0) g_cst[q] = r * (1.0f / DM); }
    }
    side_gemv<3>(&mp.w1, id * 256, w * 256, w * 256 + 256, cs, sb, p.arena, n, ph, acc);
#pragma unroll
    for (int q = 0; q < 3; q++)
#pragma unroll
        for (int j = 0; j < 8; j++) red[((t >> 5) * 3 + q) * 256 + (t & 31) * 8 + j] = acc[q][j];
    bar_sync(NB_G, 128);
    for (int i = t; i < 768; i += 128) g_vec[(i >> 8) * DM + id * 256 + (i & 255)] = (red[i] + red[768 + i]) + (red[1536 + i] + red[2304 + i]);
    if (t == 0) TL(9)
}

__global__ void __cluster_dims__(2, 1, 1) __launch_bounds__(384, 1)
k_rec(const __grid_constant__ RecMaps mp, const __grid_constant__ RecPtrs p) {
    extern __shared__ uint8_t smraw[];
    const uint32_t sb = smem_u32(smraw);
    if ((sb & 0x3FFFF) != SB0) __trap();
    const uint32_t bars = sb + SM_BAR;
    const int tid = threadIdx.x, lane = tid & 31, b = blockIdx.x;
    const int wid = __reduce_max_sync(~0u, tid >> 5);
    const uint32_t rank = b & 1;
    uint8_t* arena = p.arena;
    volatile int* sinfo = (volatile int*)(smraw + SM_BAR + 192);
    if (tid == 0) TL(0)
    if (tid == 0) sinfo[0] = INT_MIN;
    if (tid == 352) {
        for (int i = 0; i < 17; i++) mbar_init(bars + 8 * i, i == B_WO ? 4 : 1);
        asm volatile("fence.mbarrier_init.release.cluster;" ::: "memory");
        mbar_expect(bars + 8 * B_ROLE, 8);

    }
    __syncwarp();
    asm volatile("barrier.cluster.arrive.relaxed.aligned;" ::: "memory");
    int pr = 0, hA = 0;
    if (wid < 8) {
        if (b < 128) {
            const int cb = (b & 15) * 128, k0 = (b >> 4) * 128 + (tid >> 4);
            uint4 v[8];
#pragma unroll
            for (int i = 0; i < 8; i++) v[i] = __ldg((const uint4*)(p.wmod + (size_t)(k0 + 16 * i) * (6 * DM) + cb + (tid & 15) * 8));
            float acc[8] = {0, 0, 0, 0, 0, 0, 0, 0};
#pragma unroll
            for (int i = 0; i < 8; i++) {
                const float sv = silu_bf(p.c, k0 + 16 * i);
                acc[0] += sv * bflo(v[i].x); acc[1] += sv * bfhi(v[i].x); acc[2] += sv * bflo(v[i].y); acc[3] += sv * bfhi(v[i].y);
                acc[4] += sv * bflo(v[i].z); acc[5] += sv * bfhi(v[i].z); acc[6] += sv * bflo(v[i].w); acc[7] += sv * bfhi(v[i].w);
            }
            float* red = (float*)(smraw + SM_PRE);
            *(float4*)(red + (tid >> 4) * 128 + (tid & 15) * 8) = make_float4(acc[0], acc[1], acc[2], acc[3]);
            *(float4*)(red + (tid >> 4) * 128 + (tid & 15) * 8 + 4) = make_float4(acc[4], acc[5], acc[6], acc[7]);
            bar_sync(NB_FIN0, 256);
            if (wid < 4) {
                float t = 0;
#pragma unroll
                for (int i = 0; i < 16; i++) t += red[i * 128 + tid];
                stg_rlx1(&g_modp[(b >> 4) * 2 * DM + cb + tid], __float_as_uint(t) | 1u);
            }
        } else {
            rec_ln((float*)(smraw + SM_PRE), p, b - 128, 0);
        }
    } else if (wid >= 10 && b >= 128) {
        {
            const int w = (b - 128) * 2 + wid - 10;
            const uint16_t* src = (const uint16_t*)p.mem0 + (lane & 3) * 2 * DM + (w >> 2) * 512 + (w & 1) * 64 + (w & 2) * 8 + (lane >> 2);
            uint32_t v[4][4];
#pragma unroll
            for (int i = 0; i < 16; i++) v[i >> 2][i & 3] = src[(i >> 2) * 128 + (i & 2) * 16 + (i & 1) * 8] | ((uint32_t)src[DM + (i >> 2) * 128 + (i & 2) * 16 + (i & 1) * 8] << 16);
            uint8_t* d = arena + mem_row(w >> 2, w & 3, 0);
            uint8_t* e = d + 512 + (CNT32 ? lane >> 1 : lane) * 4;
            d += lane * 16;
#pragma unroll
            for (int i = 0; i < 4; i++, d += 1024, e += 1024) {
                stg_rlx4(d, v[i][0], v[i][1], v[i][2], CNT32 && !(lane & 1) ? v[i][3] : (v[i][3] & 0xffff) | CNT_ALL << 16);
                stg_rlx4(d + mem_slot(1), 0, 0, 0, 0);
                stg_rlx4(d + mem_slot(2), 0, 0, 0, 0);
                if (!CNT32 || (lane & 1)) { stg_rlx1(e, (v[i][3] & 0xffff0000u) | CNT_ALL); stg_rlx1(e + mem_slot(1), 0); stg_rlx1(e + mem_slot(2), 0); }
            }
            if (w == 0 && lane < 8) stg_rlx2(arena + (LB_TIME << 13) + lane * 1024, 0, 0);
            bar_arrive(NB_C, 320);
        }
    } else if (rank == 0) {
        uint32_t best = ~0u;
        const int pg = wid < 10 ? 0 : 1 + (b >> 1) % 3;
        uint32_t* q = (uint32_t*)(arena + (pg << 21) + (pg ? blk(b >> 1, wid & 1) : blk(LB_PROBE, wid & 1) + b * 16));
        if (lane < 8) stg_rlx1(q + lane, 0);
        uint2 tk2 = ldg_rlx2(&g_tick[0]);
        __syncwarp();
        if (lane == 0) {
            q += 3;
            uint32_t v = atomicAdd(q, 1u);
#pragma unroll 1
            for (int r = 0; r < NPROBE; r++) {
                const uint32_t t0 = clk32() + (v >> 8);
                v = atomicAdd(q + (v >> 8), 1u);
                uint32_t t1;
                asm volatile("{.reg .pred p; setp.eq.u32 p, %1, 0xffffffff; @p exit; mov.u32 %0, %%clock;}" : "=r"(t1) : "r"(v) : "memory");
                best = min(best, t1 - t0);
            }
            sinfo[wid - 6] = best;
        }
        bar_sync(NB_KDONE, b < 128 ? 128 : 64);
        if (wid == 8) {
            const int par = sinfo[2] <= sinfo[3] ? 0 : 1, ncl = gridDim.x >> 1;
            int tk = 0, it = 0;
            const uint32_t vote = b < 128 && (sinfo[4] <= sinfo[5] ? 0 : 1) != par ? 256u << (8 * ((b >> 1) % 3)) : 0u;
            if (b >= 128) {
#pragma unroll 1
                while (!__all_sync(~0u, (int)((tk2.x + tk2.y) & 255) >= ncl - 2)) { tk2 = ldg_rlx2(&g_tick[0]); spin_guard(++it); }
            }
            if (lane == 0) tk = atomicAdd(&g_tick[par], 1u + vote) & 255;
#pragma unroll 1
            while (!__all_sync(~0u, (int)((tk2.x + tk2.y) & 255) >= ncl)) { tk2 = ldg_rlx2(&g_tick[0]); spin_guard(++it); }
            if (lane == 0) g_clk[b >> 1] = make_uint2(clk32() - 2 * gtime(), smid() | par << 8);
            tk = __shfl_sync(~0u, tk, 0);
            const int n0 = tk2.x & 255, n1 = tk2.y & 255;
            hA = min(n0 >> 1, NH);
            const int q0 = 2 * hA, q1 = 2 * NH - q0;
            const int over = tk - (par ? q1 : q0), lack = max(par ? q0 - n0 : q1 - n1, 0);
            if (over < 0) pr = par ? q0 + tk : tk;
            else if (over < lack) pr = (par ? n0 : q0 + n1) + over;
            else pr = -1 - (over - lack + (par ? max(n0 - q0, 0) : 0));
#pragma unroll
            for (int i = 0; i < 3; i++) hA |= (((tk2.x + tk2.y) >> (8 + 8 * i)) & 255) > 10 ? 256 << i : 0;
        }
    }
    asm volatile("barrier.cluster.wait.aligned;" ::: "memory");
    if (wid == 8) {
        if (rank == 0) {
            if (lane == 0) {
                uint32_t rsb;
                asm("mapa.shared::cluster.u32 %0, %1, 1;" : "=r"(rsb) : "r"(sb));
                asm volatile("st.async.shared::cluster.mbarrier::complete_tx::bytes.v2.u32 [%0], {%1, %2}, [%3];"
                             ::"r"(rsb + SM_BAR + 192), "r"(pr), "r"(hA), "r"(rsb + SM_BAR + 8 * B_ROLE) : "memory");
                sinfo[0] = pr; sinfo[1] = hA;
                if (b >= 128) atomicOr(&g_tick[4], (pr < 0 ? 4u : 1u) << ((b - 128) >> 1));
            }
        } else {
            mbar_wait_w(bars + 8 * B_ROLE, 0);
            pr = sinfo[0];
        }
        TL(1)
        __syncwarp();
        bar_arrive(NB_A, 288);
        bar_arrive(NB_S, 128);
        if (b >= 128 && pr < 0) bar_sync(NB_B, 64);
        if (pr >= 0) {
            const int pu = __reduce_max_sync(~0u, pr), c0 = (pu >> 1) * 128 + rank * 64, r0 = (pu & 1) * 512;
            bool fast = false;
#pragma unroll 1
            for (int n = 0; n < 12; n++) {
                const int rot = b >= 128 ? 8 : 0, i = (n + rot) % 12;
                if (rot && n == 4) bar_sync(NB_B, 64);
                if (n >= W_INFL && !fast) {
                    const uint32_t v = ldg_rlx1(&g_tick[32 + (lane & 3) * 8]);
                    mbar_wait_w(bars + 8 * (B_W + (n - W_INFL + rot) % 12), 0);
                    fast = __all_sync(~0u, v != 0);
                }
                const int m = i < 8 ? i & 1 : 2, k = i < 8 ? i >> 1 : i - 8;
                const uint32_t dst = sb + m * 65536 + k * 16384, br = bars + 8 * (B_W + i);
                if (lane == 0) {
                    mbar_expect(br, 16384);
                    tma2d_once(dst, &mp.wq + m, c0, r0 + k * 128, br);
                    tma2d_once(dst + 8192, &mp.wq + m, c0, r0 + k * 128 + 64, br);
                }
                __syncwarp();
            }
        }
    } else {
        bar_sync(wid < 8 ? NB_A : NB_S, wid < 8 ? 288 : 128);
    }
    const int prr = __reduce_max_sync(~0u, sinfo[0]);
    hA = __reduce_max_sync(~0u, sinfo[1]);
    if (prr < 0) {
        int j = (b - 128) >> 1;
        if (b < 128) {
            uint32_t v;
            int it = 0;
#pragma unroll 1
            do { v = __reduce_max_sync(~0u, ldg_rlx1(&g_tick[4])); spin_guard(++it); } while (__popc(v) < 2);
            j = v == 3 ? -1 - prr : (v & 1) ^ 1;
        }
        rec_side((float*)smraw, mp, p, j * 2 + rank);
        return;
    }
    const int role = (prr >> 1) * 4 + rank * 2 + (prr & 1);
    rec_main(sb, &mp.wo, arena, role, hA, wid >> 2, p.zero, p.dly);
}

__device__ __forceinline__ void wgmma_ss192(float* d, uint64_t a, uint64_t b, int sc) {
    asm volatile("{.reg .pred p; setp.ne.b32 p, %98, 0;\n wgmma.mma_async.sync.aligned.m64n192k16.f32.bf16.bf16 "
                 "{%0,%1,%2,%3,%4,%5,%6,%7,%8,%9,%10,%11,%12,%13,%14,%15,%16,%17,%18,%19,%20,%21,%22,%23,%24,%25,%26,%27,%28,%29,%30,%31,%32,%33,%34,%35,%36,%37,%38,%39,%40,%41,%42,%43,%44,%45,%46,%47,%48,%49,%50,%51,%52,%53,%54,%55,%56,%57,%58,%59,%60,%61,%62,%63,%64,%65,%66,%67,%68,%69,%70,%71,%72,%73,%74,%75,%76,%77,%78,%79,%80,%81,%82,%83,%84,%85,%86,%87,%88,%89,%90,%91,%92,%93,%94,%95}, %96, %97, p, 1, 1, 0, 1;}"
                 : F16(d, 0), F16(d, 16), F16(d, 32), F16(d, 48), F16(d, 64), F16(d, 80) : "l"(a), "l"(b), "r"(sc));
}

constexpr uint32_t P_B = 81920, P_PL = 40960, P_OUT = 180224, P_VEC = 212992, P_ROW = P_VEC + 6144, P_BAR = P_ROW + 4096, P_SMEM = P_BAR + 256;
#define PPH 1
#define FLAG_ST "st.release.gpu.global.u32"
#define FLAG_LD "ld.acquire.gpu.global.u32"
#define PX 0
#define MIDF 0
#define DS_AT 3
constexpr int ST = 5;
constexpr int PB_F = 0, PB_E = 5, PB_R = 10, PB_OUT = 16;
enum { C_Y = 0, C_G = 1, C_X1 = 2, C_U = 3, C_S1 = 8, C_S3 = 9 };
enum { V_GA = 0, V_A = 1, V_B = 2, V_GB = 3, V_VA = 4, V_VB = 5, V_VC = 6, V_C3 = 7 };
struct PostMaps { CUtensorMap o, wo, y, w1, g, w2, x1, w3, u, w4, out; };
struct PostPtrs { const bf16* x; };

struct GeluK { float k0, k1, kh; };
__device__ __forceinline__ GeluK gelu_k(float c) { return {0.7978845608028654f * c, 0.7978845608028654f * 0.044715f * c * c * c, 0.5f * c}; }
__device__ __forceinline__ float gelu_s(float t, const GeluK& k) {
    const float u = t * fmaf(t * t, k.k1, k.k0);
    float th; asm("tanh.approx.f32 %0, %1;" : "=f"(th) : "f"(u));
    const float hx = k.kh * t;
    return fmaf(hx, th, hx);
}
__device__ __forceinline__ float2 ldsv(uint32_t a) {
    float2 v; asm("ld.shared.v2.f32 {%0,%1}, [%2];" : "=f"(v.x), "=f"(v.y) : "r"(a)); return v;
}
__device__ __forceinline__ void wait_smem(uint32_t a, int target) {
    int it = 0;
#pragma unroll 1
    while (true) {
        int v;
        asm volatile("ld.acquire.cta.shared.u32 %0, [%1];" : "=r"(v) : "r"(a) : "memory");
        if (__all_sync(~0u, v >= target) | (++it > SPIN_LIMIT)) break;
    }
}

#define PP(i)
#define PH_(c, w, i)
__device__ __forceinline__ void mbar_wait_b(uint32_t b, uint32_t par) {
    int it = 0;
#pragma unroll 1
    while (!__all_sync(~0u, mbar_try(b, par)) & (++it < SPIN_LIMIT)) {}
}
__device__ __forceinline__ void release(uint32_t rel, int st, bool c) {
    asm volatile("{.reg .pred p; setp.ne.u32 p, %1, 0; setp.ne.and.u32 p, %2, 0, p; @p mbarrier.arrive.shared::cluster.b64 _, [%0];}"
                 ::"r"(rel + 8 * (st ? st - 1 : ST - 1)), "r"(rel), "r"((uint32_t)c) : "memory");
}
struct Pipe { int st, ph; uint32_t rel; };
__device__ __forceinline__ void adv(Pipe& p) { if (++p.st == ST) { p.st = 0; p.ph ^= 1; } }

__device__ __forceinline__ void post_weights(uint32_t sb, const PostMaps& mp, int nb, int rank) {
    const uint32_t full = sb + P_BAR + 8 * PB_F, empty = sb + P_BAR + 8 * PB_E;
    int st = 0, pp = 1;
#pragma unroll 1
    for (int ph = 0; ph < 7; ph++) {
        const int NK = ph == 0 ? 64 : ph == 6 ? 56 : 16, km = NK == 16 ? 15 : 63;
        const CUtensorMap* tb = &mp.wo + 2 * (ph < 3 ? ph : ph < 6 ? 3 : 4);
        const bool w3 = ph >= 3 && ph < 6;
        const int n0 = w3 ? nb * 64 + (ph == 4 ? 1536 : ph == 5 ? 2560 : 0) : nb * 128, dn = w3 ? 512 : 64;
        const int rot = NK == 16 ? 2 * (nb & 6) : 0, sw = ph == 1 || ph == 3 ? 2 * rank : 0;
#pragma unroll 1
        for (int i = 0; i < NK; i++) {
            const int k0 = (((i < 4 ? i ^ sw : i) + rot) & km) * 64;
            const uint32_t a = sb + P_B + st * 8192, f = full + 8 * st;
            mbar_wait_b(empty + 8 * st, pp);
            e_expect(f, ph == 3 ? 40960 : 32768);
            e_tma2d(a, tb, n0, k0, f);
            e_tma2d(a + P_PL, tb, n0 + dn, k0, f);
            if (ph == 3) e_tma2d(a + 2 * P_PL, tb, n0 + 1024, k0, f);
            if (++st == ST) { st = 0; pp ^= 1; }
        }
    }
#pragma unroll 1
    for (int i = 0; i < ST; i++) mbar_wait_b(empty + 8 * i, pp ^ (i < st));
}
__device__ __forceinline__ void post_acts(uint32_t sb, const PostMaps& mp, int mb, int nb, int rank) {
    const int rh = 2 * mb + rank, lane = threadIdx.x & 31;
    const uint32_t full = sb + P_BAR + 8 * PB_F, empty = sb + P_BAR + 8 * PB_E;
    int st = 0, pp = 1;
#pragma unroll 1
    for (int ph = 0; ph < 7; ph++) {
        const int NK = ph == 0 ? 64 : ph == 6 ? 56 : 16, km = NK == 16 ? 15 : 63;
        const CUtensorMap* ta = &mp.o + 2 * (ph < 3 ? ph : ph < 6 ? 3 : 4);
        const int amul = ph == 0 ? 256 : 64, arow = ph == 0 ? rh * 8 : rh * 64;
        const int rot = NK == 16 ? 2 * (nb & 6) : 0, own = ph == 1 || ph == 3 ? 4 : 0;
        const uint32_t shifts = ph == 2 ? 0x04000301u : 0x02020202u;
        const uint32_t* fl = &g_pflag[(ph == 6 ? C_U : min(ph - 1, 2)) * 256 + (ph == 2 ? min(max(rh + min(lane >> 3, 2) - 1, 0), 31) : rh) * 8 + (lane & 7)];
        uint32_t have = ph == 0 || ph == 5;
        if (own) { if (st) { st--; pp ^= 1; } else st = 4; }
#pragma unroll 1
        for (int i = own; i < NK; i++) {
            const int kb = (i + rot) & km;
            const uint32_t need = ph == 6 ? 255u : (ph == 2 ? 0x10101u : 1u) << ((kb >> 1) & 7), lvl = ph == 6 ? i >> 3 : 0;
            PH_(ph == PPH && i == own, 0, 27) PH_(ph == PPH && i == own, 1, 27)
            if ((__ballot_sync(~0u, have > lvl) & need) != need) {
                int it = 0;
#pragma unroll 1
                do asm volatile(FLAG_LD " %0, [%1];" : "=r"(have) : "l"(fl) : "memory");
                while (((__ballot_sync(~0u, have > lvl) & need) != need) & (++it < SPIN_LIMIT));
                PH_(ph == PPH && i == own, 0, 23) PH_(ph == PPH, 0, 24) PH_(ph == PPH && i == own, 1, 23) PH_(ph == PPH, 1, 24)
                asm volatile("fence.proxy.async.global;" ::: "memory");
            }
            const int d = own && (i == 5 || i == 6) ? 2 : 0, s2 = st + d < ST ? st + d : st + d - ST;
            mbar_wait_b(empty + 8 * s2, pp ^ (s2 < st));
            e_tma2d_mc(sb + st * 16384 + rank * 8192, ta, kb * amul, arow + (int)((shifts >> ((kb & 12) * 2)) & 7) - 2, full + 8 * st);
            if (++st == ST) { st = 0; pp ^= 1; }
        }
    }
}

template <int PH, bool EARLY = false, class F>
__device__ __forceinline__ void post_kb(uint32_t sb, float* acc, Pipe& p, int wg, bool lead, bool first, F mid) {
    constexpr uint64_t DA = PH == 0 ? mkdesc(SB0, 128, 1024, 0) : mkdesc(SB0, 16, 1024, 1);
    constexpr uint64_t DB = mkdesc(SB0 + P_B, P_PL, 1024, 1);
    mbar_wait_b(sb + P_BAR + 8 * PB_F + 8 * p.st, p.ph);
    const uint32_t a = (uint32_t)DA + p.st * 1024 + wg * 512, b = (uint32_t)DB + p.st * 512;
    wg_fence();
#pragma unroll
    for (int k = 0; k < 4; k++) {
        const uint64_t da = (DA & 0xffffffff00000000ull) | (a + k * (PH == 0 ? 16 : 2)), db = (DB & 0xffffffff00000000ull) | (b + k * 128);
        if (PH == 3) wgmma_ss192(acc, da, db, k || !first);
        else wgmma_ss128<PH == 0>(acc, da, db, k || !first);
    }
    wg_commit();
    if (EARLY) mid();
    wg_wait<1>();
    release(p.rel, p.st, !first);
    if (!EARLY) mid();
    adv(p);
}
__device__ __forceinline__ void post_end(uint32_t sb, Pipe& p, bool lead) {
    wg_wait<0>();
    release(p.rel, p.st, true);
}
template <int PH>
__device__ __forceinline__ void post_mma(uint32_t sb, float* acc, Pipe& p, int wg, bool lead, int nout, int pi, int mb, int nb) {
#pragma unroll 1
    for (int kb = 0; kb < (PH == 0 ? 64 : 16); kb++)
        post_kb<PH>(sb, acc, p, wg, lead, kb == 0, [&]() {
            if (kb == 0) { PP(pi) if (PH == 0 && wg == 0) TL(11) }
            if (nout && kb == 0) wait_smem(sb + P_BAR + 8 * (PB_OUT + wg), nout);
        });
    post_end(sb, p, lead);
    PP(pi + 1)
}

__global__ void __cluster_dims__(2, 1, 1) __launch_bounds__(384, 1)
k_post(const __grid_constant__ PostMaps mp, const __grid_constant__ PostPtrs pp) {
    extern __shared__ uint8_t smraw[];
    const uint32_t sb = smem_u32(smraw);
    if ((sb & 0x3FFFF) != SB0) __trap();
    const int tid = threadIdx.x, lane = tid & 31;
    const int rank = blockIdx.x & 1;
    const uint32_t bars = sb + P_BAR;
    int c = 0;
    unsigned long long v = 0;
    const int wid = __reduce_max_sync(~0u, tid >> 5);
    const bool draw = tid == 352 && rank == 0;
    if (draw) {
        c = min(ldg_rlx1(&g_cls[smid() & 255]), 8u);
        asm volatile("{.reg .b64 a; cvt.u64.u32 a, %%laneid; add.u64 a, a, %1; atom.relaxed.gpu.global.add.u64 %0, [a], %2;}" : "=l"(v) : "l"(&g_pt), "l"(1ull << (7 * c)) : "memory");
    }
    if (wid < 11) {
        asm volatile("{.reg .pred p; elect.sync _|p, 0xffffffff; @p mbarrier.init.shared.b64 [%0], %1; @p prefetch.tensormap [%2]; fence.mbarrier_init.release.cluster;}"
                     ::"r"(bars + 8 * wid), "r"(wid >= PB_E && wid < PB_R ? 4 : 1), "l"(&mp.o + wid) : "memory");
        if (wid == PB_R) { sts4(bars + 8 * PB_OUT, 0, 0, 0, 0); e_expect(bars + 8 * PB_R, 4); }
    }
    __syncwarp();
    asm volatile("barrier.cluster.arrive.relaxed.aligned; barrier.cluster.wait.aligned;" ::: "memory");
    if (draw) {
        int r = (v >> (7 * c)) & 127, role = c * 8 + r;
        if (c == 8 || r >= 8) {
            int n, x, it = 0;
#pragma unroll 1
            do {
                v = ldg_u64(&g_pt); n = 0; x = c < 8 ? r - 8 : r;
#pragma unroll 1
                for (int i = 0; i < 63; i += 7) { const int m = v >> i & 127; n += m; if (i < 7 * c) x += max(m - 8, 0); }
            } while (n < gridDim.x / 2 && ++it < SPIN_LIMIT);
            role = -1;
#pragma unroll 1
            for (int i = 0; i < 64; i += 8, v >>= 7) {
                n = v & 127;
                if (x >= 0 && n + x < 8) role = i + n + x;
                x -= max(8 - n, 0);
            }
        }
#pragma unroll
        for (int i = 0; i < 2; i++)
            asm volatile("{.reg .b32 d; mapa.shared::cluster.u32 d, %0, %2; st.async.shared::cluster.mbarrier::complete_tx::bytes.u32 [d+8], %1, [d];}"
                         ::"r"(bars + 8 * PB_R), "r"(role), "r"(i) : "memory");
    }
    __syncwarp();
    mbar_wait_b(bars + 8 * PB_R, 0);
    const int pr = __reduce_max_sync(~0u, (int)lds1(bars + 8 * PB_R + 8));
    if (pr < 0) return;
    const int mb = (pr >> 5) * 8 + (pr & 7), nb = (pr >> 2 & 6) + rank, cta = pr * 2 + rank;
    if (wid >= 8) {
        asm volatile("setmaxnreg.dec.sync.aligned.u32 40;");
        const int w = wid - 8;
        if (w == 0) {
            post_weights(sb, mp, nb, rank);
        } else if (w == 3) {
            post_acts(sb, mp, mb, nb, rank);
        } else {
            const int wg = w - 1, rh = 2 * mb + wg;
            float* rowc = (float*)(smraw + P_ROW) + (wg * 64 + lane * 2) * 8;
            int nout = 0, sig = 0;
#pragma unroll 1
            for (int i = 0; i < 13; i++) {
                const int cnt = (0x4333333392180ull >> (4 * i)) & 15;
                if (cnt < C_S1) {
                    const int ng = cnt == C_U ? 1 : 2, c0 = cnt == C_U ? (i - 5) * 512 + nb * 64 : nb * 128;
                    const bool fast = (cnt == C_Y || cnt == C_X1);
#pragma unroll 1
                    for (int j = 0; j < ng; j++) {
                        const uint32_t st = j ? cnt : cnt ? 1 : 4;
                        const uint32_t src = sb + (fast ? st * 16384 + wg * 8192 : P_OUT + wg * 16384 + ((nout + j) & 1) * 8192);
                        bar_sync(4 + 4 * wg + (sig++ & 3), 160);
                        if (lane == 0) {
                            PH_(cnt == PPH - 1, wg, 20)
                            if (fast) asm volatile("mbarrier.complete_tx.relaxed.cta.shared::cta.b64 [%0], 8192;" ::"r"(bars + 8 * (PB_F + st)) : "memory");
                            asm volatile("cp.async.bulk.tensor.2d.global.shared::cta.bulk_group [%0, {%2, %3}], [%1]; cp.async.bulk.commit_group;"
                                         ::"l"(&mp.y + 2 * cnt), "r"(src), "r"(c0 + j * 64), "r"(rh * 64) : "memory");
                        }
                        __syncwarp();
                    }
                    if (lane == 0) {
                        auto to_peer = [&]() {
                            const uint32_t n = cnt ? 1 : 4;
                            mbar_wait(bars + 8 * (PB_E + (cnt ? 4 : 2)), 0);
#pragma unroll
                            for (int i = 0; i < 2; i++)
                                asm volatile("{.reg .b32 d, m; mapa.shared::cluster.u32 d, %0, %3; mapa.shared::cluster.u32 m, %2, %3;\n"
                                             " cp.async.bulk.shared::cluster.shared::cta.mbarrier::complete_tx::bytes [d], [%1], 8192, [m];}"
                                             ::"r"(sb + (cnt + 1 + i) * 16384 + wg * 8192), "r"(sb + (i ? cnt : n) * 16384 + wg * 8192), "r"(bars + 8 * (PB_F + cnt + 1 + i)), "r"(rank ^ 1) : "memory");
                        };
                        if (DS_AT == 1 && fast) to_peer();
                        asm volatile("cp.async.bulk.wait_group 0; fence.proxy.async.global;" ::: "memory");
                        asm volatile("st.release.cta.shared.u32 [%0], %1;" ::"r"(bars + 8 * (PB_OUT + wg)), "r"(nout + ng) : "memory");
                        PH_(cnt == PPH - 1, wg, 21)
                        if (DS_AT == 2 && fast) to_peer();
                        asm volatile(FLAG_ST " [%0], %1;" ::"l"(&g_pflag[cnt * 256 + rh * 8 + nb]), "r"(max(i - 4, 1)) : "memory");
                        PH_(cnt == PPH - 1, wg, 22)
                        if (DS_AT == 3 && fast) to_peer();
                    }
                    nout += ng;
                    __syncwarp();
                    continue;
                }
                bar_sync(4 + 4 * wg + (sig++ & 3), 160);
                uint32_t* c = &g_pcnt[(cnt - C_S1) * 256 + rh * 8];
                if (lane == 0) { signal_count(c); wait_count1(c, 8); }
                __syncwarp();
                const float4* sp = (const float4*)g_st + rh * 32 + lane;
                float4 u[3] = {__ldcg(sp + (cnt == C_S1 ? 0 : 3) * (S_ / 2)), __ldcg(sp + S_ / 2), __ldcg(sp + S_)};
#pragma unroll 1
                for (int h = 0; h < 2; h++) {
                    const float id = 1.0f / DM;
                    const float m = u[0].x * id, var = fmaxf(u[0].y * id - m * m, 0.f) + 1e-5f, r = rsqrtf(var);
                    float sc = r, m2 = 0.f;
                    if (cnt == C_S1) {
                        m2 = r * (u[1].x * id - m * g_cst[0]) + g_cst[3];
                        const float e2 = r * r * (u[2].x * id - 2.0f * m * u[1].y * id + m * m * g_cst[1]) + 2.0f * r * (u[2].y * id - m * g_cst[2]) + g_cst[4];
                        sc = r * rsqrtf(fmaxf(e2 - m2 * m2, 0.f) + 1e-5f);
                    }
                    const GeluK k = gelu_k(sc);
                    *(float4*)(rowc + h * 8) = make_float4(k.k0, k.k1, k.kh, -m);
                    *(float4*)(rowc + h * 8 + 4) = make_float4(var * r, -m2 * var * r, r, -m * r);
#pragma unroll
                    for (int q = 0; q < 3; q++) { u[q].x = u[q].z; u[q].y = u[q].w; }
                }
                bar_arrive(1 + wg, 160);
            }
        }
    } else {
        asm volatile("setmaxnreg.inc.sync.aligned.u32 232;");
        const bf16* xin = pp.x;
        const int wg = wid >> 2, wi = (tid >> 5) & 3, g = lane >> 2, tq = lane & 3;
        const int rh = 2 * mb + wg, row = rh * 64 + wi * 16 + g;
        const bool lead = (tid & 127) == 0;
        PP(0)
        if (tid == 0) TL(10)
        uint4 xg[8];
#pragma unroll
        for (int i = 0; i < 8; i++)
            xg[i] = __ldg((const uint4*)(xin + (size_t)(rh * 64 + wi * 16 + (i & 3) * 4 + (lane >> 3)) * DM + nb * 128 + (i >> 2) * 64 + (lane & 7) * 8));
        if (cta < 64) g_modp[cta * 256 + tid] = 0;
        if (cta == 64 && tid < 64) g_tick[tid] = 0;
        {
            float* sv = (float*)(smraw + P_VEC);
            if (tid < 128) {
                const int c = nb * 128 + tid;
                sv[V_GA * 128 + tid] = __ldcg(&g_mod[2 * DM + c]); sv[V_A * 128 + tid] = 1.0f + __ldcg(&g_mod[4 * DM + c]);
                sv[V_B * 128 + tid] = __ldcg(&g_mod[3 * DM + c]); sv[V_GB * 128 + tid] = __ldcg(&g_mod[5 * DM + c]);
            } else {
                const int c = nb * 128 + tid - 128;
                sv[V_VA * 128 + tid - 128] = __ldcg(&g_vec[c]); sv[V_VB * 128 + tid - 128] = __ldcg(&g_vec[DM + c]); sv[V_VC * 128 + tid - 128] = __ldcg(&g_vec[2 * DM + c]);
            }
            const float* c3 = &g_vec[3 * DM + (tid >> 6) * 512 + nb * 64 + (tid & 63)];
            sv[V_C3 * 128 + tid] = __ldcg(c3);
            if (tid < 192) sv[V_C3 * 128 + 256 + tid] = __ldcg(c3 + 2048);
            bar_sync(3, 256);
        }
        uint32_t vec = sb + P_VEC + tq * 8;
        asm volatile("" : "+r"(vec) :: "memory");
        const uint32_t stw = sb + (wi * 16 + ((lane >> 3) & 1) * 8 + (lane & 7)) * 128 + (((lane >> 4) ^ (lane & 7)) << 4);
        int sig = 0;
        auto signal = [&]() { bar_arrive(4 + 4 * wg + (sig++ & 3), 160); };
        auto put64 = [&](uint32_t o, const float* v) {
#pragma unroll
            for (int jj = 0; jj < 4; jj++, v += 8) stsm4((stw + o) ^ (jj << 5), pack2(v[0], v[1]), pack2(v[2], v[3]), pack2(v[4], v[5]), pack2(v[6], v[7]));
            fence_async_smem();
            signal();
        };
        auto slot = [&](int n) {
            mbar_wait_b(bars + 8 * (PB_E + n % 5), ((n / 5) & 1) ^ 1);
            return (n % 5) * 16384 + wg * 8192;
        };
        const uint32_t rowc = sb + P_ROW + (wg * 64 + wi * 16 + g) * 32, o128 = P_OUT + wg * 16384;
        Pipe pa = {0, 0, 0};
        asm("mapa.shared::cluster.u32 %0, %1, %2;" : "=r"(pa.rel) : "r"(bars + 8 * PB_E), "r"(tid & 1));
        if (tid & 126) pa.rel = 0;
        uint32_t keep[32];
#define KEEP(jn, e) (((e) & 1) ? bfhi(keep[2 * (jn) + ((e) >> 1)]) : bflo(keep[2 * (jn) + ((e) >> 1)]))
        float mu1[2], r1[2];
        {
            float acc[64];
            const uint32_t xo = sb + o128 + wi * 2048 + (lane >> 3) * 128;
#pragma unroll
            for (int i = 0; i < 8; i++) sts4(xo + (i >> 2) * 8192 + (i & 3) * 512 + (((lane & 7) ^ ((i & 1) * 4 + (lane >> 3))) << 4), xg[i].x, xg[i].y, xg[i].z, xg[i].w);
            __syncwarp();
#pragma unroll
            for (int jj = 0; jj < 8; jj++) ldsm4(keep + jj * 4, (stw + o128 + (jj >> 2) * 8192) ^ ((jj & 3) << 5));
            __syncwarp();
            post_mma<0>(sb, acc, pa, wg, lead, 0, 1, mb, nb);
            float st[2][6];
#pragma unroll
            for (int q = 0; q < 6; q++) st[0][q] = st[1][q] = 0.f;
#pragma unroll
            for (int jn = 0; jn < 16; jn++) {
                const float2 ga = ldsv(vec + V_GA * 512 + jn * 32), a = ldsv(vec + V_A * 512 + jn * 32);
                float xa[4];
#pragma unroll
                for (int e = 0; e < 4; e++) {
                    xa[e] = fmaf((e & 1) ? ga.y : ga.x, acc[4 * jn + e], KEEP(jn, e));
                    st[e >> 1][0] += xa[e]; st[e >> 1][1] = fmaf(xa[e], xa[e], st[e >> 1][1]);
                    acc[4 * jn + e] = ((e & 1) ? a.y : a.x) * xa[e];
                }
                keep[2 * jn] = pack2(xa[0], xa[1]); keep[2 * jn + 1] = pack2(xa[2], xa[3]);
                if ((jn & 7) == 7) put64(slot(64 + (jn >> 3)), acc + 4 * jn - 28);
            }
            PP(3)
#pragma unroll
            for (int jn = 0; jn < 16; jn++) {
                const float2 a = ldsv(vec + V_A * 512 + jn * 32), b = ldsv(vec + V_B * 512 + jn * 32);
#pragma unroll
                for (int e = 0; e < 4; e++) {
                    const float y = acc[4 * jn + e], aa = (e & 1) ? a.y : a.x, bb = (e & 1) ? b.y : b.x;
                    float* s = st[e >> 1];
                    s[2] += y; s[3] = fmaf(aa, y, s[3]); s[4] = fmaf(y, y, s[4]); s[5] = fmaf(bb, y, s[5]);
                }
            }
#pragma unroll
            for (int h = 0; h < 2; h++)
#pragma unroll
                for (int q = 0; q < 6; q++) { st[h][q] += __shfl_xor_sync(~0u, st[h][q], 1); st[h][q] += __shfl_xor_sync(~0u, st[h][q], 2); }
            if (tq < 3 && !(PX & 1)) {
#pragma unroll
                for (int h = 0; h < 2; h++)
                    red2(g_st + (tq * S_ + row + h * 8) * 2, tq == 0 ? st[h][0] : tq == 1 ? st[h][2] : st[h][4], tq == 0 ? st[h][1] : tq == 1 ? st[h][3] : st[h][5]);
            }
            signal();
            PP(29)
        }
        {
            float acc[64];
            post_mma<1>(sb, acc, pa, wg, lead, 2, 4, mb, nb);
            float c1[2], c2[2], c3[2];
            GeluK gk[2];
            bar_sync(1 + wg, 160);
#pragma unroll
            for (int h = 0; h < 2; h++) {
                const float4 a = lds4f(rowc + h * 256), b = lds4f(rowc + h * 256 + 16);
                gk[h] = {a.x, a.y, a.z}; c1[h] = a.w; c2[h] = b.x; c3[h] = b.y; mu1[h] = b.w; r1[h] = b.z;
            }
#pragma unroll
            for (int jn = 0; jn < 16; jn++) {
                const float2 va = ldsv(vec + V_VA * 512 + jn * 32), vb = ldsv(vec + V_VB * 512 + jn * 32), vc = ldsv(vec + V_VC * 512 + jn * 32);
#pragma unroll
                for (int e = 0; e < 4; e++) {
                    const int h = e >> 1;
                    const float t = fmaf(c1[h], (e & 1) ? va.y : va.x, fmaf(c2[h], (e & 1) ? vb.y : vb.x, fmaf(c3[h], (e & 1) ? vc.y : vc.x, acc[4 * jn + e])));
                    acc[4 * jn + e] = gelu_s(t, gk[h]);
                }
                if ((jn & 7) == 7) put64(o128 + (jn >> 3) * 8192, acc + 4 * jn - 28);
            }
            PP(6)
        }
        {
            float acc[64];
            post_mma<2>(sb, acc, pa, wg, lead, 0, 7, mb, nb);
#pragma unroll
            for (int jn = 0; jn < 16; jn++) {
                const float2 a = ldsv(vec + V_A * 512 + jn * 32), b = ldsv(vec + V_B * 512 + jn * 32);
#pragma unroll
                for (int e = 0; e < 4; e++) {
                    const int h = e >> 1;
                    acc[4 * jn + e] += fmaf(fmaf(KEEP(jn, e), r1[h], mu1[h]), (e & 1) ? a.y : a.x, (e & 1) ? b.y : b.x);
                }
                if ((jn & 7) == 7) put64(slot(96 + (jn >> 3)), acc + 4 * jn - 28);
            }
            BLOCK_FENCE
#pragma unroll
            for (int i = 0; i < 64; i += 16) asm volatile("" : F16(acc, i));
            PP(9)
            float st[2][2] = {{0.f, 0.f}, {0.f, 0.f}};
#pragma unroll
            for (int jn = 0; jn < 16; jn++) {
                const float2 gb = ldsv(vec + V_GB * 512 + jn * 32);
                float z[4];
#pragma unroll
                for (int e = 0; e < 4; e++) {
                    const float x1 = acc[4 * jn + e];
                    st[e >> 1][0] += x1; st[e >> 1][1] = fmaf(x1, x1, st[e >> 1][1]);
                    z[e] = fmaf((e & 1) ? gb.y : gb.x, x1, KEEP(jn, e));
                }
                keep[2 * jn] = pack2(z[0], z[1]); keep[2 * jn + 1] = pack2(z[2], z[3]);
            }
#pragma unroll
            for (int h = 0; h < 2; h++)
#pragma unroll
                for (int q = 0; q < 2; q++) { st[h][q] += __shfl_xor_sync(~0u, st[h][q], 1); st[h][q] += __shfl_xor_sync(~0u, st[h][q], 2); }
            if (tq < 2) red2(g_st + (3 * S_ + row + tq * 8) * 2, tq ? st[1][0] : st[0][0], tq ? st[1][1] : st[0][1]);
            signal();
            PP(30)
        }
        {
            float old[96], acc[64];
            post_mma<3>(sb, old, pa, wg, lead, 6, 10, mb, nb);
#pragma unroll
            for (int i = 0; i < 96; i += 16) asm volatile("" : F16(old, i));
            uint32_t v3 = vec + V_C3 * 512;
            bar_sync(1 + wg, 160);
            const float4 rc[2] = {lds4f(rowc), lds4f(rowc + 256)};
            float2 vc[2] = {lds2f(v3), lds2f(v3 + 32)};
            bar_sync(3, 256);
#pragma unroll 1
            for (int blk = 0; blk < 11; blk++) {
                const uint32_t o = stw + o128 + (blk & 1) * 8192;
                const int turn = blk < 7 ? wg : 2;
#pragma unroll
                for (int q = 0; q < 4; q++) {
#pragma unroll 1
                    for (int rep = 0; rep < 2; rep++) {
                        post_kb<1, MIDF>(sb, acc, pa, wg, lead, q == 0 && rep == 0 && blk < 6 && !(blk & 1), [&]() {
                        if (rep != turn) return;
                        asm volatile("" : F4(old, 8 * q), F4(old, 8 * q + 4));
                        const float2 vn[2] = {lds2f(v3 + q * 64 + 64), lds2f(v3 + q * 64 + 96)};
                        float t[8];
#pragma unroll
                        for (int i = 0; i < 8; i++) {
                            const float4& c = rc[(i >> 1) & 1];
                            t[i] = gelu_s(fmaf(c.w, (i & 1) ? vc[i >> 2].y : vc[i >> 2].x, old[8 * q + i]), GeluK{c.x, c.y, c.z});
                            old[8 * q + i] = old[32 + 8 * q + i];
                            old[32 + 8 * q + i] = old[64 + 8 * q + i];
                        }
                        stsm4(o ^ (q << 5), pack2(t[0], t[1]), pack2(t[2], t[3]), pack2(t[4], t[5]), pack2(t[6], t[7]));
                        vc[0] = vn[0]; vc[1] = vn[1];
                        if (q == 2) wait_smem(bars + 8 * (PB_OUT + wg), 6 + blk);
                        if (q == 3) { fence_async_smem(); signal(); }
                        });
                    }
                }
                v3 += 256;
                if (blk != 1 && blk != 3) continue;
                post_end(sb, pa, lead);
                PP(12 + blk)
                asm volatile("" : F16(acc, 0), F4(acc, 16), F4(acc, 20), F4(acc, 24));
                asm volatile("" : F16(acc, 28), F4(acc, 44), F4(acc, 48), F4(acc, 52));
                asm volatile("" : F4(acc, 56), F4(acc, 60));
#pragma unroll
                for (int i = 0; i < 64; i++) old[32 + i] = acc[i];
            }
            post_end(sb, pa, lead);
            PP(17)
#pragma unroll
            for (int jn = 0; jn < 16; jn++) {
                const float2 gb = ldsv(vec + V_GB * 512 + jn * 32);
#pragma unroll
                for (int e = 0; e < 4; e++) acc[4 * jn + e] = fmaf((e & 1) ? gb.y : gb.x, acc[4 * jn + e], KEEP(jn, e));
                if ((jn & 7) == 7) put64(o128 + ((jn >> 3) ^ 1) * 8192, acc + 4 * jn - 28);
            }
            PP(18)
            if (tid == 0) TL(12)
        }
    }
}

typedef CUresult (*EncFn)(CUtensorMap*, CUtensorMapDataType, cuuint32_t, void*, const cuuint64_t*, const cuuint64_t*, const cuuint32_t*,
                          const cuuint32_t*, CUtensorMapInterleave, CUtensorMapSwizzle, CUtensorMapL2promotion, CUtensorMapFloatOOBfill);

static CUtensorMap make_map(EncFn enc, const void* p, uint64_t inner, uint64_t outer, uint32_t bi = 64) {
    CUtensorMap m;
    cuuint64_t dims[2] = {inner, outer};
    cuuint64_t str[1] = {inner * 2};
    cuuint32_t box[2] = {bi, bi == 64 ? 64u : 16u};
    cuuint32_t es[2] = {1, 1};
    enc(&m, CU_TENSOR_MAP_DATA_TYPE_BFLOAT16, 2, (void*)p, dims, str, box, es, CU_TENSOR_MAP_INTERLEAVE_NONE,
        bi == 64 ? CU_TENSOR_MAP_SWIZZLE_128B : CU_TENSOR_MAP_SWIZZLE_NONE, CU_TENSOR_MAP_L2_PROMOTION_L2_256B, CU_TENSOR_MAP_FLOAT_OOB_FILL_NONE);
    return m;
}
static CUtensorMap make_map_o(EncFn enc, const void* p) {
    CUtensorMap m;
    cuuint64_t dims[2] = {16384, 256};
    cuuint64_t str[1] = {65536};
    cuuint32_t box[2] = {256, 8};
    cuuint32_t es[2] = {1, 1};
    enc(&m, CU_TENSOR_MAP_DATA_TYPE_UINT32, 2, (void*)p, dims, str, box, es, CU_TENSOR_MAP_INTERLEAVE_NONE, CU_TENSOR_MAP_SWIZZLE_NONE,
        CU_TENSOR_MAP_L2_PROMOTION_L2_256B, CU_TENSOR_MAP_FLOAT_OOB_FILL_NONE);
    return m;
}
template <class T> static T* sym(T& s) { void* p = nullptr; cudaGetSymbolAddress(&p, s); return (T*)p; }

static const Delays h_dly = {D_NEAR, D_FAR, D_X2, D_V, D_W2, D_PA, D_WF, D_TV};
extern "C" void kernel_launch(void* const* d_in, const int* in_sizes, int n_in, void* d_out, int out_size) {
    const bf16* x = (const bf16*)d_in[0];
    const bf16* mem0 = (const bf16*)d_in[1];
    const bf16 *Wq = (const bf16*)d_in[2], *Wk = (const bf16*)d_in[3], *Wv = (const bf16*)d_in[4], *Wo = (const bf16*)d_in[5];
    const bf16 *w1 = (const bf16*)d_in[8], *w2 = (const bf16*)d_in[9], *w3 = (const bf16*)d_in[10], *w4 = (const bf16*)d_in[11];
    const bf16 *c = (const bf16*)d_in[12], *wmod = (const bf16*)d_in[13];
    bf16* out = (bf16*)d_out;

    EncFn enc = nullptr;
    cudaDriverEntryPointQueryResult qr;
    cudaGetDriverEntryPoint("cuTensorMapEncodeTiled", (void**)&enc, cudaEnableDefault, &qr);
    CUtensorMap tWq = make_map(enc, Wq, NH * DH, DM), tWk = make_map(enc, Wk, NH * DH, DM), tWv = make_map(enc, Wv, NH * DH, DM);
    PostMaps mp;
    mp.o = make_map_o(enc, sym(g_O)); mp.wo = make_map(enc, Wo, DM, NH * DH);
    mp.y = make_map(enc, sym(g_y), DM, S_); mp.w1 = make_map(enc, w1, DM, DM);
    mp.g = make_map(enc, sym(g_g), DM, S_); mp.w2 = make_map(enc, w2, DM, DM);
    mp.x1 = make_map(enc, sym(g_x1), DM, S_); mp.w3 = make_map(enc, w3, FF, DM);
    mp.u = make_map(enc, sym(g_u), FF, S_); mp.w4 = make_map(enc, w4, DM, FF);
    mp.out = make_map(enc, out, DM, S_);
    cudaFuncSetAttribute(k_rec, cudaFuncAttributeMaxDynamicSharedMemorySize, SM_REC_TOTAL + 2048);
    cudaFuncSetAttribute(k_post, cudaFuncAttributeMaxDynamicSharedMemorySize, P_SMEM);

    uint8_t* arena = (uint8_t*)(((uintptr_t)sym(g_arena) + (2u << 20) - 1) & ~(uintptr_t)((2u << 20) - 1));
    const PostPtrs pp = {x};
    const RecPtrs rp = {x, mem0, c, wmod, w1, w3, arena, 0u, w2, w4, Wo, h_dly};
    const RecMaps rm = {tWq, tWk, tWv, mp.wo, make_map(enc, wmod, 6 * DM, DM, 256), make_map(enc, w3, FF, DM, 256), make_map(enc, w1, DM, DM, 256)};
    k_rec<<<132, 384, SM_REC_TOTAL + 2048>>>(rm, rp);
    k_post<<<132, 384, P_SMEM>>>(mp, pp);
}
```

```cpp
#include <cuda_runtime.h>
#include <cuda.h>
#include <cuda_bf16.h>
#include <stdint.h>
#include <limits.h>

typedef __nv_bfloat16 bf16;

constexpr int S_ = 2048, DM = 1024, NH = 32, DH = 128, NSEG = 64, FF = 3584;
constexpr int SPIN_LIMIT = 1 << 22;
#define W_INFL 2
#define XP 0
#define H_PIECES 4
#define PDL 1
#define NPROBE 3

__device__ uint8_t g_arena[10 << 20];
__device__ uint32_t g_tick[64];
__device__ uint2 g_clk[66];
__device__ uint32_t g_cls[256];
__device__ unsigned long long g_pt;
__device__ __align__(16) uint32_t g_modp[8 * 2 * DM];
__host__ __device__ constexpr uint32_t blk(uint32_t lb, uint32_t par) {
    return (lb << 13) | ((((lb) ^ (lb >> 3) ^ (lb >> 4) ^ (lb >> 6) ^ par) & 1) << 12);
}
__host__ __device__ constexpr uint32_t lb_x2(uint32_t h) { return (h & 1) | ((h >> 1) << 3); }
__host__ __device__ constexpr uint32_t mem_row(uint32_t kh, uint32_t b, uint32_t r) { return blk(128 | b, kh) + r * 1024; }
__device__ __forceinline__ uint32_t mem_slot(uint32_t s) { return ((s & 1) << 15) | ((s & 2) << 17); }
constexpr uint32_t CNT1 = 0x3d80, CNT_ALL = 0x4000;
constexpr uint32_t LB_PROBE = 6 | 64, LB_TIME = 6;
__host__ __device__ constexpr uint32_t lb_tok(uint32_t h) { return (h & 1) | ((h >> 1) << 3); }
__device__ float g_mod[6 * DM];
__device__ __align__(1024) bf16 g_himg[(S_ + 32) * DM];
__device__ __align__(1024) bf16 g_O[S_ * NH * DH];
__device__ __align__(1024) bf16 g_y[S_ * DM];
__device__ __align__(1024) bf16 g_g[S_ * DM];
__device__ __align__(1024) bf16 g_x1[S_ * DM];
__device__ __align__(16) float g_st[4 * S_ * 2];
__device__ float g_vec[3 * DM + FF];
__device__ float g_cst[8];
__device__ uint32_t g_pcnt[2 * 32 * 8], g_pflag[7 * 32 * 8];
__device__ __align__(1024) bf16 g_u[S_ * FF];

#define TL(i) {}
#define TLC(i) {}
__device__ __forceinline__ uint32_t smem_u32(const void* p) { return (uint32_t)__cvta_generic_to_shared(p); }
__device__ __forceinline__ void spin_guard(int it) {
    asm volatile("{.reg .pred p; setp.gt.s32 p, %0, %1; @p st.global.u32 [%2], %0;}" ::"r"(it), "n"(SPIN_LIMIT), "l"(1ull));
}
__device__ __forceinline__ void wg_fence() { asm volatile("wgmma.fence.sync.aligned;" ::: "memory"); }
__device__ __forceinline__ void wg_commit() { asm volatile("wgmma.commit_group.sync.aligned;" ::: "memory"); }
template <int N> __device__ __forceinline__ void wg_wait() { asm volatile("wgmma.wait_group.sync.aligned %0;" ::"n"(N) : "memory"); }
__host__ __device__ constexpr uint64_t mkdesc(uint32_t addr, uint32_t lbo, uint32_t sbo, uint32_t swz) {
    return (uint64_t)((addr & 0x3FFFF) >> 4) | ((uint64_t)(lbo >> 4) << 16) | ((uint64_t)(sbo >> 4) << 32) | ((uint64_t)swz << 62);
}
__device__ __forceinline__ uint64_t dadd(uint64_t d, uint32_t o) { return (d & 0xffffffff00000000ull) | (uint32_t)((uint32_t)d + o); }
__device__ __forceinline__ void mbar_init(uint32_t b, uint32_t c) { asm volatile("mbarrier.init.shared.b64 [%0], %1;" ::"r"(b), "r"(c) : "memory"); }
__device__ __forceinline__ void mbar_expect(uint32_t b, uint32_t tx) { asm volatile("mbarrier.arrive.expect_tx.shared.b64 _, [%0], %1;" ::"r"(b), "r"(tx) : "memory"); }
__device__ __forceinline__ void mbar_arrive(uint32_t b) { asm volatile("mbarrier.arrive.shared.b64 _, [%0];" ::"r"(b) : "memory"); }
__device__ __forceinline__ void mbar_arrive_cluster(uint32_t b, uint32_t cta) {
    asm volatile("{.reg .b32 r; mapa.shared::cluster.u32 r, %0, %1; mbarrier.arrive.shared::cluster.b64 _, [r];}" ::"r"(b), "r"(cta) : "memory");
}
__device__ __forceinline__ bool mbar_try(uint32_t b, uint32_t par) {
    uint32_t ok;
    asm volatile("{.reg .pred p; mbarrier.try_wait.parity.shared.b64 p, [%1], %2; selp.u32 %0, 1, 0, p;}" : "=r"(ok) : "r"(b), "r"(par) : "memory");
    return ok;
}
__device__ __forceinline__ void mbar_wait(uint32_t b, uint32_t par) {
    int it = 0;
#pragma unroll 1
    while (!mbar_try(b, par)) { spin_guard(++it); }
}
__device__ __forceinline__ void mbar_wait_w(uint32_t b, uint32_t par) {
    int it = 0;
    bool ok;
#pragma unroll 1
    do { ok = __all_sync(~0u, mbar_try(b, par)); spin_guard(++it); } while (!ok);
}
__device__ __forceinline__ void mbar_wait_cluster(uint32_t b, uint32_t par) {
    int it = 0;
    while (true) {
        uint32_t ok;
        asm volatile("{.reg .pred p; mbarrier.try_wait.parity.acquire.cluster.shared::cta.b64 p, [%1], %2; selp.u32 %0, 1, 0, p;}" : "=r"(ok) : "r"(b), "r"(par) : "memory");
        if (ok) break;
        spin_guard(++it);
    }
}
__device__ __forceinline__ void tma2d(uint32_t dst, const CUtensorMap* m, int c0, int c1, uint32_t bar) {
    asm volatile("cp.async.bulk.tensor.2d.shared::cluster.global.mbarrier::complete_tx::bytes [%0], [%1, {%3, %4}], [%2];" ::"r"(dst), "l"(m), "r"(bar), "r"(c0), "r"(c1) : "memory");
}
#define EVF 1
constexpr uint64_t EVICT_FIRST = 0x12F0000000000000ull;
__device__ __forceinline__ void tma2d_once(uint32_t dst, const CUtensorMap* m, int c0, int c1, uint32_t bar) {
    if (!EVF) { tma2d(dst, m, c0, c1, bar); return; }
    asm volatile("cp.async.bulk.tensor.2d.shared::cluster.global.mbarrier::complete_tx::bytes.L2::cache_hint [%0], [%1, {%3, %4}], [%2], %5;" ::"r"(dst), "l"(m), "r"(bar), "r"(c0), "r"(c1), "l"(EVICT_FIRST) : "memory");
}
__device__ __forceinline__ void tma2d_mc(uint32_t dst, const CUtensorMap* m, int c0, int c1, uint32_t bar, uint16_t mask) {
    asm volatile("cp.async.bulk.tensor.2d.shared::cluster.global.mbarrier::complete_tx::bytes.multicast::cluster [%0], [%1, {%3, %4}], [%2], %5;" ::"r"(dst), "l"(m), "r"(bar), "r"(c0), "r"(c1), "h"(mask) : "memory");
}
__device__ __forceinline__ void bulk_g2s(uint32_t dst, const void* src, uint32_t bytes, uint32_t bar) {
    asm volatile("cp.async.bulk.shared::cluster.global.mbarrier::complete_tx::bytes [%0], [%1], %2, [%3];" ::"r"(dst), "l"(src), "r"(bytes), "r"(bar) : "memory");
}
__device__ __forceinline__ void bar_sync(int id, int n) { asm volatile("bar.sync %0, %1;" ::"r"(id), "r"(n) : "memory"); }
__device__ __forceinline__ void bar_arrive(int id, int n) { asm volatile("bar.arrive %0, %1;" ::"r"(id), "r"(n) : "memory"); }
__device__ __forceinline__ void cluster_sync_all() { asm volatile("barrier.cluster.arrive.aligned; barrier.cluster.wait.aligned;" ::: "memory"); }
__device__ __forceinline__ void fence_async_smem() { asm volatile("fence.proxy.async.shared::cta;" ::: "memory"); }
__device__ __forceinline__ void ldsm4t(uint32_t* r, uint32_t a) {
    asm volatile("ldmatrix.sync.aligned.m8n8.x4.trans.shared.b16 {%0,%1,%2,%3}, [%4];" : "=r"(r[0]), "=r"(r[1]), "=r"(r[2]), "=r"(r[3]) : "r"(a) : "memory");
}
__device__ __forceinline__ void ldsm4(uint32_t* r, uint32_t a) {
    asm volatile("ldmatrix.sync.aligned.m8n8.x4.shared.b16 {%0,%1,%2,%3}, [%4];" : "=r"(r[0]), "=r"(r[1]), "=r"(r[2]), "=r"(r[3]) : "r"(a) : "memory");
}
__device__ __forceinline__ uint32_t movm(uint32_t a) {
    uint32_t d; asm volatile("movmatrix.sync.aligned.m8n8.trans.b16 %0, %1;" : "=r"(d) : "r"(a)); return d;
}
__device__ __forceinline__ void mma16816(float* d, uint32_t a0, uint32_t a1, uint32_t a2, uint32_t a3, uint32_t b0, uint32_t b1) {
    asm volatile("mma.sync.aligned.m16n8k16.row.col.f32.bf16.bf16.f32 {%0,%1,%2,%3},{%4,%5,%6,%7},{%8,%9},{%0,%1,%2,%3};"
                 : "+f"(d[0]), "+f"(d[1]), "+f"(d[2]), "+f"(d[3]) : "r"(a0), "r"(a1), "r"(a2), "r"(a3), "r"(b0), "r"(b1));
}
__device__ __forceinline__ void mma16816z(float* d, const uint32_t* a, uint32_t b0, uint32_t b1) {
    asm volatile("mma.sync.aligned.m16n8k16.row.col.f32.bf16.bf16.f32 {%0,%1,%2,%3},{%4,%5,%6,%7},{%8,%9},{%10,%10,%10,%10};"
                 : "=f"(d[0]), "=f"(d[1]), "=f"(d[2]), "=f"(d[3]) : "r"(a[0]), "r"(a[1]), "r"(a[2]), "r"(a[3]), "r"(b0), "r"(b1), "f"(0.f));
}
__device__ __forceinline__ void mma1688(float* d, uint32_t a0, uint32_t a1, uint32_t b0) {
    asm volatile("mma.sync.aligned.m16n8k8.row.col.f32.bf16.bf16.f32 {%0,%1,%2,%3},{%4,%5},{%6},{%0,%1,%2,%3};"
                 : "+f"(d[0]), "+f"(d[1]), "+f"(d[2]), "+f"(d[3]) : "r"(a0), "r"(a1), "r"(b0));
}
__device__ __forceinline__ uint32_t pack2(float lo, float hi) {
    uint32_t r; asm("cvt.rn.bf16x2.f32 %0, %1, %2;" : "=r"(r) : "f"(hi), "f"(lo)); return r;
}
__device__ __forceinline__ uint32_t hadd2(uint32_t a, uint32_t b) {
    uint32_t r; asm("add.rn.bf16x2 %0, %1, %2;" : "=r"(r) : "r"(a), "r"(b)); return r;
}
__device__ __forceinline__ float bflo(uint32_t u) { return __uint_as_float(u << 16); }
__device__ __forceinline__ float bfhi(uint32_t u) { return __uint_as_float(u & 0xffff0000u); }
__device__ __forceinline__ float ex2(float x) { float r; asm("ex2.approx.ftz.f32 %0, %1;" : "=f"(r) : "f"(x)); return r; }
__device__ __forceinline__ uint4 ldg_rlx4(const void* p) {
    uint4 v; asm volatile("ld.relaxed.gpu.global.v4.u32 {%0,%1,%2,%3}, [%4];" : "=r"(v.x), "=r"(v.y), "=r"(v.z), "=r"(v.w) : "l"(p) : "memory"); return v;
}
__device__ __forceinline__ uint2 ldg_rlx2(const void* p) {
    unsigned long long v; asm volatile("ld.relaxed.gpu.global.b64 %0, [%1];" : "=l"(v) : "l"(p) : "memory");
    return make_uint2((uint32_t)v, (uint32_t)(v >> 32));
}
__device__ __forceinline__ uint32_t ldg_rlx1(const void* p) {
    uint32_t v; asm volatile("ld.relaxed.gpu.global.u32 %0, [%1];" : "=r"(v) : "l"(p) : "memory"); return v;
}
__device__ __forceinline__ void stg_rlx1(void* p, uint32_t v) { asm volatile("st.relaxed.gpu.global.u32 [%0], %1;" ::"l"(p), "r"(v) : "memory"); }
__device__ __forceinline__ void stg_rlx2(void* p, uint32_t x, uint32_t y) {
    unsigned long long v = (unsigned long long)x | ((unsigned long long)y << 32);
    asm volatile("st.relaxed.gpu.global.b64 [%0], %1;" ::"l"(p), "l"(v) : "memory");
}
__device__ __forceinline__ void stg_rlx4(void* p, uint32_t x, uint32_t y, uint32_t z, uint32_t w) {
    asm volatile("st.relaxed.gpu.global.v4.u32 [%0], {%1,%2,%3,%4};" ::"l"(p), "r"(x), "r"(y), "r"(z), "r"(w) : "memory");
}
__device__ __forceinline__ void sts4(uint32_t a, uint32_t x, uint32_t y, uint32_t z, uint32_t w) {
    asm volatile("st.shared.v4.u32 [%0], {%1,%2,%3,%4};" ::"r"(a), "r"(x), "r"(y), "r"(z), "r"(w) : "memory");
}
__device__ __forceinline__ uint4 lds4(uint32_t a) {
    uint4 v; asm volatile("ld.shared.v4.u32 {%0,%1,%2,%3}, [%4];" : "=r"(v.x), "=r"(v.y), "=r"(v.z), "=r"(v.w) : "r"(a) : "memory"); return v;
}
__device__ __forceinline__ void st_async4(uint32_t a, float x, float y, float z, float w, uint32_t bar) {
    asm volatile("st.async.shared::cluster.mbarrier::complete_tx::bytes.v4.f32 [%0], {%1,%2,%3,%4}, [%5];" ::"r"(a), "f"(x), "f"(y), "f"(z), "f"(w), "r"(bar) : "memory");
}
#define F4(d, i) "+f"(d[i]), "+f"(d[i + 1]), "+f"(d[i + 2]), "+f"(d[i + 3])
__device__ __forceinline__ void wgmma_rs32(float* d, const uint32_t* a, uint64_t b, int sc) {
    asm volatile("{.reg .pred p; setp.ne.b32 p, %21, 0;\n wgmma.mma_async.sync.aligned.m64n32k16.f32.bf16.bf16 {%0,%1,%2,%3,%4,%5,%6,%7,%8,%9,%10,%11,%12,%13,%14,%15}, {%16,%17,%18,%19}, %20, p, 1, 1, 0;}"
                 : F4(d, 0), F4(d, 4), F4(d, 8), F4(d, 12) : "r"(a[0]), "r"(a[1]), "r"(a[2]), "r"(a[3]), "l"(b), "r"(sc));
}
__device__ __forceinline__ void wgmma_ss32(float* d, uint64_t a, uint64_t b, int sc) {
    asm volatile("{.reg .pred p; setp.ne.b32 p, %18, 0;\n wgmma.mma_async.sync.aligned.m64n32k16.f32.bf16.bf16 {%0,%1,%2,%3,%4,%5,%6,%7,%8,%9,%10,%11,%12,%13,%14,%15}, %16, %17, p, 1, 1, 1, 0;}"
                 : F4(d, 0), F4(d, 4), F4(d, 8), F4(d, 12) : "l"(a), "l"(b), "r"(sc));
}
__device__ __forceinline__ void wgmma_rs40(float* d, const uint32_t* a, uint64_t b, int sc) {
    asm volatile("{.reg .pred p; setp.ne.b32 p, %25, 0;\n wgmma.mma_async.sync.aligned.m64n40k16.f32.bf16.bf16 {%0,%1,%2,%3,%4,%5,%6,%7,%8,%9,%10,%11,%12,%13,%14,%15,%16,%17,%18,%19}, {%20,%21,%22,%23}, %24, p, 1, 1, 0;}"
                 : F4(d, 0), F4(d, 4), F4(d, 8), F4(d, 12), F4(d, 16) : "r"(a[0]), "r"(a[1]), "r"(a[2]), "r"(a[3]), "l"(b), "r"(sc));
}
__device__ __forceinline__ void wgmma_ss40(float* d, uint64_t a, uint64_t b, int sc) {
    asm volatile("{.reg .pred p; setp.ne.b32 p, %22, 0;\n wgmma.mma_async.sync.aligned.m64n40k16.f32.bf16.bf16 {%0,%1,%2,%3,%4,%5,%6,%7,%8,%9,%10,%11,%12,%13,%14,%15,%16,%17,%18,%19}, %20, %21, p, 1, 1, 1, 0;}"
                 : F4(d, 0), F4(d, 4), F4(d, 8), F4(d, 12), F4(d, 16) : "l"(a), "l"(b), "r"(sc));
}
#define F16(d, i) F4(d, i), F4(d, i + 4), F4(d, i + 8), F4(d, i + 12)
template <int TA>
__device__ __forceinline__ void wgmma_ss128(float* d, uint64_t a, uint64_t b, int sc) {
    asm volatile("{.reg .pred p; setp.ne.b32 p, %66, 0;\n wgmma.mma_async.sync.aligned.m64n128k16.f32.bf16.bf16 "
                 "{%0,%1,%2,%3,%4,%5,%6,%7,%8,%9,%10,%11,%12,%13,%14,%15,%16,%17,%18,%19,%20,%21,%22,%23,%24,%25,%26,%27,%28,%29,%30,%31,"
                 "%32,%33,%34,%35,%36,%37,%38,%39,%40,%41,%42,%43,%44,%45,%46,%47,%48,%49,%50,%51,%52,%53,%54,%55,%56,%57,%58,%59,%60,%61,%62,%63}, %64, %65, p, 1, 1, %67, 1;}"
                 : F16(d, 0), F16(d, 16), F16(d, 32), F16(d, 48) : "l"(a), "l"(b), "r"(sc), "n"(TA));
}

__device__ __forceinline__ float warp_sum(float v) {
#pragma unroll
    for (int o = 16; o; o >>= 1) v += __shfl_xor_sync(~0u, v, o);
    return v;
}
__device__ __forceinline__ float bfround(float x) { return __bfloat162float(__float2bfloat16(x)); }

__device__ __forceinline__ void wait_count1(const uint32_t* p, uint32_t target) {
    int it = 0;
#pragma unroll 1
    while (true) {
        uint32_t v;
        asm volatile("ld.acquire.gpu.global.u32 %0, [%1];" : "=r"(v) : "l"(p) : "memory");
        if (v >= target) break;
        spin_guard(++it);
    }
}
__device__ __forceinline__ void red2(float* p, float a, float b) {
    asm volatile("red.relaxed.gpu.global.add.v2.f32 [%0], {%1, %2};" ::"l"(p), "f"(a), "f"(b) : "memory");
}
__device__ __forceinline__ void l2_prefetch(const void* p, uint32_t bytes) {
    asm volatile("cp.async.bulk.prefetch.L2.global [%0], %1;" ::"l"(p), "r"(bytes) : "memory");
}
__device__ __forceinline__ void signal_count(uint32_t* p) { asm volatile("red.release.gpu.global.add.u32 [%0], 1;" ::"l"(p) : "memory"); }
__device__ __forceinline__ void e_expect(uint32_t b, uint32_t tx) {
    asm volatile("{.reg .pred p; elect.sync _|p, 0xffffffff; @p mbarrier.arrive.expect_tx.shared.b64 _, [%0], %1;}" ::"r"(b), "r"(tx) : "memory");
}
__device__ __forceinline__ void e_tma2d(uint32_t dst, const CUtensorMap* m, int c0, int c1, uint32_t bar) {
    asm volatile("{.reg .pred p; elect.sync _|p, 0xffffffff;\n @p cp.async.bulk.tensor.2d.shared::cluster.global.mbarrier::complete_tx::bytes [%0], [%1, {%3, %4}], [%2];}"
                 ::"r"(dst), "l"(m), "r"(bar), "r"(c0), "r"(c1) : "memory");
}
__device__ __forceinline__ void e_tma2d_hint(uint32_t dst, const CUtensorMap* m, int c0, int c1, uint32_t bar, uint64_t pol) {
    asm volatile("{.reg .pred p; elect.sync _|p, 0xffffffff;\n @p cp.async.bulk.tensor.2d.shared::cluster.global.mbarrier::complete_tx::bytes.L2::cache_hint [%0], [%1, {%3, %4}], [%2], %5;}"
                 ::"r"(dst), "l"(m), "r"(bar), "r"(c0), "r"(c1), "l"(pol) : "memory");
}
__device__ __forceinline__ void e_tma2d_mc(uint32_t dst, const CUtensorMap* m, int c0, int c1, uint32_t bar) {
    asm volatile("{.reg .pred p; elect.sync _|p, 0xffffffff;\n @p cp.async.bulk.tensor.2d.shared::cluster.global.mbarrier::complete_tx::bytes.multicast::cluster [%0], [%1, {%3, %4}], [%2], %5;}"
                 ::"r"(dst), "l"(m), "r"(bar), "r"(c0), "r"(c1), "h"((uint16_t)3) : "memory");
}
__device__ __forceinline__ void e_prefetch(const void* p, uint32_t bytes) {
    asm volatile("{.reg .pred p; elect.sync _|p, 0xffffffff; @p cp.async.bulk.prefetch.L2.global [%0], %1;}" ::"l"(p), "r"(bytes) : "memory");
}
__device__ __forceinline__ void wait_count_w(const uint32_t* p, uint32_t target) {
    int it = 0;
#pragma unroll 1
    while (true) {
        uint32_t v;
        asm volatile("ld.acquire.gpu.global.u32 %0, [%1];" : "=r"(v) : "l"(p) : "memory");
        if (__all_sync(~0u, v >= target)) break;
        spin_guard(++it);
    }
}

__device__ __forceinline__ void ln_row(float* x) {
    float s = 0;
#pragma unroll
    for (int i = 0; i < 32; i++) s += x[i];
    float m = warp_sum(s) * (1.0f / DM);
    float q = 0;
#pragma unroll
    for (int i = 0; i < 32; i++) { x[i] -= m; q += x[i] * x[i]; }
    float r = rsqrtf(warp_sum(q) * (1.0f / DM) + 1e-5f);
#pragma unroll
    for (int i = 0; i < 32; i++) x[i] *= r;
}
__device__ __forceinline__ uint4 pack8(const float* x) {
    return make_uint4(pack2(x[0], x[1]), pack2(x[2], x[3]), pack2(x[4], x[5]), pack2(x[6], x[7]));
}
#define NL 6
constexpr uint32_t SM_HB = 16384, HBK = 5120, SM_SX = 57344, SM_OX = 122880, SM_PX = 124928, SM_PA = 126976, SM_WO = 147456,
                   SM_TAB = 212992, SM_PRE = SM_TAB, SM_BAR = 227328, SM_REC_TOTAL = 227328 + 256;
constexpr uint32_t SB0 = 1024;
constexpr int B_WO = 0, B_HE = 1, B_ROLE = 2, B_HB = 3, B_W = 5;
constexpr int NB_MEM = 1, NB_QK = 2, NB_X1 = 3, NB_X2 = 4, NB_WIN = 5, NB_WG = 6, NB_KDONE = 7, NB_FIN0 = 8, NB_P = 9, NB_PX = 10, NB_G = 11, NB_A = 12, NB_B = 13, NB_C = 14, NB_S = 15;
#define D_TPV 100
#define V_POS 2
#define D_X2 470
#define D_TV 50
#define D_V 390
#define D_NEAR 1670
#define D_FAR (D_NEAR - 140)
#define E_MUL 28
#define D_WF 60
#define NE 0
#define D_H 0
#define D_W2 170
#define SETTLE 0
#define TV_POS 1
#define D_PA 0
#define NE1 10
#define H_POS 3
#define PA_POS 1
#define K_DLY 0
#define ST_BAR 1
#define W1_AT -1
#define ROT 2
#define ALIGN 0
#define CNT32 0
#define O_POS 1
#define Z_POS 0
#define QF_LATE 100
#define W0_E 3
#define G_AT 24
#define W0_AT 4
#define W0_RS (NL - 1)
#define P_GATE 0
#define NPF (NL + 6)

struct Delays { uint32_t near, far, x2, v, w2, pa, wf, tv; };
#define MISS(i, v)
#define MISS_INIT
#define MISS_OUT
#define HT(i)
#define PROF_INIT
#define PROF(i)
#define PROFV(i, v)
#define PROF_OUT

__device__ __forceinline__ uint32_t clk32() { uint32_t t; asm volatile("mov.u32 %0, %%clock;" : "=r"(t) :: "memory"); return t; }
__device__ __forceinline__ uint32_t smid() { uint32_t t; asm volatile("mov.u32 %0, %%smid;" : "=r"(t)); return t; }
__device__ __forceinline__ uint32_t gtime() { uint32_t t; asm volatile("mov.u32 %0, %%globaltimer_lo;" : "=r"(t) :: "memory"); return t; }
__device__ __forceinline__ void spin_until(uint32_t t0, uint32_t d) { while (clk32() - t0 < d) {} }
template <int N> __device__ __forceinline__ uint32_t delay(uint32_t zero) {
    float x = __uint_as_float(clk32());
#pragma unroll
    for (int i = 0; i < N; i++) asm volatile("ex2.approx.ftz.f32 %0, %0;" : "+f"(x));
    return __float_as_uint(x) & zero;
}
__device__ __forceinline__ uint32_t opaque(uint32_t v) { return __shfl_sync(~0u, v, threadIdx.x & 31); }
__device__ __forceinline__ uint32_t xor_or(uint32_t a, uint32_t b, uint32_t t) {
    uint32_t r; asm volatile("lop3.b32 %0, %1, %2, %3, 0x7E;" : "=r"(r) : "r"(a), "r"(b), "r"(t)); return r;
}
__device__ __forceinline__ uint32_t or3(uint32_t a, uint32_t b, uint32_t c) {
    uint32_t r; asm volatile("lop3.b32 %0, %1, %2, %3, 0xFE;" : "=r"(r) : "r"(a), "r"(b), "r"(c)); return r;
}
__device__ __forceinline__ uint32_t settag(uint32_t v, uint32_t tag) {
    uint32_t r; asm("lop3.b32 %0, %1, 1, %2, 0xB8;" : "=r"(r) : "r"(v), "r"(tag)); return r;
}
__device__ __forceinline__ void ldg4_if(uint4& v, const void* p, bool c) {
    asm volatile("{.reg .pred p; setp.ne.u32 p, %5, 0; @p ld.relaxed.gpu.global.v4.u32 {%0,%1,%2,%3}, [%4];}"
                 : "+r"(v.x), "+r"(v.y), "+r"(v.z), "+r"(v.w) : "l"(p), "r"((uint32_t)c) : "memory");
}
__device__ __forceinline__ uint4 ldg_rlx2x2(const void* p) {
    unsigned long long a, b;
    asm volatile("ld.relaxed.gpu.global.v2.b64 {%0,%1}, [%2];" : "=l"(a), "=l"(b) : "l"(p) : "memory");
    return make_uint4((uint32_t)a, (uint32_t)(a >> 32), (uint32_t)b, (uint32_t)(b >> 32));
}
__device__ __forceinline__ void stg_rlx2x2(void* p, uint32_t x, uint32_t y, uint32_t z, uint32_t w) {
    asm volatile("{.reg .b64 a, b; mov.b64 a, {%1,%2}; mov.b64 b, {%3,%4}; st.relaxed.gpu.global.v2.b64 [%0], {a, b};}" ::"l"(p), "r"(x), "r"(y), "r"(z), "r"(w) : "memory");
}
__device__ __forceinline__ void ldg1_if(uint32_t& v, const void* p, bool c) {
    asm volatile("{.reg .pred p; setp.ne.u32 p, %2, 0; @p ld.relaxed.gpu.global.u32 %0, [%1];}" : "+r"(v) : "l"(p), "r"((uint32_t)c) : "memory");
}
__device__ __forceinline__ void sts2(uint32_t a, float x, float y) { asm volatile("st.shared.v2.f32 [%0], {%1,%2};" ::"r"(a), "f"(x), "f"(y) : "memory"); }
__device__ __forceinline__ void sts4f(uint32_t a, float x, float y, float z, float w) {
    asm volatile("st.shared.v4.f32 [%0], {%1,%2,%3,%4};" ::"r"(a), "f"(x), "f"(y), "f"(z), "f"(w) : "memory");
}
__device__ __forceinline__ void sts1(uint32_t a, uint32_t x) { asm volatile("st.shared.u32 [%0], %1;" ::"r"(a), "r"(x) : "memory"); }
__device__ __forceinline__ uint32_t lds1(uint32_t a) { uint32_t v; asm volatile("ld.shared.u32 %0, [%1];" : "=r"(v) : "r"(a) : "memory"); return v; }
__device__ __forceinline__ float4 lds4f(uint32_t a) {
    float4 v; asm volatile("ld.shared.v4.f32 {%0,%1,%2,%3}, [%4];" : "=f"(v.x), "=f"(v.y), "=f"(v.z), "=f"(v.w) : "r"(a) : "memory"); return v;
}
__device__ __forceinline__ float2 lds2f(uint32_t a) {
    float2 v; asm volatile("ld.shared.v2.f32 {%0,%1}, [%2];" : "=f"(v.x), "=f"(v.y) : "r"(a) : "memory"); return v;
}
__device__ __forceinline__ bool any_bit0(uint32_t x) {
    uint32_t r;
    asm volatile("{.reg .pred p, q; .reg .b32 t; and.b32 t, %1, 1; setp.ne.u32 p, t, 0; vote.sync.any.pred q, p, 0xffffffff; selp.u32 %0, 1, 0, q;}" : "=r"(r) : "r"(x));
    return r;
}
__device__ __forceinline__ float rcp_fast(float x) { float r; asm("rcp.approx.ftz.f32 %0, %1;" : "=f"(r) : "f"(x)); return r; }
__device__ __forceinline__ void stsm4(uint32_t a, uint32_t r0, uint32_t r1, uint32_t r2, uint32_t r3) {
    asm volatile("stmatrix.sync.aligned.m8n8.x4.shared.b16 [%0], {%1,%2,%3,%4};" ::"r"(a), "r"(r0), "r"(r1), "r"(r2), "r"(r3) : "memory");
}
__device__ __forceinline__ void stsm4t(uint32_t a, uint32_t r0, uint32_t r1, uint32_t r2, uint32_t r3) {
    asm volatile("stmatrix.sync.aligned.m8n8.x4.trans.shared.b16 [%0], {%1,%2,%3,%4};" ::"r"(a), "r"(r0), "r"(r1), "r"(r2), "r"(r3) : "memory");
}
__device__ __forceinline__ uint32_t and3(uint32_t a, uint32_t b, uint32_t c) {
    uint32_t r; asm("lop3.b32 %0, %1, %2, %3, 0x80;" : "=r"(r) : "r"(a), "r"(b), "r"(c)); return r;
}
__device__ __forceinline__ void red_mem(void* p, uint32_t x, uint32_t y, uint32_t z, uint32_t w, void* q, uint32_t e, bool c) {
    asm volatile("{.reg .pred p; setp.ne.u32 p, %7, 0; red.relaxed.gpu.global.add.noftz.v4.bf16x2 [%0], {%1,%2,%3,%4}; @p red.relaxed.gpu.global.add.noftz.bf16x2 [%5], %6;}"
                 ::"l"(p), "r"(x), "r"(y), "r"(z), "r"(w), "l"(q), "r"(e), "r"((uint32_t)c) : "memory");
}
__device__ __forceinline__ void stg4_if(bool c, void* p, uint32_t x) {
    asm volatile("{.reg .pred p; setp.ne.u32 p, %2, 0; @p st.relaxed.gpu.global.v4.u32 [%0], {%1,%1,%1,%1};}" ::"l"(p), "r"(x), "r"((uint32_t)c) : "memory");
}
__device__ __forceinline__ uint32_t max3u(uint32_t a, uint32_t b, uint32_t c) { return __vimax3_u32(a, b, c); }
__device__ __forceinline__ void fence_gpu() { asm volatile("fence.acq_rel.gpu;" ::: "memory"); }

__device__ __forceinline__ void h_load(uint32_t sb, const uint8_t* hsrc, int pass, uint32_t rank, uint32_t rot) {
    const uint8_t* src = hsrc + (size_t)pass * 65536;
    const uint32_t bar = sb + SM_BAR + 8 * (B_HB + (pass & 1)), dst = sb + SM_HB + (pass & 1) * 65536 + rank * 4 * HBK;
    e_expect(bar, 32768);
#pragma unroll 1
    for (int i = 0; i < H_PIECES; i++) {
        const uint32_t o = ((i + rot) & (H_PIECES - 1)) * (16384 / H_PIECES);
        asm volatile("{.reg .pred p; elect.sync _|p, 0xffffffff;\n"
                     " @p cp.async.bulk.shared::cluster.global.mbarrier::complete_tx::bytes.multicast::cluster [%0], [%1], %4, [%2], %3;}"
                     ::"r"(dst + o + (o >> 12) * 1024), "l"(src + o), "r"(bar), "h"((uint16_t)3), "n"(16384 / H_PIECES) : "memory");
    }
}
__device__ __forceinline__ void h_piece(uint32_t sb, const uint8_t* hsrc, int pass, uint32_t rank, uint32_t i, bool first) {
    const uint32_t bar = sb + SM_BAR + 8 * (B_HB + (pass & 1));
    asm volatile("{.reg .pred p, q; elect.sync _|p, 0xffffffff; setp.le.and.s32 p, %5, 64, p; setp.ne.and.u32 q, %4, 0, p;\n"
                 " @q mbarrier.arrive.expect_tx.shared.b64 _, [%2], 32768;\n"
                 " @p cp.async.bulk.shared::cluster.global.mbarrier::complete_tx::bytes.multicast::cluster [%0], [%1], 4096, [%2], %3;}"
                 ::"r"(sb + SM_HB + (pass & 1) * 65536 + (rank * 4 + i) * HBK), "l"(hsrc + (uint32_t)(pass * 65536 + i * 4096)), "r"(bar), "h"((uint16_t)3), "r"((uint32_t)first), "r"(pass) : "memory");
}
__device__ __forceinline__ uint4 ldg_b128(const void* p) {
    uint4 v;
    asm volatile("{.reg .b128 t; .reg .b64 a, b; ld.relaxed.gpu.global.b128 t, [%4]; mov.b128 {a, b}, t; mov.b64 {%0,%1}, a; mov.b64 {%2,%3}, b;}"
                 : "=r"(v.x), "=r"(v.y), "=r"(v.z), "=r"(v.w) : "l"(p) : "memory");
    return v;
}
__device__ __forceinline__ void ldg_b128_into(uint4& v, const void* p) {
    asm volatile("{.reg .b128 t; .reg .b64 a, b; ld.relaxed.gpu.global.b128 t, [%4]; mov.b128 {a, b}, t; mov.b64 {%0,%1}, a; mov.b64 {%2,%3}, b;}"
                 : "+r"(v.x), "+r"(v.y), "+r"(v.z), "+r"(v.w) : "l"(p) : "memory");
}
__device__ __forceinline__ void stg_b128_if(bool c, void* p, uint32_t x, uint32_t y, uint32_t z, uint32_t w) {
    asm volatile("{.reg .pred p; setp.ne.u32 p, %5, 0; @p st.relaxed.gpu.global.v4.u32 [%0], {%1,%2,%3,%4};}"
                 ::"l"(p), "r"(x), "r"(y), "r"(z), "r"(w), "r"((uint32_t)c) : "memory");
}
__device__ __forceinline__ float pretag(float x, uint32_t add, uint32_t keep) { return __uint_as_float((__float_as_uint(x) + add) & keep); }

template <class F, class G>
__device__ __forceinline__ void softmax_rows(uint32_t src, uint32_t dst, uint32_t g16, int row0, F ready, G mid) {
    const uint32_t u = (g16 >> 7) & 3, e = ((g16 >> 9) << 3) | ((g16 >> 4) & 7);
    uint32_t se = src + e * 8, su = se + u * 1088, d0 = dst + e * 16 + u * 4, d1 = dst + 512 + e * 4;
    int vis = row0 + (e >> 2) - 2 * (e & 3) - 8 * u;
    asm volatile("" : "+r"(se), "+r"(su), "+r"(d0), "+r"(d1), "+r"(vis));
    ready();
    const float2 p0 = lds2f(su), p1 = lds2f(su + 256), p2 = lds2f(su + 512), p3 = lds2f(su + 768);
    const float2 m0 = lds2f(se + 4352), m1 = lds2f(se + 4352 + 256), m2 = lds2f(se + 4352 + 512), m3 = lds2f(se + 4352 + 768);
    float a0 = (p0.x + p1.x) + (p2.x + p3.x), a1 = (p0.y + p1.y) + (p2.y + p3.y);
    const float a2 = (m0.x + m1.x) + (m2.x + m3.x), a3 = (m0.y + m1.y) + (m2.y + m3.y);
    if (vis < 0) a0 = -1e9f / 0.08838834764831845f;
    if (vis < 1) a1 = -1e9f / 0.08838834764831845f;
    int k = __float_as_int(fmaxf(fmaxf(a0, a1), fmaxf(a2, a3)));
    k ^= (k >> 31) & 0x7fffffff;
    const bool hi = g16 & 64;
    const int k0 = __reduce_max_sync(~0u, hi ? INT_MIN : k), k1 = __reduce_max_sync(~0u, hi ? k : INT_MIN);
    mid();
    k = hi ? k1 : k0;
    const float m = __int_as_float(k ^ ((k >> 31) & 0x7fffffff));
    const float sl2 = 0.08838834764831845f * 1.4426950408889634f, mb = -m * sl2;
    sts1(d0, pack2(ex2(fmaf(a0, sl2, mb)), ex2(fmaf(a1, sl2, mb))));
    sts1(d1, pack2(ex2(fmaf(a2, sl2, mb)), ex2(fmaf(a3, sl2, mb))));
}

__device__ __forceinline__ uint32_t pack_h2(float lo, float hi) {
    uint32_t r; asm("cvt.rn.satfinite.f16x2.f32 %0, %1, %2;" : "=r"(r) : "f"(hi), "f"(lo)); return r;
}
__device__ __forceinline__ float2 unpack_h2(uint32_t u) {
    float2 r; asm("{.reg .b16 l, h; mov.b32 {l, h}, %2; cvt.f32.f16 %0, l; cvt.f32.f16 %1, h;}" : "=f"(r.x), "=f"(r.y) : "r"(u)); return r;
}
__device__ __forceinline__ uint32_t add_h2(uint32_t a, uint32_t b) { uint32_t r; asm("add.rn.f16x2 %0, %1, %2;" : "=r"(r) : "r"(a), "r"(b)); return r; }
__device__ __forceinline__ uint32_t max_h2(uint32_t a, uint32_t b) { uint32_t r; asm("max.f16x2 %0, %1, %2;" : "=r"(r) : "r"(a), "r"(b)); return r; }
__device__ __forceinline__ void stg2_if(bool c, void* p, uint32_t x, uint32_t y) {
    asm volatile("{.reg .pred p; .reg .b64 v; setp.ne.u32 p, %3, 0; mov.b64 v, {%1, %2}; @p st.relaxed.gpu.global.b64 [%0], v;}" ::"l"(p), "r"(x), "r"(y), "r"((uint32_t)c) : "memory");
}
__device__ __forceinline__ void stg1_if(bool c, void* p, uint32_t x) {
    asm volatile("{.reg .pred p; setp.ne.u32 p, %2, 0; @p st.relaxed.gpu.global.u32 [%0], %1;}" ::"l"(p), "r"(x), "r"((uint32_t)c) : "memory");
}
struct U2 { uint32_t x, y; };
__device__ __forceinline__ U2 ldg_u2(const void* p) {
    U2 v; asm volatile("{.reg .b64 t; ld.relaxed.gpu.global.b64 t, [%2]; mov.b64 {%0, %1}, t;}" : "=r"(v.x), "=r"(v.y) : "l"(p) : "memory"); return v;
}
constexpr int POLL_LIMIT = 1 << 16;
constexpr float SM_L2E = 0.08838834764831845f * 1.4426950408889634f;
template <int V> struct IC { static constexpr int value = V; };
typedef unsigned long long u64;
__device__ __forceinline__ uint32_t lo32(u64 v) { return (uint32_t)v; }
__device__ __forceinline__ uint32_t hi32(u64 v) { return (uint32_t)(v >> 32); }
__device__ __forceinline__ u64 ldg_u64(const void* p) { u64 v; asm volatile("ld.relaxed.gpu.global.b64 %0, [%1];" : "=l"(v) : "l"(p) : "memory"); return v; }
__device__ __forceinline__ void ldg_u64_if(u64& v, const void* p, bool c) {
    asm volatile("{.reg .pred p; setp.ne.u32 p, %2, 0; @p ld.relaxed.gpu.global.b64 %0, [%1];}" : "+l"(v) : "l"(p), "r"((uint32_t)c) : "memory");
}
__device__ __forceinline__ void rec_main(uint32_t sb, const CUtensorMap* tWo, uint8_t* arena, int role, int hinfo, int wg, uint32_t zero, const Delays& dly) {
    const int hA = hinfo & 255;
    const int tid = threadIdx.x, t = tid & 127, lane = tid & 31, wi = t >> 5;
    const uint32_t bars = sb + SM_BAR;
    const int head = role >> 2, qd = role & 3, j = blockIdx.x & 1, kh = role & 1;
    const uint32_t mypar = head >= hA;
    const bool warp0 = __all_sync(~0u, wi == 0), warp1 = __all_sync(~0u, wi == 1);
    const uint8_t* hsrc = (const uint8_t*)g_himg + kh * 32768 + j * 16384;
    auto tokbase = [&](int ty) { return ((ty + 1) << 21) + blk(lb_tok(head), mypar ^ ((hinfo >> (8 + ty)) & 1)); };
    const uint32_t tbw = tokbase(wg), tbq = tokbase(0) + (qd >> 1) * 2048 + (qd & 1) * 8;
    uint32_t w[32 - NL][4];
    const uint32_t frow = ((lane >> 4) * 8 + (lane & 7)) * 128, fx = ((lane >> 3) & 1) ^ (lane & 7);
    const uint32_t wl0 = sb + wg * 65536 + frow + ((fx ^ (2 * wi)) << 4);
    {
#pragma unroll 1
        for (int i = 0; i < 4; i++) mbar_wait_w(bars + 8 * (B_W + (wg == 2 ? 8 + i : 2 * i + wg)), 0);
#pragma unroll
        for (int p = NL; p < 32; p++) ldsm4t(w[p - NL], wl0 + p * 2048);
        fence_async_smem();
        if (wg < 2) bar_sync(NB_WG, 256);
        if (wg > 0) wait_count_w(&g_tick[32 + (lane & 3) * 8], 1);
        if (wg == 1 && warp0) {
            if (lane == 0) mbar_arrive_cluster(bars + 8 * B_HE, j ^ 1);
            asm volatile("fence.proxy.async.global;" ::: "memory");
            mbar_wait_w(bars + 8 * B_HE, 0);
#pragma unroll 1
            for (int i = 0; i < 2; i++) h_load(sb, hsrc, i, j, head);
        }
        TL(3 + wg)
    }
    uint32_t g16 = opaque(t * 16);
    auto G16 = [&]() { asm volatile("" : "+r"(g16)); return g16; };
    const uint32_t wu = __reduce_max_sync(~0u, wi), sbl = sb - wu * 512;
    const uint32_t xso = blk(lb_x2(head), mypar), cu = kh * 2048 + (2 * j + (wu >> 1)) * 512;
    const uint32_t u_xo = xso + wg * 16384 + (wu & 1) * 2048 + (cu >> 1) - wu * 256, u_to = tbw + (wu & 1) * 16384 + cu - wu * 512;
    const uint32_t mrow = wg < 2 ? mem_row(wu >> 1, wg * 2 + (wu & 1), qd) : mem_row(kh, wu, 0);
    const uint32_t u_m = mrow - wu * 512, u_e = mrow + 512 - wu * (CNT32 ? 64 : 128);
#define TAB(i) lds1(sb + SM_TAB + (i) * 512 + (G16() >> 2))
    {
        const uint32_t r8 = lane & 7;
        bar_sync(NB_X2, 384);
        if (wg == 0 && lane == 0) {
            mbar_expect(bars + 8 * B_WO, 16384);
            tma2d(sb + SM_WO + wi * 16384, tWo, (wi >> 1) * 512 + qd * 128 + (wi & 1) * 64, head * DH, bars + 8 * B_WO);
            tma2d(sb + SM_WO + wi * 16384 + 8192, tWo, (wi >> 1) * 512 + qd * 128 + (wi & 1) * 64, head * DH + 64, bars + 8 * B_WO);
        }
        __syncwarp();
        const uint32_t tb = sb + SM_TAB + wg * 1536 + t * 4, ma = sb + SM_HB + 4096 + r8 * 128;
        if (wg < 2) {
            sts1(tb, sb + SM_WO + wi * 16384 + frow + ((fx ^ (2 * wg)) << 4));
            sts1(tb + 512, wl0);
            sts1(tb + 1024, ma + (((lane >> 3) ^ r8) << 4));
        } else {
            sts1(tb, ma + (wi & 1) * HBK + ((((wi & 2) + (lane >> 4) * 4 + ((lane >> 3) & 1)) ^ r8) << 4));
            sts1(tb + 512, ((((wi & 2) + 5) ^ r8) << 4) + ((CNT32 ? (lane & 3) == 3 : lane & 1) ? ma + ((wi & 1) + (lane >> 3) * 2) * HBK : sb + SM_HB - 128));
            sts1(tb + 1024, mem_row(role >> 6, (role >> 4) & 3, (role >> 2) & 3) + (lane < 8 ? qd * 128 + lane * 16 : 512 + qd * 32 + (lane & 1) * 16));
        }
    }
    PROF_INIT
    MISS_INIT
#define HB(ks) dadd(mkdesc(SB0 + SM_HB + ((ks) >> 2) * HBK + ((ks) & 3) * 32, 16, 1024, 1), hbo)
#define STEP_CONSTS                                                                                  \
    const uint32_t tag = (s & 1) ^ 1, ttag = ((s >> 1) & 1) ^ 1, tso = (s & 1) * 32768;              \
    G16();                            \
    const int p = s + 2, b = p & 1;                                                                  \
    uint32_t hbo = b * 4096, fz[5] = {0, 0, 0, 0, 0};                                                \
    const uint32_t ftag = (((p - 1) >> 1) & 1) ^ 1, ptag = ((p >> 1) & 1) ^ 1;                       \
    const uint32_t pso = tbw + (1 << 20) + (b ^ 1) * 32768 + j * 16384 + kh * 2048;
#define SCHED_FENCE(i) fz[i] = clk32();
#define FZ ((fz[0] | fz[1] | fz[2] | fz[3] | fz[4]) & zero)
#define BLOCK_FENCE asm volatile("pmevent 0;" ::: "memory");
    constexpr int GAP = 32 / NL;
#define l16 (sbl + g16)
#define g8 (g16 >> 1)
    uint4 u, v;
    uint8_t *pdst, *fdst;
    auto tok_pack = [&](int ty, const float* acc, uint32_t ftag, uint32_t ptag, bool later = false) {
        const bool tg = ty == 2 || !(g16 & 64);
        const uint32_t add = tg ? (ftag ^ 1) << 16 : 0u, keep = tg ? 0xfffe0000u : ~0u;
        const uint32_t add1 = ty == 2 ? 0u : add, keep1 = ty == 2 ? ~0u : keep;
        const uint32_t add2 = ty == 0 ? add : 0u, keep2 = ty == 0 ? keep : ~0u;
        v = {pack2(pretag(acc[0], add, keep), pretag(acc[1], add1, keep1)), pack2(acc[2], acc[3]),
             pack2(pretag(acc[4], add2, keep2), pretag(acc[5], add2, keep2)), pack2(acc[6], acc[7])};
        if (ty < 2) { v.x = movm(v.x); v.z = movm(v.z); v.y = movm(v.y); v.w = movm(v.w); }
        u = {pack2(pretag(acc[8], (ptag ^ 1) << 16, 0xfffe0000u), acc[9]) | ptag, pack2(acc[10], acc[11]), pack2(acc[12], acc[13]), pack2(acc[14], acc[15])};
        if (later) return;
        v.x = settag(v.x, ftag);
        if (ty == 0) v.z = settag(v.z, ftag);
    };

#pragma unroll 1
    for (int s = -2; s < 0; s++) {
        STEP_CONSTS
        (void)tag; (void)ttag; (void)tso; (void)fz;
        float acc[16];
        mbar_wait_w(bars + 8 * (B_HB + b), 0);
        wg_fence();
#pragma unroll
        for (int i = 0; i < 32; i++) {
            if (i < NL) wgmma_ss32(acc, dadd(mkdesc(SB0 + i * 2048, 8192, 1024, 1), wg * 4096), HB(i), i != 0);
            else wgmma_rs32(acc, w[i < NL ? 0 : i - NL], HB(i), 1);
        }
        wg_commit();
        uint4 pa;
        int it = 0;
#pragma unroll 1
        do pa = ldg_b128(arena + (pso + g16)); while ((p > 0) & any_bit0(pa.x ^ ftag) & (++it < POLL_LIMIT));
        pdst = arena + ((pso ^ (32768 + 2048)) + G16());
        fdst = arena + ((b ^ 1) * 32768 + u_to + g16);
        wg_wait<0>();
#pragma unroll
        for (int k = 0; k < 4; k++) { acc[2 * k] += bflo((&pa.x)[k]); acc[2 * k + 1] += bfhi((&pa.x)[k]); }
        tok_pack(wg, acc, ftag, ptag);
        stg_b128_if(true, pdst, u.x, u.y, u.z, u.w);
        stg_b128_if(p > 0, fdst, v.x, v.y, v.z, v.w);
        if (p == 0) {
            TL(2)
            bar_sync(NB_MEM, 384);
            if (wg == 1 && warp0) {
                if (g16 == 0) mbar_arrive_cluster(bars + 8 * B_HE, j ^ 1);
                mbar_wait_w(bars + 8 * B_HE, 1);
                h_load(sb, hsrc, 2, j, head);
            }
        }
    }

    auto qk_loop = [&](auto wgc) {
        constexpr int WG = decltype(wgc)::value;
        uint32_t w0[NL][4], lm0;
        auto w0_load = [&]() {
            const uint32_t wl = TAB(WG * 3 + 1);
            lm0 = TAB(WG * 3 + 2);
#pragma unroll
            for (int k = 0; k < NL; k++) ldsm4t(w0[k], wl + k * 2048);
        };
        const uint32_t wlo = WG * 65536 - SM_WO - wu * 16384, wlx = __reduce_max_sync(~0u, (wi ^ WG) << 5);
        uint32_t tq0, lm, lm1;
        auto proj_pre = [&](int s) {
            uint32_t wz0 = zero;
#pragma unroll
            for (int k = 0; k < NL; k += 2) wz0 = and3(wz0, w0[k][0], w0[k + 1 < NL ? k + 1 : k][0]);
            lm = lm0 + (s & 1) * 65536 + wz0; lm1 = lm ^ 64;
            asm volatile("" : "+r"(lm), "+r"(lm1));
        };
        auto proj = [&](int s, auto mid) {
            bar_sync(NB_MEM, 384);
            float c[4][4];
            uint32_t bf[16][4];
#pragma unroll
            for (int it = 0; it < 3; it++) ldsm4(bf[it], (it & 1 ? lm1 : lm) + (it >> 1) * HBK);
            mid(-1);
#pragma unroll
            for (int it = 0; it < 16; it++) {
                const uint32_t* bfr = bf[it];
                if (it + 3 < 16) ldsm4(bf[it + 3 < 16 ? it + 3 : 0], (it & 1 ? lm : lm1) + ((it + 3) >> 1) * HBK);
                const uint32_t* wa = 2 * it < NL ? w0[2 * it < NL ? 2 * it : 0] : w[2 * it < NL ? 0 : 2 * it - NL];
                const uint32_t* wb = 2 * it + 1 < NL ? w0[2 * it + 1 < NL ? 2 * it + 1 : 0] : w[2 * it + 1 < NL ? 0 : 2 * it + 1 - NL];
                float *ca = c[(2 * it) & 3], *cb = c[(2 * it + 1) & 3];
                if (it < 2) { mma16816z(ca, wa, bfr[0], bfr[1]); mma16816z(cb, wb, bfr[2], bfr[3]); }
                else { mma16816(ca, wa[0], wa[1], wa[2], wa[3], bfr[0], bfr[1]); mma16816(cb, wb[0], wb[1], wb[2], wb[3], bfr[2], bfr[3]); }
                mid(it);
            }
            const uint32_t xo = u_xo + (G16() >> 1);
            float r[4];
#pragma unroll
            for (int e = 0; e < 4; e++) {
                constexpr float SH = SM_L2E / 64;
                r[e] = WG ? (c[0][e] + c[1][e]) + (c[2][e] + c[3][e]) : fmaf(c[2][e] + c[3][e], SH, (c[0][e] + c[1][e]) * SH);
            }
            const uint32_t r0 = pack2(r[0], r[1]), r1 = pack2(r[2], r[3]);
            const uint32_t m0 = movm(r0), m1 = movm(r1);
            tq0 = clk32();
            bar_arrive(NB_QK, 384);
            stg_rlx2(arena + xo, settag(m0, (s & 1) ^ 1), m1);
        };
        w0_load();
        proj_pre(0);
        if (WG == 1 || !ROT) bar_sync(NB_P, ROT ? 256 : 384);
        proj(0, [](int) {});
#pragma unroll 1
        for (int s = 0;; s++) {
            STEP_CONSTS
            uint4 pa;
            float acc[16];
            auto acc_init = [&]() {
#pragma unroll
                for (int k = 0; k < 4; k++) { acc[2 * k] = bflo((&pa.x)[k]); acc[2 * k + 1] = bfhi((&pa.x)[k]); acc[8 + 2 * k] = __uint_as_float((&pa.x)[k] & zero); acc[9 + 2 * k] = __uint_as_float(~(&pa.x)[k] & zero); }
            };
            uint32_t wf[NPF][4], a3;
#define WF(f) ((a3 ^ (((f) & 1) * 64)) + ((f) >> 1) * 2048)
            if (WG == 1) {
                float sc[5][4];
                uint32_t sx0 = sb + SM_SX - wu * (2560 - 16) + G16() * 5;
                asm volatile("" : "+r"(sx0));
                int it = 0;
                bool bad;
#pragma unroll 1
                do {
                    uint4 kf[2][2];
                    U2 qf[2], x[8];
                    const uint32_t gz = g16 | (it & zero);
                    const uint8_t *ts = arena + (tso + tbw + gz), *tq = arena + (tso + tbq + gz), *xp = arena + (xso + (gz >> 1));
#pragma unroll
                    for (int a = 0; a < 4; a++) kf[a >> 1][a & 1] = ldg_b128(ts + (a >> 1) * 16384 + (a & 1) * 2048);
                    if (QF_LATE) spin_until(tq0, dly.x2 - QF_LATE);
#pragma unroll
                    for (int a = 0; a < 2; a++) qf[a] = ldg_u2(tq + a * 16384);
                    spin_until(tq0, dly.x2);
#pragma unroll
                    for (int i = 0; i < 8; i++) x[i] = ldg_u2(xp + (i >> 2) * 16384 + (i & 3) * 1024);
                    PROF(8)
                    const uint32_t q0[4] = {hadd2(x[0].x, x[1].x), qf[0].x, hadd2(x[0].y, x[1].y), qf[0].y};
                    const uint32_t q1[4] = {hadd2(x[2].x, x[3].x), qf[1].x, hadd2(x[2].y, x[3].y), qf[1].y};
                    PROFV(7, clk32() + (q0[0] & zero))
                    const uint32_t bt = ((qf[0].x ^ ttag) | (qf[1].x ^ ttag)) | ((kf[0][0].x ^ ttag) | (kf[0][1].x ^ ttag)) | ((kf[1][0].x ^ ttag) | (kf[1][1].x ^ ttag));
                    uint32_t bx = 0;
#pragma unroll
                    for (int i = 0; i < 8; i += 2) bx |= (x[i].x ^ tag) | (x[i + 1].x ^ tag);
                    mma16816z(sc[0], q0, kf[0][0].x, kf[0][0].y);
                    mma16816z(sc[1], q0, kf[0][0].z, kf[0][0].w);
                    mma16816z(sc[2], q0, kf[0][1].x, kf[0][1].y);
                    mma16816z(sc[3], q0, kf[0][1].z, kf[0][1].w);
                    mma16816z(sc[4], q0, hadd2(x[4].x, x[5].x), hadd2(x[4].y, x[5].y));
                    bad = any_bit0((XP & 8 ? bt & zero : bt) | bx) & (++it < POLL_LIMIT);
                    mma16816(sc[0], q1[0], q1[1], q1[2], q1[3], kf[1][0].x, kf[1][0].y);
                    mma16816(sc[1], q1[0], q1[1], q1[2], q1[3], kf[1][0].z, kf[1][0].w);
                    mma16816(sc[2], q1[0], q1[1], q1[2], q1[3], kf[1][1].x, kf[1][1].y);
                    mma16816(sc[3], q1[0], q1[1], q1[2], q1[3], kf[1][1].z, kf[1][1].w);
                    mma16816(sc[4], q1[0], q1[1], q1[2], q1[3], hadd2(x[6].x, x[7].x), hadd2(x[6].y, x[7].y));
                } while (bad);
                PROFV(13, it - 1) MISS(1, it - 1)
                sts4(sx0, pack_h2(sc[0][0], sc[0][1]), pack_h2(sc[1][0], sc[1][1]), pack_h2(sc[2][0], sc[2][1]), pack_h2(sc[3][0], sc[3][1]));
                sts1(sx0 + 64 - wu * 12, pack_h2(sc[4][0], sc[4][1]));
                bar_arrive(NB_X1, 384);
#pragma unroll
                for (int n = 0; n < 5; n++) sts2(sb + SM_SX + 2560 + g8 + n * 1088, sc[n][2], sc[n][3]);
                PROF(3)
                a3 = TAB(WG * 3);
                softmax_rows(sb + SM_SX + 2560, sb + SM_PX + 1024, g16 | (clk32() & zero), qd * 8, [&]() { BLOCK_FENCE bar_sync(NB_PX, 128); }, [&]() {
                    BLOCK_FENCE
#pragma unroll
                    for (int f = 0; f < NE1; f++) ldsm4t(wf[f], WF(f));
                    BLOCK_FENCE
                });
                PROF(4)
            } else {
                a3 = TAB(WG * 3);
                if (warp1 && (H_POS == 4 ? (s & 3) == 0 : (s & 3) < 2)) asm volatile("fence.proxy.async.global;" ::: "memory");
                spin_until(tq0, dly.pa);
                uint4 x, y;
                int it = 0;
#pragma unroll 1
                do { x = ldg_b128(arena + (pso + g16)); y = ldg_b128(arena + (pso + tokbase(1) - tokbase(0) + g16)); }
                while (!(XP & 8) & (p <= NSEG) & any_bit0(xor_or(x.x, y.x, ftag)) & (++it < POLL_LIMIT));
                sts4(sb + SM_PA + g16, x.x, x.y, x.z, x.w);
                sts4(sb + SM_PA + 2048 + g16, y.x, y.y, y.z, y.w);
                if (NE) spin_until(tq0, dly.wf);
#pragma unroll
                for (int f = 0; f < NE; f++) ldsm4t(wf[f], WF(f));
                bar_sync(NB_X1, 384);
                if (E_MUL && g16 < 32) asm volatile("red.relaxed.gpu.global.max.u32 [%0], %1; red.relaxed.gpu.global.add.u32 [%0+4], 1;"
                                                    ::"l"(arena + ((blk(LB_TIME, 0) ^ (g16 << 8)) + qd * 1024 + (tq0 & zero))), "r"(gtime()) : "memory");
                __syncwarp();
                const uint32_t tx = clk32();
                if (H_POS == 2 && !(XP & 1) && warp1 && s + 3 <= NSEG) h_load(sb, hsrc, s + 3, j, head);
                spin_until(tx, dly.w2);
            }
#pragma unroll
            for (int f = WG ? NE1 : NE; f < NPF; f++) ldsm4t(wf[f], WF(f));
            PROF(5)
            if (s + 1 == NSEG) { bar_arrive(NB_X2, 384); break; }
            const uint32_t oa = l16 + SM_OX, slot = mem_slot(s + 1);
            float c[4][4];
            uint32_t ob[4][4];
            uint32_t wz = zero;
#pragma unroll
            for (int f = 0; f < NPF; f += 2) wz = and3(wz, wf[f][0], wf[f + 1 < NPF ? f + 1 : f][0]);
            BLOCK_FENCE
            bar_sync(NB_X2 + (SETTLE ? wz : 0), 384);
            ldsm4t(ob[0], oa);
            ldsm4t(ob[1], oa + 512);
            SCHED_FENCE(0)
#pragma unroll
            for (int f = 0; f < 16; f++) {
                const uint32_t *a = wf[f % NPF], *o = ob[f >> 2] + (f & 2);
                if (f < 4) mma16816z(c[f], a, o[0], o[1]);
                else mma16816(c[f & 3], a[0], a[1], a[2], a[3], o[0], o[1]);
                if (f == 3) ldsm4t(ob[2], oa + 1024);
                if (f == 5) { ldsm4t(ob[3], oa + 1536); if (NPF < 16) ldsm4t(wf[0], WF(NPF)); }
                if (f == 7) {
#pragma unroll
                    for (int k = NPF + 1; k < 16; k++) ldsm4t(wf[k - NPF], WF(k));
                }
                if (f == 3 || f == 5 || f == 7) SCHED_FENCE(f / 2)
                if (f == 11) {
#pragma unroll
                    for (int k = NL - W0_E; k < NL; k++) ldsm4t(w0[k], (a3 ^ wlx) + wlo + k * 2048);
                    SCHED_FENCE(4)
                }
            }
            const float last = c[1][3] + c[3][3], one = __uint_as_float(CNT1 << 16);
            red_mem(arena + (u_m + slot + G16()), pack2(c[0][0] + c[2][0], c[0][1] + c[2][1]), pack2(c[0][2] + c[2][2], c[0][3] + c[2][3]),
                    pack2(c[1][0] + c[3][0], c[1][1] + c[3][1]), pack2(c[1][2] + c[3][2], CNT32 && !(g16 & 16) ? last : one),
                    arena + (u_e + slot + (CNT32 ? (g16 >> 3) & ~3u : g16 >> 2)), pack2(one, last), !CNT32 || (g16 & 16));
            hbo += FZ;
            PROF(6)
            constexpr int NS = WG && W0_E < 0 ? NL : NL - W0_RS, GS = (32 - NL + NS) / NS;
            if (W0_E >= 0) {
                BLOCK_FENCE
#pragma unroll
                for (int k = NL - W0_E - 1; k >= 0; k--) ldsm4t(w0[k], (a3 ^ wlx) + wlo + k * 2048);
                lm0 = TAB(WG * 3 + 2);
                if (WG == 1) pa = lds4(sb + SM_PA + 2048 + g16);
            }
            if (WG == 0) {
                bar_arrive(NB_WIN, 384);
                if (W0_E < 0) spin_until(clk32(), dly.tv);
                pa = lds4(sb + SM_PA + g16);
                if (W0_E < 0) w0_load();
                acc_init();
                asm volatile("" : F16(acc, 0));
                BLOCK_FENCE
            }
            if (WG == 1 && K_DLY) spin_until(clk32(), dly.wf);
            wg_fence();
            bar_sync(WG ? NB_WIN : NB_B, WG ? 384 : 256);
#pragma unroll
            for (int i = 0; i < 32; i++) {
                const int k = i / GS;
                if (i >= 32 - NL + NS) wgmma_rs32(acc, w0[i < 32 - NL + NS ? 0 : i - 32 + NL], HB(i - 32 + NL), 1);
                else if (i % GS == GS - 1 && k < NS) wgmma_ss32(acc, mkdesc(SB0 + WG * 65536 + k * 2048, 8192, 1024, 1), HB(k), 1);
                else wgmma_rs32(acc, w[i - (k < NS ? k : NS)], HB(NL + i - (k < NS ? k : NS)), WG == 0 || i);
                if (WG == 1 && i == G_AT) bar_arrive(NB_B, 256);
                if (WG == 1 && i == W1_AT) w0_load();
            }
            wg_commit();
            BLOCK_FENCE
            if (WG == 1 && warp0 && (s & 3) == (H_POS == 4 ? 3 : 0)) wait_count_w(&g_tick[32 + ((G16() >> 4) & 3) * 8], min((s + 1) / 4 + 2, 16));
            if (WG == 1 && W0_E < 0) { pa = lds4(sb + SM_PA + 2048 + g16); if (W1_AT < 0) w0_load(); }
            auto tok_store = [&](int m) {
                if (m & 1) stg_b128_if(XP & 8 ? s == 99 : true, arena + ((b ^ 1) * 32768 + u_to + G16()), v.x, v.y, v.z, v.w);
                if (m & 2) stg_b128_if(XP & 8 ? s == 99 : p < NSEG, arena + ((pso ^ (32768 + 2048)) + G16()), u.x, u.y, u.z, u.w);
            };
            if (WG == 0) proj_pre(s + 1);
            BLOCK_FENCE
            wg_wait<0>();
            if (WG == 0 && ROT) {
                asm volatile("" : F16(acc, 0));
                proj(s + 1, [&](int it) {
                    if (it < 0) {
                        SCHED_FENCE(0)
                        asm volatile("" : F16(acc, 0));
                        tok_pack(WG, acc, ftag, ptag, true);
                        tok_store(2);
                        SCHED_FENCE(1)
                    }
                    if (it == ROT) { SCHED_FENCE(2) v.x = settag(v.x, ftag); v.z = settag(v.z, ftag); tok_store(1); SCHED_FENCE(3) }
                });
                tq0 += (fz[0] | fz[1] | fz[2] | fz[3]) & zero;
            } else {
                if (WG == 1) {
#pragma unroll
                    for (int k = 0; k < 4; k++) { acc[2 * k] += bflo((&pa.x)[k]); acc[2 * k + 1] += bfhi((&pa.x)[k]); }
                }
                tok_pack(WG, acc, ftag, ptag);
                if (WG == 1) proj_pre(s + 1);
                asm volatile("" : "+r"(u.x), "+r"(u.y), "+r"(u.z), "+r"(u.w), "+r"(v.x), "+r"(v.y), "+r"(v.z), "+r"(v.w));
                BLOCK_FENCE
                bar_sync(NB_P, ROT ? 256 : 384);
                tok_store(3);
                proj(s + 1, [](int) {});
            }
        }
    };
    if (wg == 0) {
        qk_loop(IC<0>());
    } else if (wg == 1) {
        qk_loop(IC<1>());
    } else {
        const uint32_t ONES = 0x3f803f80u, u_o = qd * 65536 + head * 2048 + wu * 384;
        uint32_t tw = 0, dl = 0, dm = 0, dst0, dx0;
        dst0 = TAB(6); dx0 = TAB(7);
        uint32_t ov[4] = {0, 0, 0, 0};
        auto o_store = [&](int s) {
            uint8_t* od = (uint8_t*)g_O + (uint32_t)(s * (32 * NH * DH * 2) + u_o + (G16() >> 2));
#pragma unroll
            for (int a = 0; a < 4; a++) stg_rlx1(od + a * 128, ov[a]);
        };
        uint4 vf[2][2], pa;
        auto vf_fetch = [&](int s) {
            const uint8_t* ts = arena + ((s & 1) * 32768 + tbw + g16);
#pragma unroll
            for (int a = 0; a < 4; a++) vf[a >> 1][a & 1] = ldg_b128(ts + (a >> 1) * 16384 + (a & 1) * 2048);
        };
        auto tok_fetch = [&](int s) {
            if (TV_POS != 1) vf_fetch(s);
            pa = ldg_b128(arena + (tbw + (1 << 20) + (~s & 1) * 32768 + j * 16384 + kh * 2048 + g16));
        };
        if (PA_POS) tok_fetch(0);
        TL(9)
        mbar_wait_w(bars + 8 * B_WO, 0);
        if (H_POS == 4 && warp0) { wait_count_w(&g_tick[32 + ((g16 >> 4) & 3) * 8], 2); asm volatile("fence.proxy.async.global;" ::: "memory"); }
        TL(6)
#pragma unroll 1
        for (int s = 0; s < NSEG; s++) {
            STEP_CONSTS
#define VFBAD ((vf[0][0].x ^ ttag) | (vf[0][1].x ^ ttag) | (vf[1][0].x ^ ttag) | (vf[1][1].x ^ ttag))
#define TOKBAD ((TV_POS == 1 ? 0 : VFBAD) | (p <= NSEG ? pa.x ^ ftag : 0))
            {
                const uint32_t dst = dst0 + b * 65536, dx = dx0 + b * 65536;
                const uint8_t *ms = arena + (u_m + mem_slot(s) + g16), *me = arena + (u_e + mem_slot(s) + (CNT32 ? (g16 >> 3) & ~3u : g16 >> 2));
                const uint32_t em = CNT32 && !(g16 & 16) ? ~0u : 0u;
                asm volatile("" : "+l"(ms), "+l"(me));
                spin_until(tw, dl);
                PROF(11)
                int it = 0;
                bool bad;
#pragma unroll 1
                do {
                    uint4 m[4];
                    uint32_t x[4];
#pragma unroll
                    for (int i = 0; i < 4; i++) m[i] = ldg_rlx4(ms + i * 1024);
#pragma unroll
                    for (int i = 0; i < 4; i++) x[i] = ldg_rlx1(me + i * 1024);
#pragma unroll
                    for (int i = 0; i < 3; i++) {
                        stsm4t(dst + i * 2 * HBK, m[i].x, m[i].y, m[i].z, m[i].w);
                        if (i == P_GATE) asm volatile("{.reg .pred p; setp.eq.s32 p, %0, 0; @p bar.arrive %1, %2;}" ::"r"(it), "n"(NB_P), "n"(ROT ? 256 : 384) : "memory");
                    }
                    uint32_t c = and3(m[0].w, m[1].w, m[2].w);
                    SCHED_FENCE(1)
                    stsm4t(dst + 6 * HBK, m[3].x, m[3].y, m[3].z, m[3].w);
                    stsm4t(dx, x[0], x[1], x[2], x[3]);
                    asm volatile("" : "+r"(c));
                    c = and3(and3(((c & m[3].w) | em) >> 16, x[0], x[1]), x[2], x[3]);
                    bad = __any_sync(~0u, !(c & CNT_ALL)) & (++it < POLL_LIMIT);
                    if (H_POS == 4) asm volatile("{.reg .pred p; setp.eq.u32 p, %0, 0; @p bar.sync %1, 384;}" ::"r"((uint32_t)bad), "n"(NB_MEM) : "memory");
                    else if (!ALIGN) asm volatile("{.reg .pred p; setp.eq.u32 p, %0, 0; @p bar.arrive %1, 384;}" ::"r"((uint32_t)bad), "n"(NB_MEM) : "memory");
                } while (bad);
                if (ALIGN) { spin_until(tw, dm); bar_arrive(NB_MEM, 384); }
                PROFV(12, it - 1)
                MISS(0, it - 1) HT(5)
                PROF(8)
            }
            if (s == 1) { TL(7) TLC(0) }
            if (s == 63) TLC(1)
            if (s == 0) TL(13)
            const uint32_t tm = clk32();
            if (H_POS == 4 && g16 == 0) mbar_arrive_cluster(bars + 8 * B_HE, j ^ 1);
            if (O_POS == 1) o_store(max(s - 1, 0));
            if (Z_POS && warp1) stg4_if(g16 < 512 + 160, arena + (TAB(8) + mem_slot(s + 3)), 0);
            fence_async_smem();
            hbo += fz[1] & zero;
            int it = 0;
            if (!PA_POS) tok_fetch(s);
#pragma unroll 1
            while (!(XP & 8) & any_bit0(TOKBAD) & (++it < POLL_LIMIT)) tok_fetch(s + (it & zero));
            float acc[20];
#pragma unroll
            for (int k = 0; k < 4; k++) { acc[2 * k] = bflo((&pa.x)[k]); acc[2 * k + 1] = bfhi((&pa.x)[k]); acc[8 + 2 * k] = acc[9 + 2 * k] = acc[16 + k] = __uint_as_float(pa.x & zero); }
            if (XP & 1 ? s < 1 : p <= NSEG) mbar_wait_w(bars + 8 * (B_HB + b), (p >> 1) & 1);
            if (H_POS == 4 && warp0) {
                mbar_wait_w(bars + 8 * B_HE, s & 1);
                spin_until(tm, dly.wf);
                if (s + 3 <= NSEG) h_load(sb, hsrc, s + 3, j, head);
            }
            asm volatile("" : F16(acc, 0), F4(acc, 16));
            BLOCK_FENCE
            wg_fence();
            bar_sync(NB_QK, 384);
#pragma unroll
            for (int i = 0; i < 32; i++) {
                const int k = i / GAP;
                if (i % GAP == GAP - 1 && k < NL) wgmma_ss40(acc, mkdesc(SB0 + 131072 + k * 2048, 8192, 1024, 1), HB(k), 1);
                else wgmma_rs40(acc, w[i - (k < NL ? k : NL)], HB(NL + i - (k < NL ? k : NL)), 1);
            }
            wg_commit();
            uint8_t* vo = arena + (u_xo + (G16() >> 1));
            pdst = arena + ((pso ^ (32768 + 2048)) + G16());
            fdst = arena + ((b ^ 1) * 32768 + u_to + g16);
            BLOCK_FENCE
            wg_wait<0>();
            PROF(9)
            stg_rlx2(vo, settag(pack2(acc[16], acc[17]), tag), pack2(acc[18], acc[19]));
            const uint32_t tv = clk32();
            if (TV_POS == 1) vf_fetch(s);
            tok_pack(2, acc, ftag, ptag);
            stg_b128_if(XP & 8 ? s == 99 : p <= NSEG, fdst, v.x, v.y, v.z, v.w);
            stg_b128_if(XP & 8 ? s == 99 : p < NSEG, pdst, u.x, u.y, u.z, u.w);
            if (O_POS == 2) o_store(max(s - 1, 0));
            if (ST_BAR) bar_sync(NB_WG, 128);
            PROF(10)
            const uint8_t* xp = arena + (xso + 32768 + (G16() >> 1));
            const uint32_t sxa = sb + SM_SX - wu * 2560 + G16() * 5;
            uint32_t xv[4], gt = 0;
            auto pv = [&](uint32_t p0, uint32_t p1, uint32_t p2, uint32_t p3, uint32_t p4, auto getv, auto done) {
                float oc[2][4], lc[4] = {0.f, 0.f, 0.f, 0.f};
                mma16816(lc, ONES, ONES, ONES, ONES, p0, p1);
                mma16816z(oc[0], &vf[0][0].x, p0, p1);
                mma16816z(oc[1], &vf[1][0].x, p0, p1);
                mma16816(lc, ONES, ONES, ONES, ONES, p2, p3);
                mma16816(oc[0], vf[0][1].x, vf[0][1].y, vf[0][1].z, vf[0][1].w, p2, p3);
                mma16816(oc[1], vf[1][1].x, vf[1][1].y, vf[1][1].z, vf[1][1].w, p2, p3);
                mma1688(lc, ONES, ONES, p4);
                getv();
                mma1688(oc[0], xv[0], xv[1], p4);
                mma1688(oc[1], xv[2], xv[3], p4);
                done(__float_as_uint(oc[0][0]) | __float_as_uint(oc[1][0]) | __float_as_uint(lc[0]));
                const float r0 = rcp_fast(lc[0]), r1 = rcp_fast(lc[1]);
                ov[0] = pack2(oc[0][0] * r0, oc[0][1] * r1); ov[1] = pack2(oc[0][2] * r0, oc[0][3] * r1);
                ov[2] = pack2(oc[1][0] * r0, oc[1][1] * r1); ov[3] = pack2(oc[1][2] * r0, oc[1][3] * r1);
            };
            bool bad;
            it = 0;
#pragma unroll 1
            do {
                U2 xr[4];
                auto load_v = [&]() {
                    if (V_POS < 3) spin_until(tv, dly.v);
#pragma unroll
                    for (int i = 0; i < 4; i++) xr[i] = ldg_u2(xp + i * 1024);
                };
                if (TV_POS == 1 && it) {
                    const uint8_t* tz = arena + (tso + tbw + (g16 | (it & zero)));
#pragma unroll
                    for (int a = 0; a < 4; a++) ldg_b128_into(vf[a >> 1][a & 1], tz + (a >> 1) * 16384 + (a & 1) * 2048);
                }
                if (!V_POS) load_v();
                if (V_POS >= 3) spin_until(tv, dly.v);
                PROF(3)
                asm volatile("{.reg .pred p; setp.eq.s32 p, %0, 0; @p bar.sync %1, 384;}" ::"r"(it), "n"(NB_X1) : "memory");
                uint4 sx[5];
                if (V_POS == 3) load_v();
#pragma unroll
                for (int i = 0; i < 5; i++) sx[i] = lds4(sxa + i * 16);
                if (V_POS == 4) load_v();
                if (it == 0) { gt = gtime(); tw = clk32(); }
                if (V_POS == 2) load_v();
                uint32_t h[5];
#pragma unroll
                for (int n = 0; n < 4; n++) h[n] = add_h2(add_h2((&sx[0].x)[n], (&sx[1].x)[n]), add_h2((&sx[2].x)[n], (&sx[3].x)[n]));
                h[4] = add_h2(add_h2(sx[4].x, sx[4].y), add_h2(sx[4].z, sx[4].w));
                uint32_t hm = max_h2(max_h2(max_h2(h[0], h[1]), h[2]), max_h2(h[3], h[4]));
                hm = max_h2(hm, __byte_perm(hm, hm, 0x1032));
                const uint32_t m1 = __shfl_xor_sync(~0u, hm, 1), m2 = __shfl_xor_sync(~0u, hm, 2), m3 = __shfl_xor_sync(~0u, hm, 3);
                float2 a[5];
#pragma unroll
                for (int n = 0; n < 5; n++) a[n] = unpack_h2(h[n]);
                if (V_POS == 1) load_v(); else SCHED_FENCE(0)
                const float mb = -64.0f * unpack_h2(max_h2(max_h2(hm, m1), max_h2(m2, m3))).x;
                uint32_t pm[5];
#pragma unroll
                for (int n = 0; n < 5; n++) pm[n] = pack2(ex2(fmaf(a[n].x, 64.0f, mb)), ex2(fmaf(a[n].y, 64.0f, mb)));
                pv(pm[0], pm[1], pm[2], pm[3], pm[4], [&]() {
                    xv[0] = hadd2(xr[0].x, xr[1].x); xv[1] = hadd2(xr[0].y, xr[1].y);
                    xv[2] = hadd2(xr[2].x, xr[3].x); xv[3] = hadd2(xr[2].y, xr[3].y);
                }, [](uint32_t) {});
                bad = any_bit0((TV_POS == 1 && !(XP & 8) ? VFBAD : 0) | (xr[0].x ^ tag) | (xr[1].x ^ tag) | (xr[2].x ^ tag) | (xr[3].x ^ tag)) & (++it < POLL_LIMIT);
                stsm4(sb + SM_OX + g16, ov[0], ov[1], ov[2], ov[3]);
            } while (bad);
            PROFV(14, it - 1) MISS(2, it - 1)
            PROF(5)
            bar_sync(NB_X2, 384);
            U2 tv2 = {0, 0};
            const uint8_t* tp = arena + (blk(LB_TIME, mypar) + (((g16 | (tw & zero)) << 6) & 0xc00));
            {
                const uint4 pp = lds4(l16 + SM_PX + 1024);
                const uint32_t p4 = lds1(sb + SM_PX + 512 + 1024 - wu * 128 + (G16() >> 2));
                if (E_MUL) tv2 = ldg_u2(tp);
                if (H_POS == 3 && !(XP & 1) && warp0 && s + 3 <= NSEG) h_load(sb, hsrc, s + 3, j, head);
                if (H_POS == 0 && !(XP & 1)) h_piece(sb, hsrc, s + 3, j, (wu + head) & 3, wu == 0);
                pv(pp.x, pp.y, pp.z, pp.w, p4, []() {}, [&](uint32_t r) { bar_arrive(NB_WIN + ((r | fz[0]) & zero), 384); });
            }
            dst0 = TAB(6); dx0 = TAB(7);
            const uint32_t zo = Z_POS ? 0 : TAB(8);
            PROF(6) HT(7)
            BLOCK_FENCE
            if (H_POS == 1 && !(XP & 1)) h_piece(sb, hsrc, s + 3, j, (wu + head) & 3, wu == 0);
            asm volatile("" : "+r"(tv2.y));
            it = 0;
#pragma unroll 1
            while (E_MUL && __any_sync(~0u, tv2.y < 32 * (s + 1)) & (++it < 16)) tv2 = ldg_u2(tp);
            const uint32_t e = __reduce_max_sync(~0u, tv2.x) - gt;
            MISS(3, it - 1) MISS(4, gt)
            if (PA_POS) tok_fetch(s + 1);
            if (O_POS == 0) o_store(s);
            if (!Z_POS) stg4_if(g16 < 160, arena + (zo + mem_slot(s + 3)), 0);
            dm = e > 4096 ? 0 : e * E_MUL >> 4;
            dl = dm + (ALIGN ? dly.near - dly.wf - (kh == mypar ? 0 : 140) : kh == mypar ? dly.near : dly.far);
            dm += dly.near;
        }
        if (O_POS) o_store(NSEG - 1);
        TL(8)
    }
    PROF_OUT
    MISS_OUT
}

struct RecMaps { CUtensorMap wq, wk, wv, wo, wmod, w3, w1; };
struct RecPtrs { const bf16 *x, *mem0, *c, *wmod, *w1, *w3; uint8_t* arena; uint32_t zero; const bf16 *w2, *w4, *wo; Delays dly; };

__device__ __forceinline__ float silu_bf(const bf16* c, int i) {
    const float v = __bfloat162float(c[i]);
    return bfround(__fdividef(v, 1.0f + __expf(-v)));
}
#define W_LATE 1000
#define W_OPEN 1400
__device__ __forceinline__ void side_window(const uint8_t* arena, uint32_t& n) {
    U2 v;
    int it = 0;
#pragma unroll 1
    while (v = ldg_u2(arena + (LB_TIME << 13)), ((v.y >> 5) == n || gtime() - v.x > W_OPEN + W_LATE) && v.y < 32 * NSEG && ++it < 64) __nanosleep(100);
    n = v.y >> 5;
    it = 0;
#pragma unroll 1
    while ((int)(gtime() - v.x - W_OPEN) < 0 && ++it < 256) {}
}
__device__ __noinline__ void rec_ln(float* coef, const RecPtrs& p, int id, int r0) {
    int r1 = 32;
    const int tid = threadIdx.x;
    const int lane = tid & 31, wid = tid >> 5;
    const uint32_t ring = smem_u32(coef) - SM_PRE + wid * 8192 + lane * 16;
    auto rowof = [&](int j) { return (j >> 1) * 64 + (id * 8 + wid) * 2 + (j & 1); };
    auto fetch = [&](int j) {
        if (j < 2 * r1) {
#pragma unroll
            for (int i = 0; i < 4; i++)
                asm volatile("cp.async.cg.shared.global [%0], [%1], 16;" ::"r"(ring + (j & 3) * 2048 + i * 512), "l"(p.x + (size_t)rowof(j) * DM + i * 256 + lane * 8) : "memory");
        }
        asm volatile("cp.async.commit_group;" ::: "memory");
    };
#pragma unroll 1
    for (int j = 2 * r0; j < 2 * r0 + 4; j++) fetch(j);
#pragma unroll 1
    for (int i = tid; i < 2 * DM / 4; i += 256) {
        uint4 v[8];
        int it = 0;
        uint32_t ok;
        do {
            ok = 1;
#pragma unroll
            for (int k = 0; k < 8; k++) v[k] = ldg_rlx4(g_modp + k * 2 * DM + i * 4);
#pragma unroll
            for (int k = 0; k < 8; k++) ok &= v[k].x & v[k].y & v[k].z & v[k].w;
            spin_guard(++it);
        } while (!ok);
        float t[4] = {0, 0, 0, 0};
#pragma unroll
        for (int k = 0; k < 8; k++) { t[0] += __uint_as_float(v[k].x); t[1] += __uint_as_float(v[k].y); t[2] += __uint_as_float(v[k].z); t[3] += __uint_as_float(v[k].w); }
#pragma unroll
        for (int j = 0; j < 4; j++) coef[i * 4 + j] = bfround(t[j]) + (i >= DM / 4 ? 1.0f : 0.0f);
    }
    bar_sync(NB_FIN0, 256);
    if (r0 == 0) {
        int v, it = 0;
#pragma unroll 1
        do { v = *(volatile int*)((uint8_t*)coef - SM_PRE + SM_BAR + 192); spin_guard(++it); } while (v == INT_MIN);
        if (v >= 0) r1 = 2;
    }
    if (tid == 0 && r0 == 0) TL(2)
#pragma unroll 1
    for (int j = 2 * r0; j < 2 * r1; j++) {
        float x[32];
        asm volatile("cp.async.wait_group 3;" ::: "memory");
#pragma unroll
        for (int i = 0; i < 4; i++) {
            const uint4 v = lds4(ring + (j & 3) * 2048 + i * 512);
            float* d = x + i * 8;
            d[0] = bflo(v.x); d[1] = bfhi(v.x); d[2] = bflo(v.y); d[3] = bfhi(v.y); d[4] = bflo(v.z); d[5] = bfhi(v.z); d[6] = bflo(v.w); d[7] = bfhi(v.w);
        }
        const int row = rowof(j), rr = row & 15;
        ln_row(x);
        fetch(j + 4);
#pragma unroll
        for (int i = 0; i < 4; i++) {
            float y[8];
            const float4* cf = (const float4*)(coef + i * 256 + lane * 8);
            const float4 s0 = cf[0], s1 = cf[1], c0 = cf[256], c1 = cf[257];
            const float sh[8] = {s0.x, s0.y, s0.z, s0.w, s1.x, s1.y, s1.z, s1.w}, sc[8] = {c0.x, c0.y, c0.z, c0.w, c1.x, c1.y, c1.z, c1.w};
#pragma unroll
            for (int e = 0; e < 8; e++) y[e] = fmaf(x[i * 8 + e], sc[e], sh[e]);
            const int own = ((row >> 4) & 1) == (i >> 1), c16 = i * 32 + lane;
            const uint32_t off = ((row >> 5) + own) * 65536 + (c16 >> 3) * 4096 + (rr + (own ? 0 : 16)) * 128 + (((c16 & 7) ^ (rr & 7)) << 4);
            *(uint4*)((uint8_t*)g_himg + off) = pack8(y);
        }
        if ((j & 3) != 3) continue;
        bar_sync(j == 3 ? NB_C : NB_FIN0, j == 3 ? 320 : 256);
        if (wid == 0) {
            if (j == 3) bar_arrive(NB_B, 64);
            if (lane == 0) { if (j == 7) wait_count1(&g_tick[32 + id * 8], 1); signal_count(&g_tick[32 + id * 8]); if (j < 8) TL(13) }
            __syncwarp();
        }
    }
}
#define SIDE_T 300
template <int NQ>
__device__ __forceinline__ void side_gemv(const CUtensorMap* tm, int c0, int k0, int k1, uint32_t cs, uint32_t sb, const uint8_t* arena, uint32_t& n, uint32_t& ph, float (*acc)[8], const uint8_t* xr = nullptr) {
    const uint32_t w = __reduce_max_sync(~0u, threadIdx.x >> 5 & 3), ring = sb + 65536 + w * 24576, bars = sb + SM_BAR + 8 * B_W + w * 24;
#pragma unroll
    for (int q = 0; q < NQ; q++)
#pragma unroll
        for (int j = 0; j < 8; j++) acc[q][j] = 0.f;
#pragma unroll 1
    for (; k0 < k1; k0 += 48, ph ^= 1) {
        const int nr = min(48, k1 - k0);
        side_window(arena, n);
        const uint32_t t0 = clk32();
        if (xr && k0 < 9 * 48) {
#pragma unroll
            for (int i = 0; i < 6; i++) asm volatile("prefetch.global.L2 [%0];" ::"l"(xr + (5 + k0 / 16 + (i >> 1)) * 131072 + (i & 1) * 16384));
        }
#pragma unroll 1
        for (int g = 0; g < 3; g++) {
            spin_until(t0, (g * 4 + w) * (SIDE_T / 4));
            e_expect(bars + 8 * g, g * 16 < nr ? 8192 : 0);
            if (g * 16 < nr) e_tma2d_hint(ring + g * 8192, tm, c0, k0 + g * 16, bars + 8 * g, xr && EVF ? EVICT_FIRST : 0x1000000000000000ull);
        }
#pragma unroll 1
        for (int r = 0; r < nr; r += 16) {
            mbar_wait_w(bars + (r >> 1), ph);
            uint4 v[16];
#pragma unroll
            for (int h = 0; h < 16; h++) v[h] = lds4(ring + (r + h) * 512 + (threadIdx.x & 31) * 16);
            float4 cf[NQ][4];
#pragma unroll
            for (int q = 0; q < NQ * 4; q++) cf[q >> 2][q & 3] = lds4f(cs + ((q >> 2) * DM + k0 + r + (q & 3) * 4) * 4);
#pragma unroll
            for (int h = 0; h < 16; h++) {
                const float f[8] = {bflo(v[h].x), bfhi(v[h].x), bflo(v[h].y), bfhi(v[h].y), bflo(v[h].z), bfhi(v[h].z), bflo(v[h].w), bfhi(v[h].w)};
#pragma unroll
                for (int q = 0; q < NQ; q++)
#pragma unroll
                    for (int j = 0; j < 8; j++) acc[q][j] = fmaf((&cf[q][h >> 2].x)[h & 3], f[j], acc[q][j]);
            }
        }
        fence_async_smem();
        __syncwarp();
    }
}
__device__ __noinline__ void rec_side(float* sm, const RecMaps& mp, const RecPtrs& p, int id) {
    const int tid = threadIdx.x;
    if (tid < 256) {
        if (blockIdx.x < 128) rec_ln(sm + SM_PRE / 4, p, id, 2);
        if (tid == 0) TL(14)
        for (int i = tid; i < 2 * S_; i += 256) g_st[id * 2 * S_ + i] = 0.f;
        if (id == 0 && tid < 64) g_pcnt[tid * 8] = 0;
        if (id == 1) for (int i = tid; i < 6 * 256; i += 256) g_pflag[i] = 0;
        if (id == 2 && tid < 66) {
            const uint2 me = __ldcg(&g_clk[tid]);
            const uint32_t c0 = __ldcg(&g_clk[0].x) - 4096;
            int r = 0;
#pragma unroll 1
            for (int i = 0; i < 66; i++) {
                const uint2 o = __ldcg(&g_clk[i]);
                r += (o.y ^ me.y) < 256 && (o.x - c0 < me.x - c0 || (o.x == me.x && i < tid));
            }
            g_cls[me.y & 255] = g_cls[(me.y ^ 1) & 255] = r < 32 ? (me.y >> 8) * 4 + (r >> 3) : 8;
            if (tid == 0) g_pt = 0;
        }
        bar_sync(NB_FIN0, 256);
        if (PDL && tid == 0) asm volatile("fence.acq_rel.gpu; griddepcontrol.launch_dependents;" ::: "memory");
        return;
    }
    const int t = tid - 256;
    float *coef = sm + 40960, *red = coef + 3 * DM;
    const uint32_t sb = smem_u32(sm), cs = smem_u32(coef);
    uint32_t n = 0, ph = 0;
    for (int i = t; i < DM; i += 128) { coef[i] = silu_bf(p.c, i); coef[2 * DM + i] = 1.0f; }
    if (t == 0) wait_count1(&g_tick[32 + id * 8], 2);
    bar_sync(NB_G, 128);
    const int w = __reduce_max_sync(~0u, t >> 5);
    float acc[3][8];
    side_gemv<1>(&mp.wmod, (2 + id) * DM + w * 256, 0, DM, cs, sb, p.arena, n, ph, acc, (const uint8_t*)p.x + id * 32768 + t * 128);
#pragma unroll
    for (int j = 0; j < 8; j++) g_mod[(2 + id) * DM + t * 8 + j] = bfround(acc[0][j]);
    bar_sync(NB_G, 128);
    if (t == 0) signal_count(&g_tick[8]);
    side_gemv<1>(&mp.w3, id * (FF / 4) + w * 256, 0, DM, cs + 8 * DM, sb, p.arena, n, ph, acc);
    if (t < FF / 32) {
#pragma unroll
        for (int j = 0; j < 8; j++) g_vec[3 * DM + id * (FF / 4) + t * 8 + j] = acc[0][j];
    }
    if (t == 0) wait_count1(&g_tick[8], 4);
    bar_sync(NB_G, 128);
    for (int i = t; i < DM; i += 128) { coef[i] = 1.0f + __ldcg(g_mod + 4 * DM + i); coef[DM + i] = __ldcg(g_mod + 3 * DM + i); }
    bar_sync(NB_G, 128);
    if (id == 1 && t < 32) {
        float u[5] = {0, 0, 0, 0, 0};
        for (int i = t; i < DM; i += 32) {
            const float a = coef[i], b = coef[DM + i];
            u[0] += a; u[1] += a * a; u[2] += a * b; u[3] += b; u[4] += b * b;
        }
#pragma unroll
        for (int q = 0; q < 5; q++) { const float r = warp_sum(u[q]); if (t == 0) g_cst[q] = r * (1.0f / DM); }
    }
    side_gemv<3>(&mp.w1, id * 256, w * 256, w * 256 + 256, cs, sb, p.arena, n, ph, acc);
#pragma unroll
    for (int q = 0; q < 3; q++)
#pragma unroll
        for (int j = 0; j < 8; j++) red[((t >> 5) * 3 + q) * 256 + (t & 31) * 8 + j] = acc[q][j];
    bar_sync(NB_G, 128);
    for (int i = t; i < 768; i += 128) g_vec[(i >> 8) * DM + id * 256 + (i & 255)] = (red[i] + red[768 + i]) + (red[1536 + i] + red[2304 + i]);
    if (t == 0) TL(9)
}

__global__ void __cluster_dims__(2, 1, 1) __launch_bounds__(384, 1)
k_rec(const __grid_constant__ RecMaps mp, const __grid_constant__ RecPtrs p) {
    extern __shared__ uint8_t smraw[];
    const uint32_t sb = smem_u32(smraw);
    if ((sb & 0x3FFFF) != SB0) __trap();
    const uint32_t bars = sb + SM_BAR;
    const int tid = threadIdx.x, lane = tid & 31, b = blockIdx.x;
    const int wid = __reduce_max_sync(~0u, tid >> 5);
    const uint32_t rank = b & 1;
    uint8_t* arena = p.arena;
    volatile int* sinfo = (volatile int*)(smraw + SM_BAR + 192);
    if (tid == 0) TL(0)
    if (tid == 0) sinfo[0] = INT_MIN;
    if (tid == 352) {
        for (int i = 0; i < 17; i++) mbar_init(bars + 8 * i, i == B_WO ? 4 : 1);
        asm volatile("fence.mbarrier_init.release.cluster;" ::: "memory");
        mbar_expect(bars + 8 * B_ROLE, 8);

    }
    __syncwarp();
    asm volatile("barrier.cluster.arrive.relaxed.aligned;" ::: "memory");
    int pr = 0, hA = 0;
    if (wid < 8) {
        if (b < 128) {
            const int cb = (b & 15) * 128, k0 = (b >> 4) * 128 + (tid >> 4);
            uint4 v[8];
#pragma unroll
            for (int i = 0; i < 8; i++) v[i] = __ldg((const uint4*)(p.wmod + (size_t)(k0 + 16 * i) * (6 * DM) + cb + (tid & 15) * 8));
            float acc[8] = {0, 0, 0, 0, 0, 0, 0, 0};
#pragma unroll
            for (int i = 0; i < 8; i++) {
                const float sv = silu_bf(p.c, k0 + 16 * i);
                acc[0] += sv * bflo(v[i].x); acc[1] += sv * bfhi(v[i].x); acc[2] += sv * bflo(v[i].y); acc[3] += sv * bfhi(v[i].y);
                acc[4] += sv * bflo(v[i].z); acc[5] += sv * bfhi(v[i].z); acc[6] += sv * bflo(v[i].w); acc[7] += sv * bfhi(v[i].w);
            }
            float* red = (float*)(smraw + SM_PRE);
            *(float4*)(red + (tid >> 4) * 128 + (tid & 15) * 8) = make_float4(acc[0], acc[1], acc[2], acc[3]);
            *(float4*)(red + (tid >> 4) * 128 + (tid & 15) * 8 + 4) = make_float4(acc[4], acc[5], acc[6], acc[7]);
            bar_sync(NB_FIN0, 256);
            if (wid < 4) {
                float t = 0;
#pragma unroll
                for (int i = 0; i < 16; i++) t += red[i * 128 + tid];
                stg_rlx1(&g_modp[(b >> 4) * 2 * DM + cb + tid], __float_as_uint(t) | 1u);
            }
        } else {
            rec_ln((float*)(smraw + SM_PRE), p, b - 128, 0);
        }
    } else if (wid >= 10 && b >= 128) {
        {
            const int w = (b - 128) * 2 + wid - 10;
            const uint16_t* src = (const uint16_t*)p.mem0 + (lane & 3) * 2 * DM + (w >> 2) * 512 + (w & 1) * 64 + (w & 2) * 8 + (lane >> 2);
            uint32_t v[4][4];
#pragma unroll
            for (int i = 0; i < 16; i++) v[i >> 2][i & 3] = src[(i >> 2) * 128 + (i & 2) * 16 + (i & 1) * 8] | ((uint32_t)src[DM + (i >> 2) * 128 + (i & 2) * 16 + (i & 1) * 8] << 16);
            uint8_t* d = arena + mem_row(w >> 2, w & 3, 0);
            uint8_t* e = d + 512 + (CNT32 ? lane >> 1 : lane) * 4;
            d += lane * 16;
#pragma unroll
            for (int i = 0; i < 4; i++, d += 1024, e += 1024) {
                stg_rlx4(d, v[i][0], v[i][1], v[i][2], CNT32 && !(lane & 1) ? v[i][3] : (v[i][3] & 0xffff) | CNT_ALL << 16);
                stg_rlx4(d + mem_slot(1), 0, 0, 0, 0);
                stg_rlx4(d + mem_slot(2), 0, 0, 0, 0);
                if (!CNT32 || (lane & 1)) { stg_rlx1(e, (v[i][3] & 0xffff0000u) | CNT_ALL); stg_rlx1(e + mem_slot(1), 0); stg_rlx1(e + mem_slot(2), 0); }
            }
            if (w == 0 && lane < 8) stg_rlx2(arena + (LB_TIME << 13) + lane * 1024, 0, 0);
            bar_arrive(NB_C, 320);
        }
    } else if (rank == 0) {
        uint32_t best = ~0u;
        const int pg = wid < 10 ? 0 : 1 + (b >> 1) % 3;
        uint32_t* q = (uint32_t*)(arena + (pg << 21) + (pg ? blk(b >> 1, wid & 1) : blk(LB_PROBE, wid & 1) + b * 16));
        if (lane < 8) stg_rlx1(q + lane, 0);
        uint2 tk2 = ldg_rlx2(&g_tick[0]);
        __syncwarp();
        if (lane == 0) {
            q += 3;
            uint32_t v = atomicAdd(q, 1u);
#pragma unroll 1
            for (int r = 0; r < NPROBE; r++) {
                const uint32_t t0 = clk32() + (v >> 8);
                v = atomicAdd(q + (v >> 8), 1u);
                uint32_t t1;
                asm volatile("{.reg .pred p; setp.eq.u32 p, %1, 0xffffffff; @p exit; mov.u32 %0, %%clock;}" : "=r"(t1) : "r"(v) : "memory");
                best = min(best, t1 - t0);
            }
            sinfo[wid - 6] = best;
        }
        bar_sync(NB_KDONE, b < 128 ? 128 : 64);
        if (wid == 8) {
            const int par = sinfo[2] <= sinfo[3] ? 0 : 1, ncl = gridDim.x >> 1;
            int tk = 0, it = 0;
            const uint32_t vote = b < 128 && (sinfo[4] <= sinfo[5] ? 0 : 1) != par ? 256u << (8 * ((b >> 1) % 3)) : 0u;
            if (b >= 128) {
#pragma unroll 1
                while (!__all_sync(~0u, (int)((tk2.x + tk2.y) & 255) >= ncl - 2)) { tk2 = ldg_rlx2(&g_tick[0]); spin_guard(++it); }
            }
            if (lane == 0) tk = atomicAdd(&g_tick[par], 1u + vote) & 255;
#pragma unroll 1
            while (!__all_sync(~0u, (int)((tk2.x + tk2.y) & 255) >= ncl)) { tk2 = ldg_rlx2(&g_tick[0]); spin_guard(++it); }
            if (lane == 0) g_clk[b >> 1] = make_uint2(clk32() - 2 * gtime(), smid() | par << 8);
            tk = __shfl_sync(~0u, tk, 0);
            const int n0 = tk2.x & 255, n1 = tk2.y & 255;
            hA = min(n0 >> 1, NH);
            const int q0 = 2 * hA, q1 = 2 * NH - q0;
            const int over = tk - (par ? q1 : q0), lack = max(par ? q0 - n0 : q1 - n1, 0);
            if (over < 0) pr = par ? q0 + tk : tk;
            else if (over < lack) pr = (par ? n0 : q0 + n1) + over;
            else pr = -1 - (over - lack + (par ? max(n0 - q0, 0) : 0));
#pragma unroll
            for (int i = 0; i < 3; i++) hA |= (((tk2.x + tk2.y) >> (8 + 8 * i)) & 255) > 10 ? 256 << i : 0;
        }
    }
    asm volatile("barrier.cluster.wait.aligned;" ::: "memory");
    if (wid == 8) {
        if (rank == 0) {
            if (lane == 0) {
                uint32_t rsb;
                asm("mapa.shared::cluster.u32 %0, %1, 1;" : "=r"(rsb) : "r"(sb));
                asm volatile("st.async.shared::cluster.mbarrier::complete_tx::bytes.v2.u32 [%0], {%1, %2}, [%3];"
                             ::"r"(rsb + SM_BAR + 192), "r"(pr), "r"(hA), "r"(rsb + SM_BAR + 8 * B_ROLE) : "memory");
                sinfo[0] = pr; sinfo[1] = hA;
                if (b >= 128) atomicOr(&g_tick[4], (pr < 0 ? 4u : 1u) << ((b - 128) >> 1));
            }
        } else {
            mbar_wait_w(bars + 8 * B_ROLE, 0);
            pr = sinfo[0];
        }
        TL(1)
        __syncwarp();
        bar_arrive(NB_A, 288);
        bar_arrive(NB_S, 128);
        if (b >= 128 && pr < 0) bar_sync(NB_B, 64);
        if (pr >= 0) {
            const int pu = __reduce_max_sync(~0u, pr), c0 = (pu >> 1) * 128 + rank * 64, r0 = (pu & 1) * 512;
            bool fast = false;
#pragma unroll 1
            for (int n = 0; n < 12; n++) {
                const int rot = b >= 128 ? 8 : 0, i = (n + rot) % 12;
                if (rot && n == 4) bar_sync(NB_B, 64);
                if (n >= W_INFL && !fast) {
                    const uint32_t v = ldg_rlx1(&g_tick[32 + (lane & 3) * 8]);
                    mbar_wait_w(bars + 8 * (B_W + (n - W_INFL + rot) % 12), 0);
                    fast = __all_sync(~0u, v != 0);
                }
                const int m = i < 8 ? i & 1 : 2, k = i < 8 ? i >> 1 : i - 8;
                const uint32_t dst = sb + m * 65536 + k * 16384, br = bars + 8 * (B_W + i);
                if (lane == 0) {
                    mbar_expect(br, 16384);
                    tma2d_once(dst, &mp.wq + m, c0, r0 + k * 128, br);
                    tma2d_once(dst + 8192, &mp.wq + m, c0, r0 + k * 128 + 64, br);
                }
                __syncwarp();
            }
        }
    } else {
        bar_sync(wid < 8 ? NB_A : NB_S, wid < 8 ? 288 : 128);
    }
    const int prr = __reduce_max_sync(~0u, sinfo[0]);
    hA = __reduce_max_sync(~0u, sinfo[1]);
    if (prr < 0) {
        int j = (b - 128) >> 1;
        if (b < 128) {
            uint32_t v;
            int it = 0;
#pragma unroll 1
            do { v = __reduce_max_sync(~0u, ldg_rlx1(&g_tick[4])); spin_guard(++it); } while (__popc(v) < 2);
            j = v == 3 ? -1 - prr : (v & 1) ^ 1;
        }
        rec_side((float*)smraw, mp, p, j * 2 + rank);
        return;
    }
    if (PDL) asm volatile("griddepcontrol.launch_dependents;" ::: "memory");
    const int role = (prr >> 1) * 4 + rank * 2 + (prr & 1);
    rec_main(sb, &mp.wo, arena, role, hA, wid >> 2, p.zero, p.dly);
}

__device__ __forceinline__ void wgmma_ss192(float* d, uint64_t a, uint64_t b, int sc) {
    asm volatile("{.reg .pred p; setp.ne.b32 p, %98, 0;\n wgmma.mma_async.sync.aligned.m64n192k16.f32.bf16.bf16 "
                 "{%0,%1,%2,%3,%4,%5,%6,%7,%8,%9,%10,%11,%12,%13,%14,%15,%16,%17,%18,%19,%20,%21,%22,%23,%24,%25,%26,%27,%28,%29,%30,%31,%32,%33,%34,%35,%36,%37,%38,%39,%40,%41,%42,%43,%44,%45,%46,%47,%48,%49,%50,%51,%52,%53,%54,%55,%56,%57,%58,%59,%60,%61,%62,%63,%64,%65,%66,%67,%68,%69,%70,%71,%72,%73,%74,%75,%76,%77,%78,%79,%80,%81,%82,%83,%84,%85,%86,%87,%88,%89,%90,%91,%92,%93,%94,%95}, %96, %97, p, 1, 1, 0, 1;}"
                 : F16(d, 0), F16(d, 16), F16(d, 32), F16(d, 48), F16(d, 64), F16(d, 80) : "l"(a), "l"(b), "r"(sc));
}

constexpr uint32_t P_B = 81920, P_PL = 40960, P_OUT = 180224, P_VEC = 212992, P_ROW = P_VEC + 6144, P_BAR = P_ROW + 4096, P_SMEM = P_BAR + 256;
#define PPH 1
#define FLAG_ST "st.release.gpu.global.u32"
#define FLAG_LD "ld.acquire.gpu.global.u32"
#define PX 0
#define MIDF 0
#define DS_AT 3
constexpr int ST = 5;
constexpr int PB_F = 0, PB_E = 5, PB_R = 10, PB_OUT = 16;
enum { C_Y = 0, C_G = 1, C_X1 = 2, C_U = 3, C_S1 = 8, C_S3 = 9 };
enum { V_GA = 0, V_A = 1, V_B = 2, V_GB = 3, V_VA = 4, V_VB = 5, V_VC = 6, V_C3 = 7 };
struct PostMaps { CUtensorMap o, wo, y, w1, g, w2, x1, w3, u, w4, out; };
struct PostPtrs { const bf16* x; };

struct GeluK { float k0, k1, kh; };
__device__ __forceinline__ GeluK gelu_k(float c) { return {0.7978845608028654f * c, 0.7978845608028654f * 0.044715f * c * c * c, 0.5f * c}; }
__device__ __forceinline__ float gelu_s(float t, const GeluK& k) {
    const float u = t * fmaf(t * t, k.k1, k.k0);
    float th; asm("tanh.approx.f32 %0, %1;" : "=f"(th) : "f"(u));
    const float hx = k.kh * t;
    return fmaf(hx, th, hx);
}
__device__ __forceinline__ float2 ldsv(uint32_t a) {
    float2 v; asm("ld.shared.v2.f32 {%0,%1}, [%2];" : "=f"(v.x), "=f"(v.y) : "r"(a)); return v;
}
__device__ __forceinline__ void wait_smem(uint32_t a, int target) {
    int it = 0;
#pragma unroll 1
    while (true) {
        int v;
        asm volatile("ld.acquire.cta.shared.u32 %0, [%1];" : "=r"(v) : "r"(a) : "memory");
        if (__all_sync(~0u, v >= target) | (++it > SPIN_LIMIT)) break;
    }
}

#define PP(i)
#define PH_(c, w, i)
__device__ __forceinline__ void mbar_wait_b(uint32_t b, uint32_t par) {
    int it = 0;
#pragma unroll 1
    while (!__all_sync(~0u, mbar_try(b, par)) & (++it < SPIN_LIMIT)) {}
}
__device__ __forceinline__ void release(uint32_t rel, int st, bool c) {
    asm volatile("{.reg .pred p; setp.ne.u32 p, %1, 0; setp.ne.and.u32 p, %2, 0, p; @p mbarrier.arrive.shared::cluster.b64 _, [%0];}"
                 ::"r"(rel + 8 * (st ? st - 1 : ST - 1)), "r"(rel), "r"((uint32_t)c) : "memory");
}
struct Pipe { int st, ph; uint32_t rel; };
__device__ __forceinline__ void adv(Pipe& p) { if (++p.st == ST) { p.st = 0; p.ph ^= 1; } }

__device__ __forceinline__ void post_weights(uint32_t sb, const PostMaps& mp, int nb, int rank) {
    const uint32_t full = sb + P_BAR + 8 * PB_F, empty = sb + P_BAR + 8 * PB_E;
    int st = 0, pp = 1;
#pragma unroll 1
    for (int ph = 0; ph < 7; ph++) {
        const int NK = ph == 0 ? 64 : ph == 6 ? 56 : 16, km = NK == 16 ? 15 : 63;
        const CUtensorMap* tb = &mp.wo + 2 * (ph < 3 ? ph : ph < 6 ? 3 : 4);
        const bool w3 = ph >= 3 && ph < 6;
        const int n0 = w3 ? nb * 64 + (ph == 4 ? 1536 : ph == 5 ? 2560 : 0) : nb * 128, dn = w3 ? 512 : 64;
        const int rot = NK == 16 ? 2 * (nb & 6) : 0, sw = ph == 1 || ph == 3 ? 2 * rank : 0;
#pragma unroll 1
        for (int i = 0; i < NK; i++) {
            const int k0 = (((i < 4 ? i ^ sw : i) + rot) & km) * 64;
            const uint32_t a = sb + P_B + st * 8192, f = full + 8 * st;
            mbar_wait_b(empty + 8 * st, pp);
            e_expect(f, ph == 3 ? 40960 : 32768);
            e_tma2d(a, tb, n0, k0, f);
            e_tma2d(a + P_PL, tb, n0 + dn, k0, f);
            if (ph == 0 && i == 0) TL(2)
            if (ph == 3) e_tma2d(a + 2 * P_PL, tb, n0 + 1024, k0, f);
            if (++st == ST) { st = 0; pp ^= 1; }
        }
    }
#pragma unroll 1
    for (int i = 0; i < ST; i++) mbar_wait_b(empty + 8 * i, pp ^ (i < st));
}
__device__ __forceinline__ void post_acts(uint32_t sb, const PostMaps& mp, int mb, int nb, int rank) {
    const int rh = 2 * mb + rank, lane = threadIdx.x & 31;
    const uint32_t full = sb + P_BAR + 8 * PB_F, empty = sb + P_BAR + 8 * PB_E;
    int st = 0, pp = 1;
#pragma unroll 1
    for (int ph = 0; ph < 7; ph++) {
        const int NK = ph == 0 ? 64 : ph == 6 ? 56 : 16, km = NK == 16 ? 15 : 63;
        const CUtensorMap* ta = &mp.o + 2 * (ph < 3 ? ph : ph < 6 ? 3 : 4);
        const int amul = ph == 0 ? 256 : 64, arow = ph == 0 ? rh * 8 : rh * 64;
        const int rot = NK == 16 ? 2 * (nb & 6) : 0, own = ph == 1 || ph == 3 ? 4 : 0;
        const uint32_t shifts = ph == 2 ? 0x04000301u : 0x02020202u;
        const uint32_t* fl = &g_pflag[(ph == 6 ? C_U : min(ph - 1, 2)) * 256 + (ph == 2 ? min(max(rh + min(lane >> 3, 2) - 1, 0), 31) : rh) * 8 + (lane & 7)];
        uint32_t have = ph == 0 || ph == 5;
        if (own) { if (st) { st--; pp ^= 1; } else st = 4; }
#pragma unroll 1
        for (int i = own; i < NK; i++) {
            const int kb = (i + rot) & km;
            const uint32_t need = ph == 6 ? 255u : (ph == 2 ? 0x10101u : 1u) << ((kb >> 1) & 7), lvl = ph == 6 ? i >> 3 : 0;
            PH_(ph == PPH && i == own, 0, 27) PH_(ph == PPH && i == own, 1, 27)
            if ((__ballot_sync(~0u, have > lvl) & need) != need) {
                int it = 0;
#pragma unroll 1
                do asm volatile(FLAG_LD " %0, [%1];" : "=r"(have) : "l"(fl) : "memory");
                while (((__ballot_sync(~0u, have > lvl) & need) != need) & (++it < SPIN_LIMIT));
                PH_(ph == PPH && i == own, 0, 23) PH_(ph == PPH, 0, 24) PH_(ph == PPH && i == own, 1, 23) PH_(ph == PPH, 1, 24)
                asm volatile("fence.proxy.async.global;" ::: "memory");
            }
            const int d = own && (i == 5 || i == 6) ? 2 : 0, s2 = st + d < ST ? st + d : st + d - ST;
            mbar_wait_b(empty + 8 * s2, pp ^ (s2 < st));
            e_tma2d_mc(sb + st * 16384 + rank * 8192, ta, kb * amul, arow + (int)((shifts >> ((kb & 12) * 2)) & 7) - 2, full + 8 * st);
            if (++st == ST) { st = 0; pp ^= 1; }
        }
    }
}

template <int PH, bool EARLY = false, class F>
__device__ __forceinline__ void post_kb(uint32_t sb, float* acc, Pipe& p, int wg, bool lead, bool first, F mid) {
    constexpr uint64_t DA = PH == 0 ? mkdesc(SB0, 128, 1024, 0) : mkdesc(SB0, 16, 1024, 1);
    constexpr uint64_t DB = mkdesc(SB0 + P_B, P_PL, 1024, 1);
    mbar_wait_b(sb + P_BAR + 8 * PB_F + 8 * p.st, p.ph);
    const uint32_t a = (uint32_t)DA + p.st * 1024 + wg * 512, b = (uint32_t)DB + p.st * 512;
    wg_fence();
#pragma unroll
    for (int k = 0; k < 4; k++) {
        const uint64_t da = (DA & 0xffffffff00000000ull) | (a + k * (PH == 0 ? 16 : 2)), db = (DB & 0xffffffff00000000ull) | (b + k * 128);
        if (PH == 3) wgmma_ss192(acc, da, db, k || !first);
        else wgmma_ss128<PH == 0>(acc, da, db, k || !first);
    }
    wg_commit();
    if (EARLY) mid();
    wg_wait<1>();
    release(p.rel, p.st, !first);
    if (!EARLY) mid();
    adv(p);
}
__device__ __forceinline__ void post_end(uint32_t sb, Pipe& p, bool lead) {
    wg_wait<0>();
    release(p.rel, p.st, true);
}
template <int PH>
__device__ __forceinline__ void post_mma(uint32_t sb, float* acc, Pipe& p, int wg, bool lead, int nout, int pi, int mb, int nb) {
#pragma unroll 1
    for (int kb = 0; kb < 16; kb++)
        post_kb<PH>(sb, acc, p, wg, lead, kb == 0, [&]() {
            if (kb == 0) { PP(pi) }
            if (nout && kb == 0) wait_smem(sb + P_BAR + 8 * (PB_OUT + wg), nout);
        });
    post_end(sb, p, lead);
    PP(pi + 1)
}

__global__ void __cluster_dims__(2, 1, 1) __launch_bounds__(384, 1)
k_post(const __grid_constant__ PostMaps mp, const __grid_constant__ PostPtrs pp) {
    extern __shared__ uint8_t smraw[];
    const uint32_t sb = smem_u32(smraw);
    if ((sb & 0x3FFFF) != SB0) __trap();
    TL(13)
    const int tid = threadIdx.x, lane = tid & 31;
    const int rank = blockIdx.x & 1;
    const uint32_t bars = sb + P_BAR;
    int c = 0;
    unsigned long long v = 0;
    const int wid = __reduce_max_sync(~0u, tid >> 5);
    const bool draw = tid == 352 && rank == 0;
    if (draw) {
        c = min(ldg_rlx1(&g_cls[smid() & 255]), 8u);
        asm volatile("{.reg .b64 a; cvt.u64.u32 a, %%laneid; add.u64 a, a, %1; atom.relaxed.gpu.global.add.u64 %0, [a], %2;}" : "=l"(v) : "l"(&g_pt), "l"(1ull << (7 * c)) : "memory");
    }
    if (wid < 11) {
        asm volatile("{.reg .pred p; elect.sync _|p, 0xffffffff; @p mbarrier.init.shared.b64 [%0], %1; @p prefetch.tensormap [%2]; fence.mbarrier_init.release.cluster;}"
                     ::"r"(bars + 8 * wid), "r"(wid >= PB_E && wid < PB_R ? 4 : 1), "l"(&mp.o + wid) : "memory");
        if (wid == PB_R) { sts4(bars + 8 * PB_OUT, 0, 0, 0, 0); e_expect(bars + 8 * PB_R, 4); }
    }
    __syncwarp();
    asm volatile("barrier.cluster.arrive.relaxed.aligned; barrier.cluster.wait.aligned;" ::: "memory");
    if (draw) {
        int r = (v >> (7 * c)) & 127, role = c * 8 + r;
        if (c == 8 || r >= 8) {
            int n, x, it = 0;
#pragma unroll 1
            do {
                __nanosleep(200);
                v = ldg_u64(&g_pt); n = 0; x = c < 8 ? r - 8 : r;
#pragma unroll 1
                for (int i = 0; i < 63; i += 7) { const int m = v >> i & 127; n += m; if (i < 7 * c) x += max(m - 8, 0); }
            } while (n < gridDim.x / 2 && ++it < SPIN_LIMIT);
            role = -1;
#pragma unroll 1
            for (int i = 0; i < 64; i += 8, v >>= 7) {
                n = v & 127;
                if (x >= 0 && n + x < 8) role = i + n + x;
                x -= max(8 - n, 0);
            }
        }
#pragma unroll
        for (int i = 0; i < 2; i++)
            asm volatile("{.reg .b32 d; mapa.shared::cluster.u32 d, %0, %2; st.async.shared::cluster.mbarrier::complete_tx::bytes.u32 [d+8], %1, [d];}"
                         ::"r"(bars + 8 * PB_R), "r"(role), "r"(i) : "memory");
    }
    __syncwarp();
    mbar_wait_b(bars + 8 * PB_R, 0);
    const int pr = __reduce_max_sync(~0u, (int)lds1(bars + 8 * PB_R + 8));
    if (pr < 0) return;
    const int mb = (pr >> 5) * 8 + (pr & 7), nb = (pr >> 2 & 6) + rank, cta = pr * 2 + rank;
    if (wid >= 8) {
        asm volatile("setmaxnreg.dec.sync.aligned.u32 40;");
        const int w = wid - 8;
        if (w == 0) {
            post_weights(sb, mp, nb, rank);
        } else if (w == 3) {
            asm volatile("griddepcontrol.wait;" ::: "memory");
            TL(15)
            post_acts(sb, mp, mb, nb, rank);
        } else {
            const int wg = w - 1, rh = 2 * mb + wg;
            float* rowc = (float*)(smraw + P_ROW) + (wg * 64 + lane * 2) * 8;
            int nout = 0, sig = 0;
#pragma unroll 1
            for (int i = 0; i < 13; i++) {
                const int cnt = (0x4333333392180ull >> (4 * i)) & 15;
                if (cnt < C_S1) {
                    const int ng = cnt == C_U ? 1 : 2, c0 = cnt == C_U ? (i - 5) * 512 + nb * 64 : nb * 128;
                    const bool fast = (cnt == C_Y || cnt == C_X1);
#pragma unroll 1
                    for (int j = 0; j < ng; j++) {
                        const uint32_t st = j ? cnt : cnt ? 1 : 4;
                        const uint32_t src = sb + (fast ? st * 16384 + wg * 8192 : P_OUT + wg * 16384 + ((nout + j) & 1) * 8192);
                        bar_sync(4 + 4 * wg + (sig++ & 3), 160);
                        if (lane == 0) {
                            PH_(cnt == PPH - 1, wg, 20)
                            if (fast) asm volatile("mbarrier.complete_tx.relaxed.cta.shared::cta.b64 [%0], 8192;" ::"r"(bars + 8 * (PB_F + st)) : "memory");
                            asm volatile("cp.async.bulk.tensor.2d.global.shared::cta.bulk_group [%0, {%2, %3}], [%1]; cp.async.bulk.commit_group;"
                                         ::"l"(&mp.y + 2 * cnt), "r"(src), "r"(c0 + j * 64), "r"(rh * 64) : "memory");
                        }
                        __syncwarp();
                    }
                    if (lane == 0) {
                        auto to_peer = [&]() {
                            const uint32_t n = cnt ? 1 : 4;
                            mbar_wait(bars + 8 * (PB_E + (cnt ? 4 : 2)), 0);
#pragma unroll
                            for (int i = 0; i < 2; i++)
                                asm volatile("{.reg .b32 d, m; mapa.shared::cluster.u32 d, %0, %3; mapa.shared::cluster.u32 m, %2, %3;\n"
                                             " cp.async.bulk.shared::cluster.shared::cta.mbarrier::complete_tx::bytes [d], [%1], 8192, [m];}"
                                             ::"r"(sb + (cnt + 1 + i) * 16384 + wg * 8192), "r"(sb + (i ? cnt : n) * 16384 + wg * 8192), "r"(bars + 8 * (PB_F + cnt + 1 + i)), "r"(rank ^ 1) : "memory");
                        };
                        if (DS_AT == 1 && fast) to_peer();
                        asm volatile("cp.async.bulk.wait_group 0; fence.proxy.async.global;" ::: "memory");
                        asm volatile("st.release.cta.shared.u32 [%0], %1;" ::"r"(bars + 8 * (PB_OUT + wg)), "r"(nout + ng) : "memory");
                        PH_(cnt == PPH - 1, wg, 21)
                        if (DS_AT == 2 && fast) to_peer();
                        asm volatile(FLAG_ST " [%0], %1;" ::"l"(&g_pflag[cnt * 256 + rh * 8 + nb]), "r"(max(i - 4, 1)) : "memory");
                        PH_(cnt == PPH - 1, wg, 22)
                        if (DS_AT == 3 && fast) to_peer();
                    }
                    nout += ng;
                    __syncwarp();
                    continue;
                }
                bar_sync(4 + 4 * wg + (sig++ & 3), 160);
                uint32_t* c = &g_pcnt[(cnt - C_S1) * 256 + rh * 8];
                if (lane == 0) { signal_count(c); wait_count1(c, 8); }
                __syncwarp();
                const float4* sp = (const float4*)g_st + rh * 32 + lane;
                float4 u[3] = {__ldcg(sp + (cnt == C_S1 ? 0 : 3) * (S_ / 2)), __ldcg(sp + S_ / 2), __ldcg(sp + S_)};
#pragma unroll 1
                for (int h = 0; h < 2; h++) {
                    const float id = 1.0f / DM;
                    const float m = u[0].x * id, var = fmaxf(u[0].y * id - m * m, 0.f) + 1e-5f, r = rsqrtf(var);
                    float sc = r, m2 = 0.f;
                    if (cnt == C_S1) {
                        m2 = r * (u[1].x * id - m * g_cst[0]) + g_cst[3];
                        const float e2 = r * r * (u[2].x * id - 2.0f * m * u[1].y * id + m * m * g_cst[1]) + 2.0f * r * (u[2].y * id - m * g_cst[2]) + g_cst[4];
                        sc = r * rsqrtf(fmaxf(e2 - m2 * m2, 0.f) + 1e-5f);
                    }
                    const GeluK k = gelu_k(sc);
                    *(float4*)(rowc + h * 8) = make_float4(k.k0, k.k1, k.kh, -m);
                    *(float4*)(rowc + h * 8 + 4) = make_float4(var * r, -m2 * var * r, r, -m * r);
#pragma unroll
                    for (int q = 0; q < 3; q++) { u[q].x = u[q].z; u[q].y = u[q].w; }
                }
                bar_arrive(1 + wg, 160);
            }
        }
    } else {
        asm volatile("setmaxnreg.inc.sync.aligned.u32 232;");
        const bf16* xin = pp.x;
        const int wg = wid >> 2, wi = (tid >> 5) & 3, g = lane >> 2, tq = lane & 3;
        const int rh = 2 * mb + wg, row = rh * 64 + wi * 16 + g;
        const bool lead = (tid & 127) == 0;
        PP(0)
        if (tid == 0) TL(10)
        uint32_t keep[32];
#pragma unroll
        for (int i = 0; i < 8; i++)
            *(uint4*)(keep + 4 * i) = __ldg((const uint4*)(xin + (size_t)(rh * 64 + wi * 16 + (i & 3) * 4 + (lane >> 3)) * DM + nb * 128 + (i >> 2) * 64 + (lane & 7) * 8));
        asm volatile("griddepcontrol.wait;" ::: "memory");
        if (cta < 64) g_modp[cta * 256 + tid] = 0;
        if (cta == 64 && tid < 64) g_tick[tid] = 0;
        const float* src = wg ? g_vec + nb * 128 + tid - 128 : g_mod + 2 * DM + nb * 128 + tid;
        const float* c3 = &g_vec[3 * DM + (tid >> 6) * 512 + nb * 64 + (tid & 63)];
        const float cv[6] = {__ldcg(src), __ldcg(src + (wg ? 1 : 2) * DM), __ldcg(src + (wg ? 2 : 1) * DM), __ldcg(src + 3 * DM), __ldcg(c3), __ldcg(c3 + (tid < 192 ? 2048 : 0))};
        uint32_t vec = sb + P_VEC + tq * 8;
        const uint32_t stw = sb + (wi * 16 + ((lane >> 3) & 1) * 8 + (lane & 7)) * 128 + (((lane >> 4) ^ (lane & 7)) << 4);
        int sig = 0;
        auto signal = [&]() { bar_arrive(4 + 4 * wg + (sig++ & 3), 160); };
        auto put64 = [&](uint32_t o, const float* v) {
#pragma unroll
            for (int jj = 0; jj < 4; jj++, v += 8) stsm4((stw + o) ^ (jj << 5), pack2(v[0], v[1]), pack2(v[2], v[3]), pack2(v[4], v[5]), pack2(v[6], v[7]));
            fence_async_smem();
            signal();
        };
        auto slot = [&](int n) {
            mbar_wait_b(bars + 8 * (PB_E + n % 5), ((n / 5) & 1) ^ 1);
            return (n % 5) * 16384 + wg * 8192;
        };
        const uint32_t rowc = sb + P_ROW + (wg * 64 + wi * 16 + g) * 32, o128 = P_OUT + wg * 16384;
        Pipe pa = {0, 0, 0};
        asm("mapa.shared::cluster.u32 %0, %1, %2;" : "=r"(pa.rel) : "r"(bars + 8 * PB_E), "r"(tid & 1));
        if (tid & 126) pa.rel = 0;
#define KEEP(jn, e) (((e) & 1) ? bfhi(keep[2 * (jn) + ((e) >> 1)]) : bflo(keep[2 * (jn) + ((e) >> 1)]))
        float mu1[2], r1[2];
        {
            float acc[64];
#pragma unroll 1
            for (int kb = 0; kb < 64; kb++) {
                post_kb<0>(sb, acc, pa, wg, lead, kb == 0, []() {});
                if (kb == 0) { PP(1) if (wg == 0) TL(11) }
                if (kb == 24) bar_sync(3, 256);
                if (kb != 8 + 8 * wg) continue;
                float* sv = (float*)(smraw + P_VEC) + tid;
                const uint32_t xo = sb + o128 + wi * 2048 + (lane >> 3) * 128;
#pragma unroll
                for (int i = 0; i < 8; i++) sts4(xo + (i >> 2) * 8192 + (i & 3) * 512 + (((lane & 7) ^ ((i & 1) * 4 + (lane >> 3))) << 4), keep[4 * i], keep[4 * i + 1], keep[4 * i + 2], keep[4 * i + 3]);
                __syncwarp();
#pragma unroll
                for (int jj = 0; jj < 8; jj++) ldsm4(keep + jj * 4, (stw + o128 + (jj >> 2) * 8192) ^ ((jj & 3) << 5));
                sv[wg * 384] = cv[0]; sv[wg * 384 + 128] = cv[1] + (wg ? 0.0f : 1.0f); sv[wg * 384 + 256] = cv[2];
                if (!wg) sv[384] = cv[3];
                sv[V_C3 * 128] = cv[4]; sv[V_C3 * 128 + 256] = cv[5];
            }
            post_end(sb, pa, lead);
            PP(2)
            asm volatile("" : "+r"(vec) :: "memory");
            float st[2][6];
#pragma unroll
            for (int q = 0; q < 6; q++) st[0][q] = st[1][q] = 0.f;
#pragma unroll
            for (int jn = 0; jn < 16; jn++) {
                const float2 ga = ldsv(vec + V_GA * 512 + jn * 32), a = ldsv(vec + V_A * 512 + jn * 32);
                float xa[4];
#pragma unroll
                for (int e = 0; e < 4; e++) {
                    xa[e] = fmaf((e & 1) ? ga.y : ga.x, acc[4 * jn + e], KEEP(jn, e));
                    st[e >> 1][0] += xa[e]; st[e >> 1][1] = fmaf(xa[e], xa[e], st[e >> 1][1]);
                    acc[4 * jn + e] = ((e & 1) ? a.y : a.x) * xa[e];
                }
                keep[2 * jn] = pack2(xa[0], xa[1]); keep[2 * jn + 1] = pack2(xa[2], xa[3]);
                if ((jn & 7) == 7) put64(slot(64 + (jn >> 3)), acc + 4 * jn - 28);
            }
            PP(3)
#pragma unroll
            for (int jn = 0; jn < 16; jn++) {
                const float2 a = ldsv(vec + V_A * 512 + jn * 32), b = ldsv(vec + V_B * 512 + jn * 32);
#pragma unroll
                for (int e = 0; e < 4; e++) {
                    const float y = acc[4 * jn + e], aa = (e & 1) ? a.y : a.x, bb = (e & 1) ? b.y : b.x;
                    float* s = st[e >> 1];
                    s[2] += y; s[3] = fmaf(aa, y, s[3]); s[4] = fmaf(y, y, s[4]); s[5] = fmaf(bb, y, s[5]);
                }
            }
#pragma unroll
            for (int h = 0; h < 2; h++)
#pragma unroll
                for (int q = 0; q < 6; q++) { st[h][q] += __shfl_xor_sync(~0u, st[h][q], 1); st[h][q] += __shfl_xor_sync(~0u, st[h][q], 2); }
            if (tq < 3 && !(PX & 1)) {
#pragma unroll
                for (int h = 0; h < 2; h++)
                    red2(g_st + (tq * S_ + row + h * 8) * 2, tq == 0 ? st[h][0] : tq == 1 ? st[h][2] : st[h][4], tq == 0 ? st[h][1] : tq == 1 ? st[h][3] : st[h][5]);
            }
            signal();
            PP(29)
        }
        {
            float acc[64];
            post_mma<1>(sb, acc, pa, wg, lead, 2, 4, mb, nb);
            float c1[2], c2[2], c3[2];
            GeluK gk[2];
            bar_sync(1 + wg, 160);
#pragma unroll
            for (int h = 0; h < 2; h++) {
                const float4 a = lds4f(rowc + h * 256), b = lds4f(rowc + h * 256 + 16);
                gk[h] = {a.x, a.y, a.z}; c1[h] = a.w; c2[h] = b.x; c3[h] = b.y; mu1[h] = b.w; r1[h] = b.z;
            }
#pragma unroll
            for (int jn = 0; jn < 16; jn++) {
                const float2 va = ldsv(vec + V_VA * 512 + jn * 32), vb = ldsv(vec + V_VB * 512 + jn * 32), vc = ldsv(vec + V_VC * 512 + jn * 32);
#pragma unroll
                for (int e = 0; e < 4; e++) {
                    const int h = e >> 1;
                    const float t = fmaf(c1[h], (e & 1) ? va.y : va.x, fmaf(c2[h], (e & 1) ? vb.y : vb.x, fmaf(c3[h], (e & 1) ? vc.y : vc.x, acc[4 * jn + e])));
                    acc[4 * jn + e] = gelu_s(t, gk[h]);
                }
                if ((jn & 7) == 7) put64(o128 + (jn >> 3) * 8192, acc + 4 * jn - 28);
            }
            PP(6)
        }
        {
            float acc[64];
            post_mma<2>(sb, acc, pa, wg, lead, 0, 7, mb, nb);
#pragma unroll
            for (int jn = 0; jn < 16; jn++) {
                const float2 a = ldsv(vec + V_A * 512 + jn * 32), b = ldsv(vec + V_B * 512 + jn * 32);
#pragma unroll
                for (int e = 0; e < 4; e++) {
                    const int h = e >> 1;
                    acc[4 * jn + e] += fmaf(fmaf(KEEP(jn, e), r1[h], mu1[h]), (e & 1) ? a.y : a.x, (e & 1) ? b.y : b.x);
                }
                if ((jn & 7) == 7) put64(slot(96 + (jn >> 3)), acc + 4 * jn - 28);
            }
            BLOCK_FENCE
#pragma unroll
            for (int i = 0; i < 64; i += 16) asm volatile("" : F16(acc, i));
            PP(9)
            float st[2][2] = {{0.f, 0.f}, {0.f, 0.f}};
#pragma unroll
            for (int jn = 0; jn < 16; jn++) {
                const float2 gb = ldsv(vec + V_GB * 512 + jn * 32);
                float z[4];
#pragma unroll
                for (int e = 0; e < 4; e++) {
                    const float x1 = acc[4 * jn + e];
                    st[e >> 1][0] += x1; st[e >> 1][1] = fmaf(x1, x1, st[e >> 1][1]);
                    z[e] = fmaf((e & 1) ? gb.y : gb.x, x1, KEEP(jn, e));
                }
                keep[2 * jn] = pack2(z[0], z[1]); keep[2 * jn + 1] = pack2(z[2], z[3]);
            }
#pragma unroll
            for (int h = 0; h < 2; h++)
#pragma unroll
                for (int q = 0; q < 2; q++) { st[h][q] += __shfl_xor_sync(~0u, st[h][q], 1); st[h][q] += __shfl_xor_sync(~0u, st[h][q], 2); }
            if (tq < 2) red2(g_st + (3 * S_ + row + tq * 8) * 2, tq ? st[1][0] : st[0][0], tq ? st[1][1] : st[0][1]);
            signal();
            PP(30)
        }
        {
            float old[96], acc[64];
            post_mma<3>(sb, old, pa, wg, lead, 6, 10, mb, nb);
#pragma unroll
            for (int i = 0; i < 96; i += 16) asm volatile("" : F16(old, i));
            uint32_t v3 = vec + V_C3 * 512;
            bar_sync(1 + wg, 160);
            const float4 rc[2] = {lds4f(rowc), lds4f(rowc + 256)};
            float2 vc[2] = {lds2f(v3), lds2f(v3 + 32)};
            bar_sync(3, 256);
#pragma unroll 1
            for (int blk = 0; blk < 11; blk++) {
                const uint32_t o = stw + o128 + (blk & 1) * 8192;
                const int turn = blk < 7 ? wg : 2;
#pragma unroll
                for (int q = 0; q < 4; q++) {
#pragma unroll 1
                    for (int rep = 0; rep < 2; rep++) {
                        post_kb<1, MIDF>(sb, acc, pa, wg, lead, q == 0 && rep == 0 && blk < 6 && !(blk & 1), [&]() {
                        if (rep != turn) return;
                        asm volatile("" : F4(old, 8 * q), F4(old, 8 * q + 4));
                        const float2 vn[2] = {lds2f(v3 + q * 64 + 64), lds2f(v3 + q * 64 + 96)};
                        float t[8];
#pragma unroll
                        for (int i = 0; i < 8; i++) {
                            const float4& c = rc[(i >> 1) & 1];
                            t[i] = gelu_s(fmaf(c.w, (i & 1) ? vc[i >> 2].y : vc[i >> 2].x, old[8 * q + i]), GeluK{c.x, c.y, c.z});
                            old[8 * q + i] = old[32 + 8 * q + i];
                            old[32 + 8 * q + i] = old[64 + 8 * q + i];
                        }
                        stsm4(o ^ (q << 5), pack2(t[0], t[1]), pack2(t[2], t[3]), pack2(t[4], t[5]), pack2(t[6], t[7]));
                        vc[0] = vn[0]; vc[1] = vn[1];
                        if (q == 2) wait_smem(bars + 8 * (PB_OUT + wg), 6 + blk);
                        if (q == 3) { fence_async_smem(); signal(); }
                        });
                    }
                }
                v3 += 256;
                if (blk != 1 && blk != 3) continue;
                post_end(sb, pa, lead);
                PP(12 + blk)
                asm volatile("" : F16(acc, 0), F4(acc, 16), F4(acc, 20), F4(acc, 24));
                asm volatile("" : F16(acc, 28), F4(acc, 44), F4(acc, 48), F4(acc, 52));
                asm volatile("" : F4(acc, 56), F4(acc, 60));
#pragma unroll
                for (int i = 0; i < 64; i++) old[32 + i] = acc[i];
            }
            post_end(sb, pa, lead);
            PP(17)
#pragma unroll
            for (int jn = 0; jn < 16; jn++) {
                const float2 gb = ldsv(vec + V_GB * 512 + jn * 32);
#pragma unroll
                for (int e = 0; e < 4; e++) acc[4 * jn + e] = fmaf((e & 1) ? gb.y : gb.x, acc[4 * jn + e], KEEP(jn, e));
                if ((jn & 7) == 7) put64(o128 + ((jn >> 3) ^ 1) * 8192, acc + 4 * jn - 28);
            }
            PP(18)
            if (tid == 0) TL(12)
        }
    }
}

typedef CUresult (*EncFn)(CUtensorMap*, CUtensorMapDataType, cuuint32_t, void*, const cuuint64_t*, const cuuint64_t*, const cuuint32_t*,
                          const cuuint32_t*, CUtensorMapInterleave, CUtensorMapSwizzle, CUtensorMapL2promotion, CUtensorMapFloatOOBfill);

static CUtensorMap make_map(EncFn enc, const void* p, uint64_t inner, uint64_t outer, uint32_t bi = 64) {
    CUtensorMap m;
    cuuint64_t dims[2] = {inner, outer};
    cuuint64_t str[1] = {inner * 2};
    cuuint32_t box[2] = {bi, bi == 64 ? 64u : 16u};
    cuuint32_t es[2] = {1, 1};
    enc(&m, CU_TENSOR_MAP_DATA_TYPE_BFLOAT16, 2, (void*)p, dims, str, box, es, CU_TENSOR_MAP_INTERLEAVE_NONE,
        bi == 64 ? CU_TENSOR_MAP_SWIZZLE_128B : CU_TENSOR_MAP_SWIZZLE_NONE, CU_TENSOR_MAP_L2_PROMOTION_L2_256B, CU_TENSOR_MAP_FLOAT_OOB_FILL_NONE);
    return m;
}
static CUtensorMap make_map_o(EncFn enc, const void* p) {
    CUtensorMap m;
    cuuint64_t dims[2] = {16384, 256};
    cuuint64_t str[1] = {65536};
    cuuint32_t box[2] = {256, 8};
    cuuint32_t es[2] = {1, 1};
    enc(&m, CU_TENSOR_MAP_DATA_TYPE_UINT32, 2, (void*)p, dims, str, box, es, CU_TENSOR_MAP_INTERLEAVE_NONE, CU_TENSOR_MAP_SWIZZLE_NONE,
        CU_TENSOR_MAP_L2_PROMOTION_L2_256B, CU_TENSOR_MAP_FLOAT_OOB_FILL_NONE);
    return m;
}
template <class T> static T* sym(T& s) { void* p = nullptr; cudaGetSymbolAddress(&p, s); return (T*)p; }

static const Delays h_dly = {D_NEAR, D_FAR, D_X2, D_V, D_W2, D_PA, D_WF, D_TV};
extern "C" void kernel_launch(void* const* d_in, const int* in_sizes, int n_in, void* d_out, int out_size) {
    const bf16* x = (const bf16*)d_in[0];
    const bf16* mem0 = (const bf16*)d_in[1];
    const bf16 *Wq = (const bf16*)d_in[2], *Wk = (const bf16*)d_in[3], *Wv = (const bf16*)d_in[4], *Wo = (const bf16*)d_in[5];
    const bf16 *w1 = (const bf16*)d_in[8], *w2 = (const bf16*)d_in[9], *w3 = (const bf16*)d_in[10], *w4 = (const bf16*)d_in[11];
    const bf16 *c = (const bf16*)d_in[12], *wmod = (const bf16*)d_in[13];
    bf16* out = (bf16*)d_out;

    EncFn enc = nullptr;
    cudaDriverEntryPointQueryResult qr;
    cudaGetDriverEntryPoint("cuTensorMapEncodeTiled", (void**)&enc, cudaEnableDefault, &qr);
    CUtensorMap tWq = make_map(enc, Wq, NH * DH, DM), tWk = make_map(enc, Wk, NH * DH, DM), tWv = make_map(enc, Wv, NH * DH, DM);
    PostMaps mp;
    mp.o = make_map_o(enc, sym(g_O)); mp.wo = make_map(enc, Wo, DM, NH * DH);
    mp.y = make_map(enc, sym(g_y), DM, S_); mp.w1 = make_map(enc, w1, DM, DM);
    mp.g = make_map(enc, sym(g_g), DM, S_); mp.w2 = make_map(enc, w2, DM, DM);
    mp.x1 = make_map(enc, sym(g_x1), DM, S_); mp.w3 = make_map(enc, w3, FF, DM);
    mp.u = make_map(enc, sym(g_u), FF, S_); mp.w4 = make_map(enc, w4, DM, FF);
    mp.out = make_map(enc, out, DM, S_);
    cudaFuncSetAttribute(k_rec, cudaFuncAttributeMaxDynamicSharedMemorySize, SM_REC_TOTAL + 2048);
    cudaFuncSetAttribute(k_post, cudaFuncAttributeMaxDynamicSharedMemorySize, P_SMEM);

    uint8_t* arena = (uint8_t*)(((uintptr_t)sym(g_arena) + (2u << 20) - 1) & ~(uintptr_t)((2u << 20) - 1));
    const PostPtrs pp = {x};
    const RecPtrs rp = {x, mem0, c, wmod, w1, w3, arena, 0u, w2, w4, Wo, h_dly};
    const RecMaps rm = {tWq, tWk, tWv, mp.wo, make_map(enc, wmod, 6 * DM, DM, 256), make_map(enc, w3, FF, DM, 256), make_map(enc, w1, DM, DM, 256)};
    k_rec<<<132, 384, SM_REC_TOTAL + 2048>>>(rm, rp);
    cudaLaunchConfig_t cfg = {};
    cfg.gridDim = dim3(132); cfg.blockDim = dim3(384); cfg.dynamicSmemBytes = P_SMEM; cfg.stream = cudaStreamPerThread;
    cudaLaunchAttribute at[1];
    at[0].id = cudaLaunchAttributeProgrammaticStreamSerialization; at[0].val.programmaticStreamSerializationAllowed = PDL;
    cfg.attrs = at; cfg.numAttrs = 1;
    cudaLaunchKernelEx(&cfg, k_post, mp, pp);
}
```

```cpp
#include <cuda_runtime.h>
#include <cuda.h>
#include <cuda_bf16.h>
#include <stdint.h>
#include <limits.h>

typedef __nv_bfloat16 bf16;

constexpr int S_ = 2048, DM = 1024, NH = 32, DH = 128, NSEG = 64, FF = 3584;
constexpr int SPIN_LIMIT = 1 << 22;
#define W_INFL 2
#define XP 0
#define H_PIECES 4
#define PDL 1
#define NPROBE 3

__device__ uint8_t g_arena[10 << 20];
__device__ __align__(128) uint32_t g_tick[64 + 132];
#define g_clk ((uint2*)(g_tick + 64))
__device__ uint32_t g_cls[256];
__device__ unsigned long long g_pt;
__device__ __align__(16) uint32_t g_modp[8 * 2 * DM];
__host__ __device__ constexpr uint32_t blk(uint32_t lb, uint32_t par) {
    return (lb << 13) | ((((lb) ^ (lb >> 3) ^ (lb >> 4) ^ (lb >> 6) ^ par) & 1) << 12);
}
__host__ __device__ constexpr uint32_t lb_x2(uint32_t h) { return (h & 1) | ((h >> 1) << 3); }
__host__ __device__ constexpr uint32_t mem_row(uint32_t kh, uint32_t b, uint32_t r) { return blk(128 | b, kh) + r * 1024; }
__device__ __forceinline__ uint32_t mem_slot(uint32_t s) { return ((s & 1) << 15) | ((s & 2) << 17); }
constexpr uint32_t CNT1 = 0x3d80, CNT_ALL = 0x4000;
constexpr uint32_t LB_PROBE = 6 | 64, LB_TIME = 6;
__host__ __device__ constexpr uint32_t lb_tok(uint32_t h) { return (h & 1) | ((h >> 1) << 3); }
__device__ float g_mod[6 * DM];
__device__ __align__(1024) bf16 g_himg[(S_ + 32) * DM];
__device__ __align__(1024) bf16 g_O[S_ * NH * DH];
__device__ __align__(1024) bf16 g_y[S_ * DM];
__device__ __align__(1024) bf16 g_g[S_ * DM];
__device__ __align__(1024) bf16 g_x1[S_ * DM];
__device__ __align__(16) float g_st[4 * S_ * 2];
__device__ float g_vec[3 * DM + FF];
__device__ float g_cst[8];
__device__ uint32_t g_pcnt[2 * 32 * 8], g_pflag[7 * 32 * 8];
__device__ __align__(1024) bf16 g_u[S_ * FF];

#define TL(i) {}
#define TLX(i) {}
#define TLP(i) TL(i)
#define TLC(i) {}
__device__ __forceinline__ uint32_t smem_u32(const void* p) { return (uint32_t)__cvta_generic_to_shared(p); }
__device__ __forceinline__ void spin_guard(int it) {
    asm volatile("{.reg .pred p; setp.gt.s32 p, %0, %1; @p st.global.u32 [%2], %0;}" ::"r"(it), "n"(SPIN_LIMIT), "l"(1ull));
}
__device__ __forceinline__ void wg_fence() { asm volatile("wgmma.fence.sync.aligned;" ::: "memory"); }
__device__ __forceinline__ void wg_commit() { asm volatile("wgmma.commit_group.sync.aligned;" ::: "memory"); }
template <int N> __device__ __forceinline__ void wg_wait() { asm volatile("wgmma.wait_group.sync.aligned %0;" ::"n"(N) : "memory"); }
__host__ __device__ constexpr uint64_t mkdesc(uint32_t addr, uint32_t lbo, uint32_t sbo, uint32_t swz) {
    return (uint64_t)((addr & 0x3FFFF) >> 4) | ((uint64_t)(lbo >> 4) << 16) | ((uint64_t)(sbo >> 4) << 32) | ((uint64_t)swz << 62);
}
__device__ __forceinline__ uint64_t dadd(uint64_t d, uint32_t o) { return (d & 0xffffffff00000000ull) | (uint32_t)((uint32_t)d + o); }
__device__ __forceinline__ void mbar_init(uint32_t b, uint32_t c) { asm volatile("mbarrier.init.shared.b64 [%0], %1;" ::"r"(b), "r"(c) : "memory"); }
__device__ __forceinline__ void mbar_expect(uint32_t b, uint32_t tx) { asm volatile("mbarrier.arrive.expect_tx.shared.b64 _, [%0], %1;" ::"r"(b), "r"(tx) : "memory"); }
__device__ __forceinline__ void mbar_arrive(uint32_t b) { asm volatile("mbarrier.arrive.shared.b64 _, [%0];" ::"r"(b) : "memory"); }
__device__ __forceinline__ void mbar_arrive_cluster(uint32_t b, uint32_t cta) {
    asm volatile("{.reg .b32 r; mapa.shared::cluster.u32 r, %0, %1; mbarrier.arrive.shared::cluster.b64 _, [r];}" ::"r"(b), "r"(cta) : "memory");
}
__device__ __forceinline__ bool mbar_try(uint32_t b, uint32_t par) {
    uint32_t ok;
    asm volatile("{.reg .pred p; mbarrier.try_wait.parity.shared.b64 p, [%1], %2; selp.u32 %0, 1, 0, p;}" : "=r"(ok) : "r"(b), "r"(par) : "memory");
    return ok;
}
__device__ __forceinline__ void mbar_wait(uint32_t b, uint32_t par) {
    int it = 0;
#pragma unroll 1
    while (!mbar_try(b, par)) { spin_guard(++it); }
}
__device__ __forceinline__ void mbar_wait_w(uint32_t b, uint32_t par) {
    int it = 0;
    bool ok;
#pragma unroll 1
    do { ok = __all_sync(~0u, mbar_try(b, par)); spin_guard(++it); } while (!ok);
}
__device__ __forceinline__ void mbar_wait_cluster(uint32_t b, uint32_t par) {
    int it = 0;
    while (true) {
        uint32_t ok;
        asm volatile("{.reg .pred p; mbarrier.try_wait.parity.acquire.cluster.shared::cta.b64 p, [%1], %2; selp.u32 %0, 1, 0, p;}" : "=r"(ok) : "r"(b), "r"(par) : "memory");
        if (ok) break;
        spin_guard(++it);
    }
}
__device__ __forceinline__ void tma2d(uint32_t dst, const CUtensorMap* m, int c0, int c1, uint32_t bar) {
    asm volatile("cp.async.bulk.tensor.2d.shared::cluster.global.mbarrier::complete_tx::bytes [%0], [%1, {%3, %4}], [%2];" ::"r"(dst), "l"(m), "r"(bar), "r"(c0), "r"(c1) : "memory");
}
constexpr uint64_t EVICT_FIRST = 0x12F0000000000000ull, EVICT_NORMAL = 0x1000000000000000ull;
__device__ __forceinline__ void tma2d_mc(uint32_t dst, const CUtensorMap* m, int c0, int c1, uint32_t bar, uint16_t mask) {
    asm volatile("cp.async.bulk.tensor.2d.shared::cluster.global.mbarrier::complete_tx::bytes.multicast::cluster [%0], [%1, {%3, %4}], [%2], %5;" ::"r"(dst), "l"(m), "r"(bar), "r"(c0), "r"(c1), "h"(mask) : "memory");
}
__device__ __forceinline__ void bulk_g2s(uint32_t dst, const void* src, uint32_t bytes, uint32_t bar) {
    asm volatile("cp.async.bulk.shared::cluster.global.mbarrier::complete_tx::bytes [%0], [%1], %2, [%3];" ::"r"(dst), "l"(src), "r"(bytes), "r"(bar) : "memory");
}
__device__ __forceinline__ void bar_sync(int id, int n) { asm volatile("bar.sync %0, %1;" ::"r"(id), "r"(n) : "memory"); }
__device__ __forceinline__ void bar_arrive(int id, int n) { asm volatile("bar.arrive %0, %1;" ::"r"(id), "r"(n) : "memory"); }
__device__ __forceinline__ void cluster_sync_all() { asm volatile("barrier.cluster.arrive.aligned; barrier.cluster.wait.aligned;" ::: "memory"); }
__device__ __forceinline__ void fence_async_smem() { asm volatile("fence.proxy.async.shared::cta;" ::: "memory"); }
__device__ __forceinline__ void ldsm4t(uint32_t* r, uint32_t a) {
    asm volatile("ldmatrix.sync.aligned.m8n8.x4.trans.shared.b16 {%0,%1,%2,%3}, [%4];" : "=r"(r[0]), "=r"(r[1]), "=r"(r[2]), "=r"(r[3]) : "r"(a) : "memory");
}
__device__ __forceinline__ void ldsm4(uint32_t* r, uint32_t a) {
    asm volatile("ldmatrix.sync.aligned.m8n8.x4.shared.b16 {%0,%1,%2,%3}, [%4];" : "=r"(r[0]), "=r"(r[1]), "=r"(r[2]), "=r"(r[3]) : "r"(a) : "memory");
}
__device__ __forceinline__ uint32_t movm(uint32_t a) {
    uint32_t d; asm volatile("movmatrix.sync.aligned.m8n8.trans.b16 %0, %1;" : "=r"(d) : "r"(a)); return d;
}
__device__ __forceinline__ void mma16816(float* d, uint32_t a0, uint32_t a1, uint32_t a2, uint32_t a3, uint32_t b0, uint32_t b1) {
    asm volatile("mma.sync.aligned.m16n8k16.row.col.f32.bf16.bf16.f32 {%0,%1,%2,%3},{%4,%5,%6,%7},{%8,%9},{%0,%1,%2,%3};"
                 : "+f"(d[0]), "+f"(d[1]), "+f"(d[2]), "+f"(d[3]) : "r"(a0), "r"(a1), "r"(a2), "r"(a3), "r"(b0), "r"(b1));
}
__device__ __forceinline__ void mma16816z(float* d, const uint32_t* a, uint32_t b0, uint32_t b1) {
    asm volatile("mma.sync.aligned.m16n8k16.row.col.f32.bf16.bf16.f32 {%0,%1,%2,%3},{%4,%5,%6,%7},{%8,%9},{%10,%10,%10,%10};"
                 : "=f"(d[0]), "=f"(d[1]), "=f"(d[2]), "=f"(d[3]) : "r"(a[0]), "r"(a[1]), "r"(a[2]), "r"(a[3]), "r"(b0), "r"(b1), "f"(0.f));
}
__device__ __forceinline__ void mma1688(float* d, uint32_t a0, uint32_t a1, uint32_t b0) {
    asm volatile("mma.sync.aligned.m16n8k8.row.col.f32.bf16.bf16.f32 {%0,%1,%2,%3},{%4,%5},{%6},{%0,%1,%2,%3};"
                 : "+f"(d[0]), "+f"(d[1]), "+f"(d[2]), "+f"(d[3]) : "r"(a0), "r"(a1), "r"(b0));
}
__device__ __forceinline__ uint32_t pack2(float lo, float hi) {
    uint32_t r; asm("cvt.rn.bf16x2.f32 %0, %1, %2;" : "=r"(r) : "f"(hi), "f"(lo)); return r;
}
__device__ __forceinline__ uint32_t hadd2(uint32_t a, uint32_t b) {
    uint32_t r; asm("add.rn.bf16x2 %0, %1, %2;" : "=r"(r) : "r"(a), "r"(b)); return r;
}
__device__ __forceinline__ float bflo(uint32_t u) { return __uint_as_float(u << 16); }
__device__ __forceinline__ float bfhi(uint32_t u) { return __uint_as_float(u & 0xffff0000u); }
__device__ __forceinline__ float ex2(float x) { float r; asm("ex2.approx.ftz.f32 %0, %1;" : "=f"(r) : "f"(x)); return r; }
__device__ __forceinline__ uint4 ldg_rlx4(const void* p) {
    uint4 v; asm volatile("ld.relaxed.gpu.global.v4.u32 {%0,%1,%2,%3}, [%4];" : "=r"(v.x), "=r"(v.y), "=r"(v.z), "=r"(v.w) : "l"(p) : "memory"); return v;
}
__device__ __forceinline__ uint2 ldg_rlx2(const void* p) {
    unsigned long long v; asm volatile("ld.relaxed.gpu.global.b64 %0, [%1];" : "=l"(v) : "l"(p) : "memory");
    return make_uint2((uint32_t)v, (uint32_t)(v >> 32));
}
__device__ __forceinline__ uint32_t ldg_rlx1(const void* p) {
    uint32_t v; asm volatile("ld.relaxed.gpu.global.u32 %0, [%1];" : "=r"(v) : "l"(p) : "memory"); return v;
}
__device__ __forceinline__ void stg_rlx1(void* p, uint32_t v) { asm volatile("st.relaxed.gpu.global.u32 [%0], %1;" ::"l"(p), "r"(v) : "memory"); }
__device__ __forceinline__ void stg_rlx2(void* p, uint32_t x, uint32_t y) {
    unsigned long long v = (unsigned long long)x | ((unsigned long long)y << 32);
    asm volatile("st.relaxed.gpu.global.b64 [%0], %1;" ::"l"(p), "l"(v) : "memory");
}
__device__ __forceinline__ void stg_rlx4(void* p, uint32_t x, uint32_t y, uint32_t z, uint32_t w) {
    asm volatile("st.relaxed.gpu.global.v4.u32 [%0], {%1,%2,%3,%4};" ::"l"(p), "r"(x), "r"(y), "r"(z), "r"(w) : "memory");
}
__device__ __forceinline__ void sts4(uint32_t a, uint32_t x, uint32_t y, uint32_t z, uint32_t w) {
    asm volatile("st.shared.v4.u32 [%0], {%1,%2,%3,%4};" ::"r"(a), "r"(x), "r"(y), "r"(z), "r"(w) : "memory");
}
__device__ __forceinline__ uint4 lds4(uint32_t a) {
    uint4 v; asm volatile("ld.shared.v4.u32 {%0,%1,%2,%3}, [%4];" : "=r"(v.x), "=r"(v.y), "=r"(v.z), "=r"(v.w) : "r"(a) : "memory"); return v;
}
__device__ __forceinline__ void st_async4(uint32_t a, float x, float y, float z, float w, uint32_t bar) {
    asm volatile("st.async.shared::cluster.mbarrier::complete_tx::bytes.v4.f32 [%0], {%1,%2,%3,%4}, [%5];" ::"r"(a), "f"(x), "f"(y), "f"(z), "f"(w), "r"(bar) : "memory");
}
#define F4(d, i) "+f"(d[i]), "+f"(d[i + 1]), "+f"(d[i + 2]), "+f"(d[i + 3])
__device__ __forceinline__ void wgmma_rs32(float* d, const uint32_t* a, uint64_t b, int sc) {
    asm volatile("{.reg .pred p; setp.ne.b32 p, %21, 0;\n wgmma.mma_async.sync.aligned.m64n32k16.f32.bf16.bf16 {%0,%1,%2,%3,%4,%5,%6,%7,%8,%9,%10,%11,%12,%13,%14,%15}, {%16,%17,%18,%19}, %20, p, 1, 1, 0;}"
                 : F4(d, 0), F4(d, 4), F4(d, 8), F4(d, 12) : "r"(a[0]), "r"(a[1]), "r"(a[2]), "r"(a[3]), "l"(b), "r"(sc));
}
__device__ __forceinline__ void wgmma_ss32(float* d, uint64_t a, uint64_t b, int sc) {
    asm volatile("{.reg .pred p; setp.ne.b32 p, %18, 0;\n wgmma.mma_async.sync.aligned.m64n32k16.f32.bf16.bf16 {%0,%1,%2,%3,%4,%5,%6,%7,%8,%9,%10,%11,%12,%13,%14,%15}, %16, %17, p, 1, 1, 1, 0;}"
                 : F4(d, 0), F4(d, 4), F4(d, 8), F4(d, 12) : "l"(a), "l"(b), "r"(sc));
}
__device__ __forceinline__ void wgmma_rs40(float* d, const uint32_t* a, uint64_t b, int sc) {
    asm volatile("{.reg .pred p; setp.ne.b32 p, %25, 0;\n wgmma.mma_async.sync.aligned.m64n40k16.f32.bf16.bf16 {%0,%1,%2,%3,%4,%5,%6,%7,%8,%9,%10,%11,%12,%13,%14,%15,%16,%17,%18,%19}, {%20,%21,%22,%23}, %24, p, 1, 1, 0;}"
                 : F4(d, 0), F4(d, 4), F4(d, 8), F4(d, 12), F4(d, 16) : "r"(a[0]), "r"(a[1]), "r"(a[2]), "r"(a[3]), "l"(b), "r"(sc));
}
__device__ __forceinline__ void wgmma_ss40(float* d, uint64_t a, uint64_t b, int sc) {
    asm volatile("{.reg .pred p; setp.ne.b32 p, %22, 0;\n wgmma.mma_async.sync.aligned.m64n40k16.f32.bf16.bf16 {%0,%1,%2,%3,%4,%5,%6,%7,%8,%9,%10,%11,%12,%13,%14,%15,%16,%17,%18,%19}, %20, %21, p, 1, 1, 1, 0;}"
                 : F4(d, 0), F4(d, 4), F4(d, 8), F4(d, 12), F4(d, 16) : "l"(a), "l"(b), "r"(sc));
}
#define F16(d, i) F4(d, i), F4(d, i + 4), F4(d, i + 8), F4(d, i + 12)
template <int TA>
__device__ __forceinline__ void wgmma_ss128(float* d, uint64_t a, uint64_t b, int sc) {
    asm volatile("{.reg .pred p; setp.ne.b32 p, %66, 0;\n wgmma.mma_async.sync.aligned.m64n128k16.f32.bf16.bf16 "
                 "{%0,%1,%2,%3,%4,%5,%6,%7,%8,%9,%10,%11,%12,%13,%14,%15,%16,%17,%18,%19,%20,%21,%22,%23,%24,%25,%26,%27,%28,%29,%30,%31,"
                 "%32,%33,%34,%35,%36,%37,%38,%39,%40,%41,%42,%43,%44,%45,%46,%47,%48,%49,%50,%51,%52,%53,%54,%55,%56,%57,%58,%59,%60,%61,%62,%63}, %64, %65, p, 1, 1, %67, 1;}"
                 : F16(d, 0), F16(d, 16), F16(d, 32), F16(d, 48) : "l"(a), "l"(b), "r"(sc), "n"(TA));
}

__device__ __forceinline__ float warp_sum(float v) {
#pragma unroll
    for (int o = 16; o; o >>= 1) v += __shfl_xor_sync(~0u, v, o);
    return v;
}
__device__ __forceinline__ float bfround(float x) { return __bfloat162float(__float2bfloat16(x)); }

__device__ __forceinline__ void wait_count1(const uint32_t* p, uint32_t target) {
    int it = 0;
#pragma unroll 1
    while (true) {
        uint32_t v;
        asm volatile("ld.acquire.gpu.global.u32 %0, [%1];" : "=r"(v) : "l"(p) : "memory");
        if (v >= target) break;
        spin_guard(++it);
    }
}
__device__ __forceinline__ void red2(float* p, float a, float b) {
    asm volatile("red.relaxed.gpu.global.add.v2.f32 [%0], {%1, %2};" ::"l"(p), "f"(a), "f"(b) : "memory");
}
__device__ __forceinline__ void l2_prefetch(const void* p, uint32_t bytes) {
    asm volatile("cp.async.bulk.prefetch.L2.global [%0], %1;" ::"l"(p), "r"(bytes) : "memory");
}
__device__ __forceinline__ void signal_count(uint32_t* p) { asm volatile("red.release.gpu.global.add.u32 [%0], 1;" ::"l"(p) : "memory"); }
__device__ __forceinline__ void e_expect(uint32_t b, uint32_t tx) {
    asm volatile("{.reg .pred p; elect.sync _|p, 0xffffffff; @p mbarrier.arrive.expect_tx.shared.b64 _, [%0], %1;}" ::"r"(b), "r"(tx) : "memory");
}
__device__ __forceinline__ void e_tma2d(uint32_t dst, const CUtensorMap* m, int c0, int c1, uint32_t bar) {
    asm volatile("{.reg .pred p; elect.sync _|p, 0xffffffff;\n @p cp.async.bulk.tensor.2d.shared::cluster.global.mbarrier::complete_tx::bytes [%0], [%1, {%3, %4}], [%2];}"
                 ::"r"(dst), "l"(m), "r"(bar), "r"(c0), "r"(c1) : "memory");
}
__device__ __forceinline__ void e_tma2d_hint(uint32_t dst, const CUtensorMap* m, int c0, int c1, uint32_t bar, uint64_t pol) {
    asm volatile("{.reg .pred p; elect.sync _|p, 0xffffffff;\n @p cp.async.bulk.tensor.2d.shared::cluster.global.mbarrier::complete_tx::bytes.L2::cache_hint [%0], [%1, {%3, %4}], [%2], %5;}"
                 ::"r"(dst), "l"(m), "r"(bar), "r"(c0), "r"(c1), "l"(pol) : "memory");
}
__device__ __forceinline__ void e_tma2d_mc(uint32_t dst, const CUtensorMap* m, int c0, int c1, uint32_t bar) {
    asm volatile("{.reg .pred p; elect.sync _|p, 0xffffffff;\n @p cp.async.bulk.tensor.2d.shared::cluster.global.mbarrier::complete_tx::bytes.multicast::cluster [%0], [%1, {%3, %4}], [%2], %5;}"
                 ::"r"(dst), "l"(m), "r"(bar), "r"(c0), "r"(c1), "h"((uint16_t)3) : "memory");
}
__device__ __forceinline__ void e_prefetch(const void* p, uint32_t bytes) {
    asm volatile("{.reg .pred p; elect.sync _|p, 0xffffffff; @p cp.async.bulk.prefetch.L2.global [%0], %1;}" ::"l"(p), "r"(bytes) : "memory");
}
__device__ __forceinline__ void wait_count_w(const uint32_t* p, uint32_t target) {
    int it = 0;
#pragma unroll 1
    while (true) {
        uint32_t v;
        asm volatile("ld.acquire.gpu.global.u32 %0, [%1];" : "=r"(v) : "l"(p) : "memory");
        if (__all_sync(~0u, v >= target) | (++it > SPIN_LIMIT)) break;
        __nanosleep(100);
    }
}

#define NL 6
constexpr uint32_t SM_HB = 16384, HBK = 5120, SM_SX = 57344, SM_OX = 122880, SM_PX = 124928, SM_PA = 126976, SM_WO = 147456,
                   SM_TAB = 212992, SM_PRE = SM_TAB + 5120, SM_BAR = 227328, SM_REC_TOTAL = 227328 + 256;
constexpr uint32_t SB0 = 1024;
constexpr int B_WO = 0, B_HE = 1, B_ROLE = 2, B_HB = 3, B_W = 5;
constexpr int NB_MEM = 1, NB_QK = 2, NB_X1 = 3, NB_X2 = 4, NB_WIN = 5, NB_WG = 6, NB_KDONE = 7, NB_FIN0 = 8, NB_P = 9, NB_PX = 10, NB_G = 11, NB_A = 12, NB_B = 13, NB_C = 14, NB_S = 15;
#define D_TPV 100
#define V_POS 2
#define D_X2 410
#define D_TV 40
#define D_V 300
#define D_NEAR 1760
#define D_FAR (D_NEAR - 120)
#define E_MUL 28
#define D_WF 60
#define NE 0
#define D_H 0
#define D_W2 170
#define SETTLE 0
#define TV_POS 1
#define D_PA 0
#define NE1 10
#define H_POS 3
#define PA_POS 1
#define K_DLY 0
#define ST_BAR 1
#define W1_AT -1
#define ROT 2
#define ALIGN 0
#define CNT32 0
#define O_POS 1
#define Z_POS 0
#define QF_LATE 100
#define W0_E 3
#define H_ROT 1
#define WO_LATE 1
#define G_AT 24
#define W0_AT 4
#define W0_RS (NL - 1)
#define P_GATE 0
#define NPF (NL + 6)

struct Delays { uint32_t near, far, x2, v, w2, pa, wf, tv; };
#define MISS(i, v)
#define MISS_INIT
#define MISS_OUT
#define HT(i)
#define PROF_INIT
#define PROF(i)
#define PROFV(i, v)
#define PROF_OUT

__device__ __forceinline__ uint32_t clk32() { uint32_t t; asm volatile("mov.u32 %0, %%clock;" : "=r"(t) :: "memory"); return t; }
__device__ __forceinline__ uint32_t smid() { uint32_t t; asm volatile("mov.u32 %0, %%smid;" : "=r"(t)); return t; }
__device__ __forceinline__ uint32_t gtime() { uint32_t t; asm volatile("mov.u32 %0, %%globaltimer_lo;" : "=r"(t) :: "memory"); return t; }
__device__ __forceinline__ void spin_until(uint32_t t0, uint32_t d) { while (clk32() - t0 < d) {} }
template <int N> __device__ __forceinline__ uint32_t delay(uint32_t zero) {
    float x = __uint_as_float(clk32());
#pragma unroll
    for (int i = 0; i < N; i++) asm volatile("ex2.approx.ftz.f32 %0, %0;" : "+f"(x));
    return __float_as_uint(x) & zero;
}
__device__ __forceinline__ uint32_t opaque(uint32_t v) { return __shfl_sync(~0u, v, threadIdx.x & 31); }
__device__ __forceinline__ uint32_t xor_or(uint32_t a, uint32_t b, uint32_t t) {
    uint32_t r; asm volatile("lop3.b32 %0, %1, %2, %3, 0x7E;" : "=r"(r) : "r"(a), "r"(b), "r"(t)); return r;
}
__device__ __forceinline__ uint32_t or3(uint32_t a, uint32_t b, uint32_t c) {
    uint32_t r; asm volatile("lop3.b32 %0, %1, %2, %3, 0xFE;" : "=r"(r) : "r"(a), "r"(b), "r"(c)); return r;
}
__device__ __forceinline__ uint32_t settag(uint32_t v, uint32_t tag) {
    uint32_t r; asm("lop3.b32 %0, %1, 1, %2, 0xB8;" : "=r"(r) : "r"(v), "r"(tag)); return r;
}
__device__ __forceinline__ void ldg4_if(uint4& v, const void* p, bool c) {
    asm volatile("{.reg .pred p; setp.ne.u32 p, %5, 0; @p ld.relaxed.gpu.global.v4.u32 {%0,%1,%2,%3}, [%4];}"
                 : "+r"(v.x), "+r"(v.y), "+r"(v.z), "+r"(v.w) : "l"(p), "r"((uint32_t)c) : "memory");
}
__device__ __forceinline__ uint4 ldg_rlx2x2(const void* p) {
    unsigned long long a, b;
    asm volatile("ld.relaxed.gpu.global.v2.b64 {%0,%1}, [%2];" : "=l"(a), "=l"(b) : "l"(p) : "memory");
    return make_uint4((uint32_t)a, (uint32_t)(a >> 32), (uint32_t)b, (uint32_t)(b >> 32));
}
__device__ __forceinline__ void stg_rlx2x2(void* p, uint32_t x, uint32_t y, uint32_t z, uint32_t w) {
    asm volatile("{.reg .b64 a, b; mov.b64 a, {%1,%2}; mov.b64 b, {%3,%4}; st.relaxed.gpu.global.v2.b64 [%0], {a, b};}" ::"l"(p), "r"(x), "r"(y), "r"(z), "r"(w) : "memory");
}
__device__ __forceinline__ void ldg1_if(uint32_t& v, const void* p, bool c) {
    asm volatile("{.reg .pred p; setp.ne.u32 p, %2, 0; @p ld.relaxed.gpu.global.u32 %0, [%1];}" : "+r"(v) : "l"(p), "r"((uint32_t)c) : "memory");
}
__device__ __forceinline__ void sts2(uint32_t a, float x, float y) { asm volatile("st.shared.v2.f32 [%0], {%1,%2};" ::"r"(a), "f"(x), "f"(y) : "memory"); }
__device__ __forceinline__ void sts4f(uint32_t a, float x, float y, float z, float w) {
    asm volatile("st.shared.v4.f32 [%0], {%1,%2,%3,%4};" ::"r"(a), "f"(x), "f"(y), "f"(z), "f"(w) : "memory");
}
__device__ __forceinline__ void sts1(uint32_t a, uint32_t x) { asm volatile("st.shared.u32 [%0], %1;" ::"r"(a), "r"(x) : "memory"); }
__device__ __forceinline__ uint32_t lds1(uint32_t a) { uint32_t v; asm volatile("ld.shared.u32 %0, [%1];" : "=r"(v) : "r"(a) : "memory"); return v; }
__device__ __forceinline__ float4 lds4f(uint32_t a) {
    float4 v; asm volatile("ld.shared.v4.f32 {%0,%1,%2,%3}, [%4];" : "=f"(v.x), "=f"(v.y), "=f"(v.z), "=f"(v.w) : "r"(a) : "memory"); return v;
}
__device__ __forceinline__ float2 lds2f(uint32_t a) {
    float2 v; asm volatile("ld.shared.v2.f32 {%0,%1}, [%2];" : "=f"(v.x), "=f"(v.y) : "r"(a) : "memory"); return v;
}
__device__ __forceinline__ bool any_bit0(uint32_t x) {
    uint32_t r;
    asm volatile("{.reg .pred p, q; .reg .b32 t; and.b32 t, %1, 1; setp.ne.u32 p, t, 0; vote.sync.any.pred q, p, 0xffffffff; selp.u32 %0, 1, 0, q;}" : "=r"(r) : "r"(x));
    return r;
}
__device__ __forceinline__ float rcp_fast(float x) { float r; asm("rcp.approx.ftz.f32 %0, %1;" : "=f"(r) : "f"(x)); return r; }
__device__ __forceinline__ void stsm4(uint32_t a, uint32_t r0, uint32_t r1, uint32_t r2, uint32_t r3) {
    asm volatile("stmatrix.sync.aligned.m8n8.x4.shared.b16 [%0], {%1,%2,%3,%4};" ::"r"(a), "r"(r0), "r"(r1), "r"(r2), "r"(r3) : "memory");
}
__device__ __forceinline__ void stsm4t(uint32_t a, uint32_t r0, uint32_t r1, uint32_t r2, uint32_t r3) {
    asm volatile("stmatrix.sync.aligned.m8n8.x4.trans.shared.b16 [%0], {%1,%2,%3,%4};" ::"r"(a), "r"(r0), "r"(r1), "r"(r2), "r"(r3) : "memory");
}
__device__ __forceinline__ uint32_t and3(uint32_t a, uint32_t b, uint32_t c) {
    uint32_t r; asm("lop3.b32 %0, %1, %2, %3, 0x80;" : "=r"(r) : "r"(a), "r"(b), "r"(c)); return r;
}
__device__ __forceinline__ void red_mem(void* p, uint32_t x, uint32_t y, uint32_t z, uint32_t w, void* q, uint32_t e, bool c) {
    asm volatile("{.reg .pred p; setp.ne.u32 p, %7, 0; red.relaxed.gpu.global.add.noftz.v4.bf16x2 [%0], {%1,%2,%3,%4}; @p red.relaxed.gpu.global.add.noftz.bf16x2 [%5], %6;}"
                 ::"l"(p), "r"(x), "r"(y), "r"(z), "r"(w), "l"(q), "r"(e), "r"((uint32_t)c) : "memory");
}
__device__ __forceinline__ void stg4_if(bool c, void* p, uint32_t x) {
    asm volatile("{.reg .pred p; setp.ne.u32 p, %2, 0; @p st.relaxed.gpu.global.v4.u32 [%0], {%1,%1,%1,%1};}" ::"l"(p), "r"(x), "r"((uint32_t)c) : "memory");
}
__device__ __forceinline__ uint32_t max3u(uint32_t a, uint32_t b, uint32_t c) { return __vimax3_u32(a, b, c); }
__device__ __forceinline__ void fence_gpu() { asm volatile("fence.acq_rel.gpu;" ::: "memory"); }

__device__ __forceinline__ void h_load(uint32_t sb, const uint8_t* hsrc, int pass, uint32_t rank, uint32_t rot) {
    const uint8_t* src = hsrc + (size_t)pass * 65536;
    const uint32_t bar = sb + SM_BAR + 8 * (B_HB + (pass & 1)), dst = sb + SM_HB + (pass & 1) * 65536 + rank * 4 * HBK;
    e_expect(bar, 32768);
#pragma unroll 1
    for (int i = 0; i < H_PIECES; i++) {
        const uint32_t o = ((i + rot) & (H_PIECES - 1)) * (16384 / H_PIECES);
        asm volatile("{.reg .pred p; elect.sync _|p, 0xffffffff;\n"
                     " @p cp.async.bulk.shared::cluster.global.mbarrier::complete_tx::bytes.multicast::cluster [%0], [%1], %4, [%2], %3;}"
                     ::"r"(dst + o + (o >> 12) * 1024), "l"(src + o), "r"(bar), "h"((uint16_t)3), "n"(16384 / H_PIECES) : "memory");
    }
}
__device__ __forceinline__ void h_piece(uint32_t sb, const uint8_t* hsrc, int pass, uint32_t rank, uint32_t i, bool first) {
    const uint32_t bar = sb + SM_BAR + 8 * (B_HB + (pass & 1));
    asm volatile("{.reg .pred p, q; elect.sync _|p, 0xffffffff; setp.le.and.s32 p, %5, 64, p; setp.ne.and.u32 q, %4, 0, p;\n"
                 " @q mbarrier.arrive.expect_tx.shared.b64 _, [%2], 32768;\n"
                 " @p cp.async.bulk.shared::cluster.global.mbarrier::complete_tx::bytes.multicast::cluster [%0], [%1], 4096, [%2], %3;}"
                 ::"r"(sb + SM_HB + (pass & 1) * 65536 + (rank * 4 + i) * HBK), "l"(hsrc + (uint32_t)(pass * 65536 + i * 4096)), "r"(bar), "h"((uint16_t)3), "r"((uint32_t)first), "r"(pass) : "memory");
}
__device__ __forceinline__ uint4 ldg_b128(const void* p) {
    uint4 v;
    asm volatile("{.reg .b128 t; .reg .b64 a, b; ld.relaxed.gpu.global.b128 t, [%4]; mov.b128 {a, b}, t; mov.b64 {%0,%1}, a; mov.b64 {%2,%3}, b;}"
                 : "=r"(v.x), "=r"(v.y), "=r"(v.z), "=r"(v.w) : "l"(p) : "memory");
    return v;
}
__device__ __forceinline__ void ldg_b128_into(uint4& v, const void* p) {
    asm volatile("{.reg .b128 t; .reg .b64 a, b; ld.relaxed.gpu.global.b128 t, [%4]; mov.b128 {a, b}, t; mov.b64 {%0,%1}, a; mov.b64 {%2,%3}, b;}"
                 : "+r"(v.x), "+r"(v.y), "+r"(v.z), "+r"(v.w) : "l"(p) : "memory");
}
__device__ __forceinline__ void stg_b128_if(bool c, void* p, uint32_t x, uint32_t y, uint32_t z, uint32_t w) {
    asm volatile("{.reg .pred p; setp.ne.u32 p, %5, 0; @p st.relaxed.gpu.global.v4.u32 [%0], {%1,%2,%3,%4};}"
                 ::"l"(p), "r"(x), "r"(y), "r"(z), "r"(w), "r"((uint32_t)c) : "memory");
}
__device__ __forceinline__ float pretag(float x, uint32_t add, uint32_t keep) { return __uint_as_float((__float_as_uint(x) + add) & keep); }

template <class F, class G>
__device__ __forceinline__ void softmax_rows(uint32_t src, uint32_t dst, uint32_t g16, int row0, F ready, G mid) {
    const uint32_t u = (g16 >> 7) & 3, e = ((g16 >> 9) << 3) | ((g16 >> 4) & 7);
    uint32_t se = src + e * 8, su = se + u * 1088, d0 = dst + e * 16 + u * 4, d1 = dst + 512 + e * 4;
    int vis = row0 + (e >> 2) - 2 * (e & 3) - 8 * u;
    asm volatile("" : "+r"(se), "+r"(su), "+r"(d0), "+r"(d1), "+r"(vis));
    ready();
    const float2 p0 = lds2f(su), p1 = lds2f(su + 256), p2 = lds2f(su + 512), p3 = lds2f(su + 768);
    const float2 m0 = lds2f(se + 4352), m1 = lds2f(se + 4352 + 256), m2 = lds2f(se + 4352 + 512), m3 = lds2f(se + 4352 + 768);
    float a0 = (p0.x + p1.x) + (p2.x + p3.x), a1 = (p0.y + p1.y) + (p2.y + p3.y);
    const float a2 = (m0.x + m1.x) + (m2.x + m3.x), a3 = (m0.y + m1.y) + (m2.y + m3.y);
    if (vis < 0) a0 = -1e9f / 0.08838834764831845f;
    if (vis < 1) a1 = -1e9f / 0.08838834764831845f;
    int k = __float_as_int(fmaxf(fmaxf(a0, a1), fmaxf(a2, a3)));
    k ^= (k >> 31) & 0x7fffffff;
    const bool hi = g16 & 64;
    const int k0 = __reduce_max_sync(~0u, hi ? INT_MIN : k), k1 = __reduce_max_sync(~0u, hi ? k : INT_MIN);
    mid();
    k = hi ? k1 : k0;
    const float m = __int_as_float(k ^ ((k >> 31) & 0x7fffffff));
    const float sl2 = 0.08838834764831845f * 1.4426950408889634f, mb = -m * sl2;
    sts1(d0, pack2(ex2(fmaf(a0, sl2, mb)), ex2(fmaf(a1, sl2, mb))));
    sts1(d1, pack2(ex2(fmaf(a2, sl2, mb)), ex2(fmaf(a3, sl2, mb))));
}

__device__ __forceinline__ uint32_t pack_h2(float lo, float hi) {
    uint32_t r; asm("cvt.rn.satfinite.f16x2.f32 %0, %1, %2;" : "=r"(r) : "f"(hi), "f"(lo)); return r;
}
__device__ __forceinline__ float2 unpack_h2(uint32_t u) {
    float2 r; asm("{.reg .b16 l, h; mov.b32 {l, h}, %2; cvt.f32.f16 %0, l; cvt.f32.f16 %1, h;}" : "=f"(r.x), "=f"(r.y) : "r"(u)); return r;
}
__device__ __forceinline__ uint32_t add_h2(uint32_t a, uint32_t b) { uint32_t r; asm("add.rn.f16x2 %0, %1, %2;" : "=r"(r) : "r"(a), "r"(b)); return r; }
__device__ __forceinline__ uint32_t max_h2(uint32_t a, uint32_t b) { uint32_t r; asm("max.f16x2 %0, %1, %2;" : "=r"(r) : "r"(a), "r"(b)); return r; }
__device__ __forceinline__ void stg2_if(bool c, void* p, uint32_t x, uint32_t y) {
    asm volatile("{.reg .pred p; .reg .b64 v; setp.ne.u32 p, %3, 0; mov.b64 v, {%1, %2}; @p st.relaxed.gpu.global.b64 [%0], v;}" ::"l"(p), "r"(x), "r"(y), "r"((uint32_t)c) : "memory");
}
__device__ __forceinline__ void stg1_if(bool c, void* p, uint32_t x) {
    asm volatile("{.reg .pred p; setp.ne.u32 p, %2, 0; @p st.relaxed.gpu.global.u32 [%0], %1;}" ::"l"(p), "r"(x), "r"((uint32_t)c) : "memory");
}
struct U2 { uint32_t x, y; };
__device__ __forceinline__ U2 ldg_u2(const void* p) {
    U2 v; asm volatile("{.reg .b64 t; ld.relaxed.gpu.global.b64 t, [%2]; mov.b64 {%0, %1}, t;}" : "=r"(v.x), "=r"(v.y) : "l"(p) : "memory"); return v;
}
constexpr int POLL_LIMIT = 1 << 16;
constexpr float SM_L2E = 0.08838834764831845f * 1.4426950408889634f;
template <int V> struct IC { static constexpr int value = V; };
typedef unsigned long long u64;
__device__ __forceinline__ uint32_t lo32(u64 v) { return (uint32_t)v; }
__device__ __forceinline__ uint32_t hi32(u64 v) { return (uint32_t)(v >> 32); }
__device__ __forceinline__ u64 ldg_u64(const void* p) { u64 v; asm volatile("ld.relaxed.gpu.global.b64 %0, [%1];" : "=l"(v) : "l"(p) : "memory"); return v; }
__device__ __forceinline__ void ldg_u64_if(u64& v, const void* p, bool c) {
    asm volatile("{.reg .pred p; setp.ne.u32 p, %2, 0; @p ld.relaxed.gpu.global.b64 %0, [%1];}" : "+l"(v) : "l"(p), "r"((uint32_t)c) : "memory");
}
__device__ __forceinline__ void rec_main(uint32_t sb, const CUtensorMap* tWo, uint8_t* arena, int role, int hinfo, int wg, uint32_t zero, const Delays& dly) {
    const int hA = hinfo & 255;
    const int tid = threadIdx.x, t = tid & 127, lane = tid & 31, wi = t >> 5;
    const uint32_t bars = sb + SM_BAR;
    const int head = role >> 2, qd = role & 3, j = blockIdx.x & 1, kh = role & 1;
    const uint32_t mypar = head >= hA;
    const uint32_t wu = __reduce_max_sync(~0u, wi);
    const bool warp0 = wu == 0, warp1 = wu == 1;
    const uint8_t* hsrc = (const uint8_t*)g_himg + kh * 32768 + j * 16384;
    auto tokbase = [&](int ty) { return ((ty + 1) << 21) + blk(lb_tok(head), mypar ^ ((hinfo >> (8 + ty)) & 1)); };
    const uint32_t tbw = tokbase(wg), tbq = tokbase(0) + (qd >> 1) * 2048 + (qd & 1) * 8;
    uint32_t w[32 - NL][4];
    const uint32_t frow = ((lane >> 4) * 8 + (lane & 7)) * 128, fx = ((lane >> 3) & 1) ^ (lane & 7);
    const uint32_t wl0 = sb + wg * 65536 + frow + ((fx ^ (2 * wi)) << 4);
    {
        if (wg > 0) wait_count_w(&g_tick[32 + (lane & 3) * 8], 1);
        if (wg == 1) asm volatile("fence.proxy.async.global;" ::: "memory");
#pragma unroll 1
        for (int i = 0; i < 4; i++) mbar_wait_w(bars + 8 * (B_W + (wg == 2 ? 8 + i : 2 * i + wg)), 0);
#pragma unroll
        for (int p = NL; p < 32; p++) ldsm4t(w[p - NL], wl0 + p * 2048);
        fence_async_smem();
        bar_sync(wg < 2 ? NB_WG : NB_X2, wg < 2 ? 256 : 128);
        if (wg == 2 && wu < 3) {
            e_expect(bars + 8 * B_WO, 16384);
            e_tma2d(sb + SM_WO + wu * 16384, tWo, (wu >> 1) * 512 + qd * 128 + (wu & 1) * 64, head * DH, bars + 8 * B_WO);
            e_tma2d(sb + SM_WO + wu * 16384 + 8192, tWo, (wu >> 1) * 512 + qd * 128 + (wu & 1) * 64, head * DH + 64, bars + 8 * B_WO);
        }
        if (wg == 1 && warp0) {
            if (lane == 0) mbar_arrive_cluster(bars + 8 * B_HE, j ^ 1);
            mbar_wait_w(bars + 8 * B_HE, 0);
#pragma unroll 1
            for (int i = 0; i < 2; i++) h_load(sb, hsrc, i, j, head);
        }
        TL(3 + wg)
    }
    uint32_t g16 = opaque(t * 16);
    auto G16 = [&]() { asm volatile("" : "+r"(g16)); return g16; };
    const uint32_t sbl = sb - wu * 512;
    const uint32_t xso = blk(lb_x2(head), mypar), cu = kh * 2048 + (2 * j + (wu >> 1)) * 512;
    const uint32_t u_xo = xso + wg * 16384 + (wu & 1) * 2048 + (cu >> 1) - wu * 256, u_to = tbw + (wu & 1) * 16384 + cu - wu * 512;
    const uint32_t mrow = wg < 2 ? mem_row(wu >> 1, wg * 2 + (wu & 1), qd) : mem_row(kh, wu, 0);
    const uint32_t u_m = mrow - wu * 512, u_e = mrow + 512 - wu * (CNT32 ? 64 : 128);
#define TAB(i) lds1(sb + SM_TAB + (i) * 512 + (G16() >> 2))
    {
        const uint32_t r8 = lane & 7;
        const uint32_t tb = sb + SM_TAB + wg * 1536 + t * 4, ma = sb + SM_HB + 4096 + r8 * 128;
        if (wg < 2) {
            sts1(tb, sb + SM_WO + wi * 16384 + frow + ((fx ^ (2 * wg)) << 4));
            sts1(tb + 512, wl0);
            sts1(tb + 1024, ma + (((lane >> 3) ^ r8) << 4));
        } else {
            sts1(tb, ma + (wi & 1) * HBK + ((((wi & 2) + (lane >> 4) * 4 + ((lane >> 3) & 1)) ^ r8) << 4));
            sts1(tb + 512, ((((wi & 2) + 5) ^ r8) << 4) + ((CNT32 ? (lane & 3) == 3 : lane & 1) ? ma + ((wi & 1) + (lane >> 3) * 2) * HBK : sb + SM_HB - 128));
            sts1(tb + 1024, mem_row(role >> 6, (role >> 4) & 3, (role >> 2) & 3) + (lane < 8 ? qd * 128 + lane * 16 : 512 + qd * 32 + (lane & 1) * 16));
        }
    }
    PROF_INIT
    MISS_INIT
#define HB(ks) dadd(mkdesc(SB0 + SM_HB + ((ks) >> 2) * HBK + ((ks) & 3) * 32, 16, 1024, 1), hbo)
#define STEP_CONSTS                                                                                  \
    const uint32_t tag = (s & 1) ^ 1, ttag = ((s >> 1) & 1) ^ 1, tso = (s & 1) * 32768;              \
    G16();                            \
    const int p = s + 2, b = p & 1;                                                                  \
    uint32_t hbo = b * 4096, fz[5] = {0, 0, 0, 0, 0};                                                \
    const uint32_t ftag = (((p - 1) >> 1) & 1) ^ 1, ptag = ((p >> 1) & 1) ^ 1;                       \
    const uint32_t pso = tbw + (1 << 20) + (b ^ 1) * 32768 + j * 16384 + kh * 2048;
#define SCHED_FENCE(i) fz[i] = clk32();
#define FZ ((fz[0] | fz[1] | fz[2] | fz[3] | fz[4]) & zero)
#define BLOCK_FENCE asm volatile("pmevent 0;" ::: "memory");
    constexpr int GAP = 32 / NL;
#define l16 (sbl + g16)
#define g8 (g16 >> 1)
    uint4 u, v;
    uint8_t *pdst, *fdst;
    auto tok_pack = [&](int ty, const float* acc, uint32_t ftag, uint32_t ptag, bool later = false) {
        const bool tg = ty == 2 || !(g16 & 64);
        const uint32_t add = tg ? (ftag ^ 1) << 16 : 0u, keep = tg ? 0xfffe0000u : ~0u;
        const uint32_t add1 = ty == 2 ? 0u : add, keep1 = ty == 2 ? ~0u : keep;
        const uint32_t add2 = ty == 0 ? add : 0u, keep2 = ty == 0 ? keep : ~0u;
        v = {pack2(pretag(acc[0], add, keep), pretag(acc[1], add1, keep1)), pack2(acc[2], acc[3]),
             pack2(pretag(acc[4], add2, keep2), pretag(acc[5], add2, keep2)), pack2(acc[6], acc[7])};
        if (ty < 2) { v.x = movm(v.x); v.z = movm(v.z); v.y = movm(v.y); v.w = movm(v.w); }
        u = {pack2(pretag(acc[8], (ptag ^ 1) << 16, 0xfffe0000u), acc[9]) | ptag, pack2(acc[10], acc[11]), pack2(acc[12], acc[13]), pack2(acc[14], acc[15])};
        if (later) return;
        v.x = settag(v.x, ftag);
        if (ty == 0) v.z = settag(v.z, ftag);
    };

#pragma unroll 1
    for (int s = -2; s < 0; s++) {
        STEP_CONSTS
        (void)tag; (void)ttag; (void)tso; (void)fz;
        float acc[16];
        mbar_wait_w(bars + 8 * (B_HB + b), 0);
        wg_fence();
#pragma unroll
        for (int i = 0; i < 32; i++) {
            if (i < NL) wgmma_ss32(acc, dadd(mkdesc(SB0 + i * 2048, 8192, 1024, 1), wg * 4096), HB(i), i != 0);
            else wgmma_rs32(acc, w[i < NL ? 0 : i - NL], HB(i), 1);
        }
        wg_commit();
        uint4 pa = {0, 0, 0, 0};
        int it = 0;
#pragma unroll 1
        while ((p > 0) & any_bit0(pa.x ^ ftag) & (++it < POLL_LIMIT)) pa = ldg_b128(arena + (pso + g16));
        pdst = arena + ((pso ^ (32768 + 2048)) + G16());
        fdst = arena + ((b ^ 1) * 32768 + u_to + g16);
        wg_wait<0>();
#pragma unroll
        for (int k = 0; k < 4; k++) { acc[2 * k] += bflo((&pa.x)[k]); acc[2 * k + 1] += bfhi((&pa.x)[k]); }
        tok_pack(wg, acc, ftag, ptag);
        stg_b128_if(true, pdst, u.x, u.y, u.z, u.w);
        stg_b128_if(p > 0, fdst, v.x, v.y, v.z, v.w);
        if (p == 0) {
            TL(2)
            if (wg != 1) bar_arrive(NB_C, 288);
        }
    }
    if (wg == 1 && warp0) {
        wait_count_w(&g_tick[32 + (lane & 3) * 8], 2);
        asm volatile("fence.proxy.async.global;" ::: "memory");
        bar_sync(NB_C, 288);
        if (g16 == 0) mbar_arrive_cluster(bars + 8 * B_HE, j ^ 1);
        mbar_wait_w(bars + 8 * B_HE, 1);
        h_load(sb, hsrc, 2, j, head);
    }

    auto qk_loop = [&](auto wgc) {
        constexpr int WG = decltype(wgc)::value;
        uint32_t w0[NL][4], lm0;
        auto w0_load = [&]() {
            const uint32_t wl = TAB(WG * 3 + 1);
            lm0 = TAB(WG * 3 + 2);
#pragma unroll
            for (int k = 0; k < NL; k++) ldsm4t(w0[k], wl + k * 2048);
        };
        const uint32_t wlo = WG * 65536 - SM_WO - wu * 16384, wlx = __reduce_max_sync(~0u, (wi ^ WG) << 5);
        uint32_t tq0, lm, lm1;
        auto proj_pre = [&](int s) {
            uint32_t wz0 = zero;
#pragma unroll
            for (int k = 0; k < NL; k += 2) wz0 = and3(wz0, w0[k][0], w0[k + 1 < NL ? k + 1 : k][0]);
            lm = lm0 + (s & 1) * 65536 + wz0; lm1 = lm ^ 64;
            asm volatile("" : "+r"(lm), "+r"(lm1));
        };
        auto proj = [&](int s, auto mid) {
            bar_sync(NB_MEM, 384);
            float c[4][4];
            uint32_t bf[16][4];
#pragma unroll
            for (int it = 0; it < 3; it++) ldsm4(bf[it], (it & 1 ? lm1 : lm) + (it >> 1) * HBK);
            mid(-1);
#pragma unroll
            for (int it = 0; it < 16; it++) {
                const uint32_t* bfr = bf[it];
                if (it + 3 < 16) ldsm4(bf[it + 3 < 16 ? it + 3 : 0], (it & 1 ? lm : lm1) + ((it + 3) >> 1) * HBK);
                const uint32_t* wa = 2 * it < NL ? w0[2 * it < NL ? 2 * it : 0] : w[2 * it < NL ? 0 : 2 * it - NL];
                const uint32_t* wb = 2 * it + 1 < NL ? w0[2 * it + 1 < NL ? 2 * it + 1 : 0] : w[2 * it + 1 < NL ? 0 : 2 * it + 1 - NL];
                float *ca = c[(2 * it) & 3], *cb = c[(2 * it + 1) & 3];
                if (it < 2) { mma16816z(ca, wa, bfr[0], bfr[1]); mma16816z(cb, wb, bfr[2], bfr[3]); }
                else { mma16816(ca, wa[0], wa[1], wa[2], wa[3], bfr[0], bfr[1]); mma16816(cb, wb[0], wb[1], wb[2], wb[3], bfr[2], bfr[3]); }
                mid(it);
            }
            const uint32_t xo = u_xo + (G16() >> 1);
            float r[4];
#pragma unroll
            for (int e = 0; e < 4; e++) {
                constexpr float SH = SM_L2E / 64;
                r[e] = WG ? (c[0][e] + c[1][e]) + (c[2][e] + c[3][e]) : fmaf(c[2][e] + c[3][e], SH, (c[0][e] + c[1][e]) * SH);
            }
            const uint32_t r0 = pack2(r[0], r[1]), r1 = pack2(r[2], r[3]);
            const uint32_t m0 = movm(r0), m1 = movm(r1);
            tq0 = clk32();
            bar_arrive(NB_QK, 384);
            stg_rlx2(arena + xo, settag(m0, (s & 1) ^ 1), m1);
        };
        w0_load();
        proj_pre(0);
        if (WG == 1 || !ROT) bar_sync(NB_P, ROT ? 256 : 384);
        proj(0, [](int) {});
        if (WO_LATE && WG == 0) mbar_wait_w(bars + 8 * B_WO, 0);
#pragma unroll 1
        for (int s = 0;; s++) {
            STEP_CONSTS
            uint4 pa;
            float acc[16];
            auto acc_init = [&]() {
#pragma unroll
                for (int k = 0; k < 4; k++) { acc[2 * k] = bflo((&pa.x)[k]); acc[2 * k + 1] = bfhi((&pa.x)[k]); acc[8 + 2 * k] = __uint_as_float((&pa.x)[k] & zero); acc[9 + 2 * k] = __uint_as_float(~(&pa.x)[k] & zero); }
            };
            uint32_t wf[NPF][4], a3;
#define WF(f) ((a3 ^ (((f) & 1) * 64)) + ((f) >> 1) * 2048)
            if (WG == 1) {
                float sc[5][4];
                uint32_t sx0 = sb + SM_SX - wu * (2560 - 16) + G16() * 5;
                asm volatile("" : "+r"(sx0));
                int it = 0;
                bool bad;
#pragma unroll 1
                do {
                    uint4 kf[2][2];
                    U2 qf[2], x[8];
                    const uint32_t gz = g16 | (it & zero);
                    const uint8_t *ts = arena + (tso + tbw + gz), *tq = arena + (tso + tbq + gz), *xp = arena + (xso + (gz >> 1));
#pragma unroll
                    for (int a = 0; a < 4; a++) kf[a >> 1][a & 1] = ldg_b128(ts + (a >> 1) * 16384 + (a & 1) * 2048);
                    if (QF_LATE) spin_until(tq0, dly.x2 - QF_LATE);
#pragma unroll
                    for (int a = 0; a < 2; a++) qf[a] = ldg_u2(tq + a * 16384);
                    spin_until(tq0, dly.x2);
#pragma unroll
                    for (int i = 0; i < 8; i++) x[i] = ldg_u2(xp + (i >> 2) * 16384 + (i & 3) * 1024);
                    PROF(8)
                    const uint32_t q0[4] = {hadd2(x[0].x, x[1].x), qf[0].x, hadd2(x[0].y, x[1].y), qf[0].y};
                    const uint32_t q1[4] = {hadd2(x[2].x, x[3].x), qf[1].x, hadd2(x[2].y, x[3].y), qf[1].y};
                    PROFV(7, clk32() + (q0[0] & zero))
                    const uint32_t bt = ((qf[0].x ^ ttag) | (qf[1].x ^ ttag)) | ((kf[0][0].x ^ ttag) | (kf[0][1].x ^ ttag)) | ((kf[1][0].x ^ ttag) | (kf[1][1].x ^ ttag));
                    uint32_t bx = 0;
#pragma unroll
                    for (int i = 0; i < 8; i += 2) bx |= (x[i].x ^ tag) | (x[i + 1].x ^ tag);
                    mma16816z(sc[0], q0, kf[0][0].x, kf[0][0].y);
                    mma16816z(sc[1], q0, kf[0][0].z, kf[0][0].w);
                    mma16816z(sc[2], q0, kf[0][1].x, kf[0][1].y);
                    mma16816z(sc[3], q0, kf[0][1].z, kf[0][1].w);
                    mma16816z(sc[4], q0, hadd2(x[4].x, x[5].x), hadd2(x[4].y, x[5].y));
                    bad = any_bit0((XP & 8 ? bt & zero : bt) | bx) & (++it < POLL_LIMIT);
                    mma16816(sc[0], q1[0], q1[1], q1[2], q1[3], kf[1][0].x, kf[1][0].y);
                    mma16816(sc[1], q1[0], q1[1], q1[2], q1[3], kf[1][0].z, kf[1][0].w);
                    mma16816(sc[2], q1[0], q1[1], q1[2], q1[3], kf[1][1].x, kf[1][1].y);
                    mma16816(sc[3], q1[0], q1[1], q1[2], q1[3], kf[1][1].z, kf[1][1].w);
                    mma16816(sc[4], q1[0], q1[1], q1[2], q1[3], hadd2(x[6].x, x[7].x), hadd2(x[6].y, x[7].y));
                } while (bad);
                PROFV(13, it - 1) MISS(1, it - 1)
                sts4(sx0, pack_h2(sc[0][0], sc[0][1]), pack_h2(sc[1][0], sc[1][1]), pack_h2(sc[2][0], sc[2][1]), pack_h2(sc[3][0], sc[3][1]));
                sts1(sx0 + 64 - wu * 12, pack_h2(sc[4][0], sc[4][1]));
                bar_arrive(NB_X1, 384);
#pragma unroll
                for (int n = 0; n < 5; n++) sts2(sb + SM_SX + 2560 + g8 + n * 1088, sc[n][2], sc[n][3]);
                PROF(3)
                a3 = TAB(WG * 3);
                if (WO_LATE && s == 0) mbar_wait_w(bars + 8 * B_WO, 0);
                softmax_rows(sb + SM_SX + 2560, sb + SM_PX + 1024, g16 | (clk32() & zero), qd * 8, [&]() { BLOCK_FENCE bar_sync(NB_PX, 128); }, [&]() {
                    BLOCK_FENCE
#pragma unroll
                    for (int f = 0; f < NE1; f++) ldsm4t(wf[f], WF(f));
                    BLOCK_FENCE
                });
                PROF(4)
            } else {
                a3 = TAB(WG * 3);
                if (warp1 && (s & 3) == 1) asm volatile("fence.proxy.async.global;" ::: "memory");
                spin_until(tq0, dly.pa);
                uint4 x, y;
                int it = 0;
#pragma unroll 1
                do { x = ldg_b128(arena + (pso + g16)); y = ldg_b128(arena + (pso + tokbase(1) - tokbase(0) + g16)); }
                while (!(XP & 8) & (p <= NSEG) & any_bit0(xor_or(x.x, y.x, ftag)) & (++it < POLL_LIMIT));
                sts4(sb + SM_PA + g16, x.x, x.y, x.z, x.w);
                sts4(sb + SM_PA + 2048 + g16, y.x, y.y, y.z, y.w);
                if (NE) spin_until(tq0, dly.wf);
#pragma unroll
                for (int f = 0; f < NE; f++) ldsm4t(wf[f], WF(f));
                bar_sync(NB_X1, 384);
                if (E_MUL && g16 < 32) asm volatile("red.relaxed.gpu.global.max.u32 [%0], %1; red.relaxed.gpu.global.add.u32 [%0+4], 1;"
                                                    ::"l"(arena + ((blk(LB_TIME, 0) ^ (g16 << 8)) + qd * 1024 + (tq0 & zero))), "r"(gtime()) : "memory");
                __syncwarp();
                const uint32_t tx = clk32();
                if (H_POS == 2 && !(XP & 1) && warp1 && s + 3 <= NSEG) h_load(sb, hsrc, s + 3, j, H_ROT ? head : 0);
                spin_until(tx, dly.w2);
            }
#pragma unroll
            for (int f = WG ? NE1 : NE; f < NPF; f++) ldsm4t(wf[f], WF(f));
            PROF(5)
            if (s + 1 == NSEG) { bar_arrive(NB_X2, 384); break; }
            const uint32_t oa = l16 + SM_OX, slot = mem_slot(s + 1);
            float c[4][4];
            uint32_t ob[4][4];
            uint32_t wz = zero;
#pragma unroll
            for (int f = 0; f < NPF; f += 2) wz = and3(wz, wf[f][0], wf[f + 1 < NPF ? f + 1 : f][0]);
            BLOCK_FENCE
            bar_sync(NB_X2 + (SETTLE ? wz : 0), 384);
            ldsm4t(ob[0], oa);
            ldsm4t(ob[1], oa + 512);
            SCHED_FENCE(0)
#pragma unroll
            for (int f = 0; f < 16; f++) {
                const uint32_t *a = wf[f % NPF], *o = ob[f >> 2] + (f & 2);
                if (f < 4) mma16816z(c[f], a, o[0], o[1]);
                else mma16816(c[f & 3], a[0], a[1], a[2], a[3], o[0], o[1]);
                if (f == 3) ldsm4t(ob[2], oa + 1024);
                if (f == 5) { ldsm4t(ob[3], oa + 1536); if (NPF < 16) ldsm4t(wf[0], WF(NPF)); }
                if (f == 7) {
#pragma unroll
                    for (int k = NPF + 1; k < 16; k++) ldsm4t(wf[k - NPF], WF(k));
                }
                if (f == 3 || f == 5 || f == 7) SCHED_FENCE(f / 2)
                if (f == 11) {
#pragma unroll
                    for (int k = NL - W0_E; k < NL; k++) ldsm4t(w0[k], (a3 ^ wlx) + wlo + k * 2048);
                    SCHED_FENCE(4)
                }
            }
            const float last = c[1][3] + c[3][3], one = __uint_as_float(CNT1 << 16);
            red_mem(arena + (u_m + slot + G16()), pack2(c[0][0] + c[2][0], c[0][1] + c[2][1]), pack2(c[0][2] + c[2][2], c[0][3] + c[2][3]),
                    pack2(c[1][0] + c[3][0], c[1][1] + c[3][1]), pack2(c[1][2] + c[3][2], CNT32 && !(g16 & 16) ? last : one),
                    arena + (u_e + slot + (CNT32 ? (g16 >> 3) & ~3u : g16 >> 2)), pack2(one, last), !CNT32 || (g16 & 16));
            hbo += FZ;
            PROF(6)
            constexpr int NS = WG && W0_E < 0 ? NL : NL - W0_RS, GS = (32 - NL + NS) / NS;
            if (W0_E >= 0) {
                BLOCK_FENCE
#pragma unroll
                for (int k = NL - W0_E - 1; k >= 0; k--) ldsm4t(w0[k], (a3 ^ wlx) + wlo + k * 2048);
                lm0 = TAB(WG * 3 + 2);
                if (WG == 1) pa = lds4(sb + SM_PA + 2048 + g16);
            }
            if (WG == 0) {
                bar_arrive(NB_WIN, 384);
                if (W0_E < 0) spin_until(clk32(), dly.tv);
                pa = lds4(sb + SM_PA + g16);
                if (W0_E < 0) w0_load();
                acc_init();
                asm volatile("" : F16(acc, 0));
                BLOCK_FENCE
            }
            if (WG == 1 && K_DLY) spin_until(clk32(), dly.wf);
            wg_fence();
            bar_sync(WG ? NB_WIN : NB_B, WG ? 384 : 256);
#pragma unroll
            for (int i = 0; i < 32; i++) {
                const int k = i / GS;
                if (i >= 32 - NL + NS) wgmma_rs32(acc, w0[i < 32 - NL + NS ? 0 : i - 32 + NL], HB(i - 32 + NL), 1);
                else if (i % GS == GS - 1 && k < NS) wgmma_ss32(acc, mkdesc(SB0 + WG * 65536 + k * 2048, 8192, 1024, 1), HB(k), 1);
                else wgmma_rs32(acc, w[i - (k < NS ? k : NS)], HB(NL + i - (k < NS ? k : NS)), WG == 0 || i);
                if (WG == 1 && i == G_AT) bar_arrive(NB_B, 256);
                if (WG == 1 && i == W1_AT) w0_load();
            }
            wg_commit();
            BLOCK_FENCE
            if (WG == 1 && warp0 && !(s & 3)) wait_count_w(&g_tick[32 + ((G16() >> 4) & 3) * 8], min((s + 1) / 4 + 3, 17));
            if (WG == 1 && W0_E < 0) { pa = lds4(sb + SM_PA + 2048 + g16); if (W1_AT < 0) w0_load(); }
            auto tok_store = [&](int m) {
                if (m & 1) stg_b128_if(XP & 8 ? s == 99 : true, arena + ((b ^ 1) * 32768 + u_to + G16()), v.x, v.y, v.z, v.w);
                if (m & 2) stg_b128_if(XP & 8 ? s == 99 : p < NSEG, arena + ((pso ^ (32768 + 2048)) + G16()), u.x, u.y, u.z, u.w);
            };
            if (WG == 0) proj_pre(s + 1);
            BLOCK_FENCE
            wg_wait<0>();
            if (WG == 0 && ROT) {
                asm volatile("" : F16(acc, 0));
                proj(s + 1, [&](int it) {
                    if (it < 0) {
                        SCHED_FENCE(0)
                        asm volatile("" : F16(acc, 0));
                        tok_pack(WG, acc, ftag, ptag, true);
                        tok_store(2);
                        SCHED_FENCE(1)
                    }
                    if (it == ROT) { SCHED_FENCE(2) v.x = settag(v.x, ftag); v.z = settag(v.z, ftag); tok_store(1); SCHED_FENCE(3) }
                });
                tq0 += (fz[0] | fz[1] | fz[2] | fz[3]) & zero;
            } else {
                if (WG == 1) {
#pragma unroll
                    for (int k = 0; k < 4; k++) { acc[2 * k] += bflo((&pa.x)[k]); acc[2 * k + 1] += bfhi((&pa.x)[k]); }
                }
                tok_pack(WG, acc, ftag, ptag);
                if (WG == 1) proj_pre(s + 1);
                asm volatile("" : "+r"(u.x), "+r"(u.y), "+r"(u.z), "+r"(u.w), "+r"(v.x), "+r"(v.y), "+r"(v.z), "+r"(v.w));
                BLOCK_FENCE
                bar_sync(NB_P, ROT ? 256 : 384);
                tok_store(3);
                proj(s + 1, [](int) {});
            }
        }
    };
    if (wg == 0) {
        qk_loop(IC<0>());
    } else if (wg == 1) {
        qk_loop(IC<1>());
    } else {
        const uint32_t ONES = 0x3f803f80u, u_o = qd * 65536 + head * 2048 + wu * 384;
        uint32_t tw = 0, dl = 0, dbase = kh == mypar ? dly.near : dly.far, dst0, dx0;
        dst0 = TAB(6); dx0 = TAB(7);
        uint32_t ov[4] = {0, 0, 0, 0};
        auto o_store = [&](int s) {
            uint8_t* od = (uint8_t*)g_O + (uint32_t)(s * (32 * NH * DH * 2) + u_o + (G16() >> 2));
#pragma unroll
            for (int a = 0; a < 4; a++) stg_rlx1(od + a * 128, ov[a]);
        };
        uint4 vf[2][2], pa;
        auto vf_fetch = [&](int s) {
            const uint8_t* ts = arena + ((s & 1) * 32768 + tbw + g16);
#pragma unroll
            for (int a = 0; a < 4; a++) vf[a >> 1][a & 1] = ldg_b128(ts + (a >> 1) * 16384 + (a & 1) * 2048);
        };
        auto tok_fetch = [&](int s) {
            if (TV_POS != 1) vf_fetch(s);
            pa = ldg_b128(arena + (tbw + (1 << 20) + (~s & 1) * 32768 + j * 16384 + kh * 2048 + g16));
        };
        if (PA_POS) tok_fetch(0);
        TL(9)
        if (!WO_LATE) mbar_wait_w(bars + 8 * B_WO, 0);
        TL(6)
#pragma unroll 1
        for (int s = 0; s < NSEG; s++) {
            STEP_CONSTS
#define VFBAD ((vf[0][0].x ^ ttag) | (vf[0][1].x ^ ttag) | (vf[1][0].x ^ ttag) | (vf[1][1].x ^ ttag))
#define TOKBAD ((TV_POS == 1 ? 0 : VFBAD) | (p <= NSEG ? pa.x ^ ftag : 0))
            {
                const uint32_t dst = dst0 + b * 65536, dx = dx0 + b * 65536;
                const uint8_t *ms = arena + (u_m + mem_slot(s) + g16), *me = arena + (u_e + mem_slot(s) + (CNT32 ? (g16 >> 3) & ~3u : g16 >> 2));
                const uint32_t em = CNT32 && !(g16 & 16) ? ~0u : 0u;
                asm volatile("" : "+l"(ms), "+l"(me));
                spin_until(tw, dl);
                PROF(11)
                int it = 0;
                bool bad;
#pragma unroll 1
                do {
                    uint4 m[4];
                    uint32_t x[4];
#pragma unroll
                    for (int i = 0; i < 4; i++) m[i] = ldg_rlx4(ms + i * 1024);
#pragma unroll
                    for (int i = 0; i < 4; i++) x[i] = ldg_rlx1(me + i * 1024);
#pragma unroll
                    for (int i = 0; i < 3; i++) {
                        stsm4t(dst + i * 2 * HBK, m[i].x, m[i].y, m[i].z, m[i].w);
                        if (i == P_GATE) asm volatile("{.reg .pred p; setp.eq.s32 p, %0, 0; @p bar.arrive %1, %2;}" ::"r"(it), "n"(NB_P), "n"(ROT ? 256 : 384) : "memory");
                    }
                    uint32_t c = and3(m[0].w, m[1].w, m[2].w);
                    SCHED_FENCE(1)
                    stsm4t(dst + 6 * HBK, m[3].x, m[3].y, m[3].z, m[3].w);
                    stsm4t(dx, x[0], x[1], x[2], x[3]);
                    asm volatile("" : "+r"(c));
                    c = and3(and3(((c & m[3].w) | em) >> 16, x[0], x[1]), x[2], x[3]);
                    bad = __any_sync(~0u, !(c & CNT_ALL)) & (++it < POLL_LIMIT);
                    asm volatile("{.reg .pred p; setp.eq.u32 p, %0, 0; @p bar.arrive %1, 384;}" ::"r"((uint32_t)bad), "n"(NB_MEM) : "memory");
                } while (bad);
                if (it > 1 && s > 1) dbase += dly.tv;
                PROFV(12, it - 1)
                MISS(0, it - 1) HT(5)
                PROF(8)
            }
            if (s == 1) { TL(7) TLC(0) }
            if (s == 63) TLC(1)
            if (s == 0) TL(13)
            if (O_POS == 1) o_store(max(s - 1, 0));
            if (Z_POS && warp1) stg4_if(g16 < 512 + 160, arena + (TAB(8) + mem_slot(s + 3)), 0);
            fence_async_smem();
            hbo += fz[1] & zero;
            int it = 0;
            if (!PA_POS) tok_fetch(s);
#pragma unroll 1
            while (!(XP & 8) & any_bit0(TOKBAD) & (++it < POLL_LIMIT)) tok_fetch(s + (it & zero));
            float acc[20];
#pragma unroll
            for (int k = 0; k < 4; k++) { acc[2 * k] = bflo((&pa.x)[k]); acc[2 * k + 1] = bfhi((&pa.x)[k]); acc[8 + 2 * k] = acc[9 + 2 * k] = acc[16 + k] = __uint_as_float(pa.x & zero); }
            if (XP & 1 ? s < 1 : p <= NSEG) mbar_wait_w(bars + 8 * (B_HB + b), (p >> 1) & 1);
            asm volatile("" : F16(acc, 0), F4(acc, 16));
            BLOCK_FENCE
            wg_fence();
            bar_sync(NB_QK, 384);
#pragma unroll
            for (int i = 0; i < 32; i++) {
                const int k = i / GAP;
                if (i % GAP == GAP - 1 && k < NL) wgmma_ss40(acc, mkdesc(SB0 + 131072 + k * 2048, 8192, 1024, 1), HB(k), 1);
                else wgmma_rs40(acc, w[i - (k < NL ? k : NL)], HB(NL + i - (k < NL ? k : NL)), 1);
            }
            wg_commit();
            uint8_t* vo = arena + (u_xo + (G16() >> 1));
            pdst = arena + ((pso ^ (32768 + 2048)) + G16());
            fdst = arena + ((b ^ 1) * 32768 + u_to + g16);
            BLOCK_FENCE
            wg_wait<0>();
            PROF(9)
            stg_rlx2(vo, settag(pack2(acc[16], acc[17]), tag), pack2(acc[18], acc[19]));
            const uint32_t tv = clk32();
            if (TV_POS == 1) vf_fetch(s);
            tok_pack(2, acc, ftag, ptag);
            stg_b128_if(XP & 8 ? s == 99 : p <= NSEG, fdst, v.x, v.y, v.z, v.w);
            stg_b128_if(XP & 8 ? s == 99 : p < NSEG, pdst, u.x, u.y, u.z, u.w);
            if (O_POS == 2) o_store(max(s - 1, 0));
            if (ST_BAR) bar_sync(NB_WG, 128);
            PROF(10)
            const uint8_t* xp = arena + (xso + 32768 + (G16() >> 1));
            const uint32_t sxa = sb + SM_SX - wu * 2560 + G16() * 5;
            uint32_t xv[4], gt = 0;
            auto pv = [&](uint32_t p0, uint32_t p1, uint32_t p2, uint32_t p3, uint32_t p4, auto getv, auto done) {
                float oc[2][4], lc[4] = {0.f, 0.f, 0.f, 0.f};
                mma16816(lc, ONES, ONES, ONES, ONES, p0, p1);
                mma16816z(oc[0], &vf[0][0].x, p0, p1);
                mma16816z(oc[1], &vf[1][0].x, p0, p1);
                mma16816(lc, ONES, ONES, ONES, ONES, p2, p3);
                mma16816(oc[0], vf[0][1].x, vf[0][1].y, vf[0][1].z, vf[0][1].w, p2, p3);
                mma16816(oc[1], vf[1][1].x, vf[1][1].y, vf[1][1].z, vf[1][1].w, p2, p3);
                mma1688(lc, ONES, ONES, p4);
                getv();
                mma1688(oc[0], xv[0], xv[1], p4);
                mma1688(oc[1], xv[2], xv[3], p4);
                done(__float_as_uint(oc[0][0]) | __float_as_uint(oc[1][0]) | __float_as_uint(lc[0]));
                const float r0 = rcp_fast(lc[0]), r1 = rcp_fast(lc[1]);
                ov[0] = pack2(oc[0][0] * r0, oc[0][1] * r1); ov[1] = pack2(oc[0][2] * r0, oc[0][3] * r1);
                ov[2] = pack2(oc[1][0] * r0, oc[1][1] * r1); ov[3] = pack2(oc[1][2] * r0, oc[1][3] * r1);
            };
            bool bad;
            it = 0;
#pragma unroll 1
            do {
                U2 xr[4];
                auto load_v = [&]() {
                    if (V_POS < 3) spin_until(tv, dly.v);
#pragma unroll
                    for (int i = 0; i < 4; i++) xr[i] = ldg_u2(xp + i * 1024);
                };
                if (TV_POS == 1 && it) {
                    const uint8_t* tz = arena + (tso + tbw + (g16 | (it & zero)));
#pragma unroll
                    for (int a = 0; a < 4; a++) ldg_b128_into(vf[a >> 1][a & 1], tz + (a >> 1) * 16384 + (a & 1) * 2048);
                }
                if (!V_POS) load_v();
                if (V_POS >= 3) spin_until(tv, dly.v);
                PROF(3)
                asm volatile("{.reg .pred p; setp.eq.s32 p, %0, 0; @p bar.sync %1, 384;}" ::"r"(it), "n"(NB_X1) : "memory");
                uint4 sx[5];
                if (V_POS == 3) load_v();
#pragma unroll
                for (int i = 0; i < 5; i++) sx[i] = lds4(sxa + i * 16);
                if (V_POS == 4) load_v();
                if (it == 0) { gt = gtime(); tw = clk32(); }
                if (V_POS == 2) load_v();
                uint32_t h[5];
#pragma unroll
                for (int n = 0; n < 4; n++) h[n] = add_h2(add_h2((&sx[0].x)[n], (&sx[1].x)[n]), add_h2((&sx[2].x)[n], (&sx[3].x)[n]));
                h[4] = add_h2(add_h2(sx[4].x, sx[4].y), add_h2(sx[4].z, sx[4].w));
                uint32_t hm = max_h2(max_h2(max_h2(h[0], h[1]), h[2]), max_h2(h[3], h[4]));
                hm = max_h2(hm, __byte_perm(hm, hm, 0x1032));
                const uint32_t m1 = __shfl_xor_sync(~0u, hm, 1), m2 = __shfl_xor_sync(~0u, hm, 2), m3 = __shfl_xor_sync(~0u, hm, 3);
                float2 a[5];
#pragma unroll
                for (int n = 0; n < 5; n++) a[n] = unpack_h2(h[n]);
                if (V_POS == 1) load_v(); else SCHED_FENCE(0)
                const float mb = -64.0f * unpack_h2(max_h2(max_h2(hm, m1), max_h2(m2, m3))).x;
                uint32_t pm[5];
#pragma unroll
                for (int n = 0; n < 5; n++) pm[n] = pack2(ex2(fmaf(a[n].x, 64.0f, mb)), ex2(fmaf(a[n].y, 64.0f, mb)));
                pv(pm[0], pm[1], pm[2], pm[3], pm[4], [&]() {
                    xv[0] = hadd2(xr[0].x, xr[1].x); xv[1] = hadd2(xr[0].y, xr[1].y);
                    xv[2] = hadd2(xr[2].x, xr[3].x); xv[3] = hadd2(xr[2].y, xr[3].y);
                }, [](uint32_t) {});
                bad = any_bit0((TV_POS == 1 && !(XP & 8) ? VFBAD : 0) | (xr[0].x ^ tag) | (xr[1].x ^ tag) | (xr[2].x ^ tag) | (xr[3].x ^ tag)) & (++it < POLL_LIMIT);
                stsm4(sb + SM_OX + g16, ov[0], ov[1], ov[2], ov[3]);
            } while (bad);
            PROFV(14, it - 1) MISS(2, it - 1)
            PROF(5)
            bar_sync(NB_X2, 384);
            U2 tv2 = {0, 0};
            const uint8_t* tp = arena + (blk(LB_TIME, mypar) + (((g16 | (tw & zero)) << 6) & 0xc00));
            {
                const uint4 pp = lds4(l16 + SM_PX + 1024);
                const uint32_t p4 = lds1(sb + SM_PX + 512 + 1024 - wu * 128 + (G16() >> 2));
                if (E_MUL) tv2 = ldg_u2(tp);
                if (H_POS == 3 && !(XP & 1) && warp0 && s + 3 <= NSEG) h_load(sb, hsrc, s + 3, j, H_ROT ? head : 0);
                if (H_POS == 0 && !(XP & 1)) h_piece(sb, hsrc, s + 3, j, (wu + (H_ROT ? head : 0)) & 3, wu == 0);
                pv(pp.x, pp.y, pp.z, pp.w, p4, []() {}, [&](uint32_t r) { bar_arrive(NB_WIN + ((r | fz[0]) & zero), 384); });
            }
            dst0 = TAB(6); dx0 = TAB(7);
            const uint32_t zo = Z_POS ? 0 : TAB(8);
            PROF(6) HT(7)
            BLOCK_FENCE
            if (H_POS == 1 && !(XP & 1)) h_piece(sb, hsrc, s + 3, j, (wu + (H_ROT ? head : 0)) & 3, wu == 0);
            asm volatile("" : "+r"(tv2.y));
            it = 0;
#pragma unroll 1
            while (E_MUL && __any_sync(~0u, tv2.y < 32 * (s + 1)) & (++it < 16)) tv2 = ldg_u2(tp);
            const uint32_t e = __reduce_max_sync(~0u, tv2.x) - gt;
            MISS(3, it - 1) MISS(4, gt)
            if (PA_POS) tok_fetch(s + 1);
            if (O_POS == 0) o_store(s);
            if (!Z_POS) stg4_if(g16 < 160, arena + (zo + mem_slot(s + 3)), 0);
            dl = dbase + (e > 4096 ? 0 : e * E_MUL >> 4);
        }
        if (O_POS) o_store(NSEG - 1);
        TL(8)
    }
    PROF_OUT
    MISS_OUT
}

struct RecMaps { CUtensorMap wq, wk, wv, wo, wmod, w3, w1; };
struct RecPtrs { const bf16 *x, *mem0, *c, *wmod, *w1, *w3; uint8_t* arena; uint32_t zero; const bf16 *w2, *w4, *wo; Delays dly; };

__device__ __forceinline__ float silu_bf(const bf16* c, int i) {
    const float v = __bfloat162float(c[i]);
    return bfround(__fdividef(v, 1.0f + __expf(-v)));
}
#define LN_SEQ 0xcba6420987531ull
#define W_LATE 1000
#define W_OPEN 1400
__device__ __noinline__ uint32_t side_window_(const uint8_t* arena, uint32_t n) {
    U2 v;
    int it = 0;
#pragma unroll 1
    while (v = ldg_u2(arena + (LB_TIME << 13)), ((v.y >> 5) == n || gtime() - v.x > W_OPEN + W_LATE) && v.y < 32 * NSEG && ++it < 64) __nanosleep(100);
    it = 0;
#pragma unroll 1
    while ((int)(gtime() - v.x - W_OPEN) < 0 && ++it < 256) {}
    return v.y >> 5;
}
#define side_window(arena, n) n = side_window_(arena, n)
__device__ __noinline__ void rec_ln(uint32_t sb, const bf16* x, const uint8_t* arena, int id, int r0) {
    int r1 = 32;
    uint32_t n = 0;
    const int tid = threadIdx.x, lane = tid & 31, wid = __reduce_max_sync(~0u, tid >> 5);
    const uint32_t ring = sb + wid * 8192 + lane * 16, coef = sb + SM_PRE;
    x += (id * 8 + wid) * 2 * DM + lane * 8;
#pragma unroll 1
    for (int r = r0 - 1; r < r1; r++) {
        if (r > 3) side_window(arena, n);
        if (r + 1 < r1) {
#pragma unroll
            for (int i = 0; i < 8; i++)
                asm volatile("cp.async.cg.shared.global [%0], [%1], 16;" ::"r"(ring + (~r & 1) * 4096 + i * 512), "l"(x + (r + 1) * 64 * DM + i * 256) : "memory");
        }
        asm volatile("cp.async.commit_group; cp.async.wait_group 1;" ::: "memory");
        if (r < r0) continue;
        const uint32_t src = ring + (r & 1) * 4096;
        float m[2] = {0.f, 0.f}, rs[2];
#pragma unroll 1
        for (int ps = 0; ps < 2; ps++) {
            float t[2][2] = {{0.f, 0.f}, {0.f, 0.f}};
#pragma unroll 1
            for (int i = 0; i < 2048; i += 512) {
#pragma unroll
                for (int h = 0; h < 2; h++) {
                    const uint4 u = lds4(src + h * 2048 + i);
#pragma unroll
                    for (int e = 0; e < 4; e++) {
                        const float a = bflo((&u.x)[e]) - m[h], c = bfhi((&u.x)[e]) - m[h];
                        t[h][0] = fmaf(a, ps ? a : 1.0f, t[h][0]); t[h][1] = fmaf(c, ps ? c : 1.0f, t[h][1]);
                    }
                }
            }
            rs[0] = t[0][0] + t[0][1]; rs[1] = t[1][0] + t[1][1];
#pragma unroll 1
            for (int o = 16; o; o >>= 1) { rs[0] += __shfl_xor_sync(~0u, rs[0], o); rs[1] += __shfl_xor_sync(~0u, rs[1], o); }
            if (!ps) { m[0] = rs[0] * (1.0f / DM); m[1] = rs[1] * (1.0f / DM); }
        }
        rs[0] = rsqrtf(rs[0] * (1.0f / DM) + 1e-5f); rs[1] = rsqrtf(rs[1] * (1.0f / DM) + 1e-5f);
        if (r == r0) {
#pragma unroll 1
            for (int i = tid; i < 2 * DM / 4; i += 256) {
                float t[4];
                int it = 0;
                uint32_t ok;
#pragma unroll 1
                do {
                    uint4 u[8];
#pragma unroll
                    for (int k = 0; k < 8; k++) u[k] = ldg_rlx4(g_modp + k * 2 * DM + i * 4);
                    ok = 1;
#pragma unroll
                    for (int k = 0; k < 32; k++) { const uint32_t w = (&u[k >> 2].x)[k & 3]; ok &= w; t[k & 3] = k < 4 ? __uint_as_float(w) : t[k & 3] + __uint_as_float(w); }
                } while (!__all_sync(~0u, ok) & (++it < SPIN_LIMIT));
                const float o = i >> 8;
                const uint32_t lo = pack2(t[0], t[1]), hi = pack2(t[2], t[3]);
                sts4f(coef + (i >> 8) * 4096 + (i & 1) * 2048 + ((i & 255) >> 1) * 16, bflo(lo) + o, bfhi(lo) + o, bflo(hi) + o, bfhi(hi) + o);
            }
            bar_sync(NB_FIN0, 256);
            if (tid == 0 && r0 == 0) TL(2)
        }
        uint8_t* dst = (uint8_t*)g_himg + (r * 2 + (id >> 1)) * 65536 + (lane >> 3) * 4096 + wid * 256;
#pragma unroll 1
        for (int i = 0; i < 4; i++) {
            const uint32_t ca = coef + i * 512 + lane * 16;
            const float4 s0 = lds4f(ca), s1 = lds4f(ca + 2048), c0 = lds4f(ca + 4096), c1 = lds4f(ca + 6144);
            const float sh[8] = {s0.x, s0.y, s0.z, s0.w, s1.x, s1.y, s1.z, s1.w}, sc[8] = {c0.x, c0.y, c0.z, c0.w, c1.x, c1.y, c1.z, c1.w};
#pragma unroll
            for (int h = 0; h < 2; h++) {
                uint4 u = lds4(src + h * 2048 + i * 512);
#pragma unroll
                for (int e = 0; e < 4; e++) {
                    uint32_t& w = (&u.x)[e];
                    w = pack2(fmaf((bflo(w) - m[h]) * rs[h], sc[2 * e], sh[2 * e]), fmaf((bfhi(w) - m[h]) * rs[h], sc[2 * e + 1], sh[2 * e + 1]));
                }
                *(uint4*)(dst + i * 16384 + ((id & 1) == (i >> 1) ? 65536 : 2048) + h * 128 + (((lane ^ (2 * wid + h)) & 7) << 4)) = u;
            }
        }
        if (r == 0) {
            if (tid == 0) TLX(10)
            int ro, it = 0;
#pragma unroll 1
            do asm volatile("ld.volatile.shared.u32 %0, [%1];" : "=r"(ro) : "r"(sb + SM_BAR + 192) : "memory"); while ((ro == INT_MIN) & (++it < SPIN_LIMIT));
            if (ro >= 0) r1 = 2;
        }
        if (r && !(r & 1)) continue;
        bar_sync(r ? NB_FIN0 : NB_C, r ? 256 : 320);
        if (tid == 0 && r == 0) TLX(11)
        if (wid == (r >> 1 & 7)) {
            if (r == 1) bar_arrive(NB_B, 64);
            if (r == 3) wait_count_w(&g_tick[32 + id * 8], 2);
            if (lane == 0) { signal_count(&g_tick[32 + id * 8]); if (r == 0) TLX(12) }
            __syncwarp();
        }
    }
}
#define SIDE_T 300
template <int NQ>
__device__ __forceinline__ void side_gemv(const CUtensorMap* tm, int c0, int k0, int k1, uint32_t cs, uint32_t sb, const uint8_t* arena, uint32_t& n, uint32_t& ph, float (*acc)[8], bool once = false) {
    const uint32_t w = __reduce_max_sync(~0u, threadIdx.x >> 5 & 3), ring = sb + 65536 + w * 24576, bars = sb + SM_BAR + 8 * B_W + w * 24;
#pragma unroll
    for (int q = 0; q < NQ; q++)
#pragma unroll
        for (int j = 0; j < 8; j++) acc[q][j] = 0.f;
#pragma unroll 1
    for (; k0 < k1; k0 += 48, ph ^= 1) {
        const int nr = min(48, k1 - k0);
        side_window(arena, n);
        const uint32_t t0 = clk32();
#pragma unroll 1
        for (int g = 0; g < 3; g++) {
            spin_until(t0, (g * 4 + w) * (SIDE_T / 4));
            e_expect(bars + 8 * g, g * 16 < nr ? 8192 : 0);
            if (g * 16 < nr) e_tma2d_hint(ring + g * 8192, tm, c0, k0 + g * 16, bars + 8 * g, once ? EVICT_FIRST : EVICT_NORMAL);
        }
#pragma unroll 1
        for (int r = 0; r < nr; r += 16) {
            mbar_wait_w(bars + (r >> 1), ph);
            uint4 v[16];
#pragma unroll
            for (int h = 0; h < 16; h++) v[h] = lds4(ring + (r + h) * 512 + (threadIdx.x & 31) * 16);
            float4 cf[NQ][4];
#pragma unroll
            for (int q = 0; q < NQ * 4; q++) cf[q >> 2][q & 3] = lds4f(cs + ((q >> 2) * DM + k0 + r + (q & 3) * 4) * 4);
#pragma unroll
            for (int h = 0; h < 16; h++) {
                const float f[8] = {bflo(v[h].x), bfhi(v[h].x), bflo(v[h].y), bfhi(v[h].y), bflo(v[h].z), bfhi(v[h].z), bflo(v[h].w), bfhi(v[h].w)};
#pragma unroll
                for (int q = 0; q < NQ; q++)
#pragma unroll
                    for (int j = 0; j < 8; j++) acc[q][j] = fmaf((&cf[q][h >> 2].x)[h & 3], f[j], acc[q][j]);
            }
        }
        fence_async_smem();
        __syncwarp();
    }
}
__device__ __noinline__ void rec_side(float* sm, const RecMaps& mp, const RecPtrs& p, int id) {
    const int tid = threadIdx.x;
    if (tid < 256) {
        if (blockIdx.x < 128) rec_ln(smem_u32(sm), p.x, p.arena, id, 2);
        if (tid == 0) TL(14)
        for (int i = tid; i < 2 * S_; i += 256) g_st[id * 2 * S_ + i] = 0.f;
        if (id == 0 && tid < 64) g_pcnt[tid * 8] = 0;
        if (id == 1) for (int i = tid; i < 6 * 256; i += 256) g_pflag[i] = 0;
        if (id == 2 && tid == 0) g_pt = 0;
        bar_sync(NB_FIN0, 256);
        if (PDL && tid == 0) asm volatile("fence.acq_rel.gpu; griddepcontrol.launch_dependents;" ::: "memory");
        return;
    }
    const int t = tid - 256;
    float *coef = sm + 40960, *red = coef + 3 * DM;
    const uint32_t sb = smem_u32(sm), cs = smem_u32(coef);
    uint32_t n = 0, ph = 0;
    for (int i = t; i < DM; i += 128) { coef[i] = silu_bf(p.c, i); coef[2 * DM + i] = 1.0f; }
    if (t == 0) wait_count1(&g_tick[32], 1);
    bar_sync(NB_G, 128);
    const int w = __reduce_max_sync(~0u, t >> 5);
    float acc[3][8];
    side_gemv<1>(&mp.wmod, (2 + id) * DM + w * 256, 0, DM, cs, sb, p.arena, n, ph, acc, true);
#pragma unroll
    for (int j = 0; j < 8; j++) g_mod[(2 + id) * DM + t * 8 + j] = bfround(acc[0][j]);
    bar_sync(NB_G, 128);
    if (t == 0) signal_count(&g_tick[8]);
    side_gemv<1>(&mp.w3, id * (FF / 4) + w * 256, 0, DM, cs + 8 * DM, sb, p.arena, n, ph, acc);
    if (t < FF / 32) {
#pragma unroll
        for (int j = 0; j < 8; j++) g_vec[3 * DM + id * (FF / 4) + t * 8 + j] = acc[0][j];
    }
    if (t == 0) wait_count1(&g_tick[8], 4);
    bar_sync(NB_G, 128);
    for (int i = t; i < DM; i += 128) { coef[i] = 1.0f + __ldcg(g_mod + 4 * DM + i); coef[DM + i] = __ldcg(g_mod + 3 * DM + i); }
    bar_sync(NB_G, 128);
    if (id == 1 && t < 32) {
        float u[5] = {0, 0, 0, 0, 0};
        for (int i = t; i < DM; i += 32) {
            const float a = coef[i], b = coef[DM + i];
            u[0] += a; u[1] += a * a; u[2] += a * b; u[3] += b; u[4] += b * b;
        }
#pragma unroll
        for (int q = 0; q < 5; q++) { const float r = warp_sum(u[q]); if (t == 0) g_cst[q] = r * (1.0f / DM); }
    }
    side_gemv<3>(&mp.w1, id * 256, w * 256, w * 256 + 256, cs, sb, p.arena, n, ph, acc);
#pragma unroll
    for (int q = 0; q < 3; q++)
#pragma unroll
        for (int j = 0; j < 8; j++) red[((t >> 5) * 3 + q) * 256 + (t & 31) * 8 + j] = acc[q][j];
    bar_sync(NB_G, 128);
    for (int i = t; i < 768; i += 128) g_vec[(i >> 8) * DM + id * 256 + (i & 255)] = (red[i] + red[768 + i]) + (red[1536 + i] + red[2304 + i]);
    if (t == 0) TL(9)
}

__global__ void __cluster_dims__(2, 1, 1) __launch_bounds__(384, 1)
k_rec(const __grid_constant__ RecMaps mp, const __grid_constant__ RecPtrs p) {
    extern __shared__ uint8_t smraw[];
    const uint32_t sb = smem_u32(smraw);
    if ((sb & 0x3FFFF) != SB0) __trap();
    const uint32_t bars = sb + SM_BAR;
    const int tid = threadIdx.x, lane = tid & 31, b = blockIdx.x;
    const int wid = __reduce_max_sync(~0u, tid >> 5);
    const uint32_t rank = b & 1;
    uint8_t* arena = p.arena;
    volatile int* sinfo = (volatile int*)(smraw + SM_BAR + 192);
    if (tid == 0) TL(0)
    if (tid == 0) sinfo[0] = INT_MIN;
    if (tid == 352) {
        for (int i = 0; i < 17; i++) mbar_init(bars + 8 * i, i == B_WO ? 4 : 1);
        asm volatile("fence.mbarrier_init.release.cluster;" ::: "memory");
    }
    __syncwarp();
    asm volatile("barrier.cluster.arrive.relaxed.aligned;" ::: "memory");
    int pr = 0, hA = 0;
    if (wid < 8) {
        if (b < 128) {
            const int cb = (b & 15) * 128, k0 = (b >> 4) * 128 + (tid >> 4);
            uint4 v[8];
#pragma unroll
            for (int i = 0; i < 8; i++) v[i] = __ldg((const uint4*)(p.wmod + (size_t)(k0 + 16 * i) * (6 * DM) + cb + (tid & 15) * 8));
            float acc[8] = {0, 0, 0, 0, 0, 0, 0, 0};
            const float s8 = silu_bf(p.c, k0 + 16 * (lane & 7));
#pragma unroll
            for (int i = 0; i < 8; i++) {
                const float sv = __shfl_sync(~0u, s8, i, 16);
                acc[0] += sv * bflo(v[i].x); acc[1] += sv * bfhi(v[i].x); acc[2] += sv * bflo(v[i].y); acc[3] += sv * bfhi(v[i].y);
                acc[4] += sv * bflo(v[i].z); acc[5] += sv * bfhi(v[i].z); acc[6] += sv * bflo(v[i].w); acc[7] += sv * bfhi(v[i].w);
            }
            float* red = (float*)(smraw + SM_PRE);
            *(float4*)(red + (tid >> 4) * 128 + (tid & 15) * 8) = make_float4(acc[0], acc[1], acc[2], acc[3]);
            *(float4*)(red + (tid >> 4) * 128 + (tid & 15) * 8 + 4) = make_float4(acc[4], acc[5], acc[6], acc[7]);
            bar_sync(NB_FIN0, 256);
            if (wid < 4) {
                float t = 0;
#pragma unroll
                for (int i = 0; i < 16; i++) t += red[i * 128 + tid];
                stg_rlx1(&g_modp[(b >> 4) * 2 * DM + cb + tid], __float_as_uint(t) | 1u);
                TLX(14)
            }
        } else {
            rec_ln(sb, p.x, p.arena, b - 128, 0);
        }
    } else if (wid >= 10 && b >= 128) {
        {
            const int w = (b - 128) * 2 + wid - 10;
            const uint16_t* src = (const uint16_t*)p.mem0 + (lane & 3) * 2 * DM + (w >> 2) * 512 + (w & 1) * 64 + (w & 2) * 8 + (lane >> 2);
            uint32_t v[4][4];
#pragma unroll
            for (int i = 0; i < 16; i++) v[i >> 2][i & 3] = src[(i >> 2) * 128 + (i & 2) * 16 + (i & 1) * 8] | ((uint32_t)src[DM + (i >> 2) * 128 + (i & 2) * 16 + (i & 1) * 8] << 16);
            uint8_t* d = arena + mem_row(w >> 2, w & 3, 0);
            uint8_t* e = d + 512 + (CNT32 ? lane >> 1 : lane) * 4;
            d += lane * 16;
#pragma unroll
            for (int i = 0; i < 4; i++, d += 1024, e += 1024) {
                stg_rlx4(d, v[i][0], v[i][1], v[i][2], CNT32 && !(lane & 1) ? v[i][3] : (v[i][3] & 0xffff) | CNT_ALL << 16);
                stg_rlx4(d + mem_slot(1), 0, 0, 0, 0);
                stg_rlx4(d + mem_slot(2), 0, 0, 0, 0);
                if (!CNT32 || (lane & 1)) { stg_rlx1(e, (v[i][3] & 0xffff0000u) | CNT_ALL); stg_rlx1(e + mem_slot(1), 0); stg_rlx1(e + mem_slot(2), 0); }
            }
            if (w == 0 && lane < 8) stg_rlx2(arena + (LB_TIME << 13) + lane * 1024, 0, 0);
            bar_arrive(NB_C, 320);
        }
    } else if (rank == 0) {
        uint32_t best = ~0u;
        const int pg = wid < 10 ? 0 : 1 + (b >> 1) / 22;
        uint32_t* q = (uint32_t*)(arena + (pg << 21) + (pg ? blk(b >> 1, wid & 1) : blk(LB_PROBE, wid & 1) + b * 16));
        if (lane < 8) stg_rlx1(q + lane, 0);
        __syncwarp();
        if (lane == 0) {
            q += 3;
            uint32_t v = atomicAdd(q, 1u);
#pragma unroll 1
            for (int r = 0; r < NPROBE; r++) {
                const uint32_t t0 = clk32() + (v >> 8);
                v = atomicAdd(q + (v >> 8), 1u);
                uint32_t t1;
                asm volatile("{.reg .pred p; setp.eq.u32 p, %1, 0xffffffff; @p exit; mov.u32 %0, %%clock;}" : "=r"(t1) : "r"(v) : "memory");
                best = min(best, t1 - t0);
            }
            sinfo[wid - 6] = best;
        }
        bar_sync(NB_KDONE, b < 128 ? 128 : 64);
        if (tid == 256) {
            const uint32_t par = sinfo[2] > sinfo[3], vote = b < 128 && (sinfo[4] > sinfo[5]) != par;
            stg_rlx2(&g_clk[b >> 1], ((clk32() - 2 * gtime()) & ~127u) | b >> 1, 1 + 2 * par + 4 * vote);
        }
    }
    if (wid == 8) {
        U2 v[3], my;
        uint32_t c0;
        const int me = b >> 1;
        int it = 0;
        __syncwarp();
#pragma unroll 1
        do {
            my = ldg_u2(&g_clk[me]);
#pragma unroll
            for (int k = 0; k < 3; k++) v[k] = ldg_u2(&g_clk[k * 22 + min(lane, 21)]);
        } while (!__all_sync(~0u, my.y & v[0].y & v[1].y & v[2].y & 1) & (++it < SPIN_LIMIT));
        TLX(15)
        c0 = __reduce_min_sync(~0u, lane ? ~0u : v[0].x) - 4096;
        const uint32_t mc = me >= 64 ? ~0u : my.x - c0;
        const int par = my.y >> 1 & 1;
        uint32_t cnt = 0, flip = 0;
#pragma unroll
        for (int k = 0; k < 3; k++) {
            const uint32_t c = v[k].x - c0, o = v[k].y >> 1 & 1;
            const bool ln = k == 2 && lane >= 20;
            cnt += o + (o == par ? (ln ? 44 + lane < me : c < mc) * 256 + (c < my.x - c0) * 65536 : 0);
            flip |= __popc(__ballot_sync(~0u, v[k].y & 4) & 0x3fffff) > 10 ? 256 << k : 0;
        }
        cnt = __reduce_add_sync(~0u, lane < 22 ? cnt : 0);
        const int n1 = cnt & 255, n0 = 66 - n1, tk = cnt >> 8 & 255;
        if (lane == 0) g_cls[smid() & 255] = cnt < 32 << 16 ? par * 4 + (cnt >> 19) : 8;
        hA = min(n0 >> 1, NH);
        const int q0 = 2 * hA, q1 = 2 * NH - q0;
        const int over = tk - (par ? q1 : q0), lack = max(par ? q0 - n0 : q1 - n1, 0);
        if (over < 0) pr = par ? q0 + tk : tk;
        else if (over < lack) pr = (par ? n0 : q0 + n1) + over;
        else pr = -1 - (over - lack + (par ? max(n0 - q0, 0) : 0));
        hA |= flip;
        if (lane == 0) {
            sinfo[1] = hA; sinfo[0] = pr;
            if (b >= 128 && rank == 0) atomicOr(&g_tick[6], (pr < 0 ? 4u : 1u) << ((b - 128) >> 1));
        }
    }
    asm volatile("barrier.cluster.wait.aligned;" ::: "memory");
    if (wid == 8) {
        TL(1)
        __syncwarp();
        bar_arrive(NB_A, 288);
        bar_arrive(NB_S, 128);
        if (b >= 128 && pr < 0) bar_sync(NB_B, 64);
        if (pr >= 0) {
            const int pu = __reduce_max_sync(~0u, pr), c0 = (pu >> 1) * 128 + rank * 64, r0 = (pu & 1) * 512;
#pragma unroll 1
            for (int n = 0; n < 13; n++) {
                const u64 seq = b >= 128 ? LN_SEQ : 0xcba9876543210ull;
                const int i = seq >> (4 * n) & 15;
                if (b >= 128 && i == 0) bar_sync(NB_B, 64);
                if (n >= W_INFL) mbar_wait_w(bars + 8 * (B_W + (seq >> (4 * (n - W_INFL)) & 15)), 0);
                const int m = i < 8 ? i & 1 : i >> 2, k = i < 8 ? i >> 1 : i & 3;
                const uint32_t dst = sb + m * 65536 + k * 16384, br = bars + 8 * (m < 3 ? B_W + i : B_WO);
                const int c = m < 3 ? c0 : 576 + rank * 256 + (pu & 1) * 128, r = m < 3 ? r0 + k * 128 : (pu >> 1) * DH;
                const uint64_t pol = m < 3 ? EVICT_FIRST : EVICT_NORMAL;
                e_expect(br, 16384);
                e_tma2d_hint(dst, &mp.wq + m, c, r, br, pol);
                e_tma2d_hint(dst + 8192, &mp.wq + m, c, r + 64, br, pol);
            }
        }
    } else {
        bar_sync(wid < 8 ? NB_A : NB_S, wid < 8 ? 288 : 128);
    }
    const int prr = __reduce_max_sync(~0u, sinfo[0]);
    hA = __reduce_max_sync(~0u, sinfo[1]);
    if (prr < 0) {
        int j = (b - 128) >> 1;
        if (b < 128) {
            uint32_t v;
            int it = 0;
#pragma unroll 1
            do { v = __reduce_max_sync(~0u, ldg_rlx1(&g_tick[6])); spin_guard(++it); } while (__popc(v) < 2);
            j = v == 3 ? -1 - prr : (v & 1) ^ 1;
        }
        rec_side((float*)smraw, mp, p, j * 2 + rank);
        return;
    }
    if (PDL) asm volatile("griddepcontrol.launch_dependents;" ::: "memory");
    const int role = (prr >> 1) * 4 + rank * 2 + (prr & 1);
    rec_main(sb, &mp.wo, arena, role, hA, wid >> 2, p.zero, p.dly);
}

__device__ __forceinline__ void wgmma_ss192(float* d, uint64_t a, uint64_t b, int sc) {
    asm volatile("{.reg .pred p; setp.ne.b32 p, %98, 0;\n wgmma.mma_async.sync.aligned.m64n192k16.f32.bf16.bf16 "
                 "{%0,%1,%2,%3,%4,%5,%6,%7,%8,%9,%10,%11,%12,%13,%14,%15,%16,%17,%18,%19,%20,%21,%22,%23,%24,%25,%26,%27,%28,%29,%30,%31,%32,%33,%34,%35,%36,%37,%38,%39,%40,%41,%42,%43,%44,%45,%46,%47,%48,%49,%50,%51,%52,%53,%54,%55,%56,%57,%58,%59,%60,%61,%62,%63,%64,%65,%66,%67,%68,%69,%70,%71,%72,%73,%74,%75,%76,%77,%78,%79,%80,%81,%82,%83,%84,%85,%86,%87,%88,%89,%90,%91,%92,%93,%94,%95}, %96, %97, p, 1, 1, 0, 1;}"
                 : F16(d, 0), F16(d, 16), F16(d, 32), F16(d, 48), F16(d, 64), F16(d, 80) : "l"(a), "l"(b), "r"(sc));
}

constexpr uint32_t P_B = 81920, P_PL = 40960, P_OUT = 180224, P_VEC = 212992, P_ROW = P_VEC + 6144, P_BAR = P_ROW + 4096, P_SMEM = P_BAR + 256;
#define PPH 1
#define FLAG_ST "st.release.gpu.global.u32"
#define FLAG_LD "ld.acquire.gpu.global.u32"
#define PX 0
#define MIDF 0
#define DS_AT 3
constexpr int ST = 5;
constexpr int PB_F = 0, PB_E = 5, PB_R = 10, PB_OUT = 16;
enum { C_Y = 0, C_G = 1, C_X1 = 2, C_U = 3, C_S1 = 8, C_S3 = 9 };
enum { V_GA = 0, V_A = 1, V_B = 2, V_GB = 3, V_VA = 4, V_VB = 5, V_VC = 6, V_C3 = 7 };
struct PostMaps { CUtensorMap o, wo, y, w1, g, w2, x1, w3, u, w4, out; };
struct PostPtrs { const bf16* x; };

struct GeluK { float k0, k1, kh; };
__device__ __forceinline__ GeluK gelu_k(float c) { return {0.7978845608028654f * c, 0.7978845608028654f * 0.044715f * c * c * c, 0.5f * c}; }
__device__ __forceinline__ float gelu_s(float t, const GeluK& k) {
    const float u = t * fmaf(t * t, k.k1, k.k0);
    float th; asm("tanh.approx.f32 %0, %1;" : "=f"(th) : "f"(u));
    const float hx = k.kh * t;
    return fmaf(hx, th, hx);
}
__device__ __forceinline__ float2 ldsv(uint32_t a) {
    float2 v; asm("ld.shared.v2.f32 {%0,%1}, [%2];" : "=f"(v.x), "=f"(v.y) : "r"(a)); return v;
}
__device__ __forceinline__ void wait_smem(uint32_t a, int target) {
    int it = 0;
#pragma unroll 1
    while (true) {
        int v;
        asm volatile("ld.acquire.cta.shared.u32 %0, [%1];" : "=r"(v) : "r"(a) : "memory");
        if (__all_sync(~0u, v >= target) | (++it > SPIN_LIMIT)) break;
    }
}

#define PP(i)
#define PH_(c, w, i)
__device__ __forceinline__ void mbar_wait_b(uint32_t b, uint32_t par) {
    int it = 0;
#pragma unroll 1
    while (!__all_sync(~0u, mbar_try(b, par)) & (++it < SPIN_LIMIT)) {}
}
__device__ __forceinline__ void release(uint32_t rel, int st, bool c) {
    asm volatile("{.reg .pred p; setp.ne.u32 p, %1, 0; setp.ne.and.u32 p, %2, 0, p; @p mbarrier.arrive.shared::cluster.b64 _, [%0];}"
                 ::"r"(rel + 8 * (st ? st - 1 : ST - 1)), "r"(rel), "r"((uint32_t)c) : "memory");
}
struct Pipe { int st, ph; uint32_t rel; };
__device__ __forceinline__ void adv(Pipe& p) { if (++p.st == ST) { p.st = 0; p.ph ^= 1; } }

__device__ __forceinline__ void post_weights(uint32_t sb, const PostMaps& mp, int nb, int rank) {
    const uint32_t full = sb + P_BAR + 8 * PB_F, empty = sb + P_BAR + 8 * PB_E;
    int st = 0, pp = 1;
#pragma unroll 1
    for (int ph = 0; ph < 7; ph++) {
        const int NK = ph == 0 ? 64 : ph == 6 ? 56 : 16, km = NK == 16 ? 15 : 63;
        const CUtensorMap* tb = &mp.wo + 2 * (ph < 3 ? ph : ph < 6 ? 3 : 4);
        const bool w3 = ph >= 3 && ph < 6;
        const int n0 = w3 ? nb * 64 + (ph == 4 ? 1536 : ph == 5 ? 2560 : 0) : nb * 128, dn = w3 ? 512 : 64;
        const int rot = NK == 16 ? 2 * (nb & 6) : 0, sw = ph == 1 || ph == 3 ? 2 * rank : 0;
#pragma unroll 1
        for (int i = 0; i < NK; i++) {
            const int k0 = (((i < 4 ? i ^ sw : i) + rot) & km) * 64;
            const uint32_t a = sb + P_B + st * 8192, f = full + 8 * st;
            mbar_wait_b(empty + 8 * st, pp);
            e_expect(f, ph == 3 ? 40960 : 32768);
            e_tma2d(a, tb, n0, k0, f);
            e_tma2d(a + P_PL, tb, n0 + dn, k0, f);
            if (ph == 3) e_tma2d(a + 2 * P_PL, tb, n0 + 1024, k0, f);
            if (++st == ST) { st = 0; pp ^= 1; }
        }
    }
#pragma unroll 1
    for (int i = 0; i < ST; i++) mbar_wait_b(empty + 8 * i, pp ^ (i < st));
}
__device__ __forceinline__ void post_acts(uint32_t sb, const PostMaps& mp, int mb, int nb, int rank) {
    const int rh = 2 * mb + rank, lane = threadIdx.x & 31;
    const uint32_t full = sb + P_BAR + 8 * PB_F, empty = sb + P_BAR + 8 * PB_E;
    int st = 0, pp = 1;
#pragma unroll 1
    for (int ph = 0; ph < 7; ph++) {
        const int NK = ph == 0 ? 64 : ph == 6 ? 56 : 16, km = NK == 16 ? 15 : 63;
        const CUtensorMap* ta = &mp.o + 2 * (ph < 3 ? ph : ph < 6 ? 3 : 4);
        const int amul = ph == 0 ? 256 : 64, arow = ph == 0 ? rh * 8 : rh * 64;
        const int rot = NK == 16 ? 2 * (nb & 6) : 0, own = ph == 1 || ph == 3 ? 4 : 0;
        const uint32_t shifts = ph == 2 ? 0x04000301u : 0x02020202u;
        const uint32_t* fl = &g_pflag[(ph == 6 ? C_U : min(ph - 1, 2)) * 256 + (ph == 2 ? min(max(rh + min(lane >> 3, 2) - 1, 0), 31) : rh) * 8 + (lane & 7)];
        uint32_t have = ph == 0 || ph == 5;
        if (own) { if (st) { st--; pp ^= 1; } else st = 4; }
#pragma unroll 1
        for (int i = own; i < NK; i++) {
            const int kb = (i + rot) & km;
            const uint32_t need = ph == 6 ? 255u : (ph == 2 ? 0x10101u : 1u) << ((kb >> 1) & 7), lvl = ph == 6 ? i >> 3 : 0;
            PH_(ph == PPH && i == own, 0, 27) PH_(ph == PPH && i == own, 1, 27)
            if ((__ballot_sync(~0u, have > lvl) & need) != need) {
                int it = 0;
#pragma unroll 1
                do asm volatile(FLAG_LD " %0, [%1];" : "=r"(have) : "l"(fl) : "memory");
                while (((__ballot_sync(~0u, have > lvl) & need) != need) & (++it < SPIN_LIMIT));
                PH_(ph == PPH && i == own, 0, 23) PH_(ph == PPH, 0, 24) PH_(ph == PPH && i == own, 1, 23) PH_(ph == PPH, 1, 24)
                asm volatile("fence.proxy.async.global;" ::: "memory");
            }
            const int d = own && (i == 5 || i == 6) ? 2 : 0, s2 = st + d < ST ? st + d : st + d - ST;
            mbar_wait_b(empty + 8 * s2, pp ^ (s2 < st));
            e_tma2d_mc(sb + st * 16384 + rank * 8192, ta, kb * amul, arow + (int)((shifts >> ((kb & 12) * 2)) & 7) - 2, full + 8 * st);
            if (++st == ST) { st = 0; pp ^= 1; }
        }
    }
}

template <int PH, bool EARLY = false, class F>
__device__ __forceinline__ void post_kb(uint32_t sb, float* acc, Pipe& p, int wg, bool lead, bool first, F mid) {
    constexpr uint64_t DA = PH == 0 ? mkdesc(SB0, 128, 1024, 0) : mkdesc(SB0, 16, 1024, 1);
    constexpr uint64_t DB = mkdesc(SB0 + P_B, P_PL, 1024, 1);
    mbar_wait_b(sb + P_BAR + 8 * PB_F + 8 * p.st, p.ph);
    const uint32_t a = (uint32_t)DA + p.st * 1024 + wg * 512, b = (uint32_t)DB + p.st * 512;
    wg_fence();
#pragma unroll
    for (int k = 0; k < 4; k++) {
        const uint64_t da = (DA & 0xffffffff00000000ull) | (a + k * (PH == 0 ? 16 : 2)), db = (DB & 0xffffffff00000000ull) | (b + k * 128);
        if (PH == 3) wgmma_ss192(acc, da, db, k || !first);
        else wgmma_ss128<PH == 0>(acc, da, db, k || !first);
    }
    wg_commit();
    if (EARLY) mid();
    wg_wait<1>();
    release(p.rel, p.st, !first);
    if (!EARLY) mid();
    adv(p);
}
__device__ __forceinline__ void post_end(uint32_t sb, Pipe& p, bool lead) {
    wg_wait<0>();
    release(p.rel, p.st, true);
}
template <int PH>
__device__ __forceinline__ void post_mma(uint32_t sb, float* acc, Pipe& p, int wg, bool lead, int nout, int pi, int mb, int nb) {
#pragma unroll 1
    for (int kb = 0; kb < 16; kb++)
        post_kb<PH>(sb, acc, p, wg, lead, kb == 0, [&]() {
            if (kb == 0) { PP(pi) }
            if (nout && kb == 0) wait_smem(sb + P_BAR + 8 * (PB_OUT + wg), nout);
        });
    post_end(sb, p, lead);
    PP(pi + 1)
}

__global__ void __cluster_dims__(2, 1, 1) __launch_bounds__(384, 1)
k_post(const __grid_constant__ PostMaps mp, const __grid_constant__ PostPtrs pp) {
    extern __shared__ uint8_t smraw[];
    const uint32_t sb = smem_u32(smraw);
    if ((sb & 0x3FFFF) != SB0) __trap();
    const int tid = threadIdx.x, lane = tid & 31;
    const int rank = blockIdx.x & 1;
    const uint32_t bars = sb + P_BAR;
    int c = 0;
    unsigned long long v = 0;
    const int wid = __reduce_max_sync(~0u, tid >> 5);
    const bool draw = tid == 352 && rank == 0;
    if (draw) {
        c = min(ldg_rlx1(&g_cls[smid() & 255]), 8u);
        asm volatile("{.reg .b64 a; cvt.u64.u32 a, %%laneid; add.u64 a, a, %1; atom.relaxed.gpu.global.add.u64 %0, [a], %2;}" : "=l"(v) : "l"(&g_pt), "l"(1ull << (7 * c)) : "memory");
    }
    if (wid < 11) {
        asm volatile("{.reg .pred p; elect.sync _|p, 0xffffffff; @p mbarrier.init.shared.b64 [%0], %1; @p prefetch.tensormap [%2]; fence.mbarrier_init.release.cluster;}"
                     ::"r"(bars + 8 * wid), "r"(wid >= PB_E && wid < PB_R ? 4 : 1), "l"(&mp.o + wid) : "memory");
        if (wid == PB_R) { sts4(bars + 8 * PB_OUT, 0, 0, 0, 0); e_expect(bars + 8 * PB_R, 4); }
    }
    __syncwarp();
    asm volatile("barrier.cluster.arrive.relaxed.aligned; barrier.cluster.wait.aligned;" ::: "memory");
    if (draw) {
        int r = (v >> (7 * c)) & 127, role = c * 8 + r;
        if (c == 8 || r >= 8) {
            int n, x, it = 0;
#pragma unroll 1
            do {
                __nanosleep(200);
                v = ldg_u64(&g_pt); n = 0; x = c < 8 ? r - 8 : r;
#pragma unroll 1
                for (int i = 0; i < 63; i += 7) { const int m = v >> i & 127; n += m; if (i < 7 * c) x += max(m - 8, 0); }
            } while (n < gridDim.x / 2 && ++it < SPIN_LIMIT);
            role = -1;
#pragma unroll 1
            for (int i = 0; i < 64; i += 8, v >>= 7) {
                n = v & 127;
                if (x >= 0 && n + x < 8) role = i + n + x;
                x -= max(8 - n, 0);
            }
        }
#pragma unroll
        for (int i = 0; i < 2; i++)
            asm volatile("{.reg .b32 d; mapa.shared::cluster.u32 d, %0, %2; st.async.shared::cluster.mbarrier::complete_tx::bytes.u32 [d+8], %1, [d];}"
                         ::"r"(bars + 8 * PB_R), "r"(role), "r"(i) : "memory");
    }
    __syncwarp();
    mbar_wait_b(bars + 8 * PB_R, 0);
    const int pr = __reduce_max_sync(~0u, (int)lds1(bars + 8 * PB_R + 8));
    if (pr < 0) return;
    const int mb = (pr >> 5) * 8 + (pr & 7), nb = (pr >> 2 & 6) + rank, cta = pr * 2 + rank;
    if (wid >= 8) {
        asm volatile("setmaxnreg.dec.sync.aligned.u32 40;");
        const int w = wid - 8;
        if (w == 0) {
            post_weights(sb, mp, nb, rank);
        } else if (w == 3) {
            asm volatile("griddepcontrol.wait;" ::: "memory");
            TLP(15)
            post_acts(sb, mp, mb, nb, rank);
        } else {
            const int wg = w - 1, rh = 2 * mb + wg;
            float* rowc = (float*)(smraw + P_ROW) + (wg * 64 + lane * 2) * 8;
            int nout = 0, sig = 0;
#pragma unroll 1
            for (int i = 0; i < 13; i++) {
                const int cnt = (0x4333333392180ull >> (4 * i)) & 15;
                if (cnt < C_S1) {
                    const int ng = cnt == C_U ? 1 : 2, c0 = cnt == C_U ? (i - 5) * 512 + nb * 64 : nb * 128;
                    const bool fast = (cnt == C_Y || cnt == C_X1);
#pragma unroll 1
                    for (int j = 0; j < ng; j++) {
                        const uint32_t st = j ? cnt : cnt ? 1 : 4;
                        const uint32_t src = sb + (fast ? st * 16384 + wg * 8192 : P_OUT + wg * 16384 + ((nout + j) & 1) * 8192);
                        bar_sync(4 + 4 * wg + (sig++ & 3), 160);
                        if (lane == 0) {
                            PH_(cnt == PPH - 1, wg, 20)
                            if (fast) asm volatile("mbarrier.complete_tx.relaxed.cta.shared::cta.b64 [%0], 8192;" ::"r"(bars + 8 * (PB_F + st)) : "memory");
                            asm volatile("cp.async.bulk.tensor.2d.global.shared::cta.bulk_group [%0, {%2, %3}], [%1]; cp.async.bulk.commit_group;"
                                         ::"l"(&mp.y + 2 * cnt), "r"(src), "r"(c0 + j * 64), "r"(rh * 64) : "memory");
                        }
                        __syncwarp();
                    }
                    if (lane == 0) {
                        auto to_peer = [&]() {
                            const uint32_t n = cnt ? 1 : 4;
                            mbar_wait(bars + 8 * (PB_E + (cnt ? 4 : 2)), 0);
#pragma unroll
                            for (int i = 0; i < 2; i++)
                                asm volatile("{.reg .b32 d, m; mapa.shared::cluster.u32 d, %0, %3; mapa.shared::cluster.u32 m, %2, %3;\n"
                                             " cp.async.bulk.shared::cluster.shared::cta.mbarrier::complete_tx::bytes [d], [%1], 8192, [m];}"
                                             ::"r"(sb + (cnt + 1 + i) * 16384 + wg * 8192), "r"(sb + (i ? cnt : n) * 16384 + wg * 8192), "r"(bars + 8 * (PB_F + cnt + 1 + i)), "r"(rank ^ 1) : "memory");
                        };
                        if (DS_AT == 1 && fast) to_peer();
                        asm volatile("cp.async.bulk.wait_group 0; fence.proxy.async.global;" ::: "memory");
                        asm volatile("st.release.cta.shared.u32 [%0], %1;" ::"r"(bars + 8 * (PB_OUT + wg)), "r"(nout + ng) : "memory");
                        PH_(cnt == PPH - 1, wg, 21)
                        if (DS_AT == 2 && fast) to_peer();
                        asm volatile(FLAG_ST " [%0], %1;" ::"l"(&g_pflag[cnt * 256 + rh * 8 + nb]), "r"(max(i - 4, 1)) : "memory");
                        PH_(cnt == PPH - 1, wg, 22)
                        if (DS_AT == 3 && fast) to_peer();
                    }
                    nout += ng;
                    __syncwarp();
                    continue;
                }
                bar_sync(4 + 4 * wg + (sig++ & 3), 160);
                uint32_t* c = &g_pcnt[(cnt - C_S1) * 256 + rh * 8];
                if (lane == 0) { signal_count(c); wait_count1(c, 8); }
                __syncwarp();
                const float4* sp = (const float4*)g_st + rh * 32 + lane;
                float4 u[3] = {__ldcg(sp + (cnt == C_S1 ? 0 : 3) * (S_ / 2)), __ldcg(sp + S_ / 2), __ldcg(sp + S_)};
#pragma unroll 1
                for (int h = 0; h < 2; h++) {
                    const float id = 1.0f / DM;
                    const float m = u[0].x * id, var = fmaxf(u[0].y * id - m * m, 0.f) + 1e-5f, r = rsqrtf(var);
                    float sc = r, m2 = 0.f;
                    if (cnt == C_S1) {
                        m2 = r * (u[1].x * id - m * g_cst[0]) + g_cst[3];
                        const float e2 = r * r * (u[2].x * id - 2.0f * m * u[1].y * id + m * m * g_cst[1]) + 2.0f * r * (u[2].y * id - m * g_cst[2]) + g_cst[4];
                        sc = r * rsqrtf(fmaxf(e2 - m2 * m2, 0.f) + 1e-5f);
                    }
                    const GeluK k = gelu_k(sc);
                    *(float4*)(rowc + h * 8) = make_float4(k.k0, k.k1, k.kh, -m);
                    *(float4*)(rowc + h * 8 + 4) = make_float4(var * r, -m2 * var * r, r, -m * r);
#pragma unroll
                    for (int q = 0; q < 3; q++) { u[q].x = u[q].z; u[q].y = u[q].w; }
                }
                bar_arrive(1 + wg, 160);
            }
        }
    } else {
        asm volatile("setmaxnreg.inc.sync.aligned.u32 232;");
        const bf16* xin = pp.x;
        const int wg = wid >> 2, wi = (tid >> 5) & 3, g = lane >> 2, tq = lane & 3;
        const int rh = 2 * mb + wg, row = rh * 64 + wi * 16 + g;
        const bool lead = (tid & 127) == 0;
        PP(0)
        if (tid == 0) TLP(10)
        uint32_t keep[32];
#pragma unroll
        for (int i = 0; i < 8; i++)
            *(uint4*)(keep + 4 * i) = __ldg((const uint4*)(xin + (size_t)(rh * 64 + wi * 16 + (i & 3) * 4 + (lane >> 3)) * DM + nb * 128 + (i >> 2) * 64 + (lane & 7) * 8));
        asm volatile("griddepcontrol.wait;" ::: "memory");
        if (cta < 64) g_modp[cta * 256 + tid] = 0;
        if (cta == 64 && tid < 196) g_tick[tid] = 0;
        const float* src = wg ? g_vec + nb * 128 + tid - 128 : g_mod + 2 * DM + nb * 128 + tid;
        const float* c3 = &g_vec[3 * DM + (tid >> 6) * 512 + nb * 64 + (tid & 63)];
        const float cv[6] = {__ldcg(src), __ldcg(src + (wg ? 1 : 2) * DM), __ldcg(src + (wg ? 2 : 1) * DM), __ldcg(src + 3 * DM), __ldcg(c3), __ldcg(c3 + (tid < 192 ? 2048 : 0))};
        uint32_t vec = sb + P_VEC + tq * 8;
        const uint32_t stw = sb + (wi * 16 + ((lane >> 3) & 1) * 8 + (lane & 7)) * 128 + (((lane >> 4) ^ (lane & 7)) << 4);
        int sig = 0;
        auto signal = [&]() { bar_arrive(4 + 4 * wg + (sig++ & 3), 160); };
        auto put64 = [&](uint32_t o, const float* v) {
#pragma unroll
            for (int jj = 0; jj < 4; jj++, v += 8) stsm4((stw + o) ^ (jj << 5), pack2(v[0], v[1]), pack2(v[2], v[3]), pack2(v[4], v[5]), pack2(v[6], v[7]));
            fence_async_smem();
            signal();
        };
        auto slot = [&](int n) {
            mbar_wait_b(bars + 8 * (PB_E + n % 5), ((n / 5) & 1) ^ 1);
            return (n % 5) * 16384 + wg * 8192;
        };
        const uint32_t rowc = sb + P_ROW + (wg * 64 + wi * 16 + g) * 32, o128 = P_OUT + wg * 16384;
        Pipe pa = {0, 0, 0};
        asm("mapa.shared::cluster.u32 %0, %1, %2;" : "=r"(pa.rel) : "r"(bars + 8 * PB_E), "r"(tid & 1));
        if (tid & 126) pa.rel = 0;
#define KEEP(jn, e) (((e) & 1) ? bfhi(keep[2 * (jn) + ((e) >> 1)]) : bflo(keep[2 * (jn) + ((e) >> 1)]))
        float mu1[2], r1[2];
        {
            float acc[64];
#pragma unroll 1
            for (int kb = 0; kb < 64; kb++) {
                post_kb<0>(sb, acc, pa, wg, lead, kb == 0, []() {});
                if (kb == 0) { PP(1) if (wg == 0) TLP(11) }
                if (kb == 24) bar_sync(3, 256);
                if (kb != 8 + 8 * wg) continue;
                float* sv = (float*)(smraw + P_VEC) + tid;
                const uint32_t xo = sb + o128 + wi * 2048 + (lane >> 3) * 128;
#pragma unroll
                for (int i = 0; i < 8; i++) sts4(xo + (i >> 2) * 8192 + (i & 3) * 512 + (((lane & 7) ^ ((i & 1) * 4 + (lane >> 3))) << 4), keep[4 * i], keep[4 * i + 1], keep[4 * i + 2], keep[4 * i + 3]);
                __syncwarp();
#pragma unroll
                for (int jj = 0; jj < 8; jj++) ldsm4(keep + jj * 4, (stw + o128 + (jj >> 2) * 8192) ^ ((jj & 3) << 5));
                sv[wg * 384] = cv[0]; sv[wg * 384 + 128] = cv[1] + (wg ? 0.0f : 1.0f); sv[wg * 384 + 256] = cv[2];
                if (!wg) sv[384] = cv[3];
                sv[V_C3 * 128] = cv[4]; sv[V_C3 * 128 + 256] = cv[5];
            }
            post_end(sb, pa, lead);
            PP(2)
            asm volatile("" : "+r"(vec) :: "memory");
            float st[2][6];
#pragma unroll
            for (int q = 0; q < 6; q++) st[0][q] = st[1][q] = 0.f;
#pragma unroll
            for (int jn = 0; jn < 16; jn++) {
                const float2 ga = ldsv(vec + V_GA * 512 + jn * 32), a = ldsv(vec + V_A * 512 + jn * 32);
                float xa[4];
#pragma unroll
                for (int e = 0; e < 4; e++) {
                    xa[e] = fmaf((e & 1) ? ga.y : ga.x, acc[4 * jn + e], KEEP(jn, e));
                    st[e >> 1][0] += xa[e]; st[e >> 1][1] = fmaf(xa[e], xa[e], st[e >> 1][1]);
                    acc[4 * jn + e] = ((e & 1) ? a.y : a.x) * xa[e];
                }
                keep[2 * jn] = pack2(xa[0], xa[1]); keep[2 * jn + 1] = pack2(xa[2], xa[3]);
                if ((jn & 7) == 7) put64(slot(64 + (jn >> 3)), acc + 4 * jn - 28);
            }
            PP(3)
#pragma unroll
            for (int jn = 0; jn < 16; jn++) {
                const float2 a = ldsv(vec + V_A * 512 + jn * 32), b = ldsv(vec + V_B * 512 + jn * 32);
#pragma unroll
                for (int e = 0; e < 4; e++) {
                    const float y = acc[4 * jn + e], aa = (e & 1) ? a.y : a.x, bb = (e & 1) ? b.y : b.x;
                    float* s = st[e >> 1];
                    s[2] += y; s[3] = fmaf(aa, y, s[3]); s[4] = fmaf(y, y, s[4]); s[5] = fmaf(bb, y, s[5]);
                }
            }
#pragma unroll
            for (int h = 0; h < 2; h++)
#pragma unroll
                for (int q = 0; q < 6; q++) { st[h][q] += __shfl_xor_sync(~0u, st[h][q], 1); st[h][q] += __shfl_xor_sync(~0u, st[h][q], 2); }
            if (tq < 3 && !(PX & 1)) {
#pragma unroll
                for (int h = 0; h < 2; h++)
                    red2(g_st + (tq * S_ + row + h * 8) * 2, tq == 0 ? st[h][0] : tq == 1 ? st[h][2] : st[h][4], tq == 0 ? st[h][1] : tq == 1 ? st[h][3] : st[h][5]);
            }
            signal();
            PP(29)
        }
        {
            float acc[64];
            post_mma<1>(sb, acc, pa, wg, lead, 2, 4, mb, nb);
            float c1[2], c2[2], c3[2];
            GeluK gk[2];
            bar_sync(1 + wg, 160);
#pragma unroll
            for (int h = 0; h < 2; h++) {
                const float4 a = lds4f(rowc + h * 256), b = lds4f(rowc + h * 256 + 16);
                gk[h] = {a.x, a.y, a.z}; c1[h] = a.w; c2[h] = b.x; c3[h] = b.y; mu1[h] = b.w; r1[h] = b.z;
            }
#pragma unroll
            for (int jn = 0; jn < 16; jn++) {
                const float2 va = ldsv(vec + V_VA * 512 + jn * 32), vb = ldsv(vec + V_VB * 512 + jn * 32), vc = ldsv(vec + V_VC * 512 + jn * 32);
#pragma unroll
                for (int e = 0; e < 4; e++) {
                    const int h = e >> 1;
                    const float t = fmaf(c1[h], (e & 1) ? va.y : va.x, fmaf(c2[h], (e & 1) ? vb.y : vb.x, fmaf(c3[h], (e & 1) ? vc.y : vc.x, acc[4 * jn + e])));
                    acc[4 * jn + e] = gelu_s(t, gk[h]);
                }
                if ((jn & 7) == 7) put64(o128 + (jn >> 3) * 8192, acc + 4 * jn - 28);
            }
            PP(6)
        }
        {
            float acc[64];
            post_mma<2>(sb, acc, pa, wg, lead, 0, 7, mb, nb);
#pragma unroll
            for (int jn = 0; jn < 16; jn++) {
                const float2 a = ldsv(vec + V_A * 512 + jn * 32), b = ldsv(vec + V_B * 512 + jn * 32);
#pragma unroll
                for (int e = 0; e < 4; e++) {
                    const int h = e >> 1;
                    acc[4 * jn + e] += fmaf(fmaf(KEEP(jn, e), r1[h], mu1[h]), (e & 1) ? a.y : a.x, (e & 1) ? b.y : b.x);
                }
                if ((jn & 7) == 7) put64(slot(96 + (jn >> 3)), acc + 4 * jn - 28);
            }
            BLOCK_FENCE
#pragma unroll
            for (int i = 0; i < 64; i += 16) asm volatile("" : F16(acc, i));
            PP(9)
            float st[2][2] = {{0.f, 0.f}, {0.f, 0.f}};
#pragma unroll
            for (int jn = 0; jn < 16; jn++) {
                const float2 gb = ldsv(vec + V_GB * 512 + jn * 32);
                float z[4];
#pragma unroll
                for (int e = 0; e < 4; e++) {
                    const float x1 = acc[4 * jn + e];
                    st[e >> 1][0] += x1; st[e >> 1][1] = fmaf(x1, x1, st[e >> 1][1]);
                    z[e] = fmaf((e & 1) ? gb.y : gb.x, x1, KEEP(jn, e));
                }
                keep[2 * jn] = pack2(z[0], z[1]); keep[2 * jn + 1] = pack2(z[2], z[3]);
            }
#pragma unroll
            for (int h = 0; h < 2; h++)
#pragma unroll
                for (int q = 0; q < 2; q++) { st[h][q] += __shfl_xor_sync(~0u, st[h][q], 1); st[h][q] += __shfl_xor_sync(~0u, st[h][q], 2); }
            if (tq < 2) red2(g_st + (3 * S_ + row + tq * 8) * 2, tq ? st[1][0] : st[0][0], tq ? st[1][1] : st[0][1]);
            signal();
            PP(30)
        }
        {
            float old[96], acc[64];
            post_mma<3>(sb, old, pa, wg, lead, 6, 10, mb, nb);
#pragma unroll
            for (int i = 0; i < 96; i += 16) asm volatile("" : F16(old, i));
            uint32_t v3 = vec + V_C3 * 512;
            bar_sync(1 + wg, 160);
            const float4 rc[2] = {lds4f(rowc), lds4f(rowc + 256)};
            float2 vc[2] = {lds2f(v3), lds2f(v3 + 32)};
            bar_sync(3, 256);
#pragma unroll 1
            for (int blk = 0; blk < 11; blk++) {
                const uint32_t o = stw + o128 + (blk & 1) * 8192;
                const int turn = blk < 7 ? wg : 2;
#pragma unroll
                for (int q = 0; q < 4; q++) {
#pragma unroll 1
                    for (int rep = 0; rep < 2; rep++) {
                        post_kb<1, MIDF>(sb, acc, pa, wg, lead, q == 0 && rep == 0 && blk < 6 && !(blk & 1), [&]() {
                        if (rep != turn) return;
                        asm volatile("" : F4(old, 8 * q), F4(old, 8 * q + 4));
                        const float2 vn[2] = {lds2f(v3 + q * 64 + 64), lds2f(v3 + q * 64 + 96)};
                        float t[8];
#pragma unroll
                        for (int i = 0; i < 8; i++) {
                            const float4& c = rc[(i >> 1) & 1];
                            t[i] = gelu_s(fmaf(c.w, (i & 1) ? vc[i >> 2].y : vc[i >> 2].x, old[8 * q + i]), GeluK{c.x, c.y, c.z});
                            old[8 * q + i] = old[32 + 8 * q + i];
                            old[32 + 8 * q + i] = old[64 + 8 * q + i];
                        }
                        stsm4(o ^ (q << 5), pack2(t[0], t[1]), pack2(t[2], t[3]), pack2(t[4], t[5]), pack2(t[6], t[7]));
                        vc[0] = vn[0]; vc[1] = vn[1];
                        if (q == 2) wait_smem(bars + 8 * (PB_OUT + wg), 6 + blk);
                        if (q == 3) { fence_async_smem(); signal(); }
                        });
                    }
                }
                v3 += 256;
                if (blk != 1 && blk != 3) continue;
                post_end(sb, pa, lead);
                PP(12 + blk)
                asm volatile("" : F16(acc, 0), F4(acc, 16), F4(acc, 20), F4(acc, 24));
                asm volatile("" : F16(acc, 28), F4(acc, 44), F4(acc, 48), F4(acc, 52));
                asm volatile("" : F4(acc, 56), F4(acc, 60));
#pragma unroll
                for (int i = 0; i < 64; i++) old[32 + i] = acc[i];
            }
            post_end(sb, pa, lead);
            PP(17)
#pragma unroll
            for (int jn = 0; jn < 16; jn++) {
                const float2 gb = ldsv(vec + V_GB * 512 + jn * 32);
#pragma unroll
                for (int e = 0; e < 4; e++) acc[4 * jn + e] = fmaf((e & 1) ? gb.y : gb.x, acc[4 * jn + e], KEEP(jn, e));
                if ((jn & 7) == 7) put64(o128 + ((jn >> 3) ^ 1) * 8192, acc + 4 * jn - 28);
            }
            PP(18)
            if (tid == 0) TLP(12)
        }
    }
}

typedef CUresult (*EncFn)(CUtensorMap*, CUtensorMapDataType, cuuint32_t, void*, const cuuint64_t*, const cuuint64_t*, const cuuint32_t*,
                          const cuuint32_t*, CUtensorMapInterleave, CUtensorMapSwizzle, CUtensorMapL2promotion, CUtensorMapFloatOOBfill);

static CUtensorMap make_map(EncFn enc, const void* p, uint64_t inner, uint64_t outer, uint32_t bi = 64) {
    CUtensorMap m;
    cuuint64_t dims[2] = {inner, outer};
    cuuint64_t str[1] = {inner * 2};
    cuuint32_t box[2] = {bi, bi == 64 ? 64u : 16u};
    cuuint32_t es[2] = {1, 1};
    enc(&m, CU_TENSOR_MAP_DATA_TYPE_BFLOAT16, 2, (void*)p, dims, str, box, es, CU_TENSOR_MAP_INTERLEAVE_NONE,
        bi == 64 ? CU_TENSOR_MAP_SWIZZLE_128B : CU_TENSOR_MAP_SWIZZLE_NONE, CU_TENSOR_MAP_L2_PROMOTION_L2_256B, CU_TENSOR_MAP_FLOAT_OOB_FILL_NONE);
    return m;
}
static CUtensorMap make_map_o(EncFn enc, const void* p) {
    CUtensorMap m;
    cuuint64_t dims[2] = {16384, 256};
    cuuint64_t str[1] = {65536};
    cuuint32_t box[2] = {256, 8};
    cuuint32_t es[2] = {1, 1};
    enc(&m, CU_TENSOR_MAP_DATA_TYPE_UINT32, 2, (void*)p, dims, str, box, es, CU_TENSOR_MAP_INTERLEAVE_NONE, CU_TENSOR_MAP_SWIZZLE_NONE,
        CU_TENSOR_MAP_L2_PROMOTION_L2_256B, CU_TENSOR_MAP_FLOAT_OOB_FILL_NONE);
    return m;
}
template <class T> static T* sym(T& s) { void* p = nullptr; cudaGetSymbolAddress(&p, s); return (T*)p; }

static const Delays h_dly = {D_NEAR, D_FAR, D_X2, D_V, D_W2, D_PA, D_WF, D_TV};
extern "C" void kernel_launch(void* const* d_in, const int* in_sizes, int n_in, void* d_out, int out_size) {
    const bf16* x = (const bf16*)d_in[0];
    const bf16* mem0 = (const bf16*)d_in[1];
    const bf16 *Wq = (const bf16*)d_in[2], *Wk = (const bf16*)d_in[3], *Wv = (const bf16*)d_in[4], *Wo = (const bf16*)d_in[5];
    const bf16 *w1 = (const bf16*)d_in[8], *w2 = (const bf16*)d_in[9], *w3 = (const bf16*)d_in[10], *w4 = (const bf16*)d_in[11];
    const bf16 *c = (const bf16*)d_in[12], *wmod = (const bf16*)d_in[13];
    bf16* out = (bf16*)d_out;

    EncFn enc = nullptr;
    cudaDriverEntryPointQueryResult qr;
    cudaGetDriverEntryPoint("cuTensorMapEncodeTiled", (void**)&enc, cudaEnableDefault, &qr);
    CUtensorMap tWq = make_map(enc, Wq, NH * DH, DM), tWk = make_map(enc, Wk, NH * DH, DM), tWv = make_map(enc, Wv, NH * DH, DM);
    PostMaps mp;
    mp.o = make_map_o(enc, sym(g_O)); mp.wo = make_map(enc, Wo, DM, NH * DH);
    mp.y = make_map(enc, sym(g_y), DM, S_); mp.w1 = make_map(enc, w1, DM, DM);
    mp.g = make_map(enc, sym(g_g), DM, S_); mp.w2 = make_map(enc, w2, DM, DM);
    mp.x1 = make_map(enc, sym(g_x1), DM, S_); mp.w3 = make_map(enc, w3, FF, DM);
    mp.u = make_map(enc, sym(g_u), FF, S_); mp.w4 = make_map(enc, w4, DM, FF);
    mp.out = make_map(enc, out, DM, S_);
    cudaFuncSetAttribute(k_rec, cudaFuncAttributeMaxDynamicSharedMemorySize, SM_REC_TOTAL + 2048);
    cudaFuncSetAttribute(k_post, cudaFuncAttributeMaxDynamicSharedMemorySize, P_SMEM);

    uint8_t* arena = (uint8_t*)(((uintptr_t)sym(g_arena) + (2u << 20) - 1) & ~(uintptr_t)((2u << 20) - 1));
    const PostPtrs pp = {x};
    const RecPtrs rp = {x, mem0, c, wmod, w1, w3, arena, 0u, w2, w4, Wo, h_dly};
    const RecMaps rm = {tWq, tWk, tWv, mp.wo, make_map(enc, wmod, 6 * DM, DM, 256), make_map(enc, w3, FF, DM, 256), make_map(enc, w1, DM, DM, 256)};
    k_rec<<<132, 384, SM_REC_TOTAL + 2048>>>(rm, rp);
    cudaLaunchConfig_t cfg = {};
    cfg.gridDim = dim3(132); cfg.blockDim = dim3(384); cfg.dynamicSmemBytes = P_SMEM; cfg.stream = cudaStreamPerThread;
    cudaLaunchAttribute at[1];
    at[0].id = cudaLaunchAttributeProgrammaticStreamSerialization; at[0].val.programmaticStreamSerializationAllowed = PDL;
    cfg.attrs = at; cfg.numAttrs = 1;
    cudaLaunchKernelEx(&cfg, k_post, mp, pp);
}
```

```cpp
#include <cuda_runtime.h>
#include <cuda.h>
#include <cuda_bf16.h>
#include <stdint.h>
#include <limits.h>

typedef __nv_bfloat16 bf16;

constexpr int S_ = 2048, DM = 1024, NH = 32, DH = 128, NSEG = 64, FF = 3584;
constexpr int SPIN_LIMIT = 1 << 22;
#define W_INFL 2
#define XP 0
#define H_PIECES 4
#define PDL 1
#define NPROBE 3

__device__ uint8_t g_arena[10 << 20];
__device__ __align__(128) uint32_t g_tick[64 + 132];
#define g_clk ((uint2*)(g_tick + 64))
__device__ uint32_t g_cls[256];
__device__ unsigned long long g_pt;
__device__ __align__(16) uint32_t g_modp[8 * 2 * DM];
__host__ __device__ constexpr uint32_t blk(uint32_t lb, uint32_t par) {
    return (lb << 13) | ((((lb) ^ (lb >> 3) ^ (lb >> 4) ^ (lb >> 6) ^ par) & 1) << 12);
}
__host__ __device__ constexpr uint32_t lb_x2(uint32_t h) { return (h & 1) | ((h >> 1) << 3); }
__host__ __device__ constexpr uint32_t mem_row(uint32_t kh, uint32_t b, uint32_t r) { return blk(128 | b, kh) + r * 1024; }
__device__ __forceinline__ uint32_t mem_slot(uint32_t s) { return ((s & 1) << 15) | ((s & 2) << 17); }
constexpr uint32_t CNT1 = 0x3d80, CNT_ALL = 0x4000;
constexpr uint32_t LB_PROBE = 6 | 64, LB_TIME = 6;
__host__ __device__ constexpr uint32_t lb_tok(uint32_t h) { return (h & 1) | ((h >> 1) << 3); }
__device__ float g_mod[6 * DM];
__device__ __align__(1024) bf16 g_himg[(S_ + 32) * DM];
__device__ __align__(1024) bf16 g_O[S_ * NH * DH];
__device__ __align__(1024) bf16 g_y[S_ * DM];
__device__ __align__(1024) bf16 g_g[S_ * DM];
__device__ __align__(1024) bf16 g_x1[S_ * DM];
__device__ __align__(16) float g_st[4 * S_ * 2];
__device__ float g_vec[3 * DM + FF];
__device__ float g_cst[8];
__device__ uint32_t g_pcnt[2 * 32 * 8], g_pflag[7 * 32 * 8];
__device__ __align__(1024) bf16 g_u[S_ * FF];

#define TL(i) {}
#define TLX(i) {}
#define TLP(i) TL(i)
#define TLC(i) {}
__device__ __forceinline__ uint32_t smem_u32(const void* p) { return (uint32_t)__cvta_generic_to_shared(p); }
__device__ __forceinline__ void spin_guard(int it) {
    asm volatile("{.reg .pred p; setp.gt.s32 p, %0, %1; @p st.global.u32 [%2], %0;}" ::"r"(it), "n"(SPIN_LIMIT), "l"(1ull));
}
__device__ __forceinline__ void wg_fence() { asm volatile("wgmma.fence.sync.aligned;" ::: "memory"); }
__device__ __forceinline__ void wg_commit() { asm volatile("wgmma.commit_group.sync.aligned;" ::: "memory"); }
template <int N> __device__ __forceinline__ void wg_wait() { asm volatile("wgmma.wait_group.sync.aligned %0;" ::"n"(N) : "memory"); }
__host__ __device__ constexpr uint64_t mkdesc(uint32_t addr, uint32_t lbo, uint32_t sbo, uint32_t swz) {
    return (uint64_t)((addr & 0x3FFFF) >> 4) | ((uint64_t)(lbo >> 4) << 16) | ((uint64_t)(sbo >> 4) << 32) | ((uint64_t)swz << 62);
}
__device__ __forceinline__ uint64_t dadd(uint64_t d, uint32_t o) { return (d & 0xffffffff00000000ull) | (uint32_t)((uint32_t)d + o); }
__device__ __forceinline__ void mbar_init(uint32_t b, uint32_t c) { asm volatile("mbarrier.init.shared.b64 [%0], %1;" ::"r"(b), "r"(c) : "memory"); }
__device__ __forceinline__ void mbar_expect(uint32_t b, uint32_t tx) { asm volatile("mbarrier.arrive.expect_tx.shared.b64 _, [%0], %1;" ::"r"(b), "r"(tx) : "memory"); }
__device__ __forceinline__ void mbar_arrive(uint32_t b) { asm volatile("mbarrier.arrive.shared.b64 _, [%0];" ::"r"(b) : "memory"); }
__device__ __forceinline__ void mbar_arrive_cluster(uint32_t b, uint32_t cta) {
    asm volatile("{.reg .b32 r; mapa.shared::cluster.u32 r, %0, %1; mbarrier.arrive.shared::cluster.b64 _, [r];}" ::"r"(b), "r"(cta) : "memory");
}
__device__ __forceinline__ bool mbar_try(uint32_t b, uint32_t par) {
    uint32_t ok;
    asm volatile("{.reg .pred p; mbarrier.try_wait.parity.shared.b64 p, [%1], %2; selp.u32 %0, 1, 0, p;}" : "=r"(ok) : "r"(b), "r"(par) : "memory");
    return ok;
}
__device__ __forceinline__ void mbar_wait(uint32_t b, uint32_t par) {
    int it = 0;
#pragma unroll 1
    while (!mbar_try(b, par)) { spin_guard(++it); }
}
__device__ __forceinline__ void mbar_wait_w(uint32_t b, uint32_t par) {
    int it = 0;
    bool ok;
#pragma unroll 1
    do { ok = __all_sync(~0u, mbar_try(b, par)); spin_guard(++it); } while (!ok);
}
__device__ __forceinline__ void mbar_wait_cluster(uint32_t b, uint32_t par) {
    int it = 0;
    while (true) {
        uint32_t ok;
        asm volatile("{.reg .pred p; mbarrier.try_wait.parity.acquire.cluster.shared::cta.b64 p, [%1], %2; selp.u32 %0, 1, 0, p;}" : "=r"(ok) : "r"(b), "r"(par) : "memory");
        if (ok) break;
        spin_guard(++it);
    }
}
__device__ __forceinline__ void tma2d(uint32_t dst, const CUtensorMap* m, int c0, int c1, uint32_t bar) {
    asm volatile("cp.async.bulk.tensor.2d.shared::cluster.global.mbarrier::complete_tx::bytes [%0], [%1, {%3, %4}], [%2];" ::"r"(dst), "l"(m), "r"(bar), "r"(c0), "r"(c1) : "memory");
}
constexpr uint64_t EVICT_FIRST = 0x12F0000000000000ull, EVICT_NORMAL = 0x1000000000000000ull;
__device__ __forceinline__ void tma2d_mc(uint32_t dst, const CUtensorMap* m, int c0, int c1, uint32_t bar, uint16_t mask) {
    asm volatile("cp.async.bulk.tensor.2d.shared::cluster.global.mbarrier::complete_tx::bytes.multicast::cluster [%0], [%1, {%3, %4}], [%2], %5;" ::"r"(dst), "l"(m), "r"(bar), "r"(c0), "r"(c1), "h"(mask) : "memory");
}
__device__ __forceinline__ void bulk_g2s(uint32_t dst, const void* src, uint32_t bytes, uint32_t bar) {
    asm volatile("cp.async.bulk.shared::cluster.global.mbarrier::complete_tx::bytes [%0], [%1], %2, [%3];" ::"r"(dst), "l"(src), "r"(bytes), "r"(bar) : "memory");
}
__device__ __forceinline__ void bar_sync(int id, int n) { asm volatile("bar.sync %0, %1;" ::"r"(id), "r"(n) : "memory"); }
__device__ __forceinline__ void bar_arrive(int id, int n) { asm volatile("bar.arrive %0, %1;" ::"r"(id), "r"(n) : "memory"); }
__device__ __forceinline__ void cluster_sync_all() { asm volatile("barrier.cluster.arrive.aligned; barrier.cluster.wait.aligned;" ::: "memory"); }
__device__ __forceinline__ void fence_async_smem() { asm volatile("fence.proxy.async.shared::cta;" ::: "memory"); }
__device__ __forceinline__ void ldsm4t(uint32_t* r, uint32_t a) {
    asm volatile("ldmatrix.sync.aligned.m8n8.x4.trans.shared.b16 {%0,%1,%2,%3}, [%4];" : "=r"(r[0]), "=r"(r[1]), "=r"(r[2]), "=r"(r[3]) : "r"(a) : "memory");
}
__device__ __forceinline__ void ldsm4(uint32_t* r, uint32_t a) {
    asm volatile("ldmatrix.sync.aligned.m8n8.x4.shared.b16 {%0,%1,%2,%3}, [%4];" : "=r"(r[0]), "=r"(r[1]), "=r"(r[2]), "=r"(r[3]) : "r"(a) : "memory");
}
__device__ __forceinline__ uint32_t movm(uint32_t a) {
    uint32_t d; asm volatile("movmatrix.sync.aligned.m8n8.trans.b16 %0, %1;" : "=r"(d) : "r"(a)); return d;
}
__device__ __forceinline__ void mma16816(float* d, uint32_t a0, uint32_t a1, uint32_t a2, uint32_t a3, uint32_t b0, uint32_t b1) {
    asm volatile("mma.sync.aligned.m16n8k16.row.col.f32.bf16.bf16.f32 {%0,%1,%2,%3},{%4,%5,%6,%7},{%8,%9},{%0,%1,%2,%3};"
                 : "+f"(d[0]), "+f"(d[1]), "+f"(d[2]), "+f"(d[3]) : "r"(a0), "r"(a1), "r"(a2), "r"(a3), "r"(b0), "r"(b1));
}
__device__ __forceinline__ void mma16816z(float* d, const uint32_t* a, uint32_t b0, uint32_t b1) {
    asm volatile("mma.sync.aligned.m16n8k16.row.col.f32.bf16.bf16.f32 {%0,%1,%2,%3},{%4,%5,%6,%7},{%8,%9},{%10,%10,%10,%10};"
                 : "=f"(d[0]), "=f"(d[1]), "=f"(d[2]), "=f"(d[3]) : "r"(a[0]), "r"(a[1]), "r"(a[2]), "r"(a[3]), "r"(b0), "r"(b1), "f"(0.f));
}
__device__ __forceinline__ void mma1688(float* d, uint32_t a0, uint32_t a1, uint32_t b0) {
    asm volatile("mma.sync.aligned.m16n8k8.row.col.f32.bf16.bf16.f32 {%0,%1,%2,%3},{%4,%5},{%6},{%0,%1,%2,%3};"
                 : "+f"(d[0]), "+f"(d[1]), "+f"(d[2]), "+f"(d[3]) : "r"(a0), "r"(a1), "r"(b0));
}
__device__ __forceinline__ uint32_t pack2(float lo, float hi) {
    uint32_t r; asm("cvt.rn.bf16x2.f32 %0, %1, %2;" : "=r"(r) : "f"(hi), "f"(lo)); return r;
}
__device__ __forceinline__ uint32_t hadd2(uint32_t a, uint32_t b) {
    uint32_t r; asm("add.rn.bf16x2 %0, %1, %2;" : "=r"(r) : "r"(a), "r"(b)); return r;
}
__device__ __forceinline__ float bflo(uint32_t u) { return __uint_as_float(u << 16); }
__device__ __forceinline__ float bfhi(uint32_t u) { return __uint_as_float(u & 0xffff0000u); }
__device__ __forceinline__ float ex2(float x) { float r; asm("ex2.approx.ftz.f32 %0, %1;" : "=f"(r) : "f"(x)); return r; }
__device__ __forceinline__ uint4 ldg_rlx4(const void* p) {
    uint4 v; asm volatile("ld.relaxed.gpu.global.v4.u32 {%0,%1,%2,%3}, [%4];" : "=r"(v.x), "=r"(v.y), "=r"(v.z), "=r"(v.w) : "l"(p) : "memory"); return v;
}
__device__ __forceinline__ uint2 ldg_rlx2(const void* p) {
    unsigned long long v; asm volatile("ld.relaxed.gpu.global.b64 %0, [%1];" : "=l"(v) : "l"(p) : "memory");
    return make_uint2((uint32_t)v, (uint32_t)(v >> 32));
}
__device__ __forceinline__ uint32_t ldg_rlx1(const void* p) {
    uint32_t v; asm volatile("ld.relaxed.gpu.global.u32 %0, [%1];" : "=r"(v) : "l"(p) : "memory"); return v;
}
__device__ __forceinline__ void stg_rlx1(void* p, uint32_t v) { asm volatile("st.relaxed.gpu.global.u32 [%0], %1;" ::"l"(p), "r"(v) : "memory"); }
__device__ __forceinline__ void stg_rlx2(void* p, uint32_t x, uint32_t y) {
    unsigned long long v = (unsigned long long)x | ((unsigned long long)y << 32);
    asm volatile("st.relaxed.gpu.global.b64 [%0], %1;" ::"l"(p), "l"(v) : "memory");
}
__device__ __forceinline__ void stg_rlx4(void* p, uint32_t x, uint32_t y, uint32_t z, uint32_t w) {
    asm volatile("st.relaxed.gpu.global.v4.u32 [%0], {%1,%2,%3,%4};" ::"l"(p), "r"(x), "r"(y), "r"(z), "r"(w) : "memory");
}
__device__ __forceinline__ void sts4(uint32_t a, uint32_t x, uint32_t y, uint32_t z, uint32_t w) {
    asm volatile("st.shared.v4.u32 [%0], {%1,%2,%3,%4};" ::"r"(a), "r"(x), "r"(y), "r"(z), "r"(w) : "memory");
}
__device__ __forceinline__ uint4 lds4(uint32_t a) {
    uint4 v; asm volatile("ld.shared.v4.u32 {%0,%1,%2,%3}, [%4];" : "=r"(v.x), "=r"(v.y), "=r"(v.z), "=r"(v.w) : "r"(a) : "memory"); return v;
}
__device__ __forceinline__ void st_async4(uint32_t a, float x, float y, float z, float w, uint32_t bar) {
    asm volatile("st.async.shared::cluster.mbarrier::complete_tx::bytes.v4.f32 [%0], {%1,%2,%3,%4}, [%5];" ::"r"(a), "f"(x), "f"(y), "f"(z), "f"(w), "r"(bar) : "memory");
}
#define F4(d, i) "+f"(d[i]), "+f"(d[i + 1]), "+f"(d[i + 2]), "+f"(d[i + 3])
__device__ __forceinline__ void wgmma_rs32(float* d, const uint32_t* a, uint64_t b, int sc) {
    asm volatile("{.reg .pred p; setp.ne.b32 p, %21, 0;\n wgmma.mma_async.sync.aligned.m64n32k16.f32.bf16.bf16 {%0,%1,%2,%3,%4,%5,%6,%7,%8,%9,%10,%11,%12,%13,%14,%15}, {%16,%17,%18,%19}, %20, p, 1, 1, 0;}"
                 : F4(d, 0), F4(d, 4), F4(d, 8), F4(d, 12) : "r"(a[0]), "r"(a[1]), "r"(a[2]), "r"(a[3]), "l"(b), "r"(sc));
}
__device__ __forceinline__ void wgmma_ss32(float* d, uint64_t a, uint64_t b, int sc) {
    asm volatile("{.reg .pred p; setp.ne.b32 p, %18, 0;\n wgmma.mma_async.sync.aligned.m64n32k16.f32.bf16.bf16 {%0,%1,%2,%3,%4,%5,%6,%7,%8,%9,%10,%11,%12,%13,%14,%15}, %16, %17, p, 1, 1, 1, 0;}"
                 : F4(d, 0), F4(d, 4), F4(d, 8), F4(d, 12) : "l"(a), "l"(b), "r"(sc));
}
__device__ __forceinline__ void wgmma_rs40(float* d, const uint32_t* a, uint64_t b, int sc) {
    asm volatile("{.reg .pred p; setp.ne.b32 p, %25, 0;\n wgmma.mma_async.sync.aligned.m64n40k16.f32.bf16.bf16 {%0,%1,%2,%3,%4,%5,%6,%7,%8,%9,%10,%11,%12,%13,%14,%15,%16,%17,%18,%19}, {%20,%21,%22,%23}, %24, p, 1, 1, 0;}"
                 : F4(d, 0), F4(d, 4), F4(d, 8), F4(d, 12), F4(d, 16) : "r"(a[0]), "r"(a[1]), "r"(a[2]), "r"(a[3]), "l"(b), "r"(sc));
}
__device__ __forceinline__ void wgmma_ss40(float* d, uint64_t a, uint64_t b, int sc) {
    asm volatile("{.reg .pred p; setp.ne.b32 p, %22, 0;\n wgmma.mma_async.sync.aligned.m64n40k16.f32.bf16.bf16 {%0,%1,%2,%3,%4,%5,%6,%7,%8,%9,%10,%11,%12,%13,%14,%15,%16,%17,%18,%19}, %20, %21, p, 1, 1, 1, 0;}"
                 : F4(d, 0), F4(d, 4), F4(d, 8), F4(d, 12), F4(d, 16) : "l"(a), "l"(b), "r"(sc));
}
#define F16(d, i) F4(d, i), F4(d, i + 4), F4(d, i + 8), F4(d, i + 12)
template <int TA>
__device__ __forceinline__ void wgmma_ss128(float* d, uint64_t a, uint64_t b, int sc) {
    asm volatile("{.reg .pred p; setp.ne.b32 p, %66, 0;\n wgmma.mma_async.sync.aligned.m64n128k16.f32.bf16.bf16 "
                 "{%0,%1,%2,%3,%4,%5,%6,%7,%8,%9,%10,%11,%12,%13,%14,%15,%16,%17,%18,%19,%20,%21,%22,%23,%24,%25,%26,%27,%28,%29,%30,%31,"
                 "%32,%33,%34,%35,%36,%37,%38,%39,%40,%41,%42,%43,%44,%45,%46,%47,%48,%49,%50,%51,%52,%53,%54,%55,%56,%57,%58,%59,%60,%61,%62,%63}, %64, %65, p, 1, 1, %67, 1;}"
                 : F16(d, 0), F16(d, 16), F16(d, 32), F16(d, 48) : "l"(a), "l"(b), "r"(sc), "n"(TA));
}

__device__ __forceinline__ float warp_sum(float v) {
#pragma unroll
    for (int o = 16; o; o >>= 1) v += __shfl_xor_sync(~0u, v, o);
    return v;
}
__device__ __forceinline__ float bfround(float x) { return __bfloat162float(__float2bfloat16(x)); }

__device__ __forceinline__ void wait_count1(const uint32_t* p, uint32_t target) {
    int it = 0;
#pragma unroll 1
    while (true) {
        uint32_t v;
        asm volatile("ld.acquire.gpu.global.u32 %0, [%1];" : "=r"(v) : "l"(p) : "memory");
        if (v >= target) break;
        spin_guard(++it);
    }
}
__device__ __forceinline__ void red2(float* p, float a, float b) {
    asm volatile("red.relaxed.gpu.global.add.v2.f32 [%0], {%1, %2};" ::"l"(p), "f"(a), "f"(b) : "memory");
}
__device__ __forceinline__ void l2_prefetch(const void* p, uint32_t bytes) {
    asm volatile("cp.async.bulk.prefetch.L2.global [%0], %1;" ::"l"(p), "r"(bytes) : "memory");
}
__device__ __forceinline__ void signal_count(uint32_t* p) { asm volatile("red.release.gpu.global.add.u32 [%0], 1;" ::"l"(p) : "memory"); }
__device__ __forceinline__ void e_expect(uint32_t b, uint32_t tx) {
    asm volatile("{.reg .pred p; elect.sync _|p, 0xffffffff; @p mbarrier.arrive.expect_tx.shared.b64 _, [%0], %1;}" ::"r"(b), "r"(tx) : "memory");
}
__device__ __forceinline__ void e_tma2d(uint32_t dst, const CUtensorMap* m, int c0, int c1, uint32_t bar) {
    asm volatile("{.reg .pred p; elect.sync _|p, 0xffffffff;\n @p cp.async.bulk.tensor.2d.shared::cluster.global.mbarrier::complete_tx::bytes [%0], [%1, {%3, %4}], [%2];}"
                 ::"r"(dst), "l"(m), "r"(bar), "r"(c0), "r"(c1) : "memory");
}
__device__ __forceinline__ void e_tma2d_hint(uint32_t dst, const CUtensorMap* m, int c0, int c1, uint32_t bar, uint64_t pol) {
    asm volatile("{.reg .pred p; elect.sync _|p, 0xffffffff;\n @p cp.async.bulk.tensor.2d.shared::cluster.global.mbarrier::complete_tx::bytes.L2::cache_hint [%0], [%1, {%3, %4}], [%2], %5;}"
                 ::"r"(dst), "l"(m), "r"(bar), "r"(c0), "r"(c1), "l"(pol) : "memory");
}
__device__ __forceinline__ void e_tma2d_mc(uint32_t dst, const CUtensorMap* m, int c0, int c1, uint32_t bar) {
    asm volatile("{.reg .pred p; elect.sync _|p, 0xffffffff;\n @p cp.async.bulk.tensor.2d.shared::cluster.global.mbarrier::complete_tx::bytes.multicast::cluster [%0], [%1, {%3, %4}], [%2], %5;}"
                 ::"r"(dst), "l"(m), "r"(bar), "r"(c0), "r"(c1), "h"((uint16_t)3) : "memory");
}
__device__ __forceinline__ void e_prefetch(const void* p, uint32_t bytes) {
    asm volatile("{.reg .pred p; elect.sync _|p, 0xffffffff; @p cp.async.bulk.prefetch.L2.global [%0], %1;}" ::"l"(p), "r"(bytes) : "memory");
}
__device__ __forceinline__ void wait_count_w(const uint32_t* p, uint32_t target) {
    int it = 0;
#pragma unroll 1
    while (true) {
        uint32_t v;
        asm volatile("ld.acquire.gpu.global.u32 %0, [%1];" : "=r"(v) : "l"(p) : "memory");
        if (__all_sync(~0u, v >= target) | (++it > SPIN_LIMIT)) break;
        __nanosleep(100);
    }
}

#define NL 6
constexpr uint32_t SM_HB = 16384, HBK = 5120, SM_SX = 57344, SM_OX = 122880, SM_PX = 124928, SM_PA = 126976, SM_WO = 147456,
                   SM_TAB = 212992, SM_PRE = SM_TAB + 5120, SM_BAR = 227328, SM_REC_TOTAL = 227328 + 256;
constexpr uint32_t SB0 = 1024;
constexpr int B_WO = 0, B_HE = 1, B_ROLE = 2, B_HB = 3, B_W = 5;
constexpr int NB_MEM = 1, NB_QK = 2, NB_X1 = 3, NB_X2 = 4, NB_WIN = 5, NB_WG = 6, NB_KDONE = 7, NB_FIN0 = 8, NB_P = 9, NB_PX = 10, NB_G = 11, NB_A = 12, NB_B = 13, NB_C = 14, NB_S = 15;
#define D_TPV 100
#define V_POS 2
#define D_X2 390
#define D_TV 40
#define D_V 320
#define D_NEAR 1680
#define D_FAR (D_NEAR - 110)
#define E_MUL 28
#define D_WF 60
#define NE 0
#define D_H 0
#define D_W2 90
#define SETTLE 0
#define TV_POS 0
#define D_PA 40
#define NE1 10
#define H_POS 3
#define PA_POS 1
#define K_DLY 0
#define ST_BAR 1
#define W1_AT -1
#define ROT 2
#define ALIGN 0
#define CNT32 0
#define O_POS 1
#define Z_POS 0
#define QF_LATE 100
#define W0_E 3
#define H_ROT 1
#define WO_LATE 1
#define QK_AT 15
#define QK_F 0
#define G_AT 24
#define W0_AT 4
#define W0_RS (NL - 1)
#define P_GATE 1
#define NPF (NL + 6)

struct Delays { uint32_t near, far, x2, v, w2, pa, wf, tv; };
#define MISS(i, v)
#define MISS_INIT
#define MISS_OUT
#define HT(i)
#define PROF_INIT
#define PROF(i)
#define PROFV(i, v)
#define PROF_OUT

__device__ __forceinline__ uint32_t clk32() { uint32_t t; asm volatile("mov.u32 %0, %%clock;" : "=r"(t) :: "memory"); return t; }
__device__ __forceinline__ uint32_t smid() { uint32_t t; asm volatile("mov.u32 %0, %%smid;" : "=r"(t)); return t; }
__device__ __forceinline__ uint32_t gtime() { uint32_t t; asm volatile("mov.u32 %0, %%globaltimer_lo;" : "=r"(t) :: "memory"); return t; }
__device__ __forceinline__ void spin_until(uint32_t t0, uint32_t d) { while (clk32() - t0 < d) {} }
template <int N> __device__ __forceinline__ uint32_t delay(uint32_t zero) {
    float x = __uint_as_float(clk32());
#pragma unroll
    for (int i = 0; i < N; i++) asm volatile("ex2.approx.ftz.f32 %0, %0;" : "+f"(x));
    return __float_as_uint(x) & zero;
}
__device__ __forceinline__ uint32_t opaque(uint32_t v) { return __shfl_sync(~0u, v, threadIdx.x & 31); }
__device__ __forceinline__ uint32_t xor_or(uint32_t a, uint32_t b, uint32_t t) {
    uint32_t r; asm volatile("lop3.b32 %0, %1, %2, %3, 0x7E;" : "=r"(r) : "r"(a), "r"(b), "r"(t)); return r;
}
__device__ __forceinline__ uint32_t or3(uint32_t a, uint32_t b, uint32_t c) {
    uint32_t r; asm volatile("lop3.b32 %0, %1, %2, %3, 0xFE;" : "=r"(r) : "r"(a), "r"(b), "r"(c)); return r;
}
__device__ __forceinline__ uint32_t settag(uint32_t v, uint32_t tag) {
    uint32_t r; asm("lop3.b32 %0, %1, 1, %2, 0xB8;" : "=r"(r) : "r"(v), "r"(tag)); return r;
}
__device__ __forceinline__ void ldg4_if(uint4& v, const void* p, bool c) {
    asm volatile("{.reg .pred p; setp.ne.u32 p, %5, 0; @p ld.relaxed.gpu.global.v4.u32 {%0,%1,%2,%3}, [%4];}"
                 : "+r"(v.x), "+r"(v.y), "+r"(v.z), "+r"(v.w) : "l"(p), "r"((uint32_t)c) : "memory");
}
__device__ __forceinline__ uint4 ldg_rlx2x2(const void* p) {
    unsigned long long a, b;
    asm volatile("ld.relaxed.gpu.global.v2.b64 {%0,%1}, [%2];" : "=l"(a), "=l"(b) : "l"(p) : "memory");
    return make_uint4((uint32_t)a, (uint32_t)(a >> 32), (uint32_t)b, (uint32_t)(b >> 32));
}
__device__ __forceinline__ void stg_rlx2x2(void* p, uint32_t x, uint32_t y, uint32_t z, uint32_t w) {
    asm volatile("{.reg .b64 a, b; mov.b64 a, {%1,%2}; mov.b64 b, {%3,%4}; st.relaxed.gpu.global.v2.b64 [%0], {a, b};}" ::"l"(p), "r"(x), "r"(y), "r"(z), "r"(w) : "memory");
}
__device__ __forceinline__ void ldg1_if(uint32_t& v, const void* p, bool c) {
    asm volatile("{.reg .pred p; setp.ne.u32 p, %2, 0; @p ld.relaxed.gpu.global.u32 %0, [%1];}" : "+r"(v) : "l"(p), "r"((uint32_t)c) : "memory");
}
__device__ __forceinline__ void sts2(uint32_t a, float x, float y) { asm volatile("st.shared.v2.f32 [%0], {%1,%2};" ::"r"(a), "f"(x), "f"(y) : "memory"); }
__device__ __forceinline__ void sts4f(uint32_t a, float x, float y, float z, float w) {
    asm volatile("st.shared.v4.f32 [%0], {%1,%2,%3,%4};" ::"r"(a), "f"(x), "f"(y), "f"(z), "f"(w) : "memory");
}
__device__ __forceinline__ void sts1(uint32_t a, uint32_t x) { asm volatile("st.shared.u32 [%0], %1;" ::"r"(a), "r"(x) : "memory"); }
__device__ __forceinline__ uint32_t lds1(uint32_t a) { uint32_t v; asm volatile("ld.shared.u32 %0, [%1];" : "=r"(v) : "r"(a) : "memory"); return v; }
__device__ __forceinline__ float4 lds4f(uint32_t a) {
    float4 v; asm volatile("ld.shared.v4.f32 {%0,%1,%2,%3}, [%4];" : "=f"(v.x), "=f"(v.y), "=f"(v.z), "=f"(v.w) : "r"(a) : "memory"); return v;
}
__device__ __forceinline__ float2 lds2f(uint32_t a) {
    float2 v; asm volatile("ld.shared.v2.f32 {%0,%1}, [%2];" : "=f"(v.x), "=f"(v.y) : "r"(a) : "memory"); return v;
}
__device__ __forceinline__ bool any_bit0(uint32_t x) {
    uint32_t r;
    asm volatile("{.reg .pred p, q; .reg .b32 t; and.b32 t, %1, 1; setp.ne.u32 p, t, 0; vote.sync.any.pred q, p, 0xffffffff; selp.u32 %0, 1, 0, q;}" : "=r"(r) : "r"(x));
    return r;
}
__device__ __forceinline__ float rcp_fast(float x) { float r; asm("rcp.approx.ftz.f32 %0, %1;" : "=f"(r) : "f"(x)); return r; }
__device__ __forceinline__ void stsm4(uint32_t a, uint32_t r0, uint32_t r1, uint32_t r2, uint32_t r3) {
    asm volatile("stmatrix.sync.aligned.m8n8.x4.shared.b16 [%0], {%1,%2,%3,%4};" ::"r"(a), "r"(r0), "r"(r1), "r"(r2), "r"(r3) : "memory");
}
__device__ __forceinline__ void stsm4t(uint32_t a, uint32_t r0, uint32_t r1, uint32_t r2, uint32_t r3) {
    asm volatile("stmatrix.sync.aligned.m8n8.x4.trans.shared.b16 [%0], {%1,%2,%3,%4};" ::"r"(a), "r"(r0), "r"(r1), "r"(r2), "r"(r3) : "memory");
}
__device__ __forceinline__ uint32_t and3(uint32_t a, uint32_t b, uint32_t c) {
    uint32_t r; asm("lop3.b32 %0, %1, %2, %3, 0x80;" : "=r"(r) : "r"(a), "r"(b), "r"(c)); return r;
}
__device__ __forceinline__ void red_mem(void* p, uint32_t x, uint32_t y, uint32_t z, uint32_t w, void* q, uint32_t e, bool c) {
    asm volatile("{.reg .pred p; setp.ne.u32 p, %7, 0; red.relaxed.gpu.global.add.noftz.v4.bf16x2 [%0], {%1,%2,%3,%4}; @p red.relaxed.gpu.global.add.noftz.bf16x2 [%5], %6;}"
                 ::"l"(p), "r"(x), "r"(y), "r"(z), "r"(w), "l"(q), "r"(e), "r"((uint32_t)c) : "memory");
}
__device__ __forceinline__ void stg4_if(bool c, void* p, uint32_t x) {
    asm volatile("{.reg .pred p; setp.ne.u32 p, %2, 0; @p st.relaxed.gpu.global.v4.u32 [%0], {%1,%1,%1,%1};}" ::"l"(p), "r"(x), "r"((uint32_t)c) : "memory");
}
__device__ __forceinline__ uint32_t max3u(uint32_t a, uint32_t b, uint32_t c) { return __vimax3_u32(a, b, c); }
__device__ __forceinline__ void fence_gpu() { asm volatile("fence.acq_rel.gpu;" ::: "memory"); }

__device__ __forceinline__ void h_load(uint32_t sb, const uint8_t* hsrc, int pass, uint32_t rank, uint32_t rot) {
    const uint8_t* src = hsrc + (size_t)pass * 65536;
    const uint32_t bar = sb + SM_BAR + 8 * (B_HB + (pass & 1)), dst = sb + SM_HB + (pass & 1) * 65536 + rank * 4 * HBK;
    e_expect(bar, 32768);
#pragma unroll 1
    for (int i = 0; i < H_PIECES; i++) {
        const uint32_t o = ((i + rot) & (H_PIECES - 1)) * (16384 / H_PIECES);
        asm volatile("{.reg .pred p; elect.sync _|p, 0xffffffff;\n"
                     " @p cp.async.bulk.shared::cluster.global.mbarrier::complete_tx::bytes.multicast::cluster [%0], [%1], %4, [%2], %3;}"
                     ::"r"(dst + o + (o >> 12) * 1024), "l"(src + o), "r"(bar), "h"((uint16_t)3), "n"(16384 / H_PIECES) : "memory");
    }
}
__device__ __forceinline__ void h_piece(uint32_t sb, const uint8_t* hsrc, int pass, uint32_t rank, uint32_t i, bool first) {
    const uint32_t bar = sb + SM_BAR + 8 * (B_HB + (pass & 1));
    asm volatile("{.reg .pred p, q; elect.sync _|p, 0xffffffff; setp.le.and.s32 p, %5, 64, p; setp.ne.and.u32 q, %4, 0, p;\n"
                 " @q mbarrier.arrive.expect_tx.shared.b64 _, [%2], 32768;\n"
                 " @p cp.async.bulk.shared::cluster.global.mbarrier::complete_tx::bytes.multicast::cluster [%0], [%1], 4096, [%2], %3;}"
                 ::"r"(sb + SM_HB + (pass & 1) * 65536 + (rank * 4 + i) * HBK), "l"(hsrc + (uint32_t)(pass * 65536 + i * 4096)), "r"(bar), "h"((uint16_t)3), "r"((uint32_t)first), "r"(pass) : "memory");
}
__device__ __forceinline__ uint4 ldg_b128(const void* p) {
    uint4 v;
    asm volatile("{.reg .b128 t; .reg .b64 a, b; ld.relaxed.gpu.global.b128 t, [%4]; mov.b128 {a, b}, t; mov.b64 {%0,%1}, a; mov.b64 {%2,%3}, b;}"
                 : "=r"(v.x), "=r"(v.y), "=r"(v.z), "=r"(v.w) : "l"(p) : "memory");
    return v;
}
__device__ __forceinline__ void ldg_b128_into(uint4& v, const void* p) {
    asm volatile("{.reg .b128 t; .reg .b64 a, b; ld.relaxed.gpu.global.b128 t, [%4]; mov.b128 {a, b}, t; mov.b64 {%0,%1}, a; mov.b64 {%2,%3}, b;}"
                 : "+r"(v.x), "+r"(v.y), "+r"(v.z), "+r"(v.w) : "l"(p) : "memory");
}
__device__ __forceinline__ void stg_b128_if(bool c, void* p, uint32_t x, uint32_t y, uint32_t z, uint32_t w) {
    asm volatile("{.reg .pred p; setp.ne.u32 p, %5, 0; @p st.relaxed.gpu.global.v4.u32 [%0], {%1,%2,%3,%4};}"
                 ::"l"(p), "r"(x), "r"(y), "r"(z), "r"(w), "r"((uint32_t)c) : "memory");
}
__device__ __forceinline__ float pretag(float x, uint32_t add, uint32_t keep) { return __uint_as_float((__float_as_uint(x) + add) & keep); }

template <class F, class G>
__device__ __forceinline__ void softmax_rows(uint32_t src, uint32_t dst, uint32_t g16, int row0, F ready, G mid) {
    const uint32_t u = (g16 >> 7) & 3, e = ((g16 >> 9) << 3) | ((g16 >> 4) & 7);
    uint32_t se = src + e * 8, su = se + u * 1088, d0 = dst + e * 16 + u * 4, d1 = dst + 512 + e * 4;
    int vis = row0 + (e >> 2) - 2 * (e & 3) - 8 * u;
    asm volatile("" : "+r"(se), "+r"(su), "+r"(d0), "+r"(d1), "+r"(vis));
    ready();
    const float2 p0 = lds2f(su), p1 = lds2f(su + 256), p2 = lds2f(su + 512), p3 = lds2f(su + 768);
    const float2 m0 = lds2f(se + 4352), m1 = lds2f(se + 4352 + 256), m2 = lds2f(se + 4352 + 512), m3 = lds2f(se + 4352 + 768);
    float a0 = (p0.x + p1.x) + (p2.x + p3.x), a1 = (p0.y + p1.y) + (p2.y + p3.y);
    const float a2 = (m0.x + m1.x) + (m2.x + m3.x), a3 = (m0.y + m1.y) + (m2.y + m3.y);
    if (vis < 0) a0 = -1e9f / 0.08838834764831845f;
    if (vis < 1) a1 = -1e9f / 0.08838834764831845f;
    int k = __float_as_int(fmaxf(fmaxf(a0, a1), fmaxf(a2, a3)));
    k ^= (k >> 31) & 0x7fffffff;
    const bool hi = g16 & 64;
    const int k0 = __reduce_max_sync(~0u, hi ? INT_MIN : k), k1 = __reduce_max_sync(~0u, hi ? k : INT_MIN);
    mid();
    k = hi ? k1 : k0;
    const float m = __int_as_float(k ^ ((k >> 31) & 0x7fffffff));
    const float sl2 = 0.08838834764831845f * 1.4426950408889634f, mb = -m * sl2;
    sts1(d0, pack2(ex2(fmaf(a0, sl2, mb)), ex2(fmaf(a1, sl2, mb))));
    sts1(d1, pack2(ex2(fmaf(a2, sl2, mb)), ex2(fmaf(a3, sl2, mb))));
}

__device__ __forceinline__ uint32_t pack_h2(float lo, float hi) {
    uint32_t r; asm("cvt.rn.satfinite.f16x2.f32 %0, %1, %2;" : "=r"(r) : "f"(hi), "f"(lo)); return r;
}
__device__ __forceinline__ float2 unpack_h2(uint32_t u) {
    float2 r; asm("{.reg .b16 l, h; mov.b32 {l, h}, %2; cvt.f32.f16 %0, l; cvt.f32.f16 %1, h;}" : "=f"(r.x), "=f"(r.y) : "r"(u)); return r;
}
__device__ __forceinline__ uint32_t add_h2(uint32_t a, uint32_t b) { uint32_t r; asm("add.rn.f16x2 %0, %1, %2;" : "=r"(r) : "r"(a), "r"(b)); return r; }
__device__ __forceinline__ uint32_t max_h2(uint32_t a, uint32_t b) { uint32_t r; asm("max.f16x2 %0, %1, %2;" : "=r"(r) : "r"(a), "r"(b)); return r; }
__device__ __forceinline__ void stg2_if(bool c, void* p, uint32_t x, uint32_t y) {
    asm volatile("{.reg .pred p; .reg .b64 v; setp.ne.u32 p, %3, 0; mov.b64 v, {%1, %2}; @p st.relaxed.gpu.global.b64 [%0], v;}" ::"l"(p), "r"(x), "r"(y), "r"((uint32_t)c) : "memory");
}
__device__ __forceinline__ void stg1_if(bool c, void* p, uint32_t x) {
    asm volatile("{.reg .pred p; setp.ne.u32 p, %2, 0; @p st.relaxed.gpu.global.u32 [%0], %1;}" ::"l"(p), "r"(x), "r"((uint32_t)c) : "memory");
}
struct U2 { uint32_t x, y; };
__device__ __forceinline__ U2 ldg_u2(const void* p) {
    U2 v; asm volatile("{.reg .b64 t; ld.relaxed.gpu.global.b64 t, [%2]; mov.b64 {%0, %1}, t;}" : "=r"(v.x), "=r"(v.y) : "l"(p) : "memory"); return v;
}
constexpr int POLL_LIMIT = 1 << 16;
constexpr float SM_L2E = 0.08838834764831845f * 1.4426950408889634f;
template <int V> struct IC { static constexpr int value = V; };
typedef unsigned long long u64;
__device__ __forceinline__ uint32_t lo32(u64 v) { return (uint32_t)v; }
__device__ __forceinline__ uint32_t hi32(u64 v) { return (uint32_t)(v >> 32); }
__device__ __forceinline__ u64 ldg_u64(const void* p) { u64 v; asm volatile("ld.relaxed.gpu.global.b64 %0, [%1];" : "=l"(v) : "l"(p) : "memory"); return v; }
__device__ __forceinline__ void ldg_u64_if(u64& v, const void* p, bool c) {
    asm volatile("{.reg .pred p; setp.ne.u32 p, %2, 0; @p ld.relaxed.gpu.global.b64 %0, [%1];}" : "+l"(v) : "l"(p), "r"((uint32_t)c) : "memory");
}
__device__ __forceinline__ void rec_main(uint32_t sb, const CUtensorMap* tWo, uint8_t* arena, int role, int hinfo, int wg, uint32_t zero, const Delays& dly) {
    const int hA = hinfo & 255;
    const int tid = threadIdx.x, t = tid & 127, lane = tid & 31, wi = t >> 5;
    const uint32_t bars = sb + SM_BAR;
    const int head = role >> 2, qd = role & 3, j = blockIdx.x & 1, kh = role & 1;
    const uint32_t mypar = head >= hA;
    const uint32_t wu = __reduce_max_sync(~0u, wi);
    const bool warp0 = wu == 0, warp1 = wu == 1;
    const uint8_t* hsrc = (const uint8_t*)g_himg + kh * 32768 + j * 16384;
    auto tokbase = [&](int ty) { return ((ty + 1) << 21) + blk(lb_tok(head), mypar ^ ((hinfo >> (8 + ty)) & 1)); };
    const uint32_t tbw = tokbase(wg), tbq = tokbase(0) + (qd >> 1) * 2048 + (qd & 1) * 8;
    uint32_t w[32 - NL][4];
    const uint32_t frow = ((lane >> 4) * 8 + (lane & 7)) * 128, fx = ((lane >> 3) & 1) ^ (lane & 7);
    const uint32_t wl0 = sb + wg * 65536 + frow + ((fx ^ (2 * wi)) << 4);
    {
        if (wg > 0) wait_count_w(&g_tick[32 + (lane & 3) * 8], 1);
        if (wg == 1) asm volatile("fence.proxy.async.global;" ::: "memory");
#pragma unroll 1
        for (int i = 0; i < 4; i++) mbar_wait_w(bars + 8 * (B_W + (wg == 2 ? 8 + i : 2 * i + wg)), 0);
#pragma unroll
        for (int p = NL; p < 32; p++) ldsm4t(w[p - NL], wl0 + p * 2048);
        fence_async_smem();
        bar_sync(wg < 2 ? NB_WG : NB_X2, wg < 2 ? 256 : 128);
        if (wg == 2 && wu < 3) {
            e_expect(bars + 8 * B_WO, 16384);
            e_tma2d(sb + SM_WO + wu * 16384, tWo, (wu >> 1) * 512 + qd * 128 + (wu & 1) * 64, head * DH, bars + 8 * B_WO);
            e_tma2d(sb + SM_WO + wu * 16384 + 8192, tWo, (wu >> 1) * 512 + qd * 128 + (wu & 1) * 64, head * DH + 64, bars + 8 * B_WO);
        }
        if (wg == 1 && warp0) {
            if (lane == 0) mbar_arrive_cluster(bars + 8 * B_HE, j ^ 1);
            mbar_wait_w(bars + 8 * B_HE, 0);
#pragma unroll 1
            for (int i = 0; i < 2; i++) h_load(sb, hsrc, i, j, head);
        }
        TL(3 + wg)
    }
    uint32_t g16 = opaque(t * 16);
    auto G16 = [&]() { asm volatile("" : "+r"(g16)); return g16; };
    const uint32_t sbl = sb - wu * 512;
    const uint32_t xso = blk(lb_x2(head), mypar), cu = kh * 2048 + (2 * j + (wu >> 1)) * 512;
    const uint32_t u_xo = xso + wg * 16384 + (wu & 1) * 2048 + (cu >> 1) - wu * 256, u_to = tbw + (wu & 1) * 16384 + cu - wu * 512;
    const uint32_t mrow = wg < 2 ? mem_row(wu >> 1, wg * 2 + (wu & 1), qd) : mem_row(kh, wu, 0);
    const uint32_t u_m = mrow - wu * 512, u_e = mrow + 512 - wu * (CNT32 ? 64 : 128);
#define TAB(i) lds1(sb + SM_TAB + (i) * 512 + (G16() >> 2))
    {
        const uint32_t r8 = lane & 7;
        const uint32_t tb = sb + SM_TAB + wg * 1536 + t * 4, ma = sb + SM_HB + 4096 + r8 * 128;
        if (wg < 2) {
            sts1(tb, sb + SM_WO + wi * 16384 + frow + ((fx ^ (2 * wg)) << 4));
            sts1(tb + 512, wl0);
            sts1(tb + 1024, ma + (((lane >> 3) ^ r8) << 4));
        } else {
            sts1(tb, ma + (wi & 1) * HBK + ((((wi & 2) + (lane >> 4) * 4 + ((lane >> 3) & 1)) ^ r8) << 4));
            sts1(tb + 512, ((((wi & 2) + 5) ^ r8) << 4) + ((CNT32 ? (lane & 3) == 3 : lane & 1) ? ma + ((wi & 1) + (lane >> 3) * 2) * HBK : sb + SM_HB - 128));
            sts1(tb + 1024, mem_row(role >> 6, (role >> 4) & 3, (role >> 2) & 3) + (lane < 8 ? qd * 128 + lane * 16 : 512 + qd * 32 + (lane & 1) * 16));
        }
    }
    PROF_INIT
    MISS_INIT
#define HB(ks) dadd(mkdesc(SB0 + SM_HB + ((ks) >> 2) * HBK + ((ks) & 3) * 32, 16, 1024, 1), hbo)
#define STEP_CONSTS                                                                                  \
    const uint32_t tag = (s & 1) ^ 1, ttag = ((s >> 1) & 1) ^ 1, tso = (s & 1) * 32768;              \
    G16();                            \
    const int p = s + 2, b = p & 1;                                                                  \
    uint32_t hbo = b * 4096, fz[5] = {0, 0, 0, 0, 0};                                                \
    const uint32_t ftag = (((p - 1) >> 1) & 1) ^ 1, ptag = ((p >> 1) & 1) ^ 1;                       \
    const uint32_t pso = tbw + (1 << 20) + (b ^ 1) * 32768 + j * 16384 + kh * 2048;
#define SCHED_FENCE(i) fz[i] = clk32();
#define FZ ((fz[0] | fz[1] | fz[2] | fz[3] | fz[4]) & zero)
#define BLOCK_FENCE asm volatile("pmevent 0;" ::: "memory");
    constexpr int GAP = 32 / NL;
#define l16 (sbl + g16)
#define g8 (g16 >> 1)
    uint4 u, v;
    uint8_t *pdst, *fdst;
    auto tok_pack = [&](int ty, const float* acc, uint32_t ftag, uint32_t ptag, bool later = false) {
        const bool tg = ty == 2 || !(g16 & 64);
        const uint32_t add = tg ? (ftag ^ 1) << 16 : 0u, keep = tg ? 0xfffe0000u : ~0u;
        const uint32_t add1 = ty == 2 ? 0u : add, keep1 = ty == 2 ? ~0u : keep;
        const uint32_t add2 = ty == 0 ? add : 0u, keep2 = ty == 0 ? keep : ~0u;
        v = {pack2(pretag(acc[0], add, keep), pretag(acc[1], add1, keep1)), pack2(acc[2], acc[3]),
             pack2(pretag(acc[4], add2, keep2), pretag(acc[5], add2, keep2)), pack2(acc[6], acc[7])};
        if (ty < 2) { v.x = movm(v.x); v.z = movm(v.z); v.y = movm(v.y); v.w = movm(v.w); }
        u = {pack2(pretag(acc[8], (ptag ^ 1) << 16, 0xfffe0000u), acc[9]) | ptag, pack2(acc[10], acc[11]), pack2(acc[12], acc[13]), pack2(acc[14], acc[15])};
        if (later) return;
        v.x = settag(v.x, ftag);
        if (ty == 0) v.z = settag(v.z, ftag);
    };

#pragma unroll 1
    for (int s = -2; s < 0; s++) {
        STEP_CONSTS
        (void)tag; (void)ttag; (void)tso; (void)fz;
        float acc[16];
        mbar_wait_w(bars + 8 * (B_HB + b), 0);
        wg_fence();
#pragma unroll
        for (int i = 0; i < 32; i++) {
            if (i < NL) wgmma_ss32(acc, dadd(mkdesc(SB0 + i * 2048, 8192, 1024, 1), wg * 4096), HB(i), i != 0);
            else wgmma_rs32(acc, w[i < NL ? 0 : i - NL], HB(i), 1);
        }
        wg_commit();
        uint4 pa = {0, 0, 0, 0};
        int it = 0;
#pragma unroll 1
        while ((p > 0) & any_bit0(pa.x ^ ftag) & (++it < POLL_LIMIT)) pa = ldg_b128(arena + (pso + g16));
        pdst = arena + ((pso ^ (32768 + 2048)) + G16());
        fdst = arena + ((b ^ 1) * 32768 + u_to + g16);
        wg_wait<0>();
#pragma unroll
        for (int k = 0; k < 4; k++) { acc[2 * k] += bflo((&pa.x)[k]); acc[2 * k + 1] += bfhi((&pa.x)[k]); }
        tok_pack(wg, acc, ftag, ptag);
        stg_b128_if(true, pdst, u.x, u.y, u.z, u.w);
        stg_b128_if(p > 0, fdst, v.x, v.y, v.z, v.w);
        if (p == 0) {
            TL(2)
            if (wg != 1) bar_arrive(NB_C, 288);
        }
    }
    if (wg == 1 && warp0) {
        wait_count_w(&g_tick[32 + (lane & 3) * 8], 2);
        asm volatile("fence.proxy.async.global;" ::: "memory");
        bar_sync(NB_C, 288);
        if (g16 == 0) mbar_arrive_cluster(bars + 8 * B_HE, j ^ 1);
        mbar_wait_w(bars + 8 * B_HE, 1);
        h_load(sb, hsrc, 2, j, head);
    }

    auto qk_loop = [&](auto wgc) {
        constexpr int WG = decltype(wgc)::value;
        uint32_t w0[NL][4], lm0;
        auto w0_load = [&]() {
            const uint32_t wl = TAB(WG * 3 + 1);
            lm0 = TAB(WG * 3 + 2);
#pragma unroll
            for (int k = 0; k < NL; k++) ldsm4t(w0[k], wl + k * 2048);
        };
        const uint32_t wlo = WG * 65536 - SM_WO - wu * 16384, wlx = __reduce_max_sync(~0u, (wi ^ WG) << 5);
        uint32_t tq0, lm, lm1;
        auto proj_pre = [&](int s) {
            uint32_t wz0 = zero;
#pragma unroll
            for (int k = 0; k < NL; k += 2) wz0 = and3(wz0, w0[k][0], w0[k + 1 < NL ? k + 1 : k][0]);
            lm = lm0 + (s & 1) * 65536 + wz0; lm1 = lm ^ 64;
            asm volatile("" : "+r"(lm), "+r"(lm1));
        };
        auto proj = [&](int s, auto mid) {
            bar_sync(NB_MEM, 384);
            float c[4][4];
            uint32_t bf[16][4], tq1 = 0, tq2 = 0;
#pragma unroll
            for (int it = 0; it < 3; it++) ldsm4(bf[it], (it & 1 ? lm1 : lm) + (it >> 1) * HBK);
            mid(-1);
#pragma unroll
            for (int it = 0; it < 16; it++) {
                const uint32_t* bfr = bf[it];
                if (it + 3 < 16) ldsm4(bf[it + 3 < 16 ? it + 3 : 0], (it & 1 ? lm : lm1) + ((it + 3) >> 1) * HBK);
                const uint32_t* wa = 2 * it < NL ? w0[2 * it < NL ? 2 * it : 0] : w[2 * it < NL ? 0 : 2 * it - NL];
                const uint32_t* wb = 2 * it + 1 < NL ? w0[2 * it + 1 < NL ? 2 * it + 1 : 0] : w[2 * it + 1 < NL ? 0 : 2 * it + 1 - NL];
                float *ca = c[(2 * it) & 3], *cb = c[(2 * it + 1) & 3];
                if (it < 2) { mma16816z(ca, wa, bfr[0], bfr[1]); mma16816z(cb, wb, bfr[2], bfr[3]); }
                else { mma16816(ca, wa[0], wa[1], wa[2], wa[3], bfr[0], bfr[1]); mma16816(cb, wb[0], wb[1], wb[2], wb[3], bfr[2], bfr[3]); }
                mid(it);
                if (it == QK_AT) { tq1 = clk32(); bar_arrive(NB_QK, 384); if (QK_F) tq2 = clk32(); }
            }
            const uint32_t xo = u_xo + (G16() >> 1);
            float r[4];
#pragma unroll
            for (int e = 0; e < 4; e++) {
                constexpr float SH = SM_L2E / 64;
                r[e] = WG ? (c[0][e] + c[1][e]) + (c[2][e] + c[3][e]) : fmaf(c[2][e] + c[3][e], SH, (c[0][e] + c[1][e]) * SH);
            }
            const uint32_t r0 = pack2(r[0], r[1]), r1 = pack2(r[2], r[3]);
            const uint32_t m0 = movm(r0), m1 = movm(r1);
            tq0 = clk32();
            if (QK_AT > 15) bar_arrive(NB_QK, 384);
            stg_rlx2(arena + xo, settag(m0, (s & 1) ^ 1), m1);
            tq0 += (tq1 | tq2) & zero;
        };
        w0_load();
        proj_pre(0);
        if (WG == 1 || !ROT) bar_sync(NB_P, ROT ? 256 : 384);
        proj(0, [](int) {});
        if (WO_LATE && WG == 0) mbar_wait_w(bars + 8 * B_WO, 0);
#pragma unroll 1
        for (int s = 0;; s++) {
            STEP_CONSTS
            uint4 pa;
            float acc[16];
            auto acc_init = [&]() {
#pragma unroll
                for (int k = 0; k < 4; k++) { acc[2 * k] = bflo((&pa.x)[k]); acc[2 * k + 1] = bfhi((&pa.x)[k]); acc[8 + 2 * k] = __uint_as_float((&pa.x)[k] & zero); acc[9 + 2 * k] = __uint_as_float(~(&pa.x)[k] & zero); }
            };
            uint32_t wf[NPF][4], a3;
#define WF(f) ((a3 ^ (((f) & 1) * 64)) + ((f) >> 1) * 2048)
            if (WG == 1) {
                float sc[5][4];
                uint32_t sx0 = sb + SM_SX - wu * (2560 - 16) + G16() * 5;
                asm volatile("" : "+r"(sx0));
                int it = 0;
                bool bad;
#pragma unroll 1
                do {
                    uint4 kf[2][2];
                    U2 qf[2], x[8];
                    const uint32_t gz = g16 | (it & zero);
                    const uint8_t *ts = arena + (tso + tbw + gz), *tq = arena + (tso + tbq + gz), *xp = arena + (xso + (gz >> 1));
#pragma unroll
                    for (int a = 0; a < 4; a++) kf[a >> 1][a & 1] = ldg_b128(ts + (a >> 1) * 16384 + (a & 1) * 2048);
                    if (QF_LATE) spin_until(tq0, dly.x2 - QF_LATE);
#pragma unroll
                    for (int a = 0; a < 2; a++) qf[a] = ldg_u2(tq + a * 16384);
                    spin_until(tq0, dly.x2);
#pragma unroll
                    for (int i = 0; i < 8; i++) x[i] = ldg_u2(xp + (i >> 2) * 16384 + (i & 3) * 1024);
                    PROF(8)
                    const uint32_t q0[4] = {hadd2(x[0].x, x[1].x), qf[0].x, hadd2(x[0].y, x[1].y), qf[0].y};
                    const uint32_t q1[4] = {hadd2(x[2].x, x[3].x), qf[1].x, hadd2(x[2].y, x[3].y), qf[1].y};
                    PROFV(7, clk32() + (q0[0] & zero))
                    const uint32_t bt = ((qf[0].x ^ ttag) | (qf[1].x ^ ttag)) | ((kf[0][0].x ^ ttag) | (kf[0][1].x ^ ttag)) | ((kf[1][0].x ^ ttag) | (kf[1][1].x ^ ttag));
                    uint32_t bx = 0;
#pragma unroll
                    for (int i = 0; i < 8; i += 2) bx |= (x[i].x ^ tag) | (x[i + 1].x ^ tag);
                    mma16816z(sc[0], q0, kf[0][0].x, kf[0][0].y);
                    mma16816z(sc[1], q0, kf[0][0].z, kf[0][0].w);
                    mma16816z(sc[2], q0, kf[0][1].x, kf[0][1].y);
                    mma16816z(sc[3], q0, kf[0][1].z, kf[0][1].w);
                    mma16816z(sc[4], q0, hadd2(x[4].x, x[5].x), hadd2(x[4].y, x[5].y));
                    bad = any_bit0((XP & 8 ? bt & zero : bt) | bx) & (++it < POLL_LIMIT);
                    mma16816(sc[0], q1[0], q1[1], q1[2], q1[3], kf[1][0].x, kf[1][0].y);
                    mma16816(sc[1], q1[0], q1[1], q1[2], q1[3], kf[1][0].z, kf[1][0].w);
                    mma16816(sc[2], q1[0], q1[1], q1[2], q1[3], kf[1][1].x, kf[1][1].y);
                    mma16816(sc[3], q1[0], q1[1], q1[2], q1[3], kf[1][1].z, kf[1][1].w);
                    mma16816(sc[4], q1[0], q1[1], q1[2], q1[3], hadd2(x[6].x, x[7].x), hadd2(x[6].y, x[7].y));
                } while (bad);
                PROFV(13, it - 1) MISS(1, it - 1)
                sts4(sx0, pack_h2(sc[0][0], sc[0][1]), pack_h2(sc[1][0], sc[1][1]), pack_h2(sc[2][0], sc[2][1]), pack_h2(sc[3][0], sc[3][1]));
                sts1(sx0 + 64 - wu * 12, pack_h2(sc[4][0], sc[4][1]));
                bar_arrive(NB_X1, 384);
#pragma unroll
                for (int n = 0; n < 5; n++) sts2(sb + SM_SX + 2560 + g8 + n * 1088, sc[n][2], sc[n][3]);
                PROF(3)
                a3 = TAB(WG * 3);
                if (WO_LATE && s == 0) mbar_wait_w(bars + 8 * B_WO, 0);
                softmax_rows(sb + SM_SX + 2560, sb + SM_PX + 1024, g16 | (clk32() & zero), qd * 8, [&]() { BLOCK_FENCE bar_sync(NB_PX, 128); }, [&]() {
                    BLOCK_FENCE
#pragma unroll
                    for (int f = 0; f < NE1; f++) ldsm4t(wf[f], WF(f));
                    BLOCK_FENCE
                });
                PROF(4)
            } else {
                a3 = TAB(WG * 3);
                if (warp1 && (s & 3) == 1) asm volatile("fence.proxy.async.global;" ::: "memory");
                spin_until(tq0, dly.pa);
                uint4 x, y;
                int it = 0;
#pragma unroll 1
                do { x = ldg_b128(arena + (pso + g16)); y = ldg_b128(arena + (pso + tokbase(1) - tokbase(0) + g16)); }
                while (!(XP & 8) & (p <= NSEG) & any_bit0(xor_or(x.x, y.x, ftag)) & (++it < POLL_LIMIT));
                sts4(sb + SM_PA + g16, x.x, x.y, x.z, x.w);
                sts4(sb + SM_PA + 2048 + g16, y.x, y.y, y.z, y.w);
                if (NE) spin_until(tq0, dly.wf);
#pragma unroll
                for (int f = 0; f < NE; f++) ldsm4t(wf[f], WF(f));
                bar_sync(NB_X1, 384);
                if (E_MUL && g16 < 32) asm volatile("red.relaxed.gpu.global.max.u32 [%0], %1; red.relaxed.gpu.global.add.u32 [%0+4], 1;"
                                                    ::"l"(arena + ((blk(LB_TIME, 0) ^ (g16 << 8)) + qd * 1024 + (tq0 & zero))), "r"(gtime()) : "memory");
                __syncwarp();
                const uint32_t tx = clk32();
                if (H_POS == 2 && !(XP & 1) && warp1 && s + 3 <= NSEG) h_load(sb, hsrc, s + 3, j, H_ROT ? head : 0);
                spin_until(tx, dly.w2);
            }
#pragma unroll
            for (int f = WG ? NE1 : NE; f < NPF; f++) ldsm4t(wf[f], WF(f));
            PROF(5)
            if (s + 1 == NSEG) { bar_arrive(NB_X2, 384); break; }
            const uint32_t oa = l16 + SM_OX, slot = mem_slot(s + 1);
            float c[4][4];
            uint32_t ob[4][4];
            uint32_t wz = zero;
#pragma unroll
            for (int f = 0; f < NPF; f += 2) wz = and3(wz, wf[f][0], wf[f + 1 < NPF ? f + 1 : f][0]);
            BLOCK_FENCE
            bar_sync(NB_X2 + (SETTLE ? wz : 0), 384);
            ldsm4t(ob[0], oa);
            ldsm4t(ob[1], oa + 512);
            SCHED_FENCE(0)
#pragma unroll
            for (int f = 0; f < 16; f++) {
                const uint32_t *a = wf[f % NPF], *o = ob[f >> 2] + (f & 2);
                if (f < 4) mma16816z(c[f], a, o[0], o[1]);
                else mma16816(c[f & 3], a[0], a[1], a[2], a[3], o[0], o[1]);
                if (f == 3) ldsm4t(ob[2], oa + 1024);
                if (f == 5) { ldsm4t(ob[3], oa + 1536); if (NPF < 16) ldsm4t(wf[0], WF(NPF)); }
                if (f == 7) {
#pragma unroll
                    for (int k = NPF + 1; k < 16; k++) ldsm4t(wf[k - NPF], WF(k));
                }
                if (f == 3 || f == 5 || f == 7) SCHED_FENCE(f / 2)
                if (f == 11) {
#pragma unroll
                    for (int k = NL - W0_E; k < NL; k++) ldsm4t(w0[k], (a3 ^ wlx) + wlo + k * 2048);
                    SCHED_FENCE(4)
                }
            }
            const float last = c[1][3] + c[3][3], one = __uint_as_float(CNT1 << 16);
            red_mem(arena + (u_m + slot + G16()), pack2(c[0][0] + c[2][0], c[0][1] + c[2][1]), pack2(c[0][2] + c[2][2], c[0][3] + c[2][3]),
                    pack2(c[1][0] + c[3][0], c[1][1] + c[3][1]), pack2(c[1][2] + c[3][2], CNT32 && !(g16 & 16) ? last : one),
                    arena + (u_e + slot + (CNT32 ? (g16 >> 3) & ~3u : g16 >> 2)), pack2(one, last), !CNT32 || (g16 & 16));
            hbo += FZ;
            PROF(6)
            constexpr int NS = WG && W0_E < 0 ? NL : NL - W0_RS, GS = (32 - NL + NS) / NS;
            if (W0_E >= 0) {
                BLOCK_FENCE
#pragma unroll
                for (int k = NL - W0_E - 1; k >= 0; k--) ldsm4t(w0[k], (a3 ^ wlx) + wlo + k * 2048);
                lm0 = TAB(WG * 3 + 2);
                if (WG == 1) pa = lds4(sb + SM_PA + 2048 + g16);
            }
            if (WG == 0) {
                bar_arrive(NB_WIN, 384);
                if (W0_E < 0) spin_until(clk32(), dly.tv);
                pa = lds4(sb + SM_PA + g16);
                if (W0_E < 0) w0_load();
                acc_init();
                asm volatile("" : F16(acc, 0));
                BLOCK_FENCE
            }
            if (WG == 1 && K_DLY) spin_until(clk32(), dly.wf);
            wg_fence();
            bar_sync(WG ? NB_WIN : NB_B, WG ? 384 : 256);
#pragma unroll
            for (int i = 0; i < 32; i++) {
                const int k = i / GS;
                if (i >= 32 - NL + NS) wgmma_rs32(acc, w0[i < 32 - NL + NS ? 0 : i - 32 + NL], HB(i - 32 + NL), 1);
                else if (i % GS == GS - 1 && k < NS) wgmma_ss32(acc, mkdesc(SB0 + WG * 65536 + k * 2048, 8192, 1024, 1), HB(k), 1);
                else wgmma_rs32(acc, w[i - (k < NS ? k : NS)], HB(NL + i - (k < NS ? k : NS)), WG == 0 || i);
                if (WG == 1 && i == G_AT) bar_arrive(NB_B, 256);
                if (WG == 1 && i == W1_AT) w0_load();
            }
            wg_commit();
            BLOCK_FENCE
            if (WG == 1 && warp0 && !(s & 3)) wait_count_w(&g_tick[32 + ((G16() >> 4) & 3) * 8], min((s + 1) / 4 + 3, 17));
            if (WG == 1 && W0_E < 0) { pa = lds4(sb + SM_PA + 2048 + g16); if (W1_AT < 0) w0_load(); }
            auto tok_store = [&](int m) {
                if (m & 1) stg_b128_if(XP & 8 ? s == 99 : true, arena + ((b ^ 1) * 32768 + u_to + G16()), v.x, v.y, v.z, v.w);
                if (m & 2) stg_b128_if(XP & 8 ? s == 99 : p < NSEG, arena + ((pso ^ (32768 + 2048)) + G16()), u.x, u.y, u.z, u.w);
            };
            if (WG == 0) proj_pre(s + 1);
            BLOCK_FENCE
            wg_wait<0>();
            if (WG == 0 && ROT) {
                asm volatile("" : F16(acc, 0));
                proj(s + 1, [&](int it) {
                    if (it < 0) {
                        SCHED_FENCE(0)
                        asm volatile("" : F16(acc, 0));
                        tok_pack(WG, acc, ftag, ptag, true);
                        tok_store(2);
                        SCHED_FENCE(1)
                    }
                    if (it == ROT) { SCHED_FENCE(2) v.x = settag(v.x, ftag); v.z = settag(v.z, ftag); tok_store(1); SCHED_FENCE(3) }
                });
                tq0 += (fz[0] | fz[1] | fz[2] | fz[3]) & zero;
            } else {
                if (WG == 1) {
#pragma unroll
                    for (int k = 0; k < 4; k++) { acc[2 * k] += bflo((&pa.x)[k]); acc[2 * k + 1] += bfhi((&pa.x)[k]); }
                }
                tok_pack(WG, acc, ftag, ptag);
                if (WG == 1) proj_pre(s + 1);
                asm volatile("" : "+r"(u.x), "+r"(u.y), "+r"(u.z), "+r"(u.w), "+r"(v.x), "+r"(v.y), "+r"(v.z), "+r"(v.w));
                BLOCK_FENCE
                bar_sync(NB_P, ROT ? 256 : 384);
                tok_store(3);
                proj(s + 1, [](int) {});
            }
        }
    };
    if (wg == 0) {
        qk_loop(IC<0>());
    } else if (wg == 1) {
        qk_loop(IC<1>());
    } else {
        const uint32_t ONES = 0x3f803f80u, u_o = qd * 65536 + head * 2048 + wu * 384;
        uint32_t tw = 0, dl = 0, dbase = kh == mypar ? dly.near : dly.far, dst0, dx0;
        dst0 = TAB(6); dx0 = TAB(7);
        uint32_t ov[4] = {0, 0, 0, 0};
        auto o_store = [&](int s) {
            uint8_t* od = (uint8_t*)g_O + (uint32_t)(s * (32 * NH * DH * 2) + u_o + (G16() >> 2));
#pragma unroll
            for (int a = 0; a < 4; a++) stg_rlx1(od + a * 128, ov[a]);
        };
        uint4 vf[2][2], pa;
        auto vf_fetch = [&](int s) {
            const uint8_t* ts = arena + ((s & 1) * 32768 + tbw + g16);
#pragma unroll
            for (int a = 0; a < 4; a++) vf[a >> 1][a & 1] = ldg_b128(ts + (a >> 1) * 16384 + (a & 1) * 2048);
        };
        auto tok_fetch = [&](int s) {
            if (TV_POS != 1) vf_fetch(s);
            pa = ldg_b128(arena + (tbw + (1 << 20) + (~s & 1) * 32768 + j * 16384 + kh * 2048 + g16));
        };
        if (PA_POS) tok_fetch(0);
        TL(9)
        if (!WO_LATE) mbar_wait_w(bars + 8 * B_WO, 0);
        TL(6)
#pragma unroll 1
        for (int s = 0; s < NSEG; s++) {
            STEP_CONSTS
#define VFBAD ((vf[0][0].x ^ ttag) | (vf[0][1].x ^ ttag) | (vf[1][0].x ^ ttag) | (vf[1][1].x ^ ttag))
#define TOKBAD ((TV_POS == 1 ? 0 : VFBAD) | (p <= NSEG ? pa.x ^ ftag : 0))
            {
                const uint32_t dst = dst0 + b * 65536, dx = dx0 + b * 65536;
                const uint8_t *ms = arena + (u_m + mem_slot(s) + g16), *me = arena + (u_e + mem_slot(s) + (CNT32 ? (g16 >> 3) & ~3u : g16 >> 2));
                const uint32_t em = CNT32 && !(g16 & 16) ? ~0u : 0u;
                asm volatile("" : "+l"(ms), "+l"(me));
                spin_until(tw, dl);
                PROF(11)
                int it = 0;
                bool bad;
#pragma unroll 1
                do {
                    uint4 m[4];
                    uint32_t x[4];
#pragma unroll
                    for (int i = 0; i < 4; i++) m[i] = ldg_rlx4(ms + i * 1024);
#pragma unroll
                    for (int i = 0; i < 4; i++) x[i] = ldg_rlx1(me + i * 1024);
#pragma unroll
                    for (int i = 0; i < 3; i++) {
                        stsm4t(dst + i * 2 * HBK, m[i].x, m[i].y, m[i].z, m[i].w);
                        if (i == P_GATE) asm volatile("{.reg .pred p; setp.eq.s32 p, %0, 0; @p bar.arrive %1, %2;}" ::"r"(it), "n"(NB_P), "n"(ROT ? 256 : 384) : "memory");
                    }
                    uint32_t c = and3(m[0].w, m[1].w, m[2].w);
                    SCHED_FENCE(1)
                    stsm4t(dst + 6 * HBK, m[3].x, m[3].y, m[3].z, m[3].w);
                    stsm4t(dx, x[0], x[1], x[2], x[3]);
                    asm volatile("" : "+r"(c));
                    c = and3(and3(((c & m[3].w) | em) >> 16, x[0], x[1]), x[2], x[3]);
                    bad = __any_sync(~0u, !(c & CNT_ALL)) & (++it < POLL_LIMIT);
                    asm volatile("{.reg .pred p; setp.eq.u32 p, %0, 0; @p bar.arrive %1, 384;}" ::"r"((uint32_t)bad), "n"(NB_MEM) : "memory");
                } while (bad);
                if (it > 1 && s > 1) dbase += dly.tv;
                PROFV(12, it - 1)
                MISS(0, it - 1) HT(5)
                PROF(8)
            }
            if (s == 1) { TL(7) TLC(0) }
            if (s == 63) TLC(1)
            if (s == 0) TL(13)
            if (O_POS == 1) o_store(max(s - 1, 0));
            if (Z_POS && warp1) stg4_if(g16 < 512 + 160, arena + (TAB(8) + mem_slot(s + 3)), 0);
            fence_async_smem();
            hbo += fz[1] & zero;
            int it = 0;
            if (!PA_POS) tok_fetch(s);
#pragma unroll 1
            while (!(XP & 8) & any_bit0(TOKBAD) & (++it < POLL_LIMIT)) tok_fetch(s + (it & zero));
            float acc[20];
#pragma unroll
            for (int k = 0; k < 4; k++) { acc[2 * k] = bflo((&pa.x)[k]); acc[2 * k + 1] = bfhi((&pa.x)[k]); acc[8 + 2 * k] = acc[9 + 2 * k] = acc[16 + k] = __uint_as_float(pa.x & zero); }
            if (XP & 1 ? s < 1 : p <= NSEG) mbar_wait_w(bars + 8 * (B_HB + b), (p >> 1) & 1);
            asm volatile("" : F16(acc, 0), F4(acc, 16));
            BLOCK_FENCE
            wg_fence();
            bar_sync(NB_QK, 384);
#pragma unroll
            for (int i = 0; i < 32; i++) {
                const int k = i / GAP;
                if (i % GAP == GAP - 1 && k < NL) wgmma_ss40(acc, mkdesc(SB0 + 131072 + k * 2048, 8192, 1024, 1), HB(k), 1);
                else wgmma_rs40(acc, w[i - (k < NL ? k : NL)], HB(NL + i - (k < NL ? k : NL)), 1);
            }
            wg_commit();
            uint8_t* vo = arena + (u_xo + (G16() >> 1));
            pdst = arena + ((pso ^ (32768 + 2048)) + G16());
            fdst = arena + ((b ^ 1) * 32768 + u_to + g16);
            BLOCK_FENCE
            wg_wait<0>();
            PROF(9)
            stg_rlx2(vo, settag(pack2(acc[16], acc[17]), tag), pack2(acc[18], acc[19]));
            const uint32_t tv = clk32();
            if (TV_POS == 1) vf_fetch(s);
            tok_pack(2, acc, ftag, ptag);
            stg_b128_if(XP & 8 ? s == 99 : p <= NSEG, fdst, v.x, v.y, v.z, v.w);
            stg_b128_if(XP & 8 ? s == 99 : p < NSEG, pdst, u.x, u.y, u.z, u.w);
            if (O_POS == 2) o_store(max(s - 1, 0));
            if (ST_BAR) bar_sync(NB_WG, 128);
            PROF(10)
            const uint8_t* xp = arena + (xso + 32768 + (G16() >> 1));
            const uint32_t sxa = sb + SM_SX - wu * 2560 + G16() * 5;
            uint32_t xv[4], gt = 0;
            auto pv = [&](uint32_t p0, uint32_t p1, uint32_t p2, uint32_t p3, uint32_t p4, auto getv, auto done) {
                float oc[2][4], lc[4] = {0.f, 0.f, 0.f, 0.f};
                mma16816(lc, ONES, ONES, ONES, ONES, p0, p1);
                mma16816z(oc[0], &vf[0][0].x, p0, p1);
                mma16816z(oc[1], &vf[1][0].x, p0, p1);
                mma16816(lc, ONES, ONES, ONES, ONES, p2, p3);
                mma16816(oc[0], vf[0][1].x, vf[0][1].y, vf[0][1].z, vf[0][1].w, p2, p3);
                mma16816(oc[1], vf[1][1].x, vf[1][1].y, vf[1][1].z, vf[1][1].w, p2, p3);
                mma1688(lc, ONES, ONES, p4);
                getv();
                mma1688(oc[0], xv[0], xv[1], p4);
                mma1688(oc[1], xv[2], xv[3], p4);
                done(__float_as_uint(oc[0][0]) | __float_as_uint(oc[1][0]) | __float_as_uint(lc[0]));
                const float r0 = rcp_fast(lc[0]), r1 = rcp_fast(lc[1]);
                ov[0] = pack2(oc[0][0] * r0, oc[0][1] * r1); ov[1] = pack2(oc[0][2] * r0, oc[0][3] * r1);
                ov[2] = pack2(oc[1][0] * r0, oc[1][1] * r1); ov[3] = pack2(oc[1][2] * r0, oc[1][3] * r1);
            };
            bool bad;
            it = 0;
#pragma unroll 1
            do {
                U2 xr[4];
                auto load_v = [&]() {
                    if (V_POS < 3) spin_until(tv, dly.v);
#pragma unroll
                    for (int i = 0; i < 4; i++) xr[i] = ldg_u2(xp + i * 1024);
                };
                if (TV_POS == 1 && it) {
                    const uint8_t* tz = arena + (tso + tbw + (g16 | (it & zero)));
#pragma unroll
                    for (int a = 0; a < 4; a++) ldg_b128_into(vf[a >> 1][a & 1], tz + (a >> 1) * 16384 + (a & 1) * 2048);
                }
                if (!V_POS) load_v();
                if (V_POS >= 3) spin_until(tv, dly.v);
                PROF(3)
                asm volatile("{.reg .pred p; setp.eq.s32 p, %0, 0; @p bar.sync %1, 384;}" ::"r"(it), "n"(NB_X1) : "memory");
                uint4 sx[5];
                if (V_POS == 3) load_v();
#pragma unroll
                for (int i = 0; i < 5; i++) sx[i] = lds4(sxa + i * 16);
                if (V_POS == 4) load_v();
                if (it == 0) { gt = gtime(); tw = clk32(); }
                if (V_POS == 2) load_v();
                uint32_t h[5];
#pragma unroll
                for (int n = 0; n < 4; n++) h[n] = add_h2(add_h2((&sx[0].x)[n], (&sx[1].x)[n]), add_h2((&sx[2].x)[n], (&sx[3].x)[n]));
                h[4] = add_h2(add_h2(sx[4].x, sx[4].y), add_h2(sx[4].z, sx[4].w));
                uint32_t hm = max_h2(max_h2(max_h2(h[0], h[1]), h[2]), max_h2(h[3], h[4]));
                hm = max_h2(hm, __byte_perm(hm, hm, 0x1032));
                const uint32_t m1 = __shfl_xor_sync(~0u, hm, 1), m2 = __shfl_xor_sync(~0u, hm, 2), m3 = __shfl_xor_sync(~0u, hm, 3);
                float2 a[5];
#pragma unroll
                for (int n = 0; n < 5; n++) a[n] = unpack_h2(h[n]);
                if (V_POS == 1) load_v(); else SCHED_FENCE(0)
                const float mb = -64.0f * unpack_h2(max_h2(max_h2(hm, m1), max_h2(m2, m3))).x;
                uint32_t pm[5];
#pragma unroll
                for (int n = 0; n < 5; n++) pm[n] = pack2(ex2(fmaf(a[n].x, 64.0f, mb)), ex2(fmaf(a[n].y, 64.0f, mb)));
                pv(pm[0], pm[1], pm[2], pm[3], pm[4], [&]() {
                    xv[0] = hadd2(xr[0].x, xr[1].x); xv[1] = hadd2(xr[0].y, xr[1].y);
                    xv[2] = hadd2(xr[2].x, xr[3].x); xv[3] = hadd2(xr[2].y, xr[3].y);
                }, [](uint32_t) {});
                bad = any_bit0((TV_POS == 1 && !(XP & 8) ? VFBAD : 0) | (xr[0].x ^ tag) | (xr[1].x ^ tag) | (xr[2].x ^ tag) | (xr[3].x ^ tag)) & (++it < POLL_LIMIT);
                stsm4(sb + SM_OX + g16, ov[0], ov[1], ov[2], ov[3]);
            } while (bad);
            PROFV(14, it - 1) MISS(2, it - 1)
            PROF(5)
            bar_sync(NB_X2, 384);
            BLOCK_FENCE
            U2 tv2 = {0, 0};
            const uint8_t* tp = arena + (blk(LB_TIME, mypar) + ((G16() << 6) & 0xc00));
            {
                const uint4 pp = lds4(l16 + SM_PX + 1024);
                const uint32_t p4 = lds1(sb + SM_PX + 512 + 1024 - wu * 128 + (G16() >> 2));
                if (E_MUL) tv2 = ldg_u2(tp);
                if (H_POS == 3 && !(XP & 1) && warp0 && s + 3 <= NSEG) h_load(sb, hsrc, s + 3, j, H_ROT ? head : 0);
                if (H_POS == 0 && !(XP & 1)) h_piece(sb, hsrc, s + 3, j, (wu + (H_ROT ? head : 0)) & 3, wu == 0);
                pv(pp.x, pp.y, pp.z, pp.w, p4, []() {}, [&](uint32_t r) { bar_arrive(NB_WIN + ((r | fz[0]) & zero), 384); });
            }
            dst0 = TAB(6); dx0 = TAB(7);
            const uint32_t zo = Z_POS ? 0 : TAB(8);
            PROF(6) HT(7)
            BLOCK_FENCE
            if (H_POS == 1 && !(XP & 1)) h_piece(sb, hsrc, s + 3, j, (wu + (H_ROT ? head : 0)) & 3, wu == 0);
            asm volatile("" : "+r"(tv2.y));
            it = 0;
#pragma unroll 1
            while (E_MUL && __any_sync(~0u, tv2.y < 32 * (s + 1)) & (++it < 16)) tv2 = ldg_u2(tp);
            const uint32_t e = __reduce_max_sync(~0u, tv2.x) - gt;
            MISS(3, it - 1) MISS(4, gt)
            if (PA_POS) tok_fetch(s + 1);
            if (O_POS == 0) o_store(s);
            if (!Z_POS) stg4_if(g16 < 160, arena + (zo + mem_slot(s + 3)), 0);
            dl = dbase + (e > 4096 ? 0 : e * E_MUL >> 4);
        }
        if (O_POS) o_store(NSEG - 1);
        TL(8)
    }
    PROF_OUT
    MISS_OUT
}

struct RecMaps { CUtensorMap wq, wk, wv, wo, wmod, w3, w1; };
struct RecPtrs { const bf16 *x, *mem0, *c, *wmod, *w1, *w3; uint8_t* arena; uint32_t zero; const bf16 *w2, *w4, *wo; Delays dly; };

__device__ __forceinline__ float silu_bf(const bf16* c, int i) {
    const float v = __bfloat162float(c[i]);
    return bfround(__fdividef(v, 1.0f + __expf(-v)));
}
#define LN_SEQ 0xcba6420987531ull
#define W_LATE 1000
#define W_OPEN 1400
__device__ __noinline__ uint32_t side_window_(const uint8_t* arena, uint32_t n) {
    U2 v;
    int it = 0;
#pragma unroll 1
    while (v = ldg_u2(arena + (LB_TIME << 13)), ((v.y >> 5) == n || gtime() - v.x > W_OPEN + W_LATE) && v.y < 32 * NSEG && ++it < 64) __nanosleep(100);
    it = 0;
#pragma unroll 1
    while ((int)(gtime() - v.x - W_OPEN) < 0 && ++it < 256) {}
    return v.y >> 5;
}
#define side_window(arena, n) n = side_window_(arena, n)
__device__ __noinline__ void rec_ln(uint32_t sb, const bf16* x, const uint8_t* arena, int id, int r0) {
    int r1 = 32;
    uint32_t n = 0;
    const int tid = threadIdx.x, lane = tid & 31, wid = __reduce_max_sync(~0u, tid >> 5);
    const uint32_t ring = sb + wid * 8192 + lane * 16, coef = sb + SM_PRE;
    x += (id * 8 + wid) * 2 * DM + lane * 8;
#pragma unroll 1
    for (int r = r0 - 1; r < r1; r++) {
        if (r > 3) side_window(arena, n);
        if (r + 1 < r1) {
#pragma unroll
            for (int i = 0; i < 8; i++)
                asm volatile("cp.async.cg.shared.global [%0], [%1], 16;" ::"r"(ring + (~r & 1) * 4096 + i * 512), "l"(x + (r + 1) * 64 * DM + i * 256) : "memory");
        }
        asm volatile("cp.async.commit_group; cp.async.wait_group 1;" ::: "memory");
        if (r < r0) continue;
        const uint32_t src = ring + (r & 1) * 4096;
        float m[2] = {0.f, 0.f}, rs[2];
#pragma unroll 1
        for (int ps = 0; ps < 2; ps++) {
            float t[2][2] = {{0.f, 0.f}, {0.f, 0.f}};
#pragma unroll 1
            for (int i = 0; i < 2048; i += 512) {
#pragma unroll
                for (int h = 0; h < 2; h++) {
                    const uint4 u = lds4(src + h * 2048 + i);
#pragma unroll
                    for (int e = 0; e < 4; e++) {
                        const float a = bflo((&u.x)[e]) - m[h], c = bfhi((&u.x)[e]) - m[h];
                        t[h][0] = fmaf(a, ps ? a : 1.0f, t[h][0]); t[h][1] = fmaf(c, ps ? c : 1.0f, t[h][1]);
                    }
                }
            }
            rs[0] = t[0][0] + t[0][1]; rs[1] = t[1][0] + t[1][1];
#pragma unroll 1
            for (int o = 16; o; o >>= 1) { rs[0] += __shfl_xor_sync(~0u, rs[0], o); rs[1] += __shfl_xor_sync(~0u, rs[1], o); }
            if (!ps) { m[0] = rs[0] * (1.0f / DM); m[1] = rs[1] * (1.0f / DM); }
        }
        rs[0] = rsqrtf(rs[0] * (1.0f / DM) + 1e-5f); rs[1] = rsqrtf(rs[1] * (1.0f / DM) + 1e-5f);
        if (r == r0) {
#pragma unroll 1
            for (int i = tid; i < 2 * DM / 4; i += 256) {
                float t[4];
                int it = 0;
                uint32_t ok;
#pragma unroll 1
                do {
                    uint4 u[8];
#pragma unroll
                    for (int k = 0; k < 8; k++) u[k] = ldg_rlx4(g_modp + k * 2 * DM + i * 4);
                    ok = 1;
#pragma unroll
                    for (int k = 0; k < 32; k++) { const uint32_t w = (&u[k >> 2].x)[k & 3]; ok &= w; t[k & 3] = k < 4 ? __uint_as_float(w) : t[k & 3] + __uint_as_float(w); }
                } while (!__all_sync(~0u, ok) & (++it < SPIN_LIMIT));
                const float o = i >> 8;
                const uint32_t lo = pack2(t[0], t[1]), hi = pack2(t[2], t[3]);
                sts4f(coef + (i >> 8) * 4096 + (i & 1) * 2048 + ((i & 255) >> 1) * 16, bflo(lo) + o, bfhi(lo) + o, bflo(hi) + o, bfhi(hi) + o);
            }
            bar_sync(NB_FIN0, 256);
            if (tid == 0 && r0 == 0) TL(2)
        }
        uint8_t* dst = (uint8_t*)g_himg + (r * 2 + (id >> 1)) * 65536 + (lane >> 3) * 4096 + wid * 256;
#pragma unroll 1
        for (int i = 0; i < 4; i++) {
            const uint32_t ca = coef + i * 512 + lane * 16;
            const float4 s0 = lds4f(ca), s1 = lds4f(ca + 2048), c0 = lds4f(ca + 4096), c1 = lds4f(ca + 6144);
            const float sh[8] = {s0.x, s0.y, s0.z, s0.w, s1.x, s1.y, s1.z, s1.w}, sc[8] = {c0.x, c0.y, c0.z, c0.w, c1.x, c1.y, c1.z, c1.w};
#pragma unroll
            for (int h = 0; h < 2; h++) {
                uint4 u = lds4(src + h * 2048 + i * 512);
#pragma unroll
                for (int e = 0; e < 4; e++) {
                    uint32_t& w = (&u.x)[e];
                    w = pack2(fmaf((bflo(w) - m[h]) * rs[h], sc[2 * e], sh[2 * e]), fmaf((bfhi(w) - m[h]) * rs[h], sc[2 * e + 1], sh[2 * e + 1]));
                }
                *(uint4*)(dst + i * 16384 + ((id & 1) == (i >> 1) ? 65536 : 2048) + h * 128 + (((lane ^ (2 * wid + h)) & 7) << 4)) = u;
            }
        }
        if (r == 0) {
            if (tid == 0) TLX(10)
            int ro, it = 0;
#pragma unroll 1
            do asm volatile("ld.volatile.shared.u32 %0, [%1];" : "=r"(ro) : "r"(sb + SM_BAR + 192) : "memory"); while ((ro == INT_MIN) & (++it < SPIN_LIMIT));
            if (ro >= 0) r1 = 2;
        }
        if (r && !(r & 1)) continue;
        bar_sync(r ? NB_FIN0 : NB_C, r ? 256 : 320);
        if (tid == 0 && r == 0) TLX(11)
        if (wid == (r >> 1 & 7)) {
            if (r == 1) bar_arrive(NB_B, 64);
            if (r == 3) wait_count_w(&g_tick[32 + id * 8], 2);
            if (lane == 0) { signal_count(&g_tick[32 + id * 8]); if (r == 0) TLX(12) }
            __syncwarp();
        }
    }
}
#define SIDE_T 300
template <int NQ>
__device__ __forceinline__ void side_gemv(const CUtensorMap* tm, int c0, int k0, int k1, uint32_t cs, uint32_t sb, const uint8_t* arena, uint32_t& n, uint32_t& ph, float (*acc)[8], bool once = false) {
    const uint32_t w = __reduce_max_sync(~0u, threadIdx.x >> 5 & 3), ring = sb + 65536 + w * 24576, bars = sb + SM_BAR + 8 * B_W + w * 24;
#pragma unroll
    for (int q = 0; q < NQ; q++)
#pragma unroll
        for (int j = 0; j < 8; j++) acc[q][j] = 0.f;
#pragma unroll 1
    for (; k0 < k1; k0 += 48, ph ^= 1) {
        const int nr = min(48, k1 - k0);
        side_window(arena, n);
        const uint32_t t0 = clk32();
#pragma unroll 1
        for (int g = 0; g < 3; g++) {
            spin_until(t0, (g * 4 + w) * (SIDE_T / 4));
            e_expect(bars + 8 * g, g * 16 < nr ? 8192 : 0);
            if (g * 16 < nr) e_tma2d_hint(ring + g * 8192, tm, c0, k0 + g * 16, bars + 8 * g, once ? EVICT_FIRST : EVICT_NORMAL);
        }
#pragma unroll 1
        for (int r = 0; r < nr; r += 16) {
            mbar_wait_w(bars + (r >> 1), ph);
            uint4 v[16];
#pragma unroll
            for (int h = 0; h < 16; h++) v[h] = lds4(ring + (r + h) * 512 + (threadIdx.x & 31) * 16);
            float4 cf[NQ][4];
#pragma unroll
            for (int q = 0; q < NQ * 4; q++) cf[q >> 2][q & 3] = lds4f(cs + ((q >> 2) * DM + k0 + r + (q & 3) * 4) * 4);
#pragma unroll
            for (int h = 0; h < 16; h++) {
                const float f[8] = {bflo(v[h].x), bfhi(v[h].x), bflo(v[h].y), bfhi(v[h].y), bflo(v[h].z), bfhi(v[h].z), bflo(v[h].w), bfhi(v[h].w)};
#pragma unroll
                for (int q = 0; q < NQ; q++)
#pragma unroll
                    for (int j = 0; j < 8; j++) acc[q][j] = fmaf((&cf[q][h >> 2].x)[h & 3], f[j], acc[q][j]);
            }
        }
        fence_async_smem();
        __syncwarp();
    }
}
__device__ __noinline__ void rec_side(float* sm, const RecMaps& mp, const RecPtrs& p, int id) {
    const int tid = threadIdx.x;
    if (tid < 256) {
        if (blockIdx.x < 128) rec_ln(smem_u32(sm), p.x, p.arena, id, 2);
        if (tid == 0) TL(14)
        for (int i = tid; i < 2 * S_; i += 256) g_st[id * 2 * S_ + i] = 0.f;
        if (id == 0 && tid < 64) g_pcnt[tid * 8] = 0;
        if (id == 1) for (int i = tid; i < 6 * 256; i += 256) g_pflag[i] = 0;
        if (id == 2 && tid == 0) g_pt = 0;
        bar_sync(NB_FIN0, 256);
        if (PDL && tid == 0) asm volatile("fence.acq_rel.gpu; griddepcontrol.launch_dependents;" ::: "memory");
        return;
    }
    const int t = tid - 256;
    float *coef = sm + 40960, *red = coef + 3 * DM;
    const uint32_t sb = smem_u32(sm), cs = smem_u32(coef);
    uint32_t n = 0, ph = 0;
    for (int i = t; i < DM; i += 128) { coef[i] = silu_bf(p.c, i); coef[2 * DM + i] = 1.0f; }
    if (t == 0) wait_count1(&g_tick[32], 1);
    bar_sync(NB_G, 128);
    const int w = __reduce_max_sync(~0u, t >> 5);
    float acc[3][8];
    side_gemv<1>(&mp.wmod, (2 + id) * DM + w * 256, 0, DM, cs, sb, p.arena, n, ph, acc, true);
#pragma unroll
    for (int j = 0; j < 8; j++) g_mod[(2 + id) * DM + t * 8 + j] = bfround(acc[0][j]);
    bar_sync(NB_G, 128);
    if (t == 0) signal_count(&g_tick[8]);
    side_gemv<1>(&mp.w3, id * (FF / 4) + w * 256, 0, DM, cs + 8 * DM, sb, p.arena, n, ph, acc);
    if (t < FF / 32) {
#pragma unroll
        for (int j = 0; j < 8; j++) g_vec[3 * DM + id * (FF / 4) + t * 8 + j] = acc[0][j];
    }
    if (t == 0) wait_count1(&g_tick[8], 4);
    bar_sync(NB_G, 128);
    for (int i = t; i < DM; i += 128) { coef[i] = 1.0f + __ldcg(g_mod + 4 * DM + i); coef[DM + i] = __ldcg(g_mod + 3 * DM + i); }
    bar_sync(NB_G, 128);
    if (id == 1 && t < 32) {
        float u[5] = {0, 0, 0, 0, 0};
        for (int i = t; i < DM; i += 32) {
            const float a = coef[i], b = coef[DM + i];
            u[0] += a; u[1] += a * a; u[2] += a * b; u[3] += b; u[4] += b * b;
        }
#pragma unroll
        for (int q = 0; q < 5; q++) { const float r = warp_sum(u[q]); if (t == 0) g_cst[q] = r * (1.0f / DM); }
    }
    side_gemv<3>(&mp.w1, id * 256, w * 256, w * 256 + 256, cs, sb, p.arena, n, ph, acc);
#pragma unroll
    for (int q = 0; q < 3; q++)
#pragma unroll
        for (int j = 0; j < 8; j++) red[((t >> 5) * 3 + q) * 256 + (t & 31) * 8 + j] = acc[q][j];
    bar_sync(NB_G, 128);
    for (int i = t; i < 768; i += 128) g_vec[(i >> 8) * DM + id * 256 + (i & 255)] = (red[i] + red[768 + i]) + (red[1536 + i] + red[2304 + i]);
    if (t == 0) TL(9)
}

__global__ void __cluster_dims__(2, 1, 1) __launch_bounds__(384, 1)
k_rec(const __grid_constant__ RecMaps mp, const __grid_constant__ RecPtrs p) {
    extern __shared__ uint8_t smraw[];
    const uint32_t sb = smem_u32(smraw);
    if ((sb & 0x3FFFF) != SB0) __trap();
    const uint32_t bars = sb + SM_BAR;
    const int tid = threadIdx.x, lane = tid & 31, b = blockIdx.x;
    const int wid = __reduce_max_sync(~0u, tid >> 5);
    const uint32_t rank = b & 1;
    uint8_t* arena = p.arena;
    volatile int* sinfo = (volatile int*)(smraw + SM_BAR + 192);
    if (tid == 0) TL(0)
    if (tid == 0) sinfo[0] = INT_MIN;
    if (tid == 352) {
        for (int i = 0; i < 17; i++) mbar_init(bars + 8 * i, i == B_WO ? 4 : 1);
        asm volatile("fence.mbarrier_init.release.cluster;" ::: "memory");
    }
    __syncwarp();
    asm volatile("barrier.cluster.arrive.relaxed.aligned;" ::: "memory");
    int pr = 0, hA = 0;
    if (wid < 8) {
        if (b < 128) {
            const int cb = (b & 15) * 128, k0 = (b >> 4) * 128 + (tid >> 4);
            uint4 v[8];
#pragma unroll
            for (int i = 0; i < 8; i++) v[i] = __ldg((const uint4*)(p.wmod + (size_t)(k0 + 16 * i) * (6 * DM) + cb + (tid & 15) * 8));
            float acc[8] = {0, 0, 0, 0, 0, 0, 0, 0};
            const float s8 = silu_bf(p.c, k0 + 16 * (lane & 7));
#pragma unroll
            for (int i = 0; i < 8; i++) {
                const float sv = __shfl_sync(~0u, s8, i, 16);
                acc[0] += sv * bflo(v[i].x); acc[1] += sv * bfhi(v[i].x); acc[2] += sv * bflo(v[i].y); acc[3] += sv * bfhi(v[i].y);
                acc[4] += sv * bflo(v[i].z); acc[5] += sv * bfhi(v[i].z); acc[6] += sv * bflo(v[i].w); acc[7] += sv * bfhi(v[i].w);
            }
            float* red = (float*)(smraw + SM_PRE);
            *(float4*)(red + (tid >> 4) * 128 + (tid & 15) * 8) = make_float4(acc[0], acc[1], acc[2], acc[3]);
            *(float4*)(red + (tid >> 4) * 128 + (tid & 15) * 8 + 4) = make_float4(acc[4], acc[5], acc[6], acc[7]);
            bar_sync(NB_FIN0, 256);
            if (wid < 4) {
                float t = 0;
#pragma unroll
                for (int i = 0; i < 16; i++) t += red[i * 128 + tid];
                stg_rlx1(&g_modp[(b >> 4) * 2 * DM + cb + tid], __float_as_uint(t) | 1u);
                TLX(14)
            }
        } else {
            rec_ln(sb, p.x, p.arena, b - 128, 0);
        }
    } else if (wid >= 10 && b >= 128) {
        {
            const int w = (b - 128) * 2 + wid - 10;
            const uint16_t* src = (const uint16_t*)p.mem0 + (lane & 3) * 2 * DM + (w >> 2) * 512 + (w & 1) * 64 + (w & 2) * 8 + (lane >> 2);
            uint32_t v[4][4];
#pragma unroll
            for (int i = 0; i < 16; i++) v[i >> 2][i & 3] = src[(i >> 2) * 128 + (i & 2) * 16 + (i & 1) * 8] | ((uint32_t)src[DM + (i >> 2) * 128 + (i & 2) * 16 + (i & 1) * 8] << 16);
            uint8_t* d = arena + mem_row(w >> 2, w & 3, 0);
            uint8_t* e = d + 512 + (CNT32 ? lane >> 1 : lane) * 4;
            d += lane * 16;
#pragma unroll
            for (int i = 0; i < 4; i++, d += 1024, e += 1024) {
                stg_rlx4(d, v[i][0], v[i][1], v[i][2], CNT32 && !(lane & 1) ? v[i][3] : (v[i][3] & 0xffff) | CNT_ALL << 16);
                stg_rlx4(d + mem_slot(1), 0, 0, 0, 0);
                stg_rlx4(d + mem_slot(2), 0, 0, 0, 0);
                if (!CNT32 || (lane & 1)) { stg_rlx1(e, (v[i][3] & 0xffff0000u) | CNT_ALL); stg_rlx1(e + mem_slot(1), 0); stg_rlx1(e + mem_slot(2), 0); }
            }
            if (w == 0 && lane < 8) stg_rlx2(arena + (LB_TIME << 13) + lane * 1024, 0, 0);
            bar_arrive(NB_C, 320);
        }
    } else if (rank == 0) {
        uint32_t best = ~0u;
        const int pg = wid < 10 ? 0 : 1 + (b >> 1) / 22;
        uint32_t* q = (uint32_t*)(arena + (pg << 21) + (pg ? blk(b >> 1, wid & 1) : blk(LB_PROBE, wid & 1) + b * 16));
        if (lane < 8) stg_rlx1(q + lane, 0);
        __syncwarp();
        if (lane == 0) {
            q += 3;
            uint32_t v = atomicAdd(q, 1u);
#pragma unroll 1
            for (int r = 0; r < NPROBE; r++) {
                const uint32_t t0 = clk32() + (v >> 8);
                v = atomicAdd(q + (v >> 8), 1u);
                uint32_t t1;
                asm volatile("{.reg .pred p; setp.eq.u32 p, %1, 0xffffffff; @p exit; mov.u32 %0, %%clock;}" : "=r"(t1) : "r"(v) : "memory");
                best = min(best, t1 - t0);
            }
            sinfo[wid - 6] = best;
        }
        bar_sync(NB_KDONE, b < 128 ? 128 : 64);
        if (tid == 256) {
            const uint32_t par = sinfo[2] > sinfo[3], vote = b < 128 && (sinfo[4] > sinfo[5]) != par;
            stg_rlx2(&g_clk[b >> 1], ((clk32() - 2 * gtime()) & ~127u) | b >> 1, 1 + 2 * par + 4 * vote);
        }
    }
    if (wid == 8) {
        U2 v[3], my;
        uint32_t c0;
        const int me = b >> 1;
        int it = 0;
        __syncwarp();
#pragma unroll 1
        do {
            my = ldg_u2(&g_clk[me]);
#pragma unroll
            for (int k = 0; k < 3; k++) v[k] = ldg_u2(&g_clk[k * 22 + min(lane, 21)]);
        } while (!__all_sync(~0u, my.y & v[0].y & v[1].y & v[2].y & 1) & (++it < SPIN_LIMIT));
        TLX(15)
        c0 = __reduce_min_sync(~0u, lane ? ~0u : v[0].x) - 4096;
        const uint32_t mc = me >= 64 ? ~0u : my.x - c0;
        const int par = my.y >> 1 & 1;
        uint32_t cnt = 0, flip = 0;
#pragma unroll
        for (int k = 0; k < 3; k++) {
            const uint32_t c = v[k].x - c0, o = v[k].y >> 1 & 1;
            const bool ln = k == 2 && lane >= 20;
            cnt += o + (o == par ? (ln ? 44 + lane < me : c < mc) * 256 + (c < my.x - c0) * 65536 : 0);
            flip |= __popc(__ballot_sync(~0u, v[k].y & 4) & 0x3fffff) > 10 ? 256 << k : 0;
        }
        cnt = __reduce_add_sync(~0u, lane < 22 ? cnt : 0);
        const int n1 = cnt & 255, n0 = 66 - n1, tk = cnt >> 8 & 255;
        if (lane == 0) g_cls[smid() & 255] = cnt < 32 << 16 ? par * 4 + (cnt >> 19) : 8;
        hA = min(n0 >> 1, NH);
        const int q0 = 2 * hA, q1 = 2 * NH - q0;
        const int over = tk - (par ? q1 : q0), lack = max(par ? q0 - n0 : q1 - n1, 0);
        if (over < 0) pr = par ? q0 + tk : tk;
        else if (over < lack) pr = (par ? n0 : q0 + n1) + over;
        else pr = -1 - (over - lack + (par ? max(n0 - q0, 0) : 0));
        hA |= flip;
        if (lane == 0) {
            sinfo[1] = hA; sinfo[0] = pr;
            if (b >= 128 && rank == 0) atomicOr(&g_tick[6], (pr < 0 ? 4u : 1u) << ((b - 128) >> 1));
        }
    }
    asm volatile("barrier.cluster.wait.aligned;" ::: "memory");
    if (wid == 8) {
        TL(1)
        __syncwarp();
        bar_arrive(NB_A, 288);
        bar_arrive(NB_S, 128);
        if (b >= 128 && pr < 0) bar_sync(NB_B, 64);
        if (pr >= 0) {
            const int pu = __reduce_max_sync(~0u, pr), c0 = (pu >> 1) * 128 + rank * 64, r0 = (pu & 1) * 512;
#pragma unroll 1
            for (int n = 0; n < 13; n++) {
                const u64 seq = b >= 128 ? LN_SEQ : 0xcba9876543210ull;
                const int i = seq >> (4 * n) & 15;
                if (b >= 128 && i == 0) bar_sync(NB_B, 64);
                if (n >= W_INFL) mbar_wait_w(bars + 8 * (B_W + (seq >> (4 * (n - W_INFL)) & 15)), 0);
                const int m = i < 8 ? i & 1 : i >> 2, k = i < 8 ? i >> 1 : i & 3;
                const uint32_t dst = sb + m * 65536 + k * 16384, br = bars + 8 * (m < 3 ? B_W + i : B_WO);
                const int c = m < 3 ? c0 : 576 + rank * 256 + (pu & 1) * 128, r = m < 3 ? r0 + k * 128 : (pu >> 1) * DH;
                const uint64_t pol = m < 3 ? EVICT_FIRST : EVICT_NORMAL;
                e_expect(br, 16384);
                e_tma2d_hint(dst, &mp.wq + m, c, r, br, pol);
                e_tma2d_hint(dst + 8192, &mp.wq + m, c, r + 64, br, pol);
            }
        }
    } else {
        bar_sync(wid < 8 ? NB_A : NB_S, wid < 8 ? 288 : 128);
    }
    const int prr = __reduce_max_sync(~0u, sinfo[0]);
    hA = __reduce_max_sync(~0u, sinfo[1]);
    if (prr < 0) {
        int j = (b - 128) >> 1;
        if (b < 128) {
            uint32_t v;
            int it = 0;
#pragma unroll 1
            do { v = __reduce_max_sync(~0u, ldg_rlx1(&g_tick[6])); spin_guard(++it); } while (__popc(v) < 2);
            j = v == 3 ? -1 - prr : (v & 1) ^ 1;
        }
        rec_side((float*)smraw, mp, p, j * 2 + rank);
        return;
    }
    if (PDL) asm volatile("griddepcontrol.launch_dependents;" ::: "memory");
    const int role = (prr >> 1) * 4 + rank * 2 + (prr & 1);
    rec_main(sb, &mp.wo, arena, role, hA, wid >> 2, p.zero, p.dly);
}

__device__ __forceinline__ void wgmma_ss192(float* d, uint64_t a, uint64_t b, int sc) {
    asm volatile("{.reg .pred p; setp.ne.b32 p, %98, 0;\n wgmma.mma_async.sync.aligned.m64n192k16.f32.bf16.bf16 "
                 "{%0,%1,%2,%3,%4,%5,%6,%7,%8,%9,%10,%11,%12,%13,%14,%15,%16,%17,%18,%19,%20,%21,%22,%23,%24,%25,%26,%27,%28,%29,%30,%31,%32,%33,%34,%35,%36,%37,%38,%39,%40,%41,%42,%43,%44,%45,%46,%47,%48,%49,%50,%51,%52,%53,%54,%55,%56,%57,%58,%59,%60,%61,%62,%63,%64,%65,%66,%67,%68,%69,%70,%71,%72,%73,%74,%75,%76,%77,%78,%79,%80,%81,%82,%83,%84,%85,%86,%87,%88,%89,%90,%91,%92,%93,%94,%95}, %96, %97, p, 1, 1, 0, 1;}"
                 : F16(d, 0), F16(d, 16), F16(d, 32), F16(d, 48), F16(d, 64), F16(d, 80) : "l"(a), "l"(b), "r"(sc));
}

constexpr uint32_t P_B = 81920, P_PL = 40960, P_OUT = 180224, P_VEC = 212992, P_ROW = P_VEC + 6144, P_BAR = P_ROW + 4096, P_SMEM = P_BAR + 256;
#define PPH 1
#define FLAG_ST "st.release.gpu.global.u32"
#define FLAG_LD "ld.acquire.gpu.global.u32"
#define PX 0
#define MIDF 0
#define DS_AT 3
constexpr int ST = 5;
constexpr int PB_F = 0, PB_E = 5, PB_R = 10, PB_OUT = 16;
enum { C_Y = 0, C_G = 1, C_X1 = 2, C_U = 3, C_S1 = 8, C_S3 = 9 };
enum { V_GA = 0, V_A = 1, V_B = 2, V_GB = 3, V_VA = 4, V_VB = 5, V_VC = 6, V_C3 = 7 };
struct PostMaps { CUtensorMap o, wo, y, w1, g, w2, x1, w3, u, w4, out; };
struct PostPtrs { const bf16* x; };

struct GeluK { float k0, k1, kh; };
__device__ __forceinline__ GeluK gelu_k(float c) { return {0.7978845608028654f * c, 0.7978845608028654f * 0.044715f * c * c * c, 0.5f * c}; }
__device__ __forceinline__ float gelu_s(float t, const GeluK& k) {
    const float u = t * fmaf(t * t, k.k1, k.k0);
    float th; asm("tanh.approx.f32 %0, %1;" : "=f"(th) : "f"(u));
    const float hx = k.kh * t;
    return fmaf(hx, th, hx);
}
__device__ __forceinline__ float2 ldsv(uint32_t a) {
    float2 v; asm("ld.shared.v2.f32 {%0,%1}, [%2];" : "=f"(v.x), "=f"(v.y) : "r"(a)); return v;
}
__device__ __forceinline__ void wait_smem(uint32_t a, int target) {
    int it = 0;
#pragma unroll 1
    while (true) {
        int v;
        asm volatile("ld.acquire.cta.shared.u32 %0, [%1];" : "=r"(v) : "r"(a) : "memory");
        if (__all_sync(~0u, v >= target) | (++it > SPIN_LIMIT)) break;
    }
}

#define PP(i)
#define PH_(c, w, i)
__device__ __forceinline__ void mbar_wait_b(uint32_t b, uint32_t par) {
    int it = 0;
#pragma unroll 1
    while (!__all_sync(~0u, mbar_try(b, par)) & (++it < SPIN_LIMIT)) {}
}
__device__ __forceinline__ void release(uint32_t rel, int st, bool c) {
    asm volatile("{.reg .pred p; setp.ne.u32 p, %1, 0; setp.ne.and.u32 p, %2, 0, p; @p mbarrier.arrive.shared::cluster.b64 _, [%0];}"
                 ::"r"(rel + 8 * (st ? st - 1 : ST - 1)), "r"(rel), "r"((uint32_t)c) : "memory");
}
struct Pipe { int st, ph; uint32_t rel; };
__device__ __forceinline__ void adv(Pipe& p) { if (++p.st == ST) { p.st = 0; p.ph ^= 1; } }

__device__ __forceinline__ void post_weights(uint32_t sb, const PostMaps& mp, int nb, int rank) {
    const uint32_t full = sb + P_BAR + 8 * PB_F, empty = sb + P_BAR + 8 * PB_E;
    int st = 0, pp = 1;
#pragma unroll 1
    for (int ph = 0; ph < 7; ph++) {
        const int NK = ph == 0 ? 64 : ph == 6 ? 56 : 16, km = NK == 16 ? 15 : 63;
        const CUtensorMap* tb = &mp.wo + 2 * (ph < 3 ? ph : ph < 6 ? 3 : 4);
        const bool w3 = ph >= 3 && ph < 6;
        const int n0 = w3 ? nb * 64 + (ph == 4 ? 1536 : ph == 5 ? 2560 : 0) : nb * 128, dn = w3 ? 512 : 64;
        const int rot = NK == 16 ? 2 * (nb & 6) : 0, sw = ph == 1 || ph == 3 ? 2 * rank : 0;
#pragma unroll 1
        for (int i = 0; i < NK; i++) {
            const int k0 = (((i < 4 ? i ^ sw : i) + rot) & km) * 64;
            const uint32_t a = sb + P_B + st * 8192, f = full + 8 * st;
            mbar_wait_b(empty + 8 * st, pp);
            e_expect(f, ph == 3 ? 40960 : 32768);
            e_tma2d(a, tb, n0, k0, f);
            e_tma2d(a + P_PL, tb, n0 + dn, k0, f);
            if (ph == 3) e_tma2d(a + 2 * P_PL, tb, n0 + 1024, k0, f);
            if (++st == ST) { st = 0; pp ^= 1; }
        }
    }
#pragma unroll 1
    for (int i = 0; i < ST; i++) mbar_wait_b(empty + 8 * i, pp ^ (i < st));
}
__device__ __forceinline__ void post_acts(uint32_t sb, const PostMaps& mp, int mb, int nb, int rank) {
    const int rh = 2 * mb + rank, lane = threadIdx.x & 31;
    const uint32_t full = sb + P_BAR + 8 * PB_F, empty = sb + P_BAR + 8 * PB_E;
    int st = 0, pp = 1;
#pragma unroll 1
    for (int ph = 0; ph < 7; ph++) {
        const int NK = ph == 0 ? 64 : ph == 6 ? 56 : 16, km = NK == 16 ? 15 : 63;
        const CUtensorMap* ta = &mp.o + 2 * (ph < 3 ? ph : ph < 6 ? 3 : 4);
        const int amul = ph == 0 ? 256 : 64, arow = ph == 0 ? rh * 8 : rh * 64;
        const int rot = NK == 16 ? 2 * (nb & 6) : 0, own = ph == 1 || ph == 3 ? 4 : 0;
        const uint32_t shifts = ph == 2 ? 0x04000301u : 0x02020202u;
        const uint32_t* fl = &g_pflag[(ph == 6 ? C_U : min(ph - 1, 2)) * 256 + (ph == 2 ? min(max(rh + min(lane >> 3, 2) - 1, 0), 31) : rh) * 8 + (lane & 7)];
        uint32_t have = ph == 0 || ph == 5;
        if (own) { if (st) { st--; pp ^= 1; } else st = 4; }
#pragma unroll 1
        for (int i = own; i < NK; i++) {
            const int kb = (i + rot) & km;
            const uint32_t need = ph == 6 ? 255u : (ph == 2 ? 0x10101u : 1u) << ((kb >> 1) & 7), lvl = ph == 6 ? i >> 3 : 0;
            PH_(ph == PPH && i == own, 0, 27) PH_(ph == PPH && i == own, 1, 27)
            if ((__ballot_sync(~0u, have > lvl) & need) != need) {
                int it = 0;
#pragma unroll 1
                do asm volatile(FLAG_LD " %0, [%1];" : "=r"(have) : "l"(fl) : "memory");
                while (((__ballot_sync(~0u, have > lvl) & need) != need) & (++it < SPIN_LIMIT));
                PH_(ph == PPH && i == own, 0, 23) PH_(ph == PPH, 0, 24) PH_(ph == PPH && i == own, 1, 23) PH_(ph == PPH, 1, 24)
                asm volatile("fence.proxy.async.global;" ::: "memory");
            }
            const int d = own && (i == 5 || i == 6) ? 2 : 0, s2 = st + d < ST ? st + d : st + d - ST;
            mbar_wait_b(empty + 8 * s2, pp ^ (s2 < st));
            e_tma2d_mc(sb + st * 16384 + rank * 8192, ta, kb * amul, arow + (int)((shifts >> ((kb & 12) * 2)) & 7) - 2, full + 8 * st);
            if (++st == ST) { st = 0; pp ^= 1; }
        }
    }
}

template <int PH, bool EARLY = false, class F>
__device__ __forceinline__ void post_kb(uint32_t sb, float* acc, Pipe& p, int wg, bool lead, bool first, F mid) {
    constexpr uint64_t DA = PH == 0 ? mkdesc(SB0, 128, 1024, 0) : mkdesc(SB0, 16, 1024, 1);
    constexpr uint64_t DB = mkdesc(SB0 + P_B, P_PL, 1024, 1);
    mbar_wait_b(sb + P_BAR + 8 * PB_F + 8 * p.st, p.ph);
    const uint32_t a = (uint32_t)DA + p.st * 1024 + wg * 512, b = (uint32_t)DB + p.st * 512;
    wg_fence();
#pragma unroll
    for (int k = 0; k < 4; k++) {
        const uint64_t da = (DA & 0xffffffff00000000ull) | (a + k * (PH == 0 ? 16 : 2)), db = (DB & 0xffffffff00000000ull) | (b + k * 128);
        if (PH == 3) wgmma_ss192(acc, da, db, k || !first);
        else wgmma_ss128<PH == 0>(acc, da, db, k || !first);
    }
    wg_commit();
    if (EARLY) mid();
    wg_wait<1>();
    release(p.rel, p.st, !first);
    if (!EARLY) mid();
    adv(p);
}
__device__ __forceinline__ void post_end(uint32_t sb, Pipe& p, bool lead) {
    wg_wait<0>();
    release(p.rel, p.st, true);
}
template <int PH>
__device__ __forceinline__ void post_mma(uint32_t sb, float* acc, Pipe& p, int wg, bool lead, int nout, int pi, int mb, int nb) {
#pragma unroll 1
    for (int kb = 0; kb < 16; kb++)
        post_kb<PH>(sb, acc, p, wg, lead, kb == 0, [&]() {
            if (kb == 0) { PP(pi) }
            if (nout && kb == 0) wait_smem(sb + P_BAR + 8 * (PB_OUT + wg), nout);
        });
    post_end(sb, p, lead);
    PP(pi + 1)
}

__global__ void __cluster_dims__(2, 1, 1) __launch_bounds__(384, 1)
k_post(const __grid_constant__ PostMaps mp, const __grid_constant__ PostPtrs pp) {
    extern __shared__ uint8_t smraw[];
    const uint32_t sb = smem_u32(smraw);
    if ((sb & 0x3FFFF) != SB0) __trap();
    const int tid = threadIdx.x, lane = tid & 31;
    const int rank = blockIdx.x & 1;
    const uint32_t bars = sb + P_BAR;
    int c = 0;
    unsigned long long v = 0;
    const int wid = __reduce_max_sync(~0u, tid >> 5);
    const bool draw = tid == 352 && rank == 0;
    if (draw) {
        c = min(ldg_rlx1(&g_cls[smid() & 255]), 8u);
        asm volatile("{.reg .b64 a; cvt.u64.u32 a, %%laneid; add.u64 a, a, %1; atom.relaxed.gpu.global.add.u64 %0, [a], %2;}" : "=l"(v) : "l"(&g_pt), "l"(1ull << (7 * c)) : "memory");
    }
    if (wid < 11) {
        asm volatile("{.reg .pred p; elect.sync _|p, 0xffffffff; @p mbarrier.init.shared.b64 [%0], %1; @p prefetch.tensormap [%2]; fence.mbarrier_init.release.cluster;}"
                     ::"r"(bars + 8 * wid), "r"(wid >= PB_E && wid < PB_R ? 4 : 1), "l"(&mp.o + wid) : "memory");
        if (wid == PB_R) { sts4(bars + 8 * PB_OUT, 0, 0, 0, 0); e_expect(bars + 8 * PB_R, 4); }
    }
    __syncwarp();
    asm volatile("barrier.cluster.arrive.relaxed.aligned; barrier.cluster.wait.aligned;" ::: "memory");
    if (draw) {
        int r = (v >> (7 * c)) & 127, role = c * 8 + r;
        if (c == 8 || r >= 8) {
            int n, x, it = 0;
#pragma unroll 1
            do {
                __nanosleep(200);
                v = ldg_u64(&g_pt); n = 0; x = c < 8 ? r - 8 : r;
#pragma unroll 1
                for (int i = 0; i < 63; i += 7) { const int m = v >> i & 127; n += m; if (i < 7 * c) x += max(m - 8, 0); }
            } while (n < gridDim.x / 2 && ++it < SPIN_LIMIT);
            role = -1;
#pragma unroll 1
            for (int i = 0; i < 64; i += 8, v >>= 7) {
                n = v & 127;
                if (x >= 0 && n + x < 8) role = i + n + x;
                x -= max(8 - n, 0);
            }
        }
#pragma unroll
        for (int i = 0; i < 2; i++)
            asm volatile("{.reg .b32 d; mapa.shared::cluster.u32 d, %0, %2; st.async.shared::cluster.mbarrier::complete_tx::bytes.u32 [d+8], %1, [d];}"
                         ::"r"(bars + 8 * PB_R), "r"(role), "r"(i) : "memory");
    }
    __syncwarp();
    mbar_wait_b(bars + 8 * PB_R, 0);
    const int pr = __reduce_max_sync(~0u, (int)lds1(bars + 8 * PB_R + 8));
    if (pr < 0) return;
    const int mb = (pr >> 5) * 8 + (pr & 7), nb = (pr >> 2 & 6) + rank, cta = pr * 2 + rank;
    if (wid >= 8) {
        asm volatile("setmaxnreg.dec.sync.aligned.u32 40;");
        const int w = wid - 8;
        if (w == 0) {
            post_weights(sb, mp, nb, rank);
        } else if (w == 3) {
            asm volatile("griddepcontrol.wait;" ::: "memory");
            TLP(15)
            post_acts(sb, mp, mb, nb, rank);
        } else {
            const int wg = w - 1, rh = 2 * mb + wg;
            float* rowc = (float*)(smraw + P_ROW) + (wg * 64 + lane * 2) * 8;
            int nout = 0, sig = 0;
#pragma unroll 1
            for (int i = 0; i < 13; i++) {
                const int cnt = (0x4333333392180ull >> (4 * i)) & 15;
                if (cnt < C_S1) {
                    const int ng = cnt == C_U ? 1 : 2, c0 = cnt == C_U ? (i - 5) * 512 + nb * 64 : nb * 128;
                    const bool fast = (cnt == C_Y || cnt == C_X1);
#pragma unroll 1
                    for (int j = 0; j < ng; j++) {
                        const uint32_t st = j ? cnt : cnt ? 1 : 4;
                        const uint32_t src = sb + (fast ? st * 16384 + wg * 8192 : P_OUT + wg * 16384 + ((nout + j) & 1) * 8192);
                        bar_sync(4 + 4 * wg + (sig++ & 3), 160);
                        if (lane == 0) {
                            PH_(cnt == PPH - 1, wg, 20)
                            if (fast) asm volatile("mbarrier.complete_tx.relaxed.cta.shared::cta.b64 [%0], 8192;" ::"r"(bars + 8 * (PB_F + st)) : "memory");
                            asm volatile("cp.async.bulk.tensor.2d.global.shared::cta.bulk_group [%0, {%2, %3}], [%1]; cp.async.bulk.commit_group;"
                                         ::"l"(&mp.y + 2 * cnt), "r"(src), "r"(c0 + j * 64), "r"(rh * 64) : "memory");
                        }
                        __syncwarp();
                    }
                    if (lane == 0) {
                        auto to_peer = [&]() {
                            const uint32_t n = cnt ? 1 : 4;
                            mbar_wait(bars + 8 * (PB_E + (cnt ? 4 : 2)), 0);
#pragma unroll
                            for (int i = 0; i < 2; i++)
                                asm volatile("{.reg .b32 d, m; mapa.shared::cluster.u32 d, %0, %3; mapa.shared::cluster.u32 m, %2, %3;\n"
                                             " cp.async.bulk.shared::cluster.shared::cta.mbarrier::complete_tx::bytes [d], [%1], 8192, [m];}"
                                             ::"r"(sb + (cnt + 1 + i) * 16384 + wg * 8192), "r"(sb + (i ? cnt : n) * 16384 + wg * 8192), "r"(bars + 8 * (PB_F + cnt + 1 + i)), "r"(rank ^ 1) : "memory");
                        };
                        if (DS_AT == 1 && fast) to_peer();
                        asm volatile("cp.async.bulk.wait_group 0; fence.proxy.async.global;" ::: "memory");
                        asm volatile("st.release.cta.shared.u32 [%0], %1;" ::"r"(bars + 8 * (PB_OUT + wg)), "r"(nout + ng) : "memory");
                        PH_(cnt == PPH - 1, wg, 21)
                        if (DS_AT == 2 && fast) to_peer();
                        asm volatile(FLAG_ST " [%0], %1;" ::"l"(&g_pflag[cnt * 256 + rh * 8 + nb]), "r"(max(i - 4, 1)) : "memory");
                        PH_(cnt == PPH - 1, wg, 22)
                        if (DS_AT == 3 && fast) to_peer();
                    }
                    nout += ng;
                    __syncwarp();
                    continue;
                }
                bar_sync(4 + 4 * wg + (sig++ & 3), 160);
                uint32_t* c = &g_pcnt[(cnt - C_S1) * 256 + rh * 8];
                if (lane == 0) { signal_count(c); wait_count1(c, 8); }
                __syncwarp();
                const float4* sp = (const float4*)g_st + rh * 32 + lane;
                float4 u[3] = {__ldcg(sp + (cnt == C_S1 ? 0 : 3) * (S_ / 2)), __ldcg(sp + S_ / 2), __ldcg(sp + S_)};
#pragma unroll 1
                for (int h = 0; h < 2; h++) {
                    const float id = 1.0f / DM;
                    const float m = u[0].x * id, var = fmaxf(u[0].y * id - m * m, 0.f) + 1e-5f, r = rsqrtf(var);
                    float sc = r, m2 = 0.f;
                    if (cnt == C_S1) {
                        m2 = r * (u[1].x * id - m * g_cst[0]) + g_cst[3];
                        const float e2 = r * r * (u[2].x * id - 2.0f * m * u[1].y * id + m * m * g_cst[1]) + 2.0f * r * (u[2].y * id - m * g_cst[2]) + g_cst[4];
                        sc = r * rsqrtf(fmaxf(e2 - m2 * m2, 0.f) + 1e-5f);
                    }
                    const GeluK k = gelu_k(sc);
                    *(float4*)(rowc + h * 8) = make_float4(k.k0, k.k1, k.kh, -m);
                    *(float4*)(rowc + h * 8 + 4) = make_float4(var * r, -m2 * var * r, r, -m * r);
#pragma unroll
                    for (int q = 0; q < 3; q++) { u[q].x = u[q].z; u[q].y = u[q].w; }
                }
                bar_arrive(1 + wg, 160);
            }
        }
    } else {
        asm volatile("setmaxnreg.inc.sync.aligned.u32 232;");
        const bf16* xin = pp.x;
        const int wg = wid >> 2, wi = (tid >> 5) & 3, g = lane >> 2, tq = lane & 3;
        const int rh = 2 * mb + wg, row = rh * 64 + wi * 16 + g;
        const bool lead = (tid & 127) == 0;
        PP(0)
        if (tid == 0) TLP(10)
        uint32_t keep[32];
#pragma unroll
        for (int i = 0; i < 8; i++)
            *(uint4*)(keep + 4 * i) = __ldg((const uint4*)(xin + (size_t)(rh * 64 + wi * 16 + (i & 3) * 4 + (lane >> 3)) * DM + nb * 128 + (i >> 2) * 64 + (lane & 7) * 8));
        asm volatile("griddepcontrol.wait;" ::: "memory");
        if (cta < 64) g_modp[cta * 256 + tid] = 0;
        if (cta == 64 && tid < 196) g_tick[tid] = 0;
        const float* src = wg ? g_vec + nb * 128 + tid - 128 : g_mod + 2 * DM + nb * 128 + tid;
        const float* c3 = &g_vec[3 * DM + (tid >> 6) * 512 + nb * 64 + (tid & 63)];
        const float cv[6] = {__ldcg(src), __ldcg(src + (wg ? 1 : 2) * DM), __ldcg(src + (wg ? 2 : 1) * DM), __ldcg(src + 3 * DM), __ldcg(c3), __ldcg(c3 + (tid < 192 ? 2048 : 0))};
        uint32_t vec = sb + P_VEC + tq * 8;
        const uint32_t stw = sb + (wi * 16 + ((lane >> 3) & 1) * 8 + (lane & 7)) * 128 + (((lane >> 4) ^ (lane & 7)) << 4);
        int sig = 0;
        auto signal = [&]() { bar_arrive(4 + 4 * wg + (sig++ & 3), 160); };
        auto put64 = [&](uint32_t o, const float* v) {
#pragma unroll
            for (int jj = 0; jj < 4; jj++, v += 8) stsm4((stw + o) ^ (jj << 5), pack2(v[0], v[1]), pack2(v[2], v[3]), pack2(v[4], v[5]), pack2(v[6], v[7]));
            fence_async_smem();
            signal();
        };
        auto slot = [&](int n) {
            mbar_wait_b(bars + 8 * (PB_E + n % 5), ((n / 5) & 1) ^ 1);
            return (n % 5) * 16384 + wg * 8192;
        };
        const uint32_t rowc = sb + P_ROW + (wg * 64 + wi * 16 + g) * 32, o128 = P_OUT + wg * 16384;
        Pipe pa = {0, 0, 0};
        asm("mapa.shared::cluster.u32 %0, %1, %2;" : "=r"(pa.rel) : "r"(bars + 8 * PB_E), "r"(tid & 1));
        if (tid & 126) pa.rel = 0;
#define KEEP(jn, e) (((e) & 1) ? bfhi(keep[2 * (jn) + ((e) >> 1)]) : bflo(keep[2 * (jn) + ((e) >> 1)]))
        float mu1[2], r1[2];
        {
            float acc[64];
#pragma unroll 1
            for (int kb = 0; kb < 64; kb++) {
                post_kb<0>(sb, acc, pa, wg, lead, kb == 0, []() {});
                if (kb == 0) { PP(1) if (wg == 0) TLP(11) }
                if (kb == 24) bar_sync(3, 256);
                if (kb != 8 + 8 * wg) continue;
                float* sv = (float*)(smraw + P_VEC) + tid;
                const uint32_t xo = sb + o128 + wi * 2048 + (lane >> 3) * 128;
#pragma unroll
                for (int i = 0; i < 8; i++) sts4(xo + (i >> 2) * 8192 + (i & 3) * 512 + (((lane & 7) ^ ((i & 1) * 4 + (lane >> 3))) << 4), keep[4 * i], keep[4 * i + 1], keep[4 * i + 2], keep[4 * i + 3]);
                __syncwarp();
#pragma unroll
                for (int jj = 0; jj < 8; jj++) ldsm4(keep + jj * 4, (stw + o128 + (jj >> 2) * 8192) ^ ((jj & 3) << 5));
                sv[wg * 384] = cv[0]; sv[wg * 384 + 128] = cv[1] + (wg ? 0.0f : 1.0f); sv[wg * 384 + 256] = cv[2];
                if (!wg) sv[384] = cv[3];
                sv[V_C3 * 128] = cv[4]; sv[V_C3 * 128 + 256] = cv[5];
            }
            post_end(sb, pa, lead);
            PP(2)
            asm volatile("" : "+r"(vec) :: "memory");
            float st[2][6];
#pragma unroll
            for (int q = 0; q < 6; q++) st[0][q] = st[1][q] = 0.f;
#pragma unroll
            for (int jn = 0; jn < 16; jn++) {
                const float2 ga = ldsv(vec + V_GA * 512 + jn * 32), a = ldsv(vec + V_A * 512 + jn * 32);
                float xa[4];
#pragma unroll
                for (int e = 0; e < 4; e++) {
                    xa[e] = fmaf((e & 1) ? ga.y : ga.x, acc[4 * jn + e], KEEP(jn, e));
                    st[e >> 1][0] += xa[e]; st[e >> 1][1] = fmaf(xa[e], xa[e], st[e >> 1][1]);
                    acc[4 * jn + e] = ((e & 1) ? a.y : a.x) * xa[e];
                }
                keep[2 * jn] = pack2(xa[0], xa[1]); keep[2 * jn + 1] = pack2(xa[2], xa[3]);
                if ((jn & 7) == 7) put64(slot(64 + (jn >> 3)), acc + 4 * jn - 28);
            }
            PP(3)
#pragma unroll
            for (int jn = 0; jn < 16; jn++) {
                const float2 a = ldsv(vec + V_A * 512 + jn * 32), b = ldsv(vec + V_B * 512 + jn * 32);
#pragma unroll
                for (int e = 0; e < 4; e++) {
                    const float y = acc[4 * jn + e], aa = (e & 1) ? a.y : a.x, bb = (e & 1) ? b.y : b.x;
                    float* s = st[e >> 1];
                    s[2] += y; s[3] = fmaf(aa, y, s[3]); s[4] = fmaf(y, y, s[4]); s[5] = fmaf(bb, y, s[5]);
                }
            }
#pragma unroll
            for (int h = 0; h < 2; h++)
#pragma unroll
                for (int q = 0; q < 6; q++) { st[h][q] += __shfl_xor_sync(~0u, st[h][q], 1); st[h][q] += __shfl_xor_sync(~0u, st[h][q], 2); }
            if (tq < 3 && !(PX & 1)) {
#pragma unroll
                for (int h = 0; h < 2; h++)
                    red2(g_st + (tq * S_ + row + h * 8) * 2, tq == 0 ? st[h][0] : tq == 1 ? st[h][2] : st[h][4], tq == 0 ? st[h][1] : tq == 1 ? st[h][3] : st[h][5]);
            }
            signal();
            PP(29)
        }
        {
            float acc[64];
            post_mma<1>(sb, acc, pa, wg, lead, 2, 4, mb, nb);
            float c1[2], c2[2], c3[2];
            GeluK gk[2];
            bar_sync(1 + wg, 160);
#pragma unroll
            for (int h = 0; h < 2; h++) {
                const float4 a = lds4f(rowc + h * 256), b = lds4f(rowc + h * 256 + 16);
                gk[h] = {a.x, a.y, a.z}; c1[h] = a.w; c2[h] = b.x; c3[h] = b.y; mu1[h] = b.w; r1[h] = b.z;
            }
#pragma unroll
            for (int jn = 0; jn < 16; jn++) {
                const float2 va = ldsv(vec + V_VA * 512 + jn * 32), vb = ldsv(vec + V_VB * 512 + jn * 32), vc = ldsv(vec + V_VC * 512 + jn * 32);
#pragma unroll
                for (int e = 0; e < 4; e++) {
                    const int h = e >> 1;
                    const float t = fmaf(c1[h], (e & 1) ? va.y : va.x, fmaf(c2[h], (e & 1) ? vb.y : vb.x, fmaf(c3[h], (e & 1) ? vc.y : vc.x, acc[4 * jn + e])));
                    acc[4 * jn + e] = gelu_s(t, gk[h]);
                }
                if ((jn & 7) == 7) put64(o128 + (jn >> 3) * 8192, acc + 4 * jn - 28);
            }
            PP(6)
        }
        {
            float acc[64];
            post_mma<2>(sb, acc, pa, wg, lead, 0, 7, mb, nb);
#pragma unroll
            for (int jn = 0; jn < 16; jn++) {
                const float2 a = ldsv(vec + V_A * 512 + jn * 32), b = ldsv(vec + V_B * 512 + jn * 32);
#pragma unroll
                for (int e = 0; e < 4; e++) {
                    const int h = e >> 1;
                    acc[4 * jn + e] += fmaf(fmaf(KEEP(jn, e), r1[h], mu1[h]), (e & 1) ? a.y : a.x, (e & 1) ? b.y : b.x);
                }
                if ((jn & 7) == 7) put64(slot(96 + (jn >> 3)), acc + 4 * jn - 28);
            }
            BLOCK_FENCE
#pragma unroll
            for (int i = 0; i < 64; i += 16) asm volatile("" : F16(acc, i));
            PP(9)
            float st[2][2] = {{0.f, 0.f}, {0.f, 0.f}};
#pragma unroll
            for (int jn = 0; jn < 16; jn++) {
                const float2 gb = ldsv(vec + V_GB * 512 + jn * 32);
                float z[4];
#pragma unroll
                for (int e = 0; e < 4; e++) {
                    const float x1 = acc[4 * jn + e];
                    st[e >> 1][0] += x1; st[e >> 1][1] = fmaf(x1, x1, st[e >> 1][1]);
                    z[e] = fmaf((e & 1) ? gb.y : gb.x, x1, KEEP(jn, e));
                }
                keep[2 * jn] = pack2(z[0], z[1]); keep[2 * jn + 1] = pack2(z[2], z[3]);
            }
#pragma unroll
            for (int h = 0; h < 2; h++)
#pragma unroll
                for (int q = 0; q < 2; q++) { st[h][q] += __shfl_xor_sync(~0u, st[h][q], 1); st[h][q] += __shfl_xor_sync(~0u, st[h][q], 2); }
            if (tq < 2) red2(g_st + (3 * S_ + row + tq * 8) * 2, tq ? st[1][0] : st[0][0], tq ? st[1][1] : st[0][1]);
            signal();
            PP(30)
        }
        {
            float old[96], acc[64];
            post_mma<3>(sb, old, pa, wg, lead, 6, 10, mb, nb);
#pragma unroll
            for (int i = 0; i < 96; i += 16) asm volatile("" : F16(old, i));
            uint32_t v3 = vec + V_C3 * 512;
            bar_sync(1 + wg, 160);
            const float4 rc[2] = {lds4f(rowc), lds4f(rowc + 256)};
            float2 vc[2] = {lds2f(v3), lds2f(v3 + 32)};
            bar_sync(3, 256);
#pragma unroll 1
            for (int blk = 0; blk < 11; blk++) {
                const uint32_t o = stw + o128 + (blk & 1) * 8192;
                const int turn = blk < 7 ? wg : 2;
#pragma unroll
                for (int q = 0; q < 4; q++) {
#pragma unroll 1
                    for (int rep = 0; rep < 2; rep++) {
                        post_kb<1, MIDF>(sb, acc, pa, wg, lead, q == 0 && rep == 0 && blk < 6 && !(blk & 1), [&]() {
                        if (rep != turn) return;
                        asm volatile("" : F4(old, 8 * q), F4(old, 8 * q + 4));
                        const float2 vn[2] = {lds2f(v3 + q * 64 + 64), lds2f(v3 + q * 64 + 96)};
                        float t[8];
#pragma unroll
                        for (int i = 0; i < 8; i++) {
                            const float4& c = rc[(i >> 1) & 1];
                            t[i] = gelu_s(fmaf(c.w, (i & 1) ? vc[i >> 2].y : vc[i >> 2].x, old[8 * q + i]), GeluK{c.x, c.y, c.z});
                            old[8 * q + i] = old[32 + 8 * q + i];
                            old[32 + 8 * q + i] = old[64 + 8 * q + i];
                        }
                        stsm4(o ^ (q << 5), pack2(t[0], t[1]), pack2(t[2], t[3]), pack2(t[4], t[5]), pack2(t[6], t[7]));
                        vc[0] = vn[0]; vc[1] = vn[1];
                        if (q == 2) wait_smem(bars + 8 * (PB_OUT + wg), 6 + blk);
                        if (q == 3) { fence_async_smem(); signal(); }
                        });
                    }
                }
                v3 += 256;
                if (blk != 1 && blk != 3) continue;
                post_end(sb, pa, lead);
                PP(12 + blk)
                asm volatile("" : F16(acc, 0), F4(acc, 16), F4(acc, 20), F4(acc, 24));
                asm volatile("" : F16(acc, 28), F4(acc, 44), F4(acc, 48), F4(acc, 52));
                asm volatile("" : F4(acc, 56), F4(acc, 60));
#pragma unroll
                for (int i = 0; i < 64; i++) old[32 + i] = acc[i];
            }
            post_end(sb, pa, lead);
            PP(17)
#pragma unroll
            for (int jn = 0; jn < 16; jn++) {
                const float2 gb = ldsv(vec + V_GB * 512 + jn * 32);
#pragma unroll
                for (int e = 0; e < 4; e++) acc[4 * jn + e] = fmaf((e & 1) ? gb.y : gb.x, acc[4 * jn + e], KEEP(jn, e));
                if ((jn & 7) == 7) put64(o128 + ((jn >> 3) ^ 1) * 8192, acc + 4 * jn - 28);
            }
            PP(18)
            if (tid == 0) TLP(12)
        }
    }
}

typedef CUresult (*EncFn)(CUtensorMap*, CUtensorMapDataType, cuuint32_t, void*, const cuuint64_t*, const cuuint64_t*, const cuuint32_t*,
                          const cuuint32_t*, CUtensorMapInterleave, CUtensorMapSwizzle, CUtensorMapL2promotion, CUtensorMapFloatOOBfill);

static CUtensorMap make_map(EncFn enc, const void* p, uint64_t inner, uint64_t outer, uint32_t bi = 64) {
    CUtensorMap m;
    cuuint64_t dims[2] = {inner, outer};
    cuuint64_t str[1] = {inner * 2};
    cuuint32_t box[2] = {bi, bi == 64 ? 64u : 16u};
    cuuint32_t es[2] = {1, 1};
    enc(&m, CU_TENSOR_MAP_DATA_TYPE_BFLOAT16, 2, (void*)p, dims, str, box, es, CU_TENSOR_MAP_INTERLEAVE_NONE,
        bi == 64 ? CU_TENSOR_MAP_SWIZZLE_128B : CU_TENSOR_MAP_SWIZZLE_NONE, CU_TENSOR_MAP_L2_PROMOTION_L2_256B, CU_TENSOR_MAP_FLOAT_OOB_FILL_NONE);
    return m;
}
static CUtensorMap make_map_o(EncFn enc, const void* p) {
    CUtensorMap m;
    cuuint64_t dims[2] = {16384, 256};
    cuuint64_t str[1] = {65536};
    cuuint32_t box[2] = {256, 8};
    cuuint32_t es[2] = {1, 1};
    enc(&m, CU_TENSOR_MAP_DATA_TYPE_UINT32, 2, (void*)p, dims, str, box, es, CU_TENSOR_MAP_INTERLEAVE_NONE, CU_TENSOR_MAP_SWIZZLE_NONE,
        CU_TENSOR_MAP_L2_PROMOTION_L2_256B, CU_TENSOR_MAP_FLOAT_OOB_FILL_NONE);
    return m;
}
template <class T> static T* sym(T& s) { void* p = nullptr; cudaGetSymbolAddress(&p, s); return (T*)p; }

static const Delays h_dly = {D_NEAR, D_FAR, D_X2, D_V, D_W2, D_PA, D_WF, D_TV};
extern "C" void kernel_launch(void* const* d_in, const int* in_sizes, int n_in, void* d_out, int out_size) {
    const bf16* x = (const bf16*)d_in[0];
    const bf16* mem0 = (const bf16*)d_in[1];
    const bf16 *Wq = (const bf16*)d_in[2], *Wk = (const bf16*)d_in[3], *Wv = (const bf16*)d_in[4], *Wo = (const bf16*)d_in[5];
    const bf16 *w1 = (const bf16*)d_in[8], *w2 = (const bf16*)d_in[9], *w3 = (const bf16*)d_in[10], *w4 = (const bf16*)d_in[11];
    const bf16 *c = (const bf16*)d_in[12], *wmod = (const bf16*)d_in[13];
    bf16* out = (bf16*)d_out;

    EncFn enc = nullptr;
    cudaDriverEntryPointQueryResult qr;
    cudaGetDriverEntryPoint("cuTensorMapEncodeTiled", (void**)&enc, cudaEnableDefault, &qr);
    CUtensorMap tWq = make_map(enc, Wq, NH * DH, DM), tWk = make_map(enc, Wk, NH * DH, DM), tWv = make_map(enc, Wv, NH * DH, DM);
    PostMaps mp;
    mp.o = make_map_o(enc, sym(g_O)); mp.wo = make_map(enc, Wo, DM, NH * DH);
    mp.y = make_map(enc, sym(g_y), DM, S_); mp.w1 = make_map(enc, w1, DM, DM);
    mp.g = make_map(enc, sym(g_g), DM, S_); mp.w2 = make_map(enc, w2, DM, DM);
    mp.x1 = make_map(enc, sym(g_x1), DM, S_); mp.w3 = make_map(enc, w3, FF, DM);
    mp.u = make_map(enc, sym(g_u), FF, S_); mp.w4 = make_map(enc, w4, DM, FF);
    mp.out = make_map(enc, out, DM, S_);
    cudaFuncSetAttribute(k_rec, cudaFuncAttributeMaxDynamicSharedMemorySize, SM_REC_TOTAL + 2048);
    cudaFuncSetAttribute(k_post, cudaFuncAttributeMaxDynamicSharedMemorySize, P_SMEM);

    uint8_t* arena = (uint8_t*)(((uintptr_t)sym(g_arena) + (2u << 20) - 1) & ~(uintptr_t)((2u << 20) - 1));
    const PostPtrs pp = {x};
    const RecPtrs rp = {x, mem0, c, wmod, w1, w3, arena, 0u, w2, w4, Wo, h_dly};
    const RecMaps rm = {tWq, tWk, tWv, mp.wo, make_map(enc, wmod, 6 * DM, DM, 256), make_map(enc, w3, FF, DM, 256), make_map(enc, w1, DM, DM, 256)};
    k_rec<<<132, 384, SM_REC_TOTAL + 2048>>>(rm, rp);
    cudaLaunchConfig_t cfg = {};
    cfg.gridDim = dim3(132); cfg.blockDim = dim3(384); cfg.dynamicSmemBytes = P_SMEM; cfg.stream = cudaStreamPerThread;
    cudaLaunchAttribute at[1];
    at[0].id = cudaLaunchAttributeProgrammaticStreamSerialization; at[0].val.programmaticStreamSerializationAllowed = PDL;
    cfg.attrs = at; cfg.numAttrs = 1;
    cudaLaunchKernelEx(&cfg, k_post, mp, pp);
}
```

```cpp
#include <cuda_runtime.h>
#include <cuda.h>
#include <cuda_bf16.h>
#include <stdint.h>
#include <limits.h>

typedef __nv_bfloat16 bf16;

constexpr int S_ = 2048, DM = 1024, NH = 32, DH = 128, NSEG = 64, FF = 3584;
constexpr int SPIN_LIMIT = 1 << 22;
#define W_INFL 2
#define XP 0
#define H_PIECES 4
#define PDL 1
#define NPROBE 3

__device__ uint8_t g_arena[10 << 20];
__device__ __align__(128) uint32_t g_tick[64 + 132];
#define g_clk ((uint2*)(g_tick + 64))
__device__ uint32_t g_cls[256];
__device__ unsigned long long g_pt;
__device__ __align__(16) uint32_t g_modp[8 * 2 * DM];
__host__ __device__ constexpr uint32_t blk(uint32_t lb, uint32_t par) {
    return (lb << 13) | ((((lb) ^ (lb >> 3) ^ (lb >> 4) ^ (lb >> 6) ^ par) & 1) << 12);
}
__host__ __device__ constexpr uint32_t lb_x2(uint32_t h) { return (h & 1) | ((h >> 1) << 3); }
__host__ __device__ constexpr uint32_t mem_row(uint32_t kh, uint32_t b, uint32_t r) { return blk(128 | b, kh) + r * 1024; }
__device__ __forceinline__ uint32_t mem_slot(uint32_t s) { return ((s & 1) << 15) | ((s & 2) << 17); }
constexpr uint32_t CNT1 = 0x3d80, CNT_ALL = 0x4000;
constexpr uint32_t LB_PROBE = 6 | 64, LB_TIME = 6;
__host__ __device__ constexpr uint32_t lb_tok(uint32_t h) { return (h & 1) | ((h >> 1) << 3); }
__device__ float g_mod[6 * DM];
__device__ __align__(1024) bf16 g_himg[(S_ + 32) * DM];
__device__ __align__(1024) bf16 g_O[S_ * NH * DH];
__device__ __align__(1024) bf16 g_y[S_ * DM];
__device__ __align__(1024) bf16 g_g[S_ * DM];
__device__ __align__(1024) bf16 g_x1[S_ * DM];
__device__ __align__(16) float g_st[4 * S_ * 2];
__device__ float g_vec[3 * DM + FF];
__device__ float g_cst[8];
__device__ uint32_t g_pcnt[2 * 32 * 8], g_pflag[7 * 32 * 8];
__device__ __align__(1024) bf16 g_u[S_ * FF];

#define TL(i) {}
#define TLX(i) {}
#define TLP(i) TL(i)
#define TLC(i) {}
__device__ __forceinline__ uint32_t smem_u32(const void* p) { return (uint32_t)__cvta_generic_to_shared(p); }
__device__ __forceinline__ void spin_guard(int it) {
    asm volatile("{.reg .pred p; setp.gt.s32 p, %0, %1; @p st.global.u32 [%2], %0;}" ::"r"(it), "n"(SPIN_LIMIT), "l"(1ull));
}
__device__ __forceinline__ void wg_fence() { asm volatile("wgmma.fence.sync.aligned;" ::: "memory"); }
__device__ __forceinline__ void wg_commit() { asm volatile("wgmma.commit_group.sync.aligned;" ::: "memory"); }
template <int N> __device__ __forceinline__ void wg_wait() { asm volatile("wgmma.wait_group.sync.aligned %0;" ::"n"(N) : "memory"); }
__host__ __device__ constexpr uint64_t mkdesc(uint32_t addr, uint32_t lbo, uint32_t sbo, uint32_t swz) {
    return (uint64_t)((addr & 0x3FFFF) >> 4) | ((uint64_t)(lbo >> 4) << 16) | ((uint64_t)(sbo >> 4) << 32) | ((uint64_t)swz << 62);
}
__device__ __forceinline__ uint64_t dadd(uint64_t d, uint32_t o) { return (d & 0xffffffff00000000ull) | (uint32_t)((uint32_t)d + o); }
__device__ __forceinline__ void mbar_init(uint32_t b, uint32_t c) { asm volatile("mbarrier.init.shared.b64 [%0], %1;" ::"r"(b), "r"(c) : "memory"); }
__device__ __forceinline__ void mbar_expect(uint32_t b, uint32_t tx) { asm volatile("mbarrier.arrive.expect_tx.shared.b64 _, [%0], %1;" ::"r"(b), "r"(tx) : "memory"); }
__device__ __forceinline__ void mbar_arrive(uint32_t b) { asm volatile("mbarrier.arrive.shared.b64 _, [%0];" ::"r"(b) : "memory"); }
__device__ __forceinline__ void mbar_arrive_cluster(uint32_t b, uint32_t cta) {
    asm volatile("{.reg .b32 r; mapa.shared::cluster.u32 r, %0, %1; mbarrier.arrive.shared::cluster.b64 _, [r];}" ::"r"(b), "r"(cta) : "memory");
}
__device__ __forceinline__ bool mbar_try(uint32_t b, uint32_t par) {
    uint32_t ok;
    asm volatile("{.reg .pred p; mbarrier.try_wait.parity.shared.b64 p, [%1], %2; selp.u32 %0, 1, 0, p;}" : "=r"(ok) : "r"(b), "r"(par) : "memory");
    return ok;
}
__device__ __forceinline__ void mbar_wait(uint32_t b, uint32_t par) {
    int it = 0;
#pragma unroll 1
    while (!mbar_try(b, par)) { spin_guard(++it); }
}
__device__ __forceinline__ void mbar_wait_w(uint32_t b, uint32_t par) {
    int it = 0;
    bool ok;
#pragma unroll 1
    do { ok = __all_sync(~0u, mbar_try(b, par)); spin_guard(++it); } while (!ok);
}
__device__ __forceinline__ void mbar_wait_cluster(uint32_t b, uint32_t par) {
    int it = 0;
    while (true) {
        uint32_t ok;
        asm volatile("{.reg .pred p; mbarrier.try_wait.parity.acquire.cluster.shared::cta.b64 p, [%1], %2; selp.u32 %0, 1, 0, p;}" : "=r"(ok) : "r"(b), "r"(par) : "memory");
        if (ok) break;
        spin_guard(++it);
    }
}
__device__ __forceinline__ void tma2d(uint32_t dst, const CUtensorMap* m, int c0, int c1, uint32_t bar) {
    asm volatile("cp.async.bulk.tensor.2d.shared::cluster.global.mbarrier::complete_tx::bytes [%0], [%1, {%3, %4}], [%2];" ::"r"(dst), "l"(m), "r"(bar), "r"(c0), "r"(c1) : "memory");
}
constexpr uint64_t EVICT_FIRST = 0x12F0000000000000ull, EVICT_NORMAL = 0x1000000000000000ull;
__device__ __forceinline__ void tma2d_mc(uint32_t dst, const CUtensorMap* m, int c0, int c1, uint32_t bar, uint16_t mask) {
    asm volatile("cp.async.bulk.tensor.2d.shared::cluster.global.mbarrier::complete_tx::bytes.multicast::cluster [%0], [%1, {%3, %4}], [%2], %5;" ::"r"(dst), "l"(m), "r"(bar), "r"(c0), "r"(c1), "h"(mask) : "memory");
}
__device__ __forceinline__ void bulk_g2s(uint32_t dst, const void* src, uint32_t bytes, uint32_t bar) {
    asm volatile("cp.async.bulk.shared::cluster.global.mbarrier::complete_tx::bytes [%0], [%1], %2, [%3];" ::"r"(dst), "l"(src), "r"(bytes), "r"(bar) : "memory");
}
__device__ __forceinline__ void bar_sync(int id, int n) { asm volatile("bar.sync %0, %1;" ::"r"(id), "r"(n) : "memory"); }
__device__ __forceinline__ void bar_arrive(int id, int n) { asm volatile("bar.arrive %0, %1;" ::"r"(id), "r"(n) : "memory"); }
__device__ __forceinline__ void cluster_sync_all() { asm volatile("barrier.cluster.arrive.aligned; barrier.cluster.wait.aligned;" ::: "memory"); }
__device__ __forceinline__ void fence_async_smem() { asm volatile("fence.proxy.async.shared::cta;" ::: "memory"); }
__device__ __forceinline__ void ldsm4t(uint32_t* r, uint32_t a) {
    asm volatile("ldmatrix.sync.aligned.m8n8.x4.trans.shared.b16 {%0,%1,%2,%3}, [%4];" : "=r"(r[0]), "=r"(r[1]), "=r"(r[2]), "=r"(r[3]) : "r"(a) : "memory");
}
__device__ __forceinline__ void ldsm4(uint32_t* r, uint32_t a) {
    asm volatile("ldmatrix.sync.aligned.m8n8.x4.shared.b16 {%0,%1,%2,%3}, [%4];" : "=r"(r[0]), "=r"(r[1]), "=r"(r[2]), "=r"(r[3]) : "r"(a) : "memory");
}
__device__ __forceinline__ uint32_t movm(uint32_t a) {
    uint32_t d; asm volatile("movmatrix.sync.aligned.m8n8.trans.b16 %0, %1;" : "=r"(d) : "r"(a)); return d;
}
__device__ __forceinline__ void mma16816(float* d, uint32_t a0, uint32_t a1, uint32_t a2, uint32_t a3, uint32_t b0, uint32_t b1) {
    asm volatile("mma.sync.aligned.m16n8k16.row.col.f32.bf16.bf16.f32 {%0,%1,%2,%3},{%4,%5,%6,%7},{%8,%9},{%0,%1,%2,%3};"
                 : "+f"(d[0]), "+f"(d[1]), "+f"(d[2]), "+f"(d[3]) : "r"(a0), "r"(a1), "r"(a2), "r"(a3), "r"(b0), "r"(b1));
}
__device__ __forceinline__ void mma16816z(float* d, const uint32_t* a, uint32_t b0, uint32_t b1) {
    asm volatile("mma.sync.aligned.m16n8k16.row.col.f32.bf16.bf16.f32 {%0,%1,%2,%3},{%4,%5,%6,%7},{%8,%9},{%10,%10,%10,%10};"
                 : "=f"(d[0]), "=f"(d[1]), "=f"(d[2]), "=f"(d[3]) : "r"(a[0]), "r"(a[1]), "r"(a[2]), "r"(a[3]), "r"(b0), "r"(b1), "f"(0.f));
}
__device__ __forceinline__ void mma1688(float* d, uint32_t a0, uint32_t a1, uint32_t b0) {
    asm volatile("mma.sync.aligned.m16n8k8.row.col.f32.bf16.bf16.f32 {%0,%1,%2,%3},{%4,%5},{%6},{%0,%1,%2,%3};"
                 : "+f"(d[0]), "+f"(d[1]), "+f"(d[2]), "+f"(d[3]) : "r"(a0), "r"(a1), "r"(b0));
}
__device__ __forceinline__ uint32_t pack2(float lo, float hi) {
    uint32_t r; asm("cvt.rn.bf16x2.f32 %0, %1, %2;" : "=r"(r) : "f"(hi), "f"(lo)); return r;
}
__device__ __forceinline__ uint32_t hadd2(uint32_t a, uint32_t b) {
    uint32_t r; asm("add.rn.bf16x2 %0, %1, %2;" : "=r"(r) : "r"(a), "r"(b)); return r;
}
__device__ __forceinline__ float bflo(uint32_t u) { return __uint_as_float(u << 16); }
__device__ __forceinline__ float bfhi(uint32_t u) { return __uint_as_float(u & 0xffff0000u); }
__device__ __forceinline__ float ex2(float x) { float r; asm("ex2.approx.ftz.f32 %0, %1;" : "=f"(r) : "f"(x)); return r; }
__device__ __forceinline__ uint4 ldg_rlx4(const void* p) {
    uint4 v; asm volatile("ld.relaxed.gpu.global.v4.u32 {%0,%1,%2,%3}, [%4];" : "=r"(v.x), "=r"(v.y), "=r"(v.z), "=r"(v.w) : "l"(p) : "memory"); return v;
}
__device__ __forceinline__ uint2 ldg_rlx2(const void* p) {
    unsigned long long v; asm volatile("ld.relaxed.gpu.global.b64 %0, [%1];" : "=l"(v) : "l"(p) : "memory");
    return make_uint2((uint32_t)v, (uint32_t)(v >> 32));
}
__device__ __forceinline__ uint32_t ldg_rlx1(const void* p) {
    uint32_t v; asm volatile("ld.relaxed.gpu.global.u32 %0, [%1];" : "=r"(v) : "l"(p) : "memory"); return v;
}
__device__ __forceinline__ void stg_rlx1(void* p, uint32_t v) { asm volatile("st.relaxed.gpu.global.u32 [%0], %1;" ::"l"(p), "r"(v) : "memory"); }
__device__ __forceinline__ void stg_rlx2(void* p, uint32_t x, uint32_t y) {
    unsigned long long v = (unsigned long long)x | ((unsigned long long)y << 32);
    asm volatile("st.relaxed.gpu.global.b64 [%0], %1;" ::"l"(p), "l"(v) : "memory");
}
__device__ __forceinline__ void stg_rlx4(void* p, uint32_t x, uint32_t y, uint32_t z, uint32_t w) {
    asm volatile("st.relaxed.gpu.global.v4.u32 [%0], {%1,%2,%3,%4};" ::"l"(p), "r"(x), "r"(y), "r"(z), "r"(w) : "memory");
}
__device__ __forceinline__ void sts4(uint32_t a, uint32_t x, uint32_t y, uint32_t z, uint32_t w) {
    asm volatile("st.shared.v4.u32 [%0], {%1,%2,%3,%4};" ::"r"(a), "r"(x), "r"(y), "r"(z), "r"(w) : "memory");
}
__device__ __forceinline__ uint4 lds4(uint32_t a) {
    uint4 v; asm volatile("ld.shared.v4.u32 {%0,%1,%2,%3}, [%4];" : "=r"(v.x), "=r"(v.y), "=r"(v.z), "=r"(v.w) : "r"(a) : "memory"); return v;
}
__device__ __forceinline__ void st_async4(uint32_t a, float x, float y, float z, float w, uint32_t bar) {
    asm volatile("st.async.shared::cluster.mbarrier::complete_tx::bytes.v4.f32 [%0], {%1,%2,%3,%4}, [%5];" ::"r"(a), "f"(x), "f"(y), "f"(z), "f"(w), "r"(bar) : "memory");
}
#define F4(d, i) "+f"(d[i]), "+f"(d[i + 1]), "+f"(d[i + 2]), "+f"(d[i + 3])
__device__ __forceinline__ void wgmma_rs32(float* d, const uint32_t* a, uint64_t b, int sc) {
    asm volatile("{.reg .pred p; setp.ne.b32 p, %21, 0;\n wgmma.mma_async.sync.aligned.m64n32k16.f32.bf16.bf16 {%0,%1,%2,%3,%4,%5,%6,%7,%8,%9,%10,%11,%12,%13,%14,%15}, {%16,%17,%18,%19}, %20, p, 1, 1, 0;}"
                 : F4(d, 0), F4(d, 4), F4(d, 8), F4(d, 12) : "r"(a[0]), "r"(a[1]), "r"(a[2]), "r"(a[3]), "l"(b), "r"(sc));
}
__device__ __forceinline__ void wgmma_ss32(float* d, uint64_t a, uint64_t b, int sc) {
    asm volatile("{.reg .pred p; setp.ne.b32 p, %18, 0;\n wgmma.mma_async.sync.aligned.m64n32k16.f32.bf16.bf16 {%0,%1,%2,%3,%4,%5,%6,%7,%8,%9,%10,%11,%12,%13,%14,%15}, %16, %17, p, 1, 1, 1, 0;}"
                 : F4(d, 0), F4(d, 4), F4(d, 8), F4(d, 12) : "l"(a), "l"(b), "r"(sc));
}
__device__ __forceinline__ void wgmma_rs40(float* d, const uint32_t* a, uint64_t b, int sc) {
    asm volatile("{.reg .pred p; setp.ne.b32 p, %25, 0;\n wgmma.mma_async.sync.aligned.m64n40k16.f32.bf16.bf16 {%0,%1,%2,%3,%4,%5,%6,%7,%8,%9,%10,%11,%12,%13,%14,%15,%16,%17,%18,%19}, {%20,%21,%22,%23}, %24, p, 1, 1, 0;}"
                 : F4(d, 0), F4(d, 4), F4(d, 8), F4(d, 12), F4(d, 16) : "r"(a[0]), "r"(a[1]), "r"(a[2]), "r"(a[3]), "l"(b), "r"(sc));
}
__device__ __forceinline__ void wgmma_ss40(float* d, uint64_t a, uint64_t b, int sc) {
    asm volatile("{.reg .pred p; setp.ne.b32 p, %22, 0;\n wgmma.mma_async.sync.aligned.m64n40k16.f32.bf16.bf16 {%0,%1,%2,%3,%4,%5,%6,%7,%8,%9,%10,%11,%12,%13,%14,%15,%16,%17,%18,%19}, %20, %21, p, 1, 1, 1, 0;}"
                 : F4(d, 0), F4(d, 4), F4(d, 8), F4(d, 12), F4(d, 16) : "l"(a), "l"(b), "r"(sc));
}
#define F16(d, i) F4(d, i), F4(d, i + 4), F4(d, i + 8), F4(d, i + 12)
template <int TA>
__device__ __forceinline__ void wgmma_ss128(float* d, uint64_t a, uint64_t b, int sc) {
    asm volatile("{.reg .pred p; setp.ne.b32 p, %66, 0;\n wgmma.mma_async.sync.aligned.m64n128k16.f32.bf16.bf16 "
                 "{%0,%1,%2,%3,%4,%5,%6,%7,%8,%9,%10,%11,%12,%13,%14,%15,%16,%17,%18,%19,%20,%21,%22,%23,%24,%25,%26,%27,%28,%29,%30,%31,"
                 "%32,%33,%34,%35,%36,%37,%38,%39,%40,%41,%42,%43,%44,%45,%46,%47,%48,%49,%50,%51,%52,%53,%54,%55,%56,%57,%58,%59,%60,%61,%62,%63}, %64, %65, p, 1, 1, %67, 1;}"
                 : F16(d, 0), F16(d, 16), F16(d, 32), F16(d, 48) : "l"(a), "l"(b), "r"(sc), "n"(TA));
}

__device__ __forceinline__ float warp_sum(float v) {
#pragma unroll
    for (int o = 16; o; o >>= 1) v += __shfl_xor_sync(~0u, v, o);
    return v;
}
__device__ __forceinline__ float bfround(float x) { return __bfloat162float(__float2bfloat16(x)); }

__device__ __forceinline__ void wait_count1(const uint32_t* p, uint32_t target) {
    int it = 0;
#pragma unroll 1
    while (true) {
        uint32_t v;
        asm volatile("ld.acquire.gpu.global.u32 %0, [%1];" : "=r"(v) : "l"(p) : "memory");
        if (v >= target) break;
        spin_guard(++it);
    }
}
__device__ __forceinline__ void red2(float* p, float a, float b) {
    asm volatile("red.relaxed.gpu.global.add.v2.f32 [%0], {%1, %2};" ::"l"(p), "f"(a), "f"(b) : "memory");
}
__device__ __forceinline__ void l2_prefetch(const void* p, uint32_t bytes) {
    asm volatile("cp.async.bulk.prefetch.L2.global [%0], %1;" ::"l"(p), "r"(bytes) : "memory");
}
__device__ __forceinline__ void signal_count(uint32_t* p) { asm volatile("red.release.gpu.global.add.u32 [%0], 1;" ::"l"(p) : "memory"); }
__device__ __forceinline__ void e_expect(uint32_t b, uint32_t tx) {
    asm volatile("{.reg .pred p; elect.sync _|p, 0xffffffff; @p mbarrier.arrive.expect_tx.shared.b64 _, [%0], %1;}" ::"r"(b), "r"(tx) : "memory");
}
__device__ __forceinline__ void e_tma2d(uint32_t dst, const CUtensorMap* m, int c0, int c1, uint32_t bar) {
    asm volatile("{.reg .pred p; elect.sync _|p, 0xffffffff;\n @p cp.async.bulk.tensor.2d.shared::cluster.global.mbarrier::complete_tx::bytes [%0], [%1, {%3, %4}], [%2];}"
                 ::"r"(dst), "l"(m), "r"(bar), "r"(c0), "r"(c1) : "memory");
}
__device__ __forceinline__ void e_tma2d_hint(uint32_t dst, const CUtensorMap* m, int c0, int c1, uint32_t bar, uint64_t pol) {
    asm volatile("{.reg .pred p; elect.sync _|p, 0xffffffff;\n @p cp.async.bulk.tensor.2d.shared::cluster.global.mbarrier::complete_tx::bytes.L2::cache_hint [%0], [%1, {%3, %4}], [%2], %5;}"
                 ::"r"(dst), "l"(m), "r"(bar), "r"(c0), "r"(c1), "l"(pol) : "memory");
}
__device__ __forceinline__ void e_tma2d_mc(uint32_t dst, const CUtensorMap* m, int c0, int c1, uint32_t bar) {
    asm volatile("{.reg .pred p; elect.sync _|p, 0xffffffff;\n @p cp.async.bulk.tensor.2d.shared::cluster.global.mbarrier::complete_tx::bytes.multicast::cluster [%0], [%1, {%3, %4}], [%2], %5;}"
                 ::"r"(dst), "l"(m), "r"(bar), "r"(c0), "r"(c1), "h"((uint16_t)3) : "memory");
}
__device__ __forceinline__ void e_prefetch(const void* p, uint32_t bytes) {
    asm volatile("{.reg .pred p; elect.sync _|p, 0xffffffff; @p cp.async.bulk.prefetch.L2.global [%0], %1;}" ::"l"(p), "r"(bytes) : "memory");
}
__device__ __forceinline__ void wait_count_w(const uint32_t* p, uint32_t target) {
    int it = 0;
#pragma unroll 1
    while (true) {
        uint32_t v;
        asm volatile("ld.acquire.gpu.global.u32 %0, [%1];" : "=r"(v) : "l"(p) : "memory");
        if (__all_sync(~0u, v >= target) | (++it > SPIN_LIMIT)) break;
        __nanosleep(100);
    }
}

#define NL 6
constexpr uint32_t SM_HB = 16384, HBK = 5120, SM_SX = 57344, SM_OX = 122880, SM_PX = 124928, SM_PA = 126976, SM_WO = 147456,
                   SM_TAB = 212992, SM_PRE = SM_TAB + 5120, SM_BAR = 227328, SM_REC_TOTAL = 227328 + 256;
constexpr uint32_t SB0 = 1024;
constexpr int B_WO = 0, B_HE = 1, B_ROLE = 2, B_HB = 3, B_W = 5;
constexpr int NB_MEM = 1, NB_QK = 2, NB_X1 = 3, NB_X2 = 4, NB_WIN = 5, NB_WG = 6, NB_KDONE = 7, NB_FIN0 = 8, NB_P = 9, NB_PX = 10, NB_G = 11, NB_A = 12, NB_B = 13, NB_C = 14, NB_S = 15;
#define D_TPV 100
#define V_POS 2
#define D_X2 390
#define D_TV 40
#define D_V 320
#define D_NEAR 1660
#define D_FAR (D_NEAR - 110)
#define E_MUL 28
#define D_WF 60
#define NE 0
#define D_H 0
#define D_W2 60
#define SETTLE 0
#define TV_POS 0
#define D_PA 40
#define NE1 10
#define H_POS 3
#define PA_POS 1
#define K_DLY 0
#define ST_BAR 0
#define W1_AT -1
#define ROT 2
#define ALIGN 0
#define CNT32 0
#define O_POS 1
#define Z_POS 0
#define QF_LATE 100
#define W0_E 3
#define H_ROT 1
#define WO_LATE 1
#define QK_AT 15
#define QK_F 0
#define MAX_MMA 1
#define STS_LATE 1
#define W0_F 0
#define TAIL_F 0
#define G_AT 24
#define W0_AT 4
#define W0_RS (NL - 1)
#define P_GATE 1
#define NPF (NL + 6)

struct Delays { uint32_t near, far, x2, v, w2, pa, wf, tv; };
#define MISS(i, v)
#define MISS_INIT
#define MISS_OUT
#define HT(i)
#define PROF_INIT
#define PROF(i)
#define PROFV(i, v)
#define PROF_OUT

__device__ __forceinline__ uint32_t clk32() { uint32_t t; asm volatile("mov.u32 %0, %%clock;" : "=r"(t) :: "memory"); return t; }
__device__ __forceinline__ uint32_t smid() { uint32_t t; asm volatile("mov.u32 %0, %%smid;" : "=r"(t)); return t; }
__device__ __forceinline__ uint32_t gtime() { uint32_t t; asm volatile("mov.u32 %0, %%globaltimer_lo;" : "=r"(t) :: "memory"); return t; }
__device__ __forceinline__ void spin_until(uint32_t t0, uint32_t d) { while (clk32() - t0 < d) {} }
template <int N> __device__ __forceinline__ uint32_t delay(uint32_t zero) {
    float x = __uint_as_float(clk32());
#pragma unroll
    for (int i = 0; i < N; i++) asm volatile("ex2.approx.ftz.f32 %0, %0;" : "+f"(x));
    return __float_as_uint(x) & zero;
}
__device__ __forceinline__ uint32_t opaque(uint32_t v) { return __shfl_sync(~0u, v, threadIdx.x & 31); }
__device__ __forceinline__ uint32_t xor_or(uint32_t a, uint32_t b, uint32_t t) {
    uint32_t r; asm volatile("lop3.b32 %0, %1, %2, %3, 0x7E;" : "=r"(r) : "r"(a), "r"(b), "r"(t)); return r;
}
__device__ __forceinline__ uint32_t or3(uint32_t a, uint32_t b, uint32_t c) {
    uint32_t r; asm volatile("lop3.b32 %0, %1, %2, %3, 0xFE;" : "=r"(r) : "r"(a), "r"(b), "r"(c)); return r;
}
__device__ __forceinline__ uint32_t settag(uint32_t v, uint32_t tag) {
    uint32_t r; asm("lop3.b32 %0, %1, 1, %2, 0xB8;" : "=r"(r) : "r"(v), "r"(tag)); return r;
}
__device__ __forceinline__ void ldg4_if(uint4& v, const void* p, bool c) {
    asm volatile("{.reg .pred p; setp.ne.u32 p, %5, 0; @p ld.relaxed.gpu.global.v4.u32 {%0,%1,%2,%3}, [%4];}"
                 : "+r"(v.x), "+r"(v.y), "+r"(v.z), "+r"(v.w) : "l"(p), "r"((uint32_t)c) : "memory");
}
__device__ __forceinline__ uint4 ldg_rlx2x2(const void* p) {
    unsigned long long a, b;
    asm volatile("ld.relaxed.gpu.global.v2.b64 {%0,%1}, [%2];" : "=l"(a), "=l"(b) : "l"(p) : "memory");
    return make_uint4((uint32_t)a, (uint32_t)(a >> 32), (uint32_t)b, (uint32_t)(b >> 32));
}
__device__ __forceinline__ void stg_rlx2x2(void* p, uint32_t x, uint32_t y, uint32_t z, uint32_t w) {
    asm volatile("{.reg .b64 a, b; mov.b64 a, {%1,%2}; mov.b64 b, {%3,%4}; st.relaxed.gpu.global.v2.b64 [%0], {a, b};}" ::"l"(p), "r"(x), "r"(y), "r"(z), "r"(w) : "memory");
}
__device__ __forceinline__ void ldg1_if(uint32_t& v, const void* p, bool c) {
    asm volatile("{.reg .pred p; setp.ne.u32 p, %2, 0; @p ld.relaxed.gpu.global.u32 %0, [%1];}" : "+r"(v) : "l"(p), "r"((uint32_t)c) : "memory");
}
__device__ __forceinline__ void sts2(uint32_t a, float x, float y) { asm volatile("st.shared.v2.f32 [%0], {%1,%2};" ::"r"(a), "f"(x), "f"(y) : "memory"); }
__device__ __forceinline__ void sts4f(uint32_t a, float x, float y, float z, float w) {
    asm volatile("st.shared.v4.f32 [%0], {%1,%2,%3,%4};" ::"r"(a), "f"(x), "f"(y), "f"(z), "f"(w) : "memory");
}
__device__ __forceinline__ void sts1(uint32_t a, uint32_t x) { asm volatile("st.shared.u32 [%0], %1;" ::"r"(a), "r"(x) : "memory"); }
__device__ __forceinline__ uint32_t lds1(uint32_t a) { uint32_t v; asm volatile("ld.shared.u32 %0, [%1];" : "=r"(v) : "r"(a) : "memory"); return v; }
__device__ __forceinline__ float4 lds4f(uint32_t a) {
    float4 v; asm volatile("ld.shared.v4.f32 {%0,%1,%2,%3}, [%4];" : "=f"(v.x), "=f"(v.y), "=f"(v.z), "=f"(v.w) : "r"(a) : "memory"); return v;
}
__device__ __forceinline__ float2 lds2f(uint32_t a) {
    float2 v; asm volatile("ld.shared.v2.f32 {%0,%1}, [%2];" : "=f"(v.x), "=f"(v.y) : "r"(a) : "memory"); return v;
}
__device__ __forceinline__ bool any_bit0(uint32_t x) {
    uint32_t r;
    asm volatile("{.reg .pred p, q; .reg .b32 t; and.b32 t, %1, 1; setp.ne.u32 p, t, 0; vote.sync.any.pred q, p, 0xffffffff; selp.u32 %0, 1, 0, q;}" : "=r"(r) : "r"(x));
    return r;
}
__device__ __forceinline__ float rcp_fast(float x) { float r; asm("rcp.approx.ftz.f32 %0, %1;" : "=f"(r) : "f"(x)); return r; }
__device__ __forceinline__ void stsm4(uint32_t a, uint32_t r0, uint32_t r1, uint32_t r2, uint32_t r3) {
    asm volatile("stmatrix.sync.aligned.m8n8.x4.shared.b16 [%0], {%1,%2,%3,%4};" ::"r"(a), "r"(r0), "r"(r1), "r"(r2), "r"(r3) : "memory");
}
__device__ __forceinline__ void stsm4t(uint32_t a, uint32_t r0, uint32_t r1, uint32_t r2, uint32_t r3) {
    asm volatile("stmatrix.sync.aligned.m8n8.x4.trans.shared.b16 [%0], {%1,%2,%3,%4};" ::"r"(a), "r"(r0), "r"(r1), "r"(r2), "r"(r3) : "memory");
}
__device__ __forceinline__ uint32_t and3(uint32_t a, uint32_t b, uint32_t c) {
    uint32_t r; asm("lop3.b32 %0, %1, %2, %3, 0x80;" : "=r"(r) : "r"(a), "r"(b), "r"(c)); return r;
}
__device__ __forceinline__ void red_mem(void* p, uint32_t x, uint32_t y, uint32_t z, uint32_t w, void* q, uint32_t e, bool c) {
    asm volatile("{.reg .pred p; setp.ne.u32 p, %7, 0; red.relaxed.gpu.global.add.noftz.v4.bf16x2 [%0], {%1,%2,%3,%4}; @p red.relaxed.gpu.global.add.noftz.bf16x2 [%5], %6;}"
                 ::"l"(p), "r"(x), "r"(y), "r"(z), "r"(w), "l"(q), "r"(e), "r"((uint32_t)c) : "memory");
}
__device__ __forceinline__ void stg4_if(bool c, void* p, uint32_t x) {
    asm volatile("{.reg .pred p; setp.ne.u32 p, %2, 0; @p st.relaxed.gpu.global.v4.u32 [%0], {%1,%1,%1,%1};}" ::"l"(p), "r"(x), "r"((uint32_t)c) : "memory");
}
__device__ __forceinline__ uint32_t max3u(uint32_t a, uint32_t b, uint32_t c) { return __vimax3_u32(a, b, c); }
__device__ __forceinline__ void fence_gpu() { asm volatile("fence.acq_rel.gpu;" ::: "memory"); }

__device__ __forceinline__ void h_load(uint32_t sb, const uint8_t* hsrc, int pass, uint32_t rank, uint32_t rot) {
    const uint8_t* src = hsrc + (size_t)pass * 65536;
    const uint32_t bar = sb + SM_BAR + 8 * (B_HB + (pass & 1)), dst = sb + SM_HB + (pass & 1) * 65536 + rank * 4 * HBK;
    e_expect(bar, 32768);
#pragma unroll 1
    for (int i = 0; i < H_PIECES; i++) {
        const uint32_t o = ((i + rot) & (H_PIECES - 1)) * (16384 / H_PIECES);
        asm volatile("{.reg .pred p; elect.sync _|p, 0xffffffff;\n"
                     " @p cp.async.bulk.shared::cluster.global.mbarrier::complete_tx::bytes.multicast::cluster [%0], [%1], %4, [%2], %3;}"
                     ::"r"(dst + o + (o >> 12) * 1024), "l"(src + o), "r"(bar), "h"((uint16_t)3), "n"(16384 / H_PIECES) : "memory");
    }
}
__device__ __forceinline__ void h_piece(uint32_t sb, const uint8_t* hsrc, int pass, uint32_t rank, uint32_t i, bool first) {
    const uint32_t bar = sb + SM_BAR + 8 * (B_HB + (pass & 1));
    asm volatile("{.reg .pred p, q; elect.sync _|p, 0xffffffff; setp.le.and.s32 p, %5, 64, p; setp.ne.and.u32 q, %4, 0, p;\n"
                 " @q mbarrier.arrive.expect_tx.shared.b64 _, [%2], 32768;\n"
                 " @p cp.async.bulk.shared::cluster.global.mbarrier::complete_tx::bytes.multicast::cluster [%0], [%1], 4096, [%2], %3;}"
                 ::"r"(sb + SM_HB + (pass & 1) * 65536 + (rank * 4 + i) * HBK), "l"(hsrc + (uint32_t)(pass * 65536 + i * 4096)), "r"(bar), "h"((uint16_t)3), "r"((uint32_t)first), "r"(pass) : "memory");
}
__device__ __forceinline__ uint4 ldg_b128(const void* p) {
    uint4 v;
    asm volatile("{.reg .b128 t; .reg .b64 a, b; ld.relaxed.gpu.global.b128 t, [%4]; mov.b128 {a, b}, t; mov.b64 {%0,%1}, a; mov.b64 {%2,%3}, b;}"
                 : "=r"(v.x), "=r"(v.y), "=r"(v.z), "=r"(v.w) : "l"(p) : "memory");
    return v;
}
__device__ __forceinline__ void ldg_b128_into(uint4& v, const void* p) {
    asm volatile("{.reg .b128 t; .reg .b64 a, b; ld.relaxed.gpu.global.b128 t, [%4]; mov.b128 {a, b}, t; mov.b64 {%0,%1}, a; mov.b64 {%2,%3}, b;}"
                 : "+r"(v.x), "+r"(v.y), "+r"(v.z), "+r"(v.w) : "l"(p) : "memory");
}
__device__ __forceinline__ void stg_b128_if(bool c, void* p, uint32_t x, uint32_t y, uint32_t z, uint32_t w) {
    asm volatile("{.reg .pred p; setp.ne.u32 p, %5, 0; @p st.relaxed.gpu.global.v4.u32 [%0], {%1,%2,%3,%4};}"
                 ::"l"(p), "r"(x), "r"(y), "r"(z), "r"(w), "r"((uint32_t)c) : "memory");
}
__device__ __forceinline__ float pretag(float x, uint32_t add, uint32_t keep) { return __uint_as_float((__float_as_uint(x) + add) & keep); }

template <class F, class G>
__device__ __forceinline__ void softmax_rows(uint32_t src, uint32_t dst, uint32_t g16, int row0, F ready, G mid) {
    const uint32_t u = (g16 >> 7) & 3, e = ((g16 >> 9) << 3) | ((g16 >> 4) & 7);
    uint32_t se = src + e * 8, su = se + u * 1088, d0 = dst + e * 16 + u * 4, d1 = dst + 512 + e * 4;
    int vis = row0 + (e >> 2) - 2 * (e & 3) - 8 * u;
    asm volatile("" : "+r"(se), "+r"(su), "+r"(d0), "+r"(d1), "+r"(vis));
    ready();
    const float2 p0 = lds2f(su), p1 = lds2f(su + 256), p2 = lds2f(su + 512), p3 = lds2f(su + 768);
    const float2 m0 = lds2f(se + 4352), m1 = lds2f(se + 4352 + 256), m2 = lds2f(se + 4352 + 512), m3 = lds2f(se + 4352 + 768);
    float a0 = (p0.x + p1.x) + (p2.x + p3.x), a1 = (p0.y + p1.y) + (p2.y + p3.y);
    const float a2 = (m0.x + m1.x) + (m2.x + m3.x), a3 = (m0.y + m1.y) + (m2.y + m3.y);
    if (vis < 0) a0 = -1e9f / 0.08838834764831845f;
    if (vis < 1) a1 = -1e9f / 0.08838834764831845f;
    int k = __float_as_int(fmaxf(fmaxf(a0, a1), fmaxf(a2, a3)));
    k ^= (k >> 31) & 0x7fffffff;
    const bool hi = g16 & 64;
    const int k0 = __reduce_max_sync(~0u, hi ? INT_MIN : k), k1 = __reduce_max_sync(~0u, hi ? k : INT_MIN);
    mid();
    k = hi ? k1 : k0;
    const float m = __int_as_float(k ^ ((k >> 31) & 0x7fffffff));
    const float sl2 = 0.08838834764831845f * 1.4426950408889634f, mb = -m * sl2;
    sts1(d0, pack2(ex2(fmaf(a0, sl2, mb)), ex2(fmaf(a1, sl2, mb))));
    sts1(d1, pack2(ex2(fmaf(a2, sl2, mb)), ex2(fmaf(a3, sl2, mb))));
}

__device__ __forceinline__ uint32_t pack_h2(float lo, float hi) {
    uint32_t r; asm("cvt.rn.satfinite.f16x2.f32 %0, %1, %2;" : "=r"(r) : "f"(hi), "f"(lo)); return r;
}
__device__ __forceinline__ float2 unpack_h2(uint32_t u) {
    float2 r; asm("{.reg .b16 l, h; mov.b32 {l, h}, %2; cvt.f32.f16 %0, l; cvt.f32.f16 %1, h;}" : "=f"(r.x), "=f"(r.y) : "r"(u)); return r;
}
__device__ __forceinline__ uint32_t add_h2(uint32_t a, uint32_t b) { uint32_t r; asm("add.rn.f16x2 %0, %1, %2;" : "=r"(r) : "r"(a), "r"(b)); return r; }
__device__ __forceinline__ uint32_t max_h2(uint32_t a, uint32_t b) { uint32_t r; asm("max.f16x2 %0, %1, %2;" : "=r"(r) : "r"(a), "r"(b)); return r; }
__device__ __forceinline__ void stg2_if(bool c, void* p, uint32_t x, uint32_t y) {
    asm volatile("{.reg .pred p; .reg .b64 v; setp.ne.u32 p, %3, 0; mov.b64 v, {%1, %2}; @p st.relaxed.gpu.global.b64 [%0], v;}" ::"l"(p), "r"(x), "r"(y), "r"((uint32_t)c) : "memory");
}
__device__ __forceinline__ void stg1_if(bool c, void* p, uint32_t x) {
    asm volatile("{.reg .pred p; setp.ne.u32 p, %2, 0; @p st.relaxed.gpu.global.u32 [%0], %1;}" ::"l"(p), "r"(x), "r"((uint32_t)c) : "memory");
}
struct U2 { uint32_t x, y; };
__device__ __forceinline__ U2 ldg_u2(const void* p) {
    U2 v; asm volatile("{.reg .b64 t; ld.relaxed.gpu.global.b64 t, [%2]; mov.b64 {%0, %1}, t;}" : "=r"(v.x), "=r"(v.y) : "l"(p) : "memory"); return v;
}
constexpr int POLL_LIMIT = 1 << 16;
constexpr float SM_L2E = 0.08838834764831845f * 1.4426950408889634f;
template <int V> struct IC { static constexpr int value = V; };
typedef unsigned long long u64;
__device__ __forceinline__ uint32_t lo32(u64 v) { return (uint32_t)v; }
__device__ __forceinline__ uint32_t hi32(u64 v) { return (uint32_t)(v >> 32); }
__device__ __forceinline__ u64 ldg_u64(const void* p) { u64 v; asm volatile("ld.relaxed.gpu.global.b64 %0, [%1];" : "=l"(v) : "l"(p) : "memory"); return v; }
__device__ __forceinline__ void ldg_u64_if(u64& v, const void* p, bool c) {
    asm volatile("{.reg .pred p; setp.ne.u32 p, %2, 0; @p ld.relaxed.gpu.global.b64 %0, [%1];}" : "+l"(v) : "l"(p), "r"((uint32_t)c) : "memory");
}
__device__ __forceinline__ void rec_main(uint32_t sb, const CUtensorMap* tWo, uint8_t* arena, int role, int hinfo, int wg, uint32_t zero, const Delays& dly) {
    const int hA = hinfo & 255;
    const int tid = threadIdx.x, t = tid & 127, lane = tid & 31, wi = t >> 5;
    const uint32_t bars = sb + SM_BAR;
    const int head = role >> 2, qd = role & 3, j = blockIdx.x & 1, kh = role & 1;
    const uint32_t mypar = head >= hA;
    const uint32_t wu = __reduce_max_sync(~0u, wi);
    const bool warp0 = wu == 0, warp1 = wu == 1;
    const uint8_t* hsrc = (const uint8_t*)g_himg + kh * 32768 + j * 16384;
    auto tokbase = [&](int ty) { return ((ty + 1) << 21) + blk(lb_tok(head), mypar ^ ((hinfo >> (8 + ty)) & 1)); };
    const uint32_t tbw = tokbase(wg), tbq = tokbase(0) + (qd >> 1) * 2048 + (qd & 1) * 8;
    uint32_t w[32 - NL][4];
    const uint32_t frow = ((lane >> 4) * 8 + (lane & 7)) * 128, fx = ((lane >> 3) & 1) ^ (lane & 7);
    const uint32_t wl0 = sb + wg * 65536 + frow + ((fx ^ (2 * wi)) << 4);
    {
        if (wg > 0) wait_count_w(&g_tick[32 + (lane & 3) * 8], 1);
        if (wg == 1) asm volatile("fence.proxy.async.global;" ::: "memory");
#pragma unroll 1
        for (int i = 0; i < 4; i++) mbar_wait_w(bars + 8 * (B_W + (wg == 2 ? 8 + i : 2 * i + wg)), 0);
#pragma unroll
        for (int p = NL; p < 32; p++) ldsm4t(w[p - NL], wl0 + p * 2048);
        fence_async_smem();
        bar_sync(wg < 2 ? NB_WG : NB_X2, wg < 2 ? 256 : 128);
        if (wg == 2 && wu < 3) {
            e_expect(bars + 8 * B_WO, 16384);
            e_tma2d(sb + SM_WO + wu * 16384, tWo, (wu >> 1) * 512 + qd * 128 + (wu & 1) * 64, head * DH, bars + 8 * B_WO);
            e_tma2d(sb + SM_WO + wu * 16384 + 8192, tWo, (wu >> 1) * 512 + qd * 128 + (wu & 1) * 64, head * DH + 64, bars + 8 * B_WO);
        }
        if (wg == 1 && warp0) {
            if (lane == 0) mbar_arrive_cluster(bars + 8 * B_HE, j ^ 1);
            mbar_wait_w(bars + 8 * B_HE, 0);
#pragma unroll 1
            for (int i = 0; i < 2; i++) h_load(sb, hsrc, i, j, head);
        }
        TL(3 + wg)
    }
    uint32_t g16 = opaque(t * 16);
    auto G16 = [&]() { asm volatile("" : "+r"(g16)); return g16; };
    const uint32_t sbl = sb - wu * 512;
    const uint32_t xso = blk(lb_x2(head), mypar), cu = kh * 2048 + (2 * j + (wu >> 1)) * 512;
    const uint32_t u_xo = xso + wg * 16384 + (wu & 1) * 2048 + (cu >> 1) - wu * 256, u_to = tbw + (wu & 1) * 16384 + cu - wu * 512;
    const uint32_t mrow = wg < 2 ? mem_row(wu >> 1, wg * 2 + (wu & 1), qd) : mem_row(kh, wu, 0);
    const uint32_t u_m = mrow - wu * 512, u_e = mrow + 512 - wu * (CNT32 ? 64 : 128);
#define TAB(i) lds1(sb + SM_TAB + (i) * 512 + (G16() >> 2))
    {
        const uint32_t r8 = lane & 7;
        const uint32_t tb = sb + SM_TAB + wg * 1536 + t * 4, ma = sb + SM_HB + 4096 + r8 * 128;
        if (wg < 2) {
            sts1(tb, sb + SM_WO + wi * 16384 + frow + ((fx ^ (2 * wg)) << 4));
            sts1(tb + 512, wl0);
            sts1(tb + 1024, ma + (((lane >> 3) ^ r8) << 4));
        } else {
            sts1(tb, ma + (wi & 1) * HBK + ((((wi & 2) + (lane >> 4) * 4 + ((lane >> 3) & 1)) ^ r8) << 4));
            sts1(tb + 512, ((((wi & 2) + 5) ^ r8) << 4) + ((CNT32 ? (lane & 3) == 3 : lane & 1) ? ma + ((wi & 1) + (lane >> 3) * 2) * HBK : sb + SM_HB - 128));
            sts1(tb + 1024, mem_row(role >> 6, (role >> 4) & 3, (role >> 2) & 3) + (lane < 8 ? qd * 128 + lane * 16 : 512 + qd * 32 + (lane & 1) * 16));
        }
    }
    PROF_INIT
    MISS_INIT
#define HB(ks) dadd(mkdesc(SB0 + SM_HB + ((ks) >> 2) * HBK + ((ks) & 3) * 32, 16, 1024, 1), hbo)
#define STEP_CONSTS                                                                                  \
    const uint32_t tag = (s & 1) ^ 1, ttag = ((s >> 1) & 1) ^ 1, tso = (s & 1) * 32768;              \
    G16();                            \
    const int p = s + 2, b = p & 1;                                                                  \
    uint32_t hbo = b * 4096, fz[6] = {0, 0, 0, 0, 0, 0};                                                \
    const uint32_t ftag = (((p - 1) >> 1) & 1) ^ 1, ptag = ((p >> 1) & 1) ^ 1;                       \
    const uint32_t pso = tbw + (1 << 20) + (b ^ 1) * 32768 + j * 16384 + kh * 2048;
#define SCHED_FENCE(i) fz[i] = clk32();
#define FZ ((fz[0] | fz[1] | fz[2] | fz[3] | fz[4] | fz[5]) & zero)
#define BLOCK_FENCE asm volatile("pmevent 0;" ::: "memory");
    constexpr int GAP = 32 / NL;
#define l16 (sbl + g16)
#define g8 (g16 >> 1)
    uint4 u, v;
    uint8_t *pdst, *fdst;
    auto tok_pack = [&](int ty, const float* acc, uint32_t ftag, uint32_t ptag, uint32_t* later = nullptr) {
        const bool tg = ty == 2 || !(g16 & 64);
        const uint32_t add = tg ? (ftag ^ 1) << 16 : 0u, keep = tg ? 0xfffe0000u : ~0u;
        const uint32_t add1 = ty == 2 ? 0u : add, keep1 = ty == 2 ? ~0u : keep;
        const uint32_t add2 = ty == 0 ? add : 0u, keep2 = ty == 0 ? keep : ~0u;
        v = {pack2(pretag(acc[0], add, keep), pretag(acc[1], add1, keep1)), pack2(acc[2], acc[3]),
             pack2(pretag(acc[4], add2, keep2), pretag(acc[5], add2, keep2)), pack2(acc[6], acc[7])};
        if (ty < 2) { v.x = movm(v.x); v.z = movm(v.z); v.y = movm(v.y); v.w = movm(v.w); }
        if (later && TAIL_F) *later = clk32();
        u = {pack2(pretag(acc[8], (ptag ^ 1) << 16, 0xfffe0000u), acc[9]) | ptag, pack2(acc[10], acc[11]), pack2(acc[12], acc[13]), pack2(acc[14], acc[15])};
        if (later) return;
        v.x = settag(v.x, ftag);
        if (ty == 0) v.z = settag(v.z, ftag);
    };

#pragma unroll 1
    for (int s = -2; s < 0; s++) {
        STEP_CONSTS
        (void)tag; (void)ttag; (void)tso; (void)fz;
        float acc[16];
        mbar_wait_w(bars + 8 * (B_HB + b), 0);
        wg_fence();
#pragma unroll
        for (int i = 0; i < 32; i++) {
            if (i < NL) wgmma_ss32(acc, dadd(mkdesc(SB0 + i * 2048, 8192, 1024, 1), wg * 4096), HB(i), i != 0);
            else wgmma_rs32(acc, w[i < NL ? 0 : i - NL], HB(i), 1);
        }
        wg_commit();
        uint4 pa = {0, 0, 0, 0};
        int it = 0;
#pragma unroll 1
        while ((p > 0) & any_bit0(pa.x ^ ftag) & (++it < POLL_LIMIT)) pa = ldg_b128(arena + (pso + g16));
        pdst = arena + ((pso ^ (32768 + 2048)) + G16());
        fdst = arena + ((b ^ 1) * 32768 + u_to + g16);
        wg_wait<0>();
#pragma unroll
        for (int k = 0; k < 4; k++) { acc[2 * k] += bflo((&pa.x)[k]); acc[2 * k + 1] += bfhi((&pa.x)[k]); }
        tok_pack(wg, acc, ftag, ptag);
        stg_b128_if(true, pdst, u.x, u.y, u.z, u.w);
        stg_b128_if(p > 0, fdst, v.x, v.y, v.z, v.w);
        if (p == 0) {
            TL(2)
            if (wg != 1) bar_arrive(NB_C, 288);
        }
    }
    if (wg == 1 && warp0) {
        wait_count_w(&g_tick[32 + (lane & 3) * 8], 2);
        asm volatile("fence.proxy.async.global;" ::: "memory");
        bar_sync(NB_C, 288);
        if (g16 == 0) mbar_arrive_cluster(bars + 8 * B_HE, j ^ 1);
        mbar_wait_w(bars + 8 * B_HE, 1);
        h_load(sb, hsrc, 2, j, head);
    }

    auto qk_loop = [&](auto wgc) {
        constexpr int WG = decltype(wgc)::value;
        uint32_t w0[NL][4], lm0;
        auto w0_load = [&]() {
            const uint32_t wl = TAB(WG * 3 + 1);
            lm0 = TAB(WG * 3 + 2);
#pragma unroll
            for (int k = 0; k < NL; k++) ldsm4t(w0[k], wl + k * 2048);
        };
        const uint32_t wlo = WG * 65536 - SM_WO - wu * 16384, wlx = __reduce_max_sync(~0u, (wi ^ WG) << 5);
        uint32_t tq0, lm, lm1;
        auto proj_pre = [&](int s) {
            uint32_t wz0 = zero;
#pragma unroll
            for (int k = 0; k < NL; k += 2) wz0 = and3(wz0, w0[k][0], w0[k + 1 < NL ? k + 1 : k][0]);
            lm = lm0 + (s & 1) * 65536 + wz0; lm1 = lm ^ 64;
            asm volatile("" : "+r"(lm), "+r"(lm1));
        };
        auto proj = [&](int s, auto mid) {
            bar_sync(NB_MEM, 384);
            float c[4][4];
            uint32_t bf[16][4], tq1 = 0, tq2 = 0;
#pragma unroll
            for (int it = 0; it < 3; it++) ldsm4(bf[it], (it & 1 ? lm1 : lm) + (it >> 1) * HBK);
            mid(-1);
#pragma unroll
            for (int it = 0; it < 16; it++) {
                const uint32_t* bfr = bf[it];
                if (it + 3 < 16) ldsm4(bf[it + 3 < 16 ? it + 3 : 0], (it & 1 ? lm : lm1) + ((it + 3) >> 1) * HBK);
                const uint32_t* wa = 2 * it < NL ? w0[2 * it < NL ? 2 * it : 0] : w[2 * it < NL ? 0 : 2 * it - NL];
                const uint32_t* wb = 2 * it + 1 < NL ? w0[2 * it + 1 < NL ? 2 * it + 1 : 0] : w[2 * it + 1 < NL ? 0 : 2 * it + 1 - NL];
                float *ca = c[(2 * it) & 3], *cb = c[(2 * it + 1) & 3];
                if (it < 2) { mma16816z(ca, wa, bfr[0], bfr[1]); mma16816z(cb, wb, bfr[2], bfr[3]); }
                else { mma16816(ca, wa[0], wa[1], wa[2], wa[3], bfr[0], bfr[1]); mma16816(cb, wb[0], wb[1], wb[2], wb[3], bfr[2], bfr[3]); }
                mid(it);
                if (it == QK_AT) { tq1 = clk32(); bar_arrive(NB_QK, 384); if (QK_F) tq2 = clk32(); }
            }
            const uint32_t xo = u_xo + (G16() >> 1);
            float r[4];
#pragma unroll
            for (int e = 0; e < 4; e++) {
                constexpr float SH = SM_L2E / 64;
                r[e] = WG ? (c[0][e] + c[1][e]) + (c[2][e] + c[3][e]) : fmaf(c[2][e] + c[3][e], SH, (c[0][e] + c[1][e]) * SH);
            }
            const uint32_t r0 = pack2(r[0], r[1]), r1 = pack2(r[2], r[3]);
            const uint32_t m0 = movm(r0), m1 = movm(r1);
            tq0 = clk32();
            if (QK_AT > 15) bar_arrive(NB_QK, 384);
            stg_rlx2(arena + xo, settag(m0, (s & 1) ^ 1), m1);
            tq0 += (tq1 | tq2) & zero;
        };
        w0_load();
        proj_pre(0);
        if (WG == 1 || !ROT) bar_sync(NB_P, ROT ? 256 : 384);
        proj(0, [](int) {});
        if (WO_LATE && WG == 0) mbar_wait_w(bars + 8 * B_WO, 0);
#pragma unroll 1
        for (int s = 0;; s++) {
            STEP_CONSTS
            uint4 pa;
            float acc[16];
            auto acc_init = [&]() {
#pragma unroll
                for (int k = 0; k < 4; k++) { acc[2 * k] = bflo((&pa.x)[k]); acc[2 * k + 1] = bfhi((&pa.x)[k]); acc[8 + 2 * k] = __uint_as_float((&pa.x)[k] & zero); acc[9 + 2 * k] = __uint_as_float(~(&pa.x)[k] & zero); }
            };
            uint32_t wf[NPF][4], a3;
#define WF(f) ((a3 ^ (((f) & 1) * 64)) + ((f) >> 1) * 2048)
            if (WG == 1) {
                float sc[5][4];
                uint32_t sx0 = sb + SM_SX - wu * (2560 - 16) + G16() * 5;
                asm volatile("" : "+r"(sx0));
                int it = 0;
                bool bad;
#pragma unroll 1
                do {
                    uint4 kf[2][2];
                    U2 qf[2], x[8];
                    const uint32_t gz = g16 | (it & zero);
                    const uint8_t *ts = arena + (tso + tbw + gz), *tq = arena + (tso + tbq + gz), *xp = arena + (xso + (gz >> 1));
#pragma unroll
                    for (int a = 0; a < 4; a++) kf[a >> 1][a & 1] = ldg_b128(ts + (a >> 1) * 16384 + (a & 1) * 2048);
                    if (QF_LATE) spin_until(tq0, dly.x2 - QF_LATE);
#pragma unroll
                    for (int a = 0; a < 2; a++) qf[a] = ldg_u2(tq + a * 16384);
                    spin_until(tq0, dly.x2);
#pragma unroll
                    for (int i = 0; i < 8; i++) x[i] = ldg_u2(xp + (i >> 2) * 16384 + (i & 3) * 1024);
                    PROF(8)
                    const uint32_t q0[4] = {hadd2(x[0].x, x[1].x), qf[0].x, hadd2(x[0].y, x[1].y), qf[0].y};
                    const uint32_t q1[4] = {hadd2(x[2].x, x[3].x), qf[1].x, hadd2(x[2].y, x[3].y), qf[1].y};
                    PROFV(7, clk32() + (q0[0] & zero))
                    const uint32_t bt = ((qf[0].x ^ ttag) | (qf[1].x ^ ttag)) | ((kf[0][0].x ^ ttag) | (kf[0][1].x ^ ttag)) | ((kf[1][0].x ^ ttag) | (kf[1][1].x ^ ttag));
                    uint32_t bx = 0;
#pragma unroll
                    for (int i = 0; i < 8; i += 2) bx |= (x[i].x ^ tag) | (x[i + 1].x ^ tag);
                    mma16816z(sc[0], q0, kf[0][0].x, kf[0][0].y);
                    mma16816z(sc[1], q0, kf[0][0].z, kf[0][0].w);
                    mma16816z(sc[2], q0, kf[0][1].x, kf[0][1].y);
                    mma16816z(sc[3], q0, kf[0][1].z, kf[0][1].w);
                    mma16816z(sc[4], q0, hadd2(x[4].x, x[5].x), hadd2(x[4].y, x[5].y));
                    bad = any_bit0((XP & 8 ? bt & zero : bt) | bx) & (++it < POLL_LIMIT);
                    mma16816(sc[0], q1[0], q1[1], q1[2], q1[3], kf[1][0].x, kf[1][0].y);
                    mma16816(sc[1], q1[0], q1[1], q1[2], q1[3], kf[1][0].z, kf[1][0].w);
                    mma16816(sc[2], q1[0], q1[1], q1[2], q1[3], kf[1][1].x, kf[1][1].y);
                    mma16816(sc[3], q1[0], q1[1], q1[2], q1[3], kf[1][1].z, kf[1][1].w);
                    mma16816(sc[4], q1[0], q1[1], q1[2], q1[3], hadd2(x[6].x, x[7].x), hadd2(x[6].y, x[7].y));
                } while (bad);
                PROFV(13, it - 1) MISS(1, it - 1)
                sts4(sx0, pack_h2(sc[0][0], sc[0][1]), pack_h2(sc[1][0], sc[1][1]), pack_h2(sc[2][0], sc[2][1]), pack_h2(sc[3][0], sc[3][1]));
                sts1(sx0 + 64 - wu * 12, pack_h2(sc[4][0], sc[4][1]));
                bar_arrive(NB_X1, 384);
                auto tok_sts = [&]() {
#pragma unroll
                    for (int n = 0; n < 5; n++) sts2(sb + SM_SX + 2560 + g8 + n * 1088, sc[n][2], sc[n][3]);
                };
                if (!STS_LATE) tok_sts();
                PROF(3)
                a3 = TAB(WG * 3);
                if (WO_LATE && s == 0) mbar_wait_w(bars + 8 * B_WO, 0);
                softmax_rows(sb + SM_SX + 2560, sb + SM_PX + 1024, g16 | (clk32() & zero), qd * 8, [&]() { BLOCK_FENCE if (STS_LATE) tok_sts(); bar_sync(NB_PX, 128); }, [&]() {
                    BLOCK_FENCE
#pragma unroll
                    for (int f = 0; f < NE1; f++) ldsm4t(wf[f], WF(f));
                    BLOCK_FENCE
                });
                PROF(4)
            } else {
                a3 = TAB(WG * 3);
                if (warp1 && (s & 3) == 1) asm volatile("fence.proxy.async.global;" ::: "memory");
                spin_until(tq0, dly.pa);
                uint4 x, y;
                int it = 0;
#pragma unroll 1
                do { x = ldg_b128(arena + (pso + g16)); y = ldg_b128(arena + (pso + tokbase(1) - tokbase(0) + g16)); }
                while (!(XP & 8) & (p <= NSEG) & any_bit0(xor_or(x.x, y.x, ftag)) & (++it < POLL_LIMIT));
                sts4(sb + SM_PA + g16, x.x, x.y, x.z, x.w);
                sts4(sb + SM_PA + 2048 + g16, y.x, y.y, y.z, y.w);
                if (NE) spin_until(tq0, dly.wf);
#pragma unroll
                for (int f = 0; f < NE; f++) ldsm4t(wf[f], WF(f));
                bar_sync(NB_X1, 384);
                if (E_MUL && g16 < 32) asm volatile("red.relaxed.gpu.global.max.u32 [%0], %1; red.relaxed.gpu.global.add.u32 [%0+4], 1;"
                                                    ::"l"(arena + ((blk(LB_TIME, 0) ^ (g16 << 8)) + qd * 1024 + (tq0 & zero))), "r"(gtime()) : "memory");
                __syncwarp();
                const uint32_t tx = clk32();
                if (H_POS == 2 && !(XP & 1) && warp1 && s + 3 <= NSEG) h_load(sb, hsrc, s + 3, j, H_ROT ? head : 0);
                spin_until(tx, dly.w2);
            }
#pragma unroll
            for (int f = WG ? NE1 : NE; f < NPF; f++) ldsm4t(wf[f], WF(f));
            PROF(5)
            if (s + 1 == NSEG) { bar_arrive(NB_X2, 384); break; }
            const uint32_t oa = l16 + SM_OX, slot = mem_slot(s + 1);
            float c[4][4];
            uint32_t ob[4][4];
            uint32_t wz = zero;
#pragma unroll
            for (int f = 0; f < NPF; f += 2) wz = and3(wz, wf[f][0], wf[f + 1 < NPF ? f + 1 : f][0]);
            BLOCK_FENCE
            bar_sync(NB_X2 + (SETTLE ? wz : 0), 384);
            ldsm4t(ob[0], oa);
            ldsm4t(ob[1], oa + 512);
            SCHED_FENCE(0)
#pragma unroll
            for (int f = 0; f < 16; f++) {
                const uint32_t *a = wf[f % NPF], *o = ob[f >> 2] + (f & 2);
                if (f < 4) mma16816z(c[f], a, o[0], o[1]);
                else mma16816(c[f & 3], a[0], a[1], a[2], a[3], o[0], o[1]);
                if (f == 3) ldsm4t(ob[2], oa + 1024);
                if (f == 5) { ldsm4t(ob[3], oa + 1536); if (NPF < 16) ldsm4t(wf[0], WF(NPF)); }
                if (f == 7) {
#pragma unroll
                    for (int k = NPF + 1; k < 16; k++) ldsm4t(wf[k - NPF], WF(k));
                }
                if (f == 3 || f == 5 || f == 7) SCHED_FENCE(f / 2)
                if (f == 11) {
                    if (W0_F) SCHED_FENCE(5)
#pragma unroll
                    for (int k = NL - W0_E; k < NL; k++) ldsm4t(w0[k], (a3 ^ wlx) + wlo + k * 2048);
                    SCHED_FENCE(4)
                }
            }
            const float last = c[1][3] + c[3][3], one = __uint_as_float(CNT1 << 16);
            red_mem(arena + (u_m + slot + G16()), pack2(c[0][0] + c[2][0], c[0][1] + c[2][1]), pack2(c[0][2] + c[2][2], c[0][3] + c[2][3]),
                    pack2(c[1][0] + c[3][0], c[1][1] + c[3][1]), pack2(c[1][2] + c[3][2], CNT32 && !(g16 & 16) ? last : one),
                    arena + (u_e + slot + (CNT32 ? (g16 >> 3) & ~3u : g16 >> 2)), pack2(one, last), !CNT32 || (g16 & 16));
            hbo += FZ;
            PROF(6)
            constexpr int NS = WG && W0_E < 0 ? NL : NL - W0_RS, GS = (32 - NL + NS) / NS;
            if (W0_E >= 0) {
                BLOCK_FENCE
#pragma unroll
                for (int k = NL - W0_E - 1; k >= 0; k--) ldsm4t(w0[k], (a3 ^ wlx) + wlo + k * 2048);
                lm0 = TAB(WG * 3 + 2);
                if (WG == 1) pa = lds4(sb + SM_PA + 2048 + g16);
            }
            if (WG == 0) {
                bar_arrive(NB_WIN, 384);
                if (W0_E < 0) spin_until(clk32(), dly.tv);
                pa = lds4(sb + SM_PA + g16);
                if (W0_E < 0) w0_load();
                acc_init();
                asm volatile("" : F16(acc, 0));
                BLOCK_FENCE
            }
            if (WG == 1 && K_DLY) spin_until(clk32(), dly.wf);
            wg_fence();
            bar_sync(WG ? NB_WIN : NB_B, WG ? 384 : 256);
#pragma unroll
            for (int i = 0; i < 32; i++) {
                const int k = i / GS;
                if (i >= 32 - NL + NS) wgmma_rs32(acc, w0[i < 32 - NL + NS ? 0 : i - 32 + NL], HB(i - 32 + NL), 1);
                else if (i % GS == GS - 1 && k < NS) wgmma_ss32(acc, mkdesc(SB0 + WG * 65536 + k * 2048, 8192, 1024, 1), HB(k), 1);
                else wgmma_rs32(acc, w[i - (k < NS ? k : NS)], HB(NL + i - (k < NS ? k : NS)), WG == 0 || i);
                if (WG == 1 && i == G_AT) bar_arrive(NB_B, 256);
                if (WG == 1 && i == W1_AT) w0_load();
            }
            wg_commit();
            BLOCK_FENCE
            if (WG == 1 && warp0 && !(s & 3)) wait_count_w(&g_tick[32 + ((G16() >> 4) & 3) * 8], min((s + 1) / 4 + 3, 17));
            if (WG == 1 && W0_E < 0) { pa = lds4(sb + SM_PA + 2048 + g16); if (W1_AT < 0) w0_load(); }
            auto tok_store = [&](int m) {
                if (m & 1) stg_b128_if(XP & 8 ? s == 99 : true, arena + ((b ^ 1) * 32768 + u_to + G16()), v.x, v.y, v.z, v.w);
                if (m & 2) stg_b128_if(XP & 8 ? s == 99 : p < NSEG, arena + ((pso ^ (32768 + 2048)) + G16()), u.x, u.y, u.z, u.w);
            };
            if (WG == 0) proj_pre(s + 1);
            BLOCK_FENCE
            wg_wait<0>();
            if (WG == 0 && ROT) {
                asm volatile("" : F16(acc, 0));
                proj(s + 1, [&](int it) {
                    if (it < 0) {
                        SCHED_FENCE(0)
                        asm volatile("" : F16(acc, 0));
                        tok_pack(WG, acc, ftag, ptag, fz + 4);
                        tok_store(2);
                        SCHED_FENCE(1)
                    }
                    if (it == ROT) { SCHED_FENCE(2) v.x = settag(v.x, ftag); v.z = settag(v.z, ftag); tok_store(1); SCHED_FENCE(3) }
                });
                tq0 += (fz[0] | fz[1] | fz[2] | fz[3] | (TAIL_F ? fz[4] : 0)) & zero;
            } else {
                if (WG == 1) {
#pragma unroll
                    for (int k = 0; k < 4; k++) { acc[2 * k] += bflo((&pa.x)[k]); acc[2 * k + 1] += bfhi((&pa.x)[k]); }
                }
                tok_pack(WG, acc, ftag, ptag);
                if (WG == 1) proj_pre(s + 1);
                asm volatile("" : "+r"(u.x), "+r"(u.y), "+r"(u.z), "+r"(u.w), "+r"(v.x), "+r"(v.y), "+r"(v.z), "+r"(v.w));
                BLOCK_FENCE
                bar_sync(NB_P, ROT ? 256 : 384);
                tok_store(3);
                proj(s + 1, [](int) {});
            }
        }
    };
    if (wg == 0) {
        qk_loop(IC<0>());
    } else if (wg == 1) {
        qk_loop(IC<1>());
    } else {
        const uint32_t ONES = 0x3f803f80u, u_o = qd * 65536 + head * 2048 + wu * 384;
        uint32_t tw = 0, dl = 0, dbase = kh == mypar ? dly.near : dly.far, dst0, dx0;
        dst0 = TAB(6); dx0 = TAB(7);
        uint32_t ov[4] = {0, 0, 0, 0};
        auto o_store = [&](int s) {
            uint8_t* od = (uint8_t*)g_O + (uint32_t)(s * (32 * NH * DH * 2) + u_o + (G16() >> 2));
#pragma unroll
            for (int a = 0; a < 4; a++) stg_rlx1(od + a * 128, ov[a]);
        };
        uint4 vf[2][2], pa;
        auto vf_fetch = [&](int s) {
            const uint8_t* ts = arena + ((s & 1) * 32768 + tbw + g16);
#pragma unroll
            for (int a = 0; a < 4; a++) vf[a >> 1][a & 1] = ldg_b128(ts + (a >> 1) * 16384 + (a & 1) * 2048);
        };
        auto tok_fetch = [&](int s) {
            if (TV_POS != 1) vf_fetch(s);
            pa = ldg_b128(arena + (tbw + (1 << 20) + (~s & 1) * 32768 + j * 16384 + kh * 2048 + g16));
        };
        if (PA_POS) tok_fetch(0);
        TL(9)
        if (!WO_LATE) mbar_wait_w(bars + 8 * B_WO, 0);
        TL(6)
#pragma unroll 1
        for (int s = 0; s < NSEG; s++) {
            STEP_CONSTS
#define VFBAD ((vf[0][0].x ^ ttag) | (vf[0][1].x ^ ttag) | (vf[1][0].x ^ ttag) | (vf[1][1].x ^ ttag))
#define TOKBAD ((TV_POS == 1 ? 0 : VFBAD) | (p <= NSEG ? pa.x ^ ftag : 0))
            {
                const uint32_t dst = dst0 + b * 65536, dx = dx0 + b * 65536;
                const uint8_t *ms = arena + (u_m + mem_slot(s) + g16), *me = arena + (u_e + mem_slot(s) + (CNT32 ? (g16 >> 3) & ~3u : g16 >> 2));
                const uint32_t em = CNT32 && !(g16 & 16) ? ~0u : 0u;
                asm volatile("" : "+l"(ms), "+l"(me));
                spin_until(tw, dl);
                PROF(11)
                int it = 0;
                bool bad;
#pragma unroll 1
                do {
                    uint4 m[4];
                    uint32_t x[4];
#pragma unroll
                    for (int i = 0; i < 4; i++) m[i] = ldg_rlx4(ms + i * 1024);
#pragma unroll
                    for (int i = 0; i < 4; i++) x[i] = ldg_rlx1(me + i * 1024);
#pragma unroll
                    for (int i = 0; i < 3; i++) {
                        stsm4t(dst + i * 2 * HBK, m[i].x, m[i].y, m[i].z, m[i].w);
                        if (i == P_GATE) asm volatile("{.reg .pred p; setp.eq.s32 p, %0, 0; @p bar.arrive %1, %2;}" ::"r"(it), "n"(NB_P), "n"(ROT ? 256 : 384) : "memory");
                    }
                    uint32_t c = and3(m[0].w, m[1].w, m[2].w);
                    SCHED_FENCE(1)
                    stsm4t(dst + 6 * HBK, m[3].x, m[3].y, m[3].z, m[3].w);
                    stsm4t(dx, x[0], x[1], x[2], x[3]);
                    asm volatile("" : "+r"(c));
                    c = and3(and3(((c & m[3].w) | em) >> 16, x[0], x[1]), x[2], x[3]);
                    bad = __any_sync(~0u, !(c & CNT_ALL)) & (++it < POLL_LIMIT);
                    asm volatile("{.reg .pred p; setp.eq.u32 p, %0, 0; @p bar.arrive %1, 384;}" ::"r"((uint32_t)bad), "n"(NB_MEM) : "memory");
                } while (bad);
                if (it > 1 && s > 1) dbase += dly.tv;
                PROFV(12, it - 1)
                MISS(0, it - 1) HT(5)
                PROF(8)
            }
            if (s == 1) { TL(7) TLC(0) }
            if (s == 63) TLC(1)
            if (s == 0) TL(13)
            if (O_POS == 1) o_store(max(s - 1, 0));
            if (Z_POS && warp1) stg4_if(g16 < 512 + 160, arena + (TAB(8) + mem_slot(s + 3)), 0);
            fence_async_smem();
            hbo += fz[1] & zero;
            int it = 0;
            if (!PA_POS) tok_fetch(s);
#pragma unroll 1
            while (!(XP & 8) & any_bit0(TOKBAD) & (++it < POLL_LIMIT)) tok_fetch(s + (it & zero));
            float acc[20];
#pragma unroll
            for (int k = 0; k < 4; k++) { acc[2 * k] = bflo((&pa.x)[k]); acc[2 * k + 1] = bfhi((&pa.x)[k]); acc[8 + 2 * k] = acc[9 + 2 * k] = acc[16 + k] = __uint_as_float(pa.x & zero); }
            if (XP & 1 ? s < 1 : p <= NSEG) mbar_wait_w(bars + 8 * (B_HB + b), (p >> 1) & 1);
            asm volatile("" : F16(acc, 0), F4(acc, 16));
            BLOCK_FENCE
            wg_fence();
            bar_sync(NB_QK, 384);
#pragma unroll
            for (int i = 0; i < 32; i++) {
                const int k = i / GAP;
                if (i % GAP == GAP - 1 && k < NL) wgmma_ss40(acc, mkdesc(SB0 + 131072 + k * 2048, 8192, 1024, 1), HB(k), 1);
                else wgmma_rs40(acc, w[i - (k < NL ? k : NL)], HB(NL + i - (k < NL ? k : NL)), 1);
            }
            wg_commit();
            uint8_t* vo = arena + (u_xo + (G16() >> 1));
            pdst = arena + ((pso ^ (32768 + 2048)) + G16());
            fdst = arena + ((b ^ 1) * 32768 + u_to + g16);
            BLOCK_FENCE
            wg_wait<0>();
            PROF(9)
            stg_rlx2(vo, settag(pack2(acc[16], acc[17]), tag), pack2(acc[18], acc[19]));
            const uint32_t tv = clk32();
            if (TV_POS == 1) vf_fetch(s);
            tok_pack(2, acc, ftag, ptag);
            stg_b128_if(XP & 8 ? s == 99 : p <= NSEG, fdst, v.x, v.y, v.z, v.w);
            stg_b128_if(XP & 8 ? s == 99 : p < NSEG, pdst, u.x, u.y, u.z, u.w);
            if (O_POS == 2) o_store(max(s - 1, 0));
            if (ST_BAR) bar_sync(NB_WG, 128);
            PROF(10)
            const uint8_t* xp = arena + (xso + 32768 + (G16() >> 1));
            const uint32_t sxa = sb + SM_SX - wu * 2560 + G16() * 5;
            uint32_t sel[2];
            {
                const uint32_t q = (G16() >> 4 ^ g16 >> 6 & 1) & 3;
                sel[0] = q == 0 ? 0x3c00 : 0; sel[1] = q == 2 ? 0x3c00 : 0;
                asm volatile("" : "+r"(sel[0]), "+r"(sel[1]));
            }
            uint32_t xv[4], gt = 0;
            auto pv = [&](uint32_t p0, uint32_t p1, uint32_t p2, uint32_t p3, uint32_t p4, auto getv, auto done) {
                float oc[2][4], lc[4] = {0.f, 0.f, 0.f, 0.f};
                mma16816(lc, ONES, ONES, ONES, ONES, p0, p1);
                mma16816z(oc[0], &vf[0][0].x, p0, p1);
                mma16816z(oc[1], &vf[1][0].x, p0, p1);
                mma16816(lc, ONES, ONES, ONES, ONES, p2, p3);
                mma16816(oc[0], vf[0][1].x, vf[0][1].y, vf[0][1].z, vf[0][1].w, p2, p3);
                mma16816(oc[1], vf[1][1].x, vf[1][1].y, vf[1][1].z, vf[1][1].w, p2, p3);
                mma1688(lc, ONES, ONES, p4);
                getv();
                mma1688(oc[0], xv[0], xv[1], p4);
                mma1688(oc[1], xv[2], xv[3], p4);
                done(__float_as_uint(oc[0][0]) | __float_as_uint(oc[1][0]) | __float_as_uint(lc[0]));
                const float r0 = rcp_fast(lc[0]), r1 = rcp_fast(lc[1]);
                ov[0] = pack2(oc[0][0] * r0, oc[0][1] * r1); ov[1] = pack2(oc[0][2] * r0, oc[0][3] * r1);
                ov[2] = pack2(oc[1][0] * r0, oc[1][1] * r1); ov[3] = pack2(oc[1][2] * r0, oc[1][3] * r1);
            };
            bool bad;
            it = 0;
#pragma unroll 1
            do {
                U2 xr[4];
                auto load_v = [&]() {
                    if (V_POS < 3) spin_until(tv, dly.v);
#pragma unroll
                    for (int i = 0; i < 4; i++) xr[i] = ldg_u2(xp + i * 1024);
                };
                if (TV_POS == 1 && it) {
                    const uint8_t* tz = arena + (tso + tbw + (g16 | (it & zero)));
#pragma unroll
                    for (int a = 0; a < 4; a++) ldg_b128_into(vf[a >> 1][a & 1], tz + (a >> 1) * 16384 + (a & 1) * 2048);
                }
                if (!V_POS) load_v();
                if (V_POS >= 3) spin_until(tv, dly.v);
                PROF(3)
                asm volatile("{.reg .pred p; setp.eq.s32 p, %0, 0; @p bar.sync %1, 384;}" ::"r"(it), "n"(NB_X1) : "memory");
                uint4 sx[5];
                if (V_POS == 3) load_v();
#pragma unroll
                for (int i = 0; i < 5; i++) sx[i] = lds4(sxa + i * 16);
                if (V_POS == 4) load_v();
                if (it == 0) { gt = gtime(); tw = clk32(); }
                if (V_POS == 2) load_v();
                uint32_t h[5], h0[4];
#pragma unroll
                for (int n = 0; n < 4; n++) h0[n] = add_h2((&sx[0].x)[n], (&sx[1].x)[n]);
                if (V_POS == 5) { SCHED_FENCE(2) load_v(); SCHED_FENCE(3) }
#pragma unroll
                for (int n = 0; n < 4; n++) h[n] = add_h2(h0[n], add_h2((&sx[2].x)[n], (&sx[3].x)[n]));
                h[4] = add_h2(add_h2(sx[4].x, sx[4].y), add_h2(sx[4].z, sx[4].w));
                uint32_t hm = max_h2(max_h2(max_h2(h[0], h[1]), h[2]), max_h2(h[3], h[4]));
                float2 a[5];
                float mb;
                if (MAX_MMA) {
                    float d[2][4];
                    const uint32_t hs = __byte_perm(hm, hm, 0x1032);
#pragma unroll
                    for (int k = 0; k < 2; k++)
                        asm volatile("mma.sync.aligned.m16n8k8.row.col.f32.f16.f16.f32 {%0,%1,%2,%3},{%4,%5},{%6},{%7,%7,%7,%7};"
                                     : "=f"(d[k][0]), "=f"(d[k][1]), "=f"(d[k][2]), "=f"(d[k][3]) : "r"(hm), "r"(hs), "r"(sel[k]), "f"(0.f));
#pragma unroll
                    for (int n = 0; n < 5; n++) a[n] = unpack_h2(h[n]);
                    mb = -64.0f * fmaxf(fmaxf(fmaxf(d[0][0], d[0][1]), fmaxf(d[0][2], d[0][3])), fmaxf(fmaxf(d[1][0], d[1][1]), fmaxf(d[1][2], d[1][3])));
                } else {
                    hm = max_h2(hm, __byte_perm(hm, hm, 0x1032));
                    const uint32_t m1 = __shfl_xor_sync(~0u, hm, 1), m2 = __shfl_xor_sync(~0u, hm, 2), m3 = __shfl_xor_sync(~0u, hm, 3);
#pragma unroll
                    for (int n = 0; n < 5; n++) a[n] = unpack_h2(h[n]);
                    if (V_POS == 1) load_v(); else SCHED_FENCE(0)
                    mb = -64.0f * unpack_h2(max_h2(max_h2(hm, m1), max_h2(m2, m3))).x;
                }
                uint32_t pm[5];
#pragma unroll
                for (int n = 0; n < 5; n++) pm[n] = pack2(ex2(fmaf(a[n].x, 64.0f, mb)), ex2(fmaf(a[n].y, 64.0f, mb)));
                pv(pm[0], pm[1], pm[2], pm[3], pm[4], [&]() {
                    xv[0] = hadd2(xr[0].x, xr[1].x); xv[1] = hadd2(xr[0].y, xr[1].y);
                    xv[2] = hadd2(xr[2].x, xr[3].x); xv[3] = hadd2(xr[2].y, xr[3].y);
                }, [](uint32_t) {});
                bad = any_bit0((TV_POS == 1 && !(XP & 8) ? VFBAD : 0) | (xr[0].x ^ tag) | (xr[1].x ^ tag) | (xr[2].x ^ tag) | (xr[3].x ^ tag)) & (++it < POLL_LIMIT);
                stsm4(sb + SM_OX + g16, ov[0], ov[1], ov[2], ov[3]);
            } while (bad);
            PROFV(14, it - 1) MISS(2, it - 1)
            PROF(5)
            bar_sync(NB_X2, 384);
            BLOCK_FENCE
            U2 tv2 = {0, 0};
            const uint8_t* tp = arena + (blk(LB_TIME, mypar) + ((G16() << 6) & 0xc00));
            {
                const uint4 pp = lds4(l16 + SM_PX + 1024);
                const uint32_t p4 = lds1(sb + SM_PX + 512 + 1024 - wu * 128 + (G16() >> 2));
                if (E_MUL) tv2 = ldg_u2(tp);
                if (H_POS == 3 && !(XP & 1) && warp0 && s + 3 <= NSEG) h_load(sb, hsrc, s + 3, j, H_ROT ? head : 0);
                if (H_POS == 0 && !(XP & 1)) h_piece(sb, hsrc, s + 3, j, (wu + (H_ROT ? head : 0)) & 3, wu == 0);
                pv(pp.x, pp.y, pp.z, pp.w, p4, []() {}, [&](uint32_t r) { bar_arrive(NB_WIN + ((r | fz[0] | fz[2] | fz[3]) & zero), 384); });
            }
            dst0 = TAB(6); dx0 = TAB(7);
            const uint32_t zo = Z_POS ? 0 : TAB(8);
            PROF(6) HT(7)
            BLOCK_FENCE
            if (H_POS == 1 && !(XP & 1)) h_piece(sb, hsrc, s + 3, j, (wu + (H_ROT ? head : 0)) & 3, wu == 0);
            asm volatile("" : "+r"(tv2.y));
            it = 0;
#pragma unroll 1
            while (E_MUL && __any_sync(~0u, tv2.y < 32 * (s + 1)) & (++it < 16)) tv2 = ldg_u2(tp);
            const uint32_t e = __reduce_max_sync(~0u, tv2.x) - gt;
            MISS(3, it - 1) MISS(4, gt)
            if (PA_POS) tok_fetch(s + 1);
            if (O_POS == 0) o_store(s);
            if (!Z_POS) stg4_if(g16 < 160, arena + (zo + mem_slot(s + 3)), 0);
            dl = dbase + (e > 4096 ? 0 : e * E_MUL >> 4);
        }
        if (O_POS) o_store(NSEG - 1);
        TL(8)
    }
    PROF_OUT
    MISS_OUT
}

struct RecMaps { CUtensorMap wq, wk, wv, wo, wmod, w3, w1; };
struct RecPtrs { const bf16 *x, *mem0, *c, *wmod, *w1, *w3; uint8_t* arena; uint32_t zero; const bf16 *w2, *w4, *wo; Delays dly; };

__device__ __forceinline__ float silu_bf(const bf16* c, int i) {
    const float v = __bfloat162float(c[i]);
    return bfround(__fdividef(v, 1.0f + __expf(-v)));
}
#define LN_SEQ 0xcba6420987531ull
#define W_LATE 1000
#define W_OPEN 1400
__device__ __noinline__ uint32_t side_window_(const uint8_t* arena, uint32_t n) {
    U2 v;
    int it = 0;
#pragma unroll 1
    while (v = ldg_u2(arena + (LB_TIME << 13)), ((v.y >> 5) == n || gtime() - v.x > W_OPEN + W_LATE) && v.y < 32 * NSEG && ++it < 64) __nanosleep(100);
    it = 0;
#pragma unroll 1
    while ((int)(gtime() - v.x - W_OPEN) < 0 && ++it < 256) {}
    return v.y >> 5;
}
#define side_window(arena, n) n = side_window_(arena, n)
__device__ __noinline__ void rec_ln(uint32_t sb, const bf16* x, const uint8_t* arena, int id, int r0) {
    int r1 = 32;
    uint32_t n = 0;
    const int tid = threadIdx.x, lane = tid & 31, wid = __reduce_max_sync(~0u, tid >> 5);
    const uint32_t ring = sb + wid * 8192 + lane * 16, coef = sb + SM_PRE;
    x += (id * 8 + wid) * 2 * DM + lane * 8;
#pragma unroll 1
    for (int r = r0 - 1; r < r1; r++) {
        if (r > 3) side_window(arena, n);
        if (r + 1 < r1) {
#pragma unroll
            for (int i = 0; i < 8; i++)
                asm volatile("cp.async.cg.shared.global [%0], [%1], 16;" ::"r"(ring + (~r & 1) * 4096 + i * 512), "l"(x + (r + 1) * 64 * DM + i * 256) : "memory");
        }
        asm volatile("cp.async.commit_group; cp.async.wait_group 1;" ::: "memory");
        if (r < r0) continue;
        const uint32_t src = ring + (r & 1) * 4096;
        float m[2] = {0.f, 0.f}, rs[2];
#pragma unroll 1
        for (int ps = 0; ps < 2; ps++) {
            float t[2][2] = {{0.f, 0.f}, {0.f, 0.f}};
#pragma unroll 1
            for (int i = 0; i < 2048; i += 512) {
#pragma unroll
                for (int h = 0; h < 2; h++) {
                    const uint4 u = lds4(src + h * 2048 + i);
#pragma unroll
                    for (int e = 0; e < 4; e++) {
                        const float a = bflo((&u.x)[e]) - m[h], c = bfhi((&u.x)[e]) - m[h];
                        t[h][0] = fmaf(a, ps ? a : 1.0f, t[h][0]); t[h][1] = fmaf(c, ps ? c : 1.0f, t[h][1]);
                    }
                }
            }
            rs[0] = t[0][0] + t[0][1]; rs[1] = t[1][0] + t[1][1];
#pragma unroll 1
            for (int o = 16; o; o >>= 1) { rs[0] += __shfl_xor_sync(~0u, rs[0], o); rs[1] += __shfl_xor_sync(~0u, rs[1], o); }
            if (!ps) { m[0] = rs[0] * (1.0f / DM); m[1] = rs[1] * (1.0f / DM); }
        }
        rs[0] = rsqrtf(rs[0] * (1.0f / DM) + 1e-5f); rs[1] = rsqrtf(rs[1] * (1.0f / DM) + 1e-5f);
        if (r == r0) {
#pragma unroll 1
            for (int i = tid; i < 2 * DM / 4; i += 256) {
                float t[4];
                int it = 0;
                uint32_t ok;
#pragma unroll 1
                do {
                    uint4 u[8];
#pragma unroll
                    for (int k = 0; k < 8; k++) u[k] = ldg_rlx4(g_modp + k * 2 * DM + i * 4);
                    ok = 1;
#pragma unroll
                    for (int k = 0; k < 32; k++) { const uint32_t w = (&u[k >> 2].x)[k & 3]; ok &= w; t[k & 3] = k < 4 ? __uint_as_float(w) : t[k & 3] + __uint_as_float(w); }
                } while (!__all_sync(~0u, ok) & (++it < SPIN_LIMIT));
                const float o = i >> 8;
                const uint32_t lo = pack2(t[0], t[1]), hi = pack2(t[2], t[3]);
                sts4f(coef + (i >> 8) * 4096 + (i & 1) * 2048 + ((i & 255) >> 1) * 16, bflo(lo) + o, bfhi(lo) + o, bflo(hi) + o, bfhi(hi) + o);
            }
            bar_sync(NB_FIN0, 256);
            if (tid == 0 && r0 == 0) TL(2)
        }
        uint8_t* dst = (uint8_t*)g_himg + (r * 2 + (id >> 1)) * 65536 + (lane >> 3) * 4096 + wid * 256;
#pragma unroll 1
        for (int i = 0; i < 4; i++) {
            const uint32_t ca = coef + i * 512 + lane * 16;
            const float4 s0 = lds4f(ca), s1 = lds4f(ca + 2048), c0 = lds4f(ca + 4096), c1 = lds4f(ca + 6144);
            const float sh[8] = {s0.x, s0.y, s0.z, s0.w, s1.x, s1.y, s1.z, s1.w}, sc[8] = {c0.x, c0.y, c0.z, c0.w, c1.x, c1.y, c1.z, c1.w};
#pragma unroll
            for (int h = 0; h < 2; h++) {
                uint4 u = lds4(src + h * 2048 + i * 512);
#pragma unroll
                for (int e = 0; e < 4; e++) {
                    uint32_t& w = (&u.x)[e];
                    w = pack2(fmaf((bflo(w) - m[h]) * rs[h], sc[2 * e], sh[2 * e]), fmaf((bfhi(w) - m[h]) * rs[h], sc[2 * e + 1], sh[2 * e + 1]));
                }
                *(uint4*)(dst + i * 16384 + ((id & 1) == (i >> 1) ? 65536 : 2048) + h * 128 + (((lane ^ (2 * wid + h)) & 7) << 4)) = u;
            }
        }
        if (r == 0) {
            if (tid == 0) TLX(10)
            int ro, it = 0;
#pragma unroll 1
            do asm volatile("ld.volatile.shared.u32 %0, [%1];" : "=r"(ro) : "r"(sb + SM_BAR + 192) : "memory"); while ((ro == INT_MIN) & (++it < SPIN_LIMIT));
            if (ro >= 0) r1 = 2;
        }
        if (r && !(r & 1)) continue;
        bar_sync(r ? NB_FIN0 : NB_C, r ? 256 : 320);
        if (tid == 0 && r == 0) TLX(11)
        if (wid == (r >> 1 & 7)) {
            if (r == 1) bar_arrive(NB_B, 64);
            if (r == 3) wait_count_w(&g_tick[32 + id * 8], 2);
            if (lane == 0) { signal_count(&g_tick[32 + id * 8]); if (r == 0) TLX(12) }
            __syncwarp();
        }
    }
}
#define SIDE_T 300
template <int NQ>
__device__ __forceinline__ void side_gemv(const CUtensorMap* tm, int c0, int k0, int k1, uint32_t cs, uint32_t sb, const uint8_t* arena, uint32_t& n, uint32_t& ph, float (*acc)[8], bool once = false) {
    const uint32_t w = __reduce_max_sync(~0u, threadIdx.x >> 5 & 3), ring = sb + 65536 + w * 24576, bars = sb + SM_BAR + 8 * B_W + w * 24;
#pragma unroll
    for (int q = 0; q < NQ; q++)
#pragma unroll
        for (int j = 0; j < 8; j++) acc[q][j] = 0.f;
#pragma unroll 1
    for (; k0 < k1; k0 += 48, ph ^= 1) {
        const int nr = min(48, k1 - k0);
        side_window(arena, n);
        const uint32_t t0 = clk32();
#pragma unroll 1
        for (int g = 0; g < 3; g++) {
            spin_until(t0, (g * 4 + w) * (SIDE_T / 4));
            e_expect(bars + 8 * g, g * 16 < nr ? 8192 : 0);
            if (g * 16 < nr) e_tma2d_hint(ring + g * 8192, tm, c0, k0 + g * 16, bars + 8 * g, once ? EVICT_FIRST : EVICT_NORMAL);
        }
#pragma unroll 1
        for (int r = 0; r < nr; r += 16) {
            mbar_wait_w(bars + (r >> 1), ph);
            uint4 v[16];
#pragma unroll
            for (int h = 0; h < 16; h++) v[h] = lds4(ring + (r + h) * 512 + (threadIdx.x & 31) * 16);
            float4 cf[NQ][4];
#pragma unroll
            for (int q = 0; q < NQ * 4; q++) cf[q >> 2][q & 3] = lds4f(cs + ((q >> 2) * DM + k0 + r + (q & 3) * 4) * 4);
#pragma unroll
            for (int h = 0; h < 16; h++) {
                const float f[8] = {bflo(v[h].x), bfhi(v[h].x), bflo(v[h].y), bfhi(v[h].y), bflo(v[h].z), bfhi(v[h].z), bflo(v[h].w), bfhi(v[h].w)};
#pragma unroll
                for (int q = 0; q < NQ; q++)
#pragma unroll
                    for (int j = 0; j < 8; j++) acc[q][j] = fmaf((&cf[q][h >> 2].x)[h & 3], f[j], acc[q][j]);
            }
        }
        fence_async_smem();
        __syncwarp();
    }
}
__device__ __noinline__ void rec_side(float* sm, const RecMaps& mp, const RecPtrs& p, int id) {
    const int tid = threadIdx.x;
    if (tid < 256) {
        if (blockIdx.x < 128) rec_ln(smem_u32(sm), p.x, p.arena, id, 2);
        if (tid == 0) TL(14)
        for (int i = tid; i < 2 * S_; i += 256) g_st[id * 2 * S_ + i] = 0.f;
        if (id == 0 && tid < 64) g_pcnt[tid * 8] = 0;
        if (id == 1) for (int i = tid; i < 6 * 256; i += 256) g_pflag[i] = 0;
        if (id == 2 && tid == 0) g_pt = 0;
        bar_sync(NB_FIN0, 256);
        if (PDL && tid == 0) asm volatile("fence.acq_rel.gpu; griddepcontrol.launch_dependents;" ::: "memory");
        return;
    }
    const int t = tid - 256;
    float *coef = sm + 40960, *red = coef + 3 * DM;
    const uint32_t sb = smem_u32(sm), cs = smem_u32(coef);
    uint32_t n = 0, ph = 0;
    for (int i = t; i < DM; i += 128) { coef[i] = silu_bf(p.c, i); coef[2 * DM + i] = 1.0f; }
    if (t == 0) wait_count1(&g_tick[32], 1);
    bar_sync(NB_G, 128);
    const int w = __reduce_max_sync(~0u, t >> 5);
    float acc[3][8];
    side_gemv<1>(&mp.wmod, (2 + id) * DM + w * 256, 0, DM, cs, sb, p.arena, n, ph, acc, true);
#pragma unroll
    for (int j = 0; j < 8; j++) g_mod[(2 + id) * DM + t * 8 + j] = bfround(acc[0][j]);
    bar_sync(NB_G, 128);
    if (t == 0) signal_count(&g_tick[8]);
    side_gemv<1>(&mp.w3, id * (FF / 4) + w * 256, 0, DM, cs + 8 * DM, sb, p.arena, n, ph, acc);
    if (t < FF / 32) {
#pragma unroll
        for (int j = 0; j < 8; j++) g_vec[3 * DM + id * (FF / 4) + t * 8 + j] = acc[0][j];
    }
    if (t == 0) wait_count1(&g_tick[8], 4);
    bar_sync(NB_G, 128);
    for (int i = t; i < DM; i += 128) { coef[i] = 1.0f + __ldcg(g_mod + 4 * DM + i); coef[DM + i] = __ldcg(g_mod + 3 * DM + i); }
    bar_sync(NB_G, 128);
    if (id == 1 && t < 32) {
        float u[5] = {0, 0, 0, 0, 0};
        for (int i = t; i < DM; i += 32) {
            const float a = coef[i], b = coef[DM + i];
            u[0] += a; u[1] += a * a; u[2] += a * b; u[3] += b; u[4] += b * b;
        }
#pragma unroll
        for (int q = 0; q < 5; q++) { const float r = warp_sum(u[q]); if (t == 0) g_cst[q] = r * (1.0f / DM); }
    }
    side_gemv<3>(&mp.w1, id * 256, w * 256, w * 256 + 256, cs, sb, p.arena, n, ph, acc);
#pragma unroll
    for (int q = 0; q < 3; q++)
#pragma unroll
        for (int j = 0; j < 8; j++) red[((t >> 5) * 3 + q) * 256 + (t & 31) * 8 + j] = acc[q][j];
    bar_sync(NB_G, 128);
    for (int i = t; i < 768; i += 128) g_vec[(i >> 8) * DM + id * 256 + (i & 255)] = (red[i] + red[768 + i]) + (red[1536 + i] + red[2304 + i]);
    if (t == 0) TL(9)
}

__global__ void __cluster_dims__(2, 1, 1) __launch_bounds__(384, 1)
k_rec(const __grid_constant__ RecMaps mp, const __grid_constant__ RecPtrs p) {
    extern __shared__ uint8_t smraw[];
    const uint32_t sb = smem_u32(smraw);
    if ((sb & 0x3FFFF) != SB0) __trap();
    const uint32_t bars = sb + SM_BAR;
    const int tid = threadIdx.x, lane = tid & 31, b = blockIdx.x;
    const int wid = __reduce_max_sync(~0u, tid >> 5);
    const uint32_t rank = b & 1;
    uint8_t* arena = p.arena;
    volatile int* sinfo = (volatile int*)(smraw + SM_BAR + 192);
    if (tid == 0) TL(0)
    if (tid == 0) sinfo[0] = INT_MIN;
    if (tid == 352) {
        for (int i = 0; i < 17; i++) mbar_init(bars + 8 * i, i == B_WO ? 4 : 1);
        asm volatile("fence.mbarrier_init.release.cluster;" ::: "memory");
    }
    __syncwarp();
    asm volatile("barrier.cluster.arrive.relaxed.aligned;" ::: "memory");
    int pr = 0, hA = 0;
    if (wid < 8) {
        if (b < 128) {
            const int cb = (b & 15) * 128, k0 = (b >> 4) * 128 + (tid >> 4);
            uint4 v[8];
#pragma unroll
            for (int i = 0; i < 8; i++) v[i] = __ldg((const uint4*)(p.wmod + (size_t)(k0 + 16 * i) * (6 * DM) + cb + (tid & 15) * 8));
            float acc[8] = {0, 0, 0, 0, 0, 0, 0, 0};
            const float s8 = silu_bf(p.c, k0 + 16 * (lane & 7));
#pragma unroll
            for (int i = 0; i < 8; i++) {
                const float sv = __shfl_sync(~0u, s8, i, 16);
                acc[0] += sv * bflo(v[i].x); acc[1] += sv * bfhi(v[i].x); acc[2] += sv * bflo(v[i].y); acc[3] += sv * bfhi(v[i].y);
                acc[4] += sv * bflo(v[i].z); acc[5] += sv * bfhi(v[i].z); acc[6] += sv * bflo(v[i].w); acc[7] += sv * bfhi(v[i].w);
            }
            float* red = (float*)(smraw + SM_PRE);
            *(float4*)(red + (tid >> 4) * 128 + (tid & 15) * 8) = make_float4(acc[0], acc[1], acc[2], acc[3]);
            *(float4*)(red + (tid >> 4) * 128 + (tid & 15) * 8 + 4) = make_float4(acc[4], acc[5], acc[6], acc[7]);
            bar_sync(NB_FIN0, 256);
            if (wid < 4) {
                float t = 0;
#pragma unroll
                for (int i = 0; i < 16; i++) t += red[i * 128 + tid];
                stg_rlx1(&g_modp[(b >> 4) * 2 * DM + cb + tid], __float_as_uint(t) | 1u);
                TLX(14)
            }
        } else {
            rec_ln(sb, p.x, p.arena, b - 128, 0);
        }
    } else if (wid >= 10 && b >= 128) {
        {
            const int w = (b - 128) * 2 + wid - 10;
            const uint16_t* src = (const uint16_t*)p.mem0 + (lane & 3) * 2 * DM + (w >> 2) * 512 + (w & 1) * 64 + (w & 2) * 8 + (lane >> 2);
            uint32_t v[4][4];
#pragma unroll
            for (int i = 0; i < 16; i++) v[i >> 2][i & 3] = src[(i >> 2) * 128 + (i & 2) * 16 + (i & 1) * 8] | ((uint32_t)src[DM + (i >> 2) * 128 + (i & 2) * 16 + (i & 1) * 8] << 16);
            uint8_t* d = arena + mem_row(w >> 2, w & 3, 0);
            uint8_t* e = d + 512 + (CNT32 ? lane >> 1 : lane) * 4;
            d += lane * 16;
#pragma unroll
            for (int i = 0; i < 4; i++, d += 1024, e += 1024) {
                stg_rlx4(d, v[i][0], v[i][1], v[i][2], CNT32 && !(lane & 1) ? v[i][3] : (v[i][3] & 0xffff) | CNT_ALL << 16);
                stg_rlx4(d + mem_slot(1), 0, 0, 0, 0);
                stg_rlx4(d + mem_slot(2), 0, 0, 0, 0);
                if (!CNT32 || (lane & 1)) { stg_rlx1(e, (v[i][3] & 0xffff0000u) | CNT_ALL); stg_rlx1(e + mem_slot(1), 0); stg_rlx1(e + mem_slot(2), 0); }
            }
            if (w == 0 && lane < 8) stg_rlx2(arena + (LB_TIME << 13) + lane * 1024, 0, 0);
            bar_arrive(NB_C, 320);
        }
    } else if (rank == 0) {
        uint32_t best = ~0u;
        const int pg = wid < 10 ? 0 : 1 + (b >> 1) / 22;
        uint32_t* q = (uint32_t*)(arena + (pg << 21) + (pg ? blk(b >> 1, wid & 1) : blk(LB_PROBE, wid & 1) + b * 16));
        if (lane < 8) stg_rlx1(q + lane, 0);
        __syncwarp();
        if (lane == 0) {
            q += 3;
            uint32_t v = atomicAdd(q, 1u);
#pragma unroll 1
            for (int r = 0; r < NPROBE; r++) {
                const uint32_t t0 = clk32() + (v >> 8);
                v = atomicAdd(q + (v >> 8), 1u);
                uint32_t t1;
                asm volatile("{.reg .pred p; setp.eq.u32 p, %1, 0xffffffff; @p exit; mov.u32 %0, %%clock;}" : "=r"(t1) : "r"(v) : "memory");
                best = min(best, t1 - t0);
            }
            sinfo[wid - 6] = best;
        }
        bar_sync(NB_KDONE, b < 128 ? 128 : 64);
        if (tid == 256) {
            const uint32_t par = sinfo[2] > sinfo[3], vote = b < 128 && (sinfo[4] > sinfo[5]) != par;
            stg_rlx2(&g_clk[b >> 1], ((clk32() - 2 * gtime()) & ~127u) | b >> 1, 1 + 2 * par + 4 * vote);
        }
    }
    if (wid == 8) {
        U2 v[3], my;
        uint32_t c0;
        const int me = b >> 1;
        int it = 0;
        __syncwarp();
#pragma unroll 1
        do {
            my = ldg_u2(&g_clk[me]);
#pragma unroll
            for (int k = 0; k < 3; k++) v[k] = ldg_u2(&g_clk[k * 22 + min(lane, 21)]);
        } while (!__all_sync(~0u, my.y & v[0].y & v[1].y & v[2].y & 1) & (++it < SPIN_LIMIT));
        TLX(15)
        c0 = __reduce_min_sync(~0u, lane ? ~0u : v[0].x) - 4096;
        const uint32_t mc = me >= 64 ? ~0u : my.x - c0;
        const int par = my.y >> 1 & 1;
        uint32_t cnt = 0, flip = 0;
#pragma unroll
        for (int k = 0; k < 3; k++) {
            const uint32_t c = v[k].x - c0, o = v[k].y >> 1 & 1;
            const bool ln = k == 2 && lane >= 20;
            cnt += o + (o == par ? (ln ? 44 + lane < me : c < mc) * 256 + (c < my.x - c0) * 65536 : 0);
            flip |= __popc(__ballot_sync(~0u, v[k].y & 4) & 0x3fffff) > 10 ? 256 << k : 0;
        }
        cnt = __reduce_add_sync(~0u, lane < 22 ? cnt : 0);
        const int n1 = cnt & 255, n0 = 66 - n1, tk = cnt >> 8 & 255;
        if (lane == 0) g_cls[smid() & 255] = cnt < 32 << 16 ? par * 4 + (cnt >> 19) : 8;
        hA = min(n0 >> 1, NH);
        const int q0 = 2 * hA, q1 = 2 * NH - q0;
        const int over = tk - (par ? q1 : q0), lack = max(par ? q0 - n0 : q1 - n1, 0);
        if (over < 0) pr = par ? q0 + tk : tk;
        else if (over < lack) pr = (par ? n0 : q0 + n1) + over;
        else pr = -1 - (over - lack + (par ? max(n0 - q0, 0) : 0));
        hA |= flip;
        if (lane == 0) {
            sinfo[1] = hA; sinfo[0] = pr;
            if (b >= 128 && rank == 0) atomicOr(&g_tick[6], (pr < 0 ? 4u : 1u) << ((b - 128) >> 1));
        }
    }
    asm volatile("barrier.cluster.wait.aligned;" ::: "memory");
    if (wid == 8) {
        TL(1)
        __syncwarp();
        bar_arrive(NB_A, 288);
        bar_arrive(NB_S, 128);
        if (b >= 128 && pr < 0) bar_sync(NB_B, 64);
        if (pr >= 0) {
            const int pu = __reduce_max_sync(~0u, pr), c0 = (pu >> 1) * 128 + rank * 64, r0 = (pu & 1) * 512;
#pragma unroll 1
            for (int n = 0; n < 13; n++) {
                const u64 seq = b >= 128 ? LN_SEQ : 0xcba9876543210ull;
                const int i = seq >> (4 * n) & 15;
                if (b >= 128 && i == 0) bar_sync(NB_B, 64);
                if (n >= W_INFL) mbar_wait_w(bars + 8 * (B_W + (seq >> (4 * (n - W_INFL)) & 15)), 0);
                const int m = i < 8 ? i & 1 : i >> 2, k = i < 8 ? i >> 1 : i & 3;
                const uint32_t dst = sb + m * 65536 + k * 16384, br = bars + 8 * (m < 3 ? B_W + i : B_WO);
                const int c = m < 3 ? c0 : 576 + rank * 256 + (pu & 1) * 128, r = m < 3 ? r0 + k * 128 : (pu >> 1) * DH;
                const uint64_t pol = m < 3 ? EVICT_FIRST : EVICT_NORMAL;
                e_expect(br, 16384);
                e_tma2d_hint(dst, &mp.wq + m, c, r, br, pol);
                e_tma2d_hint(dst + 8192, &mp.wq + m, c, r + 64, br, pol);
            }
        }
    } else {
        bar_sync(wid < 8 ? NB_A : NB_S, wid < 8 ? 288 : 128);
    }
    const int prr = __reduce_max_sync(~0u, sinfo[0]);
    hA = __reduce_max_sync(~0u, sinfo[1]);
    if (prr < 0) {
        int j = (b - 128) >> 1;
        if (b < 128) {
            uint32_t v;
            int it = 0;
#pragma unroll 1
            do { v = __reduce_max_sync(~0u, ldg_rlx1(&g_tick[6])); spin_guard(++it); } while (__popc(v) < 2);
            j = v == 3 ? -1 - prr : (v & 1) ^ 1;
        }
        rec_side((float*)smraw, mp, p, j * 2 + rank);
        return;
    }
    if (PDL) asm volatile("griddepcontrol.launch_dependents;" ::: "memory");
    const int role = (prr >> 1) * 4 + rank * 2 + (prr & 1);
    rec_main(sb, &mp.wo, arena, role, hA, wid >> 2, p.zero, p.dly);
}

__device__ __forceinline__ void wgmma_ss192(float* d, uint64_t a, uint64_t b, int sc) {
    asm volatile("{.reg .pred p; setp.ne.b32 p, %98, 0;\n wgmma.mma_async.sync.aligned.m64n192k16.f32.bf16.bf16 "
                 "{%0,%1,%2,%3,%4,%5,%6,%7,%8,%9,%10,%11,%12,%13,%14,%15,%16,%17,%18,%19,%20,%21,%22,%23,%24,%25,%26,%27,%28,%29,%30,%31,%32,%33,%34,%35,%36,%37,%38,%39,%40,%41,%42,%43,%44,%45,%46,%47,%48,%49,%50,%51,%52,%53,%54,%55,%56,%57,%58,%59,%60,%61,%62,%63,%64,%65,%66,%67,%68,%69,%70,%71,%72,%73,%74,%75,%76,%77,%78,%79,%80,%81,%82,%83,%84,%85,%86,%87,%88,%89,%90,%91,%92,%93,%94,%95}, %96, %97, p, 1, 1, 0, 1;}"
                 : F16(d, 0), F16(d, 16), F16(d, 32), F16(d, 48), F16(d, 64), F16(d, 80) : "l"(a), "l"(b), "r"(sc));
}

constexpr uint32_t P_B = 81920, P_PL = 40960, P_OUT = 180224, P_VEC = 212992, P_ROW = P_VEC + 6144, P_BAR = P_ROW + 4096, P_SMEM = P_BAR + 256;
#define PPH 1
#define FLAG_ST "st.release.gpu.global.u32"
#define FLAG_LD "ld.acquire.gpu.global.u32"
#define PX 0
#define MIDF 0
#define END_FAST 1
#define DS_AT 3
constexpr int ST = 5;
constexpr int PB_F = 0, PB_E = 5, PB_R = 10, PB_OUT = 16;
enum { C_Y = 0, C_G = 1, C_X1 = 2, C_U = 3, C_S1 = 8, C_S3 = 9 };
enum { V_GA = 0, V_A = 1, V_B = 2, V_GB = 3, V_VA = 4, V_VB = 5, V_VC = 6, V_C3 = 7 };
struct PostMaps { CUtensorMap o, wo, y, w1, g, w2, x1, w3, u, w4, out; };
struct PostPtrs { const bf16* x; };

struct GeluK { float k0, k1, kh; };
__device__ __forceinline__ GeluK gelu_k(float c) { return {0.7978845608028654f * c, 0.7978845608028654f * 0.044715f * c * c * c, 0.5f * c}; }
__device__ __forceinline__ float gelu_s(float t, const GeluK& k) {
    const float u = t * fmaf(t * t, k.k1, k.k0);
    float th; asm("tanh.approx.f32 %0, %1;" : "=f"(th) : "f"(u));
    const float hx = k.kh * t;
    return fmaf(hx, th, hx);
}
__device__ __forceinline__ float2 ldsv(uint32_t a) {
    float2 v; asm("ld.shared.v2.f32 {%0,%1}, [%2];" : "=f"(v.x), "=f"(v.y) : "r"(a)); return v;
}
__device__ __forceinline__ void wait_smem(uint32_t a, int target) {
    int it = 0;
#pragma unroll 1
    while (true) {
        int v;
        asm volatile("ld.acquire.cta.shared.u32 %0, [%1];" : "=r"(v) : "r"(a) : "memory");
        if (__all_sync(~0u, v >= target) | (++it > SPIN_LIMIT)) break;
    }
}

#define PP(i)
#define PH_(c, w, i)
__device__ __forceinline__ void mbar_wait_b(uint32_t b, uint32_t par) {
    int it = 0;
#pragma unroll 1
    while (!__all_sync(~0u, mbar_try(b, par)) & (++it < SPIN_LIMIT)) {}
}
__device__ __forceinline__ void release(uint32_t rel, int st, bool c) {
    asm volatile("{.reg .pred p; setp.ne.u32 p, %1, 0; setp.ne.and.u32 p, %2, 0, p; @p mbarrier.arrive.shared::cluster.b64 _, [%0];}"
                 ::"r"(rel + 8 * (st ? st - 1 : ST - 1)), "r"(rel), "r"((uint32_t)c) : "memory");
}
struct Pipe { int st, ph; uint32_t rel; };
__device__ __forceinline__ void adv(Pipe& p) { if (++p.st == ST) { p.st = 0; p.ph ^= 1; } }

__device__ __forceinline__ void post_weights(uint32_t sb, const PostMaps& mp, int nb, int rank) {
    const uint32_t full = sb + P_BAR + 8 * PB_F, empty = sb + P_BAR + 8 * PB_E;
    int st = 0, pp = 1;
#pragma unroll 1
    for (int ph = 0; ph < 7; ph++) {
        const int NK = ph == 0 ? 64 : ph == 6 ? 56 : 16, km = NK == 16 ? 15 : 63;
        const CUtensorMap* tb = &mp.wo + 2 * (ph < 3 ? ph : ph < 6 ? 3 : 4);
        const bool w3 = ph >= 3 && ph < 6;
        const int n0 = w3 ? nb * 64 + (ph == 4 ? 1536 : ph == 5 ? 2560 : 0) : nb * 128, dn = w3 ? 512 : 64;
        const int rot = NK == 16 ? 2 * (nb & 6) : 0, sw = ph == 1 || ph == 3 ? 2 * rank : 0;
#pragma unroll 1
        for (int i = 0; i < NK; i++) {
            const int k0 = (((i < 4 ? i ^ sw : i) + rot) & km) * 64;
            const uint32_t a = sb + P_B + st * 8192, f = full + 8 * st;
            mbar_wait_b(empty + 8 * st, pp);
            e_expect(f, ph == 3 ? 40960 : 32768);
            e_tma2d(a, tb, n0, k0, f);
            e_tma2d(a + P_PL, tb, n0 + dn, k0, f);
            if (ph == 3) e_tma2d(a + 2 * P_PL, tb, n0 + 1024, k0, f);
            if (++st == ST) { st = 0; pp ^= 1; }
        }
    }
#pragma unroll 1
    for (int i = 0; i < ST; i++) mbar_wait_b(empty + 8 * i, pp ^ (i < st));
}
__device__ __forceinline__ void post_acts(uint32_t sb, const PostMaps& mp, int mb, int nb, int rank) {
    const int rh = 2 * mb + rank, lane = threadIdx.x & 31;
    const uint32_t full = sb + P_BAR + 8 * PB_F, empty = sb + P_BAR + 8 * PB_E;
    int st = 0, pp = 1;
#pragma unroll 1
    for (int ph = 0; ph < 7; ph++) {
        const int NK = ph == 0 ? 64 : ph == 6 ? 56 : 16, km = NK == 16 ? 15 : 63;
        const CUtensorMap* ta = &mp.o + 2 * (ph < 3 ? ph : ph < 6 ? 3 : 4);
        const int amul = ph == 0 ? 256 : 64, arow = ph == 0 ? rh * 8 : rh * 64;
        const int rot = NK == 16 ? 2 * (nb & 6) : 0, own = ph == 1 || ph == 3 ? 4 : 0;
        const uint32_t shifts = ph == 2 ? 0x04000301u : 0x02020202u;
        const uint32_t* fl = &g_pflag[(ph == 6 ? C_U : min(ph - 1, 2)) * 256 + (ph == 2 ? min(max(rh + min(lane >> 3, 2) - 1, 0), 31) : rh) * 8 + (lane & 7)];
        uint32_t have = ph == 0 || ph == 5;
        if (own) { if (st) { st--; pp ^= 1; } else st = 4; }
#pragma unroll 1
        for (int i = own; i < NK; i++) {
            const int kb = (i + rot) & km;
            const uint32_t need = ph == 6 ? 255u : (ph == 2 ? 0x10101u : 1u) << ((kb >> 1) & 7), lvl = ph == 6 ? i >> 3 : 0;
            PH_(ph == PPH && i == own, 0, 27) PH_(ph == PPH && i == own, 1, 27)
            if ((__ballot_sync(~0u, have > lvl) & need) != need) {
                int it = 0;
#pragma unroll 1
                do asm volatile(FLAG_LD " %0, [%1];" : "=r"(have) : "l"(fl) : "memory");
                while (((__ballot_sync(~0u, have > lvl) & need) != need) & (++it < SPIN_LIMIT));
                PH_(ph == PPH && i == own, 0, 23) PH_(ph == PPH, 0, 24) PH_(ph == PPH && i == own, 1, 23) PH_(ph == PPH, 1, 24)
                asm volatile("fence.proxy.async.global;" ::: "memory");
            }
            const int d = own && (i == 5 || i == 6) ? 2 : 0, s2 = st + d < ST ? st + d : st + d - ST;
            mbar_wait_b(empty + 8 * s2, pp ^ (s2 < st));
            e_tma2d_mc(sb + st * 16384 + rank * 8192, ta, kb * amul, arow + (int)((shifts >> ((kb & 12) * 2)) & 7) - 2, full + 8 * st);
            if (++st == ST) { st = 0; pp ^= 1; }
        }
    }
}

template <int PH, bool EARLY = false, class F>
__device__ __forceinline__ void post_kb(uint32_t sb, float* acc, Pipe& p, int wg, bool lead, bool first, F mid) {
    constexpr uint64_t DA = PH == 0 ? mkdesc(SB0, 128, 1024, 0) : mkdesc(SB0, 16, 1024, 1);
    constexpr uint64_t DB = mkdesc(SB0 + P_B, P_PL, 1024, 1);
    mbar_wait_b(sb + P_BAR + 8 * PB_F + 8 * p.st, p.ph);
    const uint32_t a = (uint32_t)DA + p.st * 1024 + wg * 512, b = (uint32_t)DB + p.st * 512;
    wg_fence();
#pragma unroll
    for (int k = 0; k < 4; k++) {
        const uint64_t da = (DA & 0xffffffff00000000ull) | (a + k * (PH == 0 ? 16 : 2)), db = (DB & 0xffffffff00000000ull) | (b + k * 128);
        if (PH == 3) wgmma_ss192(acc, da, db, k || !first);
        else wgmma_ss128<PH == 0>(acc, da, db, k || !first);
    }
    wg_commit();
    if (EARLY) mid();
    wg_wait<1>();
    release(p.rel, p.st, !first);
    if (!EARLY) mid();
    adv(p);
}
__device__ __forceinline__ void post_end(uint32_t sb, Pipe& p, bool lead) {
    wg_wait<0>();
    release(p.rel, p.st, true);
}
template <int PH>
__device__ __forceinline__ void post_mma(uint32_t sb, float* acc, Pipe& p, int wg, bool lead, int nout, int pi, int mb, int nb) {
#pragma unroll 1
    for (int kb = 0; kb < 16; kb++)
        post_kb<PH>(sb, acc, p, wg, lead, kb == 0, [&]() {
            if (kb == 0) { PP(pi) }
            if (nout && kb == 0) wait_smem(sb + P_BAR + 8 * (PB_OUT + wg), nout);
        });
    post_end(sb, p, lead);
    PP(pi + 1)
}

__global__ void __cluster_dims__(2, 1, 1) __launch_bounds__(384, 1)
k_post(const __grid_constant__ PostMaps mp, const __grid_constant__ PostPtrs pp) {
    extern __shared__ uint8_t smraw[];
    const uint32_t sb = smem_u32(smraw);
    if ((sb & 0x3FFFF) != SB0) __trap();
    const int tid = threadIdx.x, lane = tid & 31;
    const int rank = blockIdx.x & 1;
    const uint32_t bars = sb + P_BAR;
    int c = 0;
    unsigned long long v = 0;
    const int wid = __reduce_max_sync(~0u, tid >> 5);
    const bool draw = tid == 352 && rank == 0;
    if (draw) {
        c = min(ldg_rlx1(&g_cls[smid() & 255]), 8u);
        asm volatile("{.reg .b64 a; cvt.u64.u32 a, %%laneid; add.u64 a, a, %1; atom.relaxed.gpu.global.add.u64 %0, [a], %2;}" : "=l"(v) : "l"(&g_pt), "l"(1ull << (7 * c)) : "memory");
    }
    if (wid < 11) {
        asm volatile("{.reg .pred p; elect.sync _|p, 0xffffffff; @p mbarrier.init.shared.b64 [%0], %1; @p prefetch.tensormap [%2]; fence.mbarrier_init.release.cluster;}"
                     ::"r"(bars + 8 * wid), "r"(wid >= PB_E && wid < PB_R ? 4 : 1), "l"(&mp.o + wid) : "memory");
        if (wid == PB_R) { sts4(bars + 8 * PB_OUT, 0, 0, 0, 0); e_expect(bars + 8 * PB_R, 4); }
    }
    __syncwarp();
    asm volatile("barrier.cluster.arrive.relaxed.aligned; barrier.cluster.wait.aligned;" ::: "memory");
    if (draw) {
        int r = (v >> (7 * c)) & 127, role = c * 8 + r;
        if (c == 8 || r >= 8) {
            int n, x, it = 0;
#pragma unroll 1
            do {
                __nanosleep(200);
                v = ldg_u64(&g_pt); n = 0; x = c < 8 ? r - 8 : r;
#pragma unroll 1
                for (int i = 0; i < 63; i += 7) { const int m = v >> i & 127; n += m; if (i < 7 * c) x += max(m - 8, 0); }
            } while (n < gridDim.x / 2 && ++it < SPIN_LIMIT);
            role = -1;
#pragma unroll 1
            for (int i = 0; i < 64; i += 8, v >>= 7) {
                n = v & 127;
                if (x >= 0 && n + x < 8) role = i + n + x;
                x -= max(8 - n, 0);
            }
        }
#pragma unroll
        for (int i = 0; i < 2; i++)
            asm volatile("{.reg .b32 d; mapa.shared::cluster.u32 d, %0, %2; st.async.shared::cluster.mbarrier::complete_tx::bytes.u32 [d+8], %1, [d];}"
                         ::"r"(bars + 8 * PB_R), "r"(role), "r"(i) : "memory");
    }
    __syncwarp();
    mbar_wait_b(bars + 8 * PB_R, 0);
    const int pr = __reduce_max_sync(~0u, (int)lds1(bars + 8 * PB_R + 8));
    if (pr < 0) return;
    const int mb = (pr >> 5) * 8 + (pr & 7), nb = (pr >> 2 & 6) + rank, cta = pr * 2 + rank;
    if (wid >= 8) {
        asm volatile("setmaxnreg.dec.sync.aligned.u32 40;");
        const int w = wid - 8;
        if (w == 0) {
            post_weights(sb, mp, nb, rank);
        } else if (w == 3) {
            asm volatile("griddepcontrol.wait;" ::: "memory");
            TLP(15)
            post_acts(sb, mp, mb, nb, rank);
        } else {
            const int wg = w - 1, rh = 2 * mb + wg;
            float* rowc = (float*)(smraw + P_ROW) + (wg * 64 + lane * 2) * 8;
            int nout = 0, sig = 0;
#pragma unroll 1
            for (int i = 0; i < 13; i++) {
                const int cnt = (0x4333333392180ull >> (4 * i)) & 15;
                if (cnt < C_S1) {
                    const int ng = cnt == C_U ? 1 : 2, c0 = cnt == C_U ? (i - 5) * 512 + nb * 64 : nb * 128;
                    const bool fast = (cnt == C_Y || cnt == C_X1);
#pragma unroll 1
                    for (int j = 0; j < ng; j++) {
                        const uint32_t st = j ? cnt : cnt ? 1 : 4;
                        const uint32_t src = sb + (fast ? st * 16384 + wg * 8192 : P_OUT + wg * 16384 + ((nout + j) & 1) * 8192);
                        bar_sync(4 + 4 * wg + (sig++ & 3), 160);
                        if (lane == 0) {
                            PH_(cnt == PPH - 1, wg, 20)
                            if (fast) asm volatile("mbarrier.complete_tx.relaxed.cta.shared::cta.b64 [%0], 8192;" ::"r"(bars + 8 * (PB_F + st)) : "memory");
                            asm volatile("cp.async.bulk.tensor.2d.global.shared::cta.bulk_group [%0, {%2, %3}], [%1]; cp.async.bulk.commit_group;"
                                         ::"l"(&mp.y + 2 * cnt), "r"(src), "r"(c0 + j * 64), "r"(rh * 64) : "memory");
                        }
                        __syncwarp();
                    }
                    if (lane == 0) {
                        auto to_peer = [&]() {
                            const uint32_t n = cnt ? 1 : 4;
                            mbar_wait(bars + 8 * (PB_E + (cnt ? 4 : 2)), 0);
#pragma unroll
                            for (int i = 0; i < 2; i++)
                                asm volatile("{.reg .b32 d, m; mapa.shared::cluster.u32 d, %0, %3; mapa.shared::cluster.u32 m, %2, %3;\n"
                                             " cp.async.bulk.shared::cluster.shared::cta.mbarrier::complete_tx::bytes [d], [%1], 8192, [m];}"
                                             ::"r"(sb + (cnt + 1 + i) * 16384 + wg * 8192), "r"(sb + (i ? cnt : n) * 16384 + wg * 8192), "r"(bars + 8 * (PB_F + cnt + 1 + i)), "r"(rank ^ 1) : "memory");
                        };
                        if (DS_AT == 1 && fast) to_peer();
                        asm volatile("cp.async.bulk.wait_group 0; fence.proxy.async.global;" ::: "memory");
                        asm volatile("st.release.cta.shared.u32 [%0], %1;" ::"r"(bars + 8 * (PB_OUT + wg)), "r"(nout + ng) : "memory");
                        PH_(cnt == PPH - 1, wg, 21)
                        if (DS_AT == 2 && fast) to_peer();
                        if (i < 12 || !END_FAST) asm volatile(FLAG_ST " [%0], %1;" ::"l"(&g_pflag[cnt * 256 + rh * 8 + nb]), "r"(max(i - 4, 1)) : "memory");
                        PH_(cnt == PPH - 1, wg, 22)
                        if (DS_AT == 3 && fast) to_peer();
                    }
                    nout += ng;
                    __syncwarp();
                    continue;
                }
                bar_sync(4 + 4 * wg + (sig++ & 3), 160);
                uint32_t* c = &g_pcnt[(cnt - C_S1) * 256 + rh * 8];
                if (lane == 0) { signal_count(c); wait_count1(c, 8); }
                __syncwarp();
                const float4* sp = (const float4*)g_st + rh * 32 + lane;
                float4 u[3] = {__ldcg(sp + (cnt == C_S1 ? 0 : 3) * (S_ / 2)), __ldcg(sp + S_ / 2), __ldcg(sp + S_)};
#pragma unroll 1
                for (int h = 0; h < 2; h++) {
                    const float id = 1.0f / DM;
                    const float m = u[0].x * id, var = fmaxf(u[0].y * id - m * m, 0.f) + 1e-5f, r = rsqrtf(var);
                    float sc = r, m2 = 0.f;
                    if (cnt == C_S1) {
                        m2 = r * (u[1].x * id - m * g_cst[0]) + g_cst[3];
                        const float e2 = r * r * (u[2].x * id - 2.0f * m * u[1].y * id + m * m * g_cst[1]) + 2.0f * r * (u[2].y * id - m * g_cst[2]) + g_cst[4];
                        sc = r * rsqrtf(fmaxf(e2 - m2 * m2, 0.f) + 1e-5f);
                    }
                    const GeluK k = gelu_k(sc);
                    *(float4*)(rowc + h * 8) = make_float4(k.k0, k.k1, k.kh, -m);
                    *(float4*)(rowc + h * 8 + 4) = make_float4(var * r, -m2 * var * r, r, -m * r);
#pragma unroll
                    for (int q = 0; q < 3; q++) { u[q].x = u[q].z; u[q].y = u[q].w; }
                }
                bar_arrive(1 + wg, 160);
            }
        }
    } else {
        asm volatile("setmaxnreg.inc.sync.aligned.u32 232;");
        const bf16* xin = pp.x;
        const int wg = wid >> 2, wi = (tid >> 5) & 3, g = lane >> 2, tq = lane & 3;
        const int rh = 2 * mb + wg, row = rh * 64 + wi * 16 + g;
        const bool lead = (tid & 127) == 0;
        PP(0)
        if (tid == 0) TLP(10)
        uint32_t keep[32];
#pragma unroll
        for (int i = 0; i < 8; i++)
            *(uint4*)(keep + 4 * i) = __ldg((const uint4*)(xin + (size_t)(rh * 64 + wi * 16 + (i & 3) * 4 + (lane >> 3)) * DM + nb * 128 + (i >> 2) * 64 + (lane & 7) * 8));
        asm volatile("griddepcontrol.wait;" ::: "memory");
        if (cta < 64) g_modp[cta * 256 + tid] = 0;
        if (cta == 64 && tid < 196) g_tick[tid] = 0;
        const float* src = wg ? g_vec + nb * 128 + tid - 128 : g_mod + 2 * DM + nb * 128 + tid;
        const float* c3 = &g_vec[3 * DM + (tid >> 6) * 512 + nb * 64 + (tid & 63)];
        const float cv[6] = {__ldcg(src), __ldcg(src + (wg ? 1 : 2) * DM), __ldcg(src + (wg ? 2 : 1) * DM), __ldcg(src + 3 * DM), __ldcg(c3), __ldcg(c3 + (tid < 192 ? 2048 : 0))};
        uint32_t vec = sb + P_VEC + tq * 8;
        const uint32_t stw = sb + (wi * 16 + ((lane >> 3) & 1) * 8 + (lane & 7)) * 128 + (((lane >> 4) ^ (lane & 7)) << 4);
        int sig = 0;
        auto signal = [&]() { bar_arrive(4 + 4 * wg + (sig++ & 3), 160); };
        auto put64 = [&](uint32_t o, const float* v) {
#pragma unroll
            for (int jj = 0; jj < 4; jj++, v += 8) stsm4((stw + o) ^ (jj << 5), pack2(v[0], v[1]), pack2(v[2], v[3]), pack2(v[4], v[5]), pack2(v[6], v[7]));
            fence_async_smem();
            signal();
        };
        auto slot = [&](int n) {
            mbar_wait_b(bars + 8 * (PB_E + n % 5), ((n / 5) & 1) ^ 1);
            return (n % 5) * 16384 + wg * 8192;
        };
        const uint32_t rowc = sb + P_ROW + (wg * 64 + wi * 16 + g) * 32, o128 = P_OUT + wg * 16384;
        Pipe pa = {0, 0, 0};
        asm("mapa.shared::cluster.u32 %0, %1, %2;" : "=r"(pa.rel) : "r"(bars + 8 * PB_E), "r"(tid & 1));
        if (tid & 126) pa.rel = 0;
#define KEEP(jn, e) (((e) & 1) ? bfhi(keep[2 * (jn) + ((e) >> 1)]) : bflo(keep[2 * (jn) + ((e) >> 1)]))
        float mu1[2], r1[2];
        {
            float acc[64];
#pragma unroll 1
            for (int kb = 0; kb < 64; kb++) {
                post_kb<0>(sb, acc, pa, wg, lead, kb == 0, []() {});
                if (kb == 0) { PP(1) if (wg == 0) TLP(11) }
                if (kb == 24) bar_sync(3, 256);
                if (kb != 8 + 8 * wg) continue;
                float* sv = (float*)(smraw + P_VEC) + tid;
                const uint32_t xo = sb + o128 + wi * 2048 + (lane >> 3) * 128;
#pragma unroll
                for (int i = 0; i < 8; i++) sts4(xo + (i >> 2) * 8192 + (i & 3) * 512 + (((lane & 7) ^ ((i & 1) * 4 + (lane >> 3))) << 4), keep[4 * i], keep[4 * i + 1], keep[4 * i + 2], keep[4 * i + 3]);
                __syncwarp();
#pragma unroll
                for (int jj = 0; jj < 8; jj++) ldsm4(keep + jj * 4, (stw + o128 + (jj >> 2) * 8192) ^ ((jj & 3) << 5));
                sv[wg * 384] = cv[0]; sv[wg * 384 + 128] = cv[1] + (wg ? 0.0f : 1.0f); sv[wg * 384 + 256] = cv[2];
                if (!wg) sv[384] = cv[3];
                sv[V_C3 * 128] = cv[4]; sv[V_C3 * 128 + 256] = cv[5];
            }
            post_end(sb, pa, lead);
            PP(2)
            asm volatile("" : "+r"(vec) :: "memory");
            float st[2][6];
#pragma unroll
            for (int q = 0; q < 6; q++) st[0][q] = st[1][q] = 0.f;
#pragma unroll
            for (int jn = 0; jn < 16; jn++) {
                const float2 ga = ldsv(vec + V_GA * 512 + jn * 32), a = ldsv(vec + V_A * 512 + jn * 32);
                float xa[4];
#pragma unroll
                for (int e = 0; e < 4; e++) {
                    xa[e] = fmaf((e & 1) ? ga.y : ga.x, acc[4 * jn + e], KEEP(jn, e));
                    st[e >> 1][0] += xa[e]; st[e >> 1][1] = fmaf(xa[e], xa[e], st[e >> 1][1]);
                    acc[4 * jn + e] = ((e & 1) ? a.y : a.x) * xa[e];
                }
                keep[2 * jn] = pack2(xa[0], xa[1]); keep[2 * jn + 1] = pack2(xa[2], xa[3]);
                if ((jn & 7) == 7) put64(slot(64 + (jn >> 3)), acc + 4 * jn - 28);
            }
            PP(3)
#pragma unroll
            for (int jn = 0; jn < 16; jn++) {
                const float2 a = ldsv(vec + V_A * 512 + jn * 32), b = ldsv(vec + V_B * 512 + jn * 32);
#pragma unroll
                for (int e = 0; e < 4; e++) {
                    const float y = acc[4 * jn + e], aa = (e & 1) ? a.y : a.x, bb = (e & 1) ? b.y : b.x;
                    float* s = st[e >> 1];
                    s[2] += y; s[3] = fmaf(aa, y, s[3]); s[4] = fmaf(y, y, s[4]); s[5] = fmaf(bb, y, s[5]);
                }
            }
#pragma unroll
            for (int h = 0; h < 2; h++)
#pragma unroll
                for (int q = 0; q < 6; q++) { st[h][q] += __shfl_xor_sync(~0u, st[h][q], 1); st[h][q] += __shfl_xor_sync(~0u, st[h][q], 2); }
            if (tq < 3 && !(PX & 1)) {
#pragma unroll
                for (int h = 0; h < 2; h++)
                    red2(g_st + (tq * S_ + row + h * 8) * 2, tq == 0 ? st[h][0] : tq == 1 ? st[h][2] : st[h][4], tq == 0 ? st[h][1] : tq == 1 ? st[h][3] : st[h][5]);
            }
            signal();
            PP(29)
        }
        {
            float acc[64];
            post_mma<1>(sb, acc, pa, wg, lead, 2, 4, mb, nb);
            float c1[2], c2[2], c3[2];
            GeluK gk[2];
            bar_sync(1 + wg, 160);
#pragma unroll
            for (int h = 0; h < 2; h++) {
                const float4 a = lds4f(rowc + h * 256), b = lds4f(rowc + h * 256 + 16);
                gk[h] = {a.x, a.y, a.z}; c1[h] = a.w; c2[h] = b.x; c3[h] = b.y; mu1[h] = b.w; r1[h] = b.z;
            }
#pragma unroll
            for (int jn = 0; jn < 16; jn++) {
                const float2 va = ldsv(vec + V_VA * 512 + jn * 32), vb = ldsv(vec + V_VB * 512 + jn * 32), vc = ldsv(vec + V_VC * 512 + jn * 32);
#pragma unroll
                for (int e = 0; e < 4; e++) {
                    const int h = e >> 1;
                    const float t = fmaf(c1[h], (e & 1) ? va.y : va.x, fmaf(c2[h], (e & 1) ? vb.y : vb.x, fmaf(c3[h], (e & 1) ? vc.y : vc.x, acc[4 * jn + e])));
                    acc[4 * jn + e] = gelu_s(t, gk[h]);
                }
                if ((jn & 7) == 7) put64(o128 + (jn >> 3) * 8192, acc + 4 * jn - 28);
            }
            PP(6)
        }
        {
            float acc[64];
            post_mma<2>(sb, acc, pa, wg, lead, 0, 7, mb, nb);
#pragma unroll
            for (int jn = 0; jn < 16; jn++) {
                const float2 a = ldsv(vec + V_A * 512 + jn * 32), b = ldsv(vec + V_B * 512 + jn * 32);
#pragma unroll
                for (int e = 0; e < 4; e++) {
                    const int h = e >> 1;
                    acc[4 * jn + e] += fmaf(fmaf(KEEP(jn, e), r1[h], mu1[h]), (e & 1) ? a.y : a.x, (e & 1) ? b.y : b.x);
                }
                if ((jn & 7) == 7) put64(slot(96 + (jn >> 3)), acc + 4 * jn - 28);
            }
            BLOCK_FENCE
#pragma unroll
            for (int i = 0; i < 64; i += 16) asm volatile("" : F16(acc, i));
            PP(9)
            float st[2][2] = {{0.f, 0.f}, {0.f, 0.f}};
#pragma unroll
            for (int jn = 0; jn < 16; jn++) {
                const float2 gb = ldsv(vec + V_GB * 512 + jn * 32);
                float z[4];
#pragma unroll
                for (int e = 0; e < 4; e++) {
                    const float x1 = acc[4 * jn + e];
                    st[e >> 1][0] += x1; st[e >> 1][1] = fmaf(x1, x1, st[e >> 1][1]);
                    z[e] = fmaf((e & 1) ? gb.y : gb.x, x1, KEEP(jn, e));
                }
                keep[2 * jn] = pack2(z[0], z[1]); keep[2 * jn + 1] = pack2(z[2], z[3]);
            }
#pragma unroll
            for (int h = 0; h < 2; h++)
#pragma unroll
                for (int q = 0; q < 2; q++) { st[h][q] += __shfl_xor_sync(~0u, st[h][q], 1); st[h][q] += __shfl_xor_sync(~0u, st[h][q], 2); }
            if (tq < 2) red2(g_st + (3 * S_ + row + tq * 8) * 2, tq ? st[1][0] : st[0][0], tq ? st[1][1] : st[0][1]);
            signal();
            PP(30)
        }
        {
            float old[96], acc[64];
            post_mma<3>(sb, old, pa, wg, lead, 6, 10, mb, nb);
#pragma unroll
            for (int i = 0; i < 96; i += 16) asm volatile("" : F16(old, i));
            uint32_t v3 = vec + V_C3 * 512;
            bar_sync(1 + wg, 160);
            const float4 rc[2] = {lds4f(rowc), lds4f(rowc + 256)};
            float2 vc[2] = {lds2f(v3), lds2f(v3 + 32)};
            bar_sync(3, 256);
#pragma unroll 1
            for (int blk = 0; blk < 11; blk++) {
                const uint32_t o = stw + o128 + (blk & 1) * 8192;
                const int turn = blk < 7 ? wg : 2;
#pragma unroll
                for (int q = 0; q < 4; q++) {
#pragma unroll 1
                    for (int rep = 0; rep < 2; rep++) {
                        post_kb<1, MIDF>(sb, acc, pa, wg, lead, q == 0 && rep == 0 && blk < 6 && !(blk & 1), [&]() {
                        if (rep != turn) return;
                        asm volatile("" : F4(old, 8 * q), F4(old, 8 * q + 4));
                        const float2 vn[2] = {lds2f(v3 + q * 64 + 64), lds2f(v3 + q * 64 + 96)};
                        float t[8];
#pragma unroll
                        for (int i = 0; i < 8; i++) {
                            const float4& c = rc[(i >> 1) & 1];
                            t[i] = gelu_s(fmaf(c.w, (i & 1) ? vc[i >> 2].y : vc[i >> 2].x, old[8 * q + i]), GeluK{c.x, c.y, c.z});
                            old[8 * q + i] = old[32 + 8 * q + i];
                            old[32 + 8 * q + i] = old[64 + 8 * q + i];
                        }
                        stsm4(o ^ (q << 5), pack2(t[0], t[1]), pack2(t[2], t[3]), pack2(t[4], t[5]), pack2(t[6], t[7]));
                        vc[0] = vn[0]; vc[1] = vn[1];
                        if (q == 2) wait_smem(bars + 8 * (PB_OUT + wg), 6 + blk);
                        if (q == 3) { fence_async_smem(); signal(); }
                        });
                    }
                }
                v3 += 256;
                if (blk != 1 && blk != 3) continue;
                post_end(sb, pa, lead);
                PP(12 + blk)
                asm volatile("" : F16(acc, 0), F4(acc, 16), F4(acc, 20), F4(acc, 24));
                asm volatile("" : F16(acc, 28), F4(acc, 44), F4(acc, 48), F4(acc, 52));
                asm volatile("" : F4(acc, 56), F4(acc, 60));
#pragma unroll
                for (int i = 0; i < 64; i++) old[32 + i] = acc[i];
            }
            post_end(sb, pa, lead);
            PP(17)
#pragma unroll
            for (int jn = 0; jn < 16; jn++) {
                const float2 gb = ldsv(vec + V_GB * 512 + jn * 32);
#pragma unroll
                for (int e = 0; e < 4; e++) acc[4 * jn + e] = fmaf((e & 1) ? gb.y : gb.x, acc[4 * jn + e], KEEP(jn, e));
                if ((jn & 7) == 7) put64(o128 + ((jn >> 3) ^ 1) * 8192, acc + 4 * jn - 28);
            }
            PP(18)
            if (tid == 0) TLP(12)
        }
    }
}

typedef CUresult (*EncFn)(CUtensorMap*, CUtensorMapDataType, cuuint32_t, void*, const cuuint64_t*, const cuuint64_t*, const cuuint32_t*,
                          const cuuint32_t*, CUtensorMapInterleave, CUtensorMapSwizzle, CUtensorMapL2promotion, CUtensorMapFloatOOBfill);

static CUtensorMap make_map(EncFn enc, const void* p, uint64_t inner, uint64_t outer, uint32_t bi = 64) {
    CUtensorMap m;
    cuuint64_t dims[2] = {inner, outer};
    cuuint64_t str[1] = {inner * 2};
    cuuint32_t box[2] = {bi, bi == 64 ? 64u : 16u};
    cuuint32_t es[2] = {1, 1};
    enc(&m, CU_TENSOR_MAP_DATA_TYPE_BFLOAT16, 2, (void*)p, dims, str, box, es, CU_TENSOR_MAP_INTERLEAVE_NONE,
        bi == 64 ? CU_TENSOR_MAP_SWIZZLE_128B : CU_TENSOR_MAP_SWIZZLE_NONE, CU_TENSOR_MAP_L2_PROMOTION_L2_256B, CU_TENSOR_MAP_FLOAT_OOB_FILL_NONE);
    return m;
}
static CUtensorMap make_map_o(EncFn enc, const void* p) {
    CUtensorMap m;
    cuuint64_t dims[2] = {16384, 256};
    cuuint64_t str[1] = {65536};
    cuuint32_t box[2] = {256, 8};
    cuuint32_t es[2] = {1, 1};
    enc(&m, CU_TENSOR_MAP_DATA_TYPE_UINT32, 2, (void*)p, dims, str, box, es, CU_TENSOR_MAP_INTERLEAVE_NONE, CU_TENSOR_MAP_SWIZZLE_NONE,
        CU_TENSOR_MAP_L2_PROMOTION_L2_256B, CU_TENSOR_MAP_FLOAT_OOB_FILL_NONE);
    return m;
}
template <class T> static T* sym(T& s) { void* p = nullptr; cudaGetSymbolAddress(&p, s); return (T*)p; }

static const Delays h_dly = {D_NEAR, D_FAR, D_X2, D_V, D_W2, D_PA, D_WF, D_TV};
extern "C" void kernel_launch(void* const* d_in, const int* in_sizes, int n_in, void* d_out, int out_size) {
    const bf16* x = (const bf16*)d_in[0];
    const bf16* mem0 = (const bf16*)d_in[1];
    const bf16 *Wq = (const bf16*)d_in[2], *Wk = (const bf16*)d_in[3], *Wv = (const bf16*)d_in[4], *Wo = (const bf16*)d_in[5];
    const bf16 *w1 = (const bf16*)d_in[8], *w2 = (const bf16*)d_in[9], *w3 = (const bf16*)d_in[10], *w4 = (const bf16*)d_in[11];
    const bf16 *c = (const bf16*)d_in[12], *wmod = (const bf16*)d_in[13];
    bf16* out = (bf16*)d_out;

    EncFn enc = nullptr;
    cudaDriverEntryPointQueryResult qr;
    cudaGetDriverEntryPoint("cuTensorMapEncodeTiled", (void**)&enc, cudaEnableDefault, &qr);
    CUtensorMap tWq = make_map(enc, Wq, NH * DH, DM), tWk = make_map(enc, Wk, NH * DH, DM), tWv = make_map(enc, Wv, NH * DH, DM);
    PostMaps mp;
    mp.o = make_map_o(enc, sym(g_O)); mp.wo = make_map(enc, Wo, DM, NH * DH);
    mp.y = make_map(enc, sym(g_y), DM, S_); mp.w1 = make_map(enc, w1, DM, DM);
    mp.g = make_map(enc, sym(g_g), DM, S_); mp.w2 = make_map(enc, w2, DM, DM);
    mp.x1 = make_map(enc, sym(g_x1), DM, S_); mp.w3 = make_map(enc, w3, FF, DM);
    mp.u = make_map(enc, sym(g_u), FF, S_); mp.w4 = make_map(enc, w4, DM, FF);
    mp.out = make_map(enc, out, DM, S_);
    cudaFuncSetAttribute(k_rec, cudaFuncAttributeMaxDynamicSharedMemorySize, SM_REC_TOTAL + 2048);
    cudaFuncSetAttribute(k_post, cudaFuncAttributeMaxDynamicSharedMemorySize, P_SMEM);

    uint8_t* arena = (uint8_t*)(((uintptr_t)sym(g_arena) + (2u << 20) - 1) & ~(uintptr_t)((2u << 20) - 1));
    const PostPtrs pp = {x};
    const RecPtrs rp = {x, mem0, c, wmod, w1, w3, arena, 0u, w2, w4, Wo, h_dly};
    const RecMaps rm = {tWq, tWk, tWv, mp.wo, make_map(enc, wmod, 6 * DM, DM, 256), make_map(enc, w3, FF, DM, 256), make_map(enc, w1, DM, DM, 256)};
    k_rec<<<132, 384, SM_REC_TOTAL + 2048>>>(rm, rp);
    cudaLaunchConfig_t cfg = {};
    cfg.gridDim = dim3(132); cfg.blockDim = dim3(384); cfg.dynamicSmemBytes = P_SMEM; cfg.stream = cudaStreamPerThread;
    cudaLaunchAttribute at[1];
    at[0].id = cudaLaunchAttributeProgrammaticStreamSerialization; at[0].val.programmaticStreamSerializationAllowed = PDL;
    cfg.attrs = at; cfg.numAttrs = 1;
    cudaLaunchKernelEx(&cfg, k_post, mp, pp);
}
```

```cpp
#include <cuda_runtime.h>
#include <cuda.h>
#include <cuda_bf16.h>
#include <stdint.h>
#include <limits.h>

typedef __nv_bfloat16 bf16;

constexpr int S_ = 2048, DM = 1024, NH = 32, DH = 128, NSEG = 64, FF = 3584;
constexpr int SPIN_LIMIT = 1 << 22;
#define W_INFL 2
#define XP 0
#define H_PIECES 4
#define PDL 1
#define NPROBE 3

__device__ uint8_t g_arena[10 << 20];
__device__ __align__(128) uint32_t g_tick[64 + 132];
#define g_clk ((uint2*)(g_tick + 64))
__device__ uint32_t g_cls[256];
__device__ unsigned long long g_pt;
__device__ __align__(16) uint32_t g_modp[8 * 2 * DM];
__host__ __device__ constexpr uint32_t blk(uint32_t lb, uint32_t par) {
    return (lb << 13) | ((((lb) ^ (lb >> 3) ^ (lb >> 4) ^ (lb >> 6) ^ par) & 1) << 12);
}
__host__ __device__ constexpr uint32_t lb_x2(uint32_t h) { return (h & 1) | ((h >> 1) << 3); }
__host__ __device__ constexpr uint32_t mem_row(uint32_t kh, uint32_t b, uint32_t r) { return blk(128 | b, kh) + r * 1024; }
__device__ __forceinline__ uint32_t mem_slot(uint32_t s) { return ((s & 1) << 15) | ((s & 2) << 17); }
constexpr uint32_t CNT1 = 0x3d80, CNT_ALL = 0x4000;
constexpr uint32_t LB_PROBE = 6 | 64, LB_TIME = 6;
__host__ __device__ constexpr uint32_t lb_tok(uint32_t h) { return (h & 1) | ((h >> 1) << 3); }
__device__ float g_mod[6 * DM];
__device__ __align__(1024) bf16 g_himg[(S_ + 32) * DM];
__device__ __align__(1024) bf16 g_O[S_ * NH * DH];
__device__ __align__(1024) bf16 g_y[S_ * DM];
__device__ __align__(1024) bf16 g_g[S_ * DM];
__device__ __align__(1024) bf16 g_x1[S_ * DM];
__device__ __align__(16) float g_st[4 * S_ * 2];
__device__ float g_vec[3 * DM + FF];
__device__ float g_cst[8];
__device__ uint32_t g_pcnt[2 * 32 * 8], g_pflag[7 * 32 * 8];
__device__ __align__(1024) bf16 g_u[S_ * FF];

#define TL(i) {}
#define TLX(i) {}
#define TLP(i) TL(i)
#define TLC(i) {}
__device__ __forceinline__ uint32_t smem_u32(const void* p) { return (uint32_t)__cvta_generic_to_shared(p); }
__device__ __forceinline__ void spin_guard(int it) {
    asm volatile("{.reg .pred p; setp.gt.s32 p, %0, %1; @p st.global.u32 [%2], %0;}" ::"r"(it), "n"(SPIN_LIMIT), "l"(1ull));
}
__device__ __forceinline__ void wg_fence() { asm volatile("wgmma.fence.sync.aligned;" ::: "memory"); }
__device__ __forceinline__ void wg_commit() { asm volatile("wgmma.commit_group.sync.aligned;" ::: "memory"); }
template <int N> __device__ __forceinline__ void wg_wait() { asm volatile("wgmma.wait_group.sync.aligned %0;" ::"n"(N) : "memory"); }
__host__ __device__ constexpr uint64_t mkdesc(uint32_t addr, uint32_t lbo, uint32_t sbo, uint32_t swz) {
    return (uint64_t)((addr & 0x3FFFF) >> 4) | ((uint64_t)(lbo >> 4) << 16) | ((uint64_t)(sbo >> 4) << 32) | ((uint64_t)swz << 62);
}
__device__ __forceinline__ uint64_t dadd(uint64_t d, uint32_t o) { return (d & 0xffffffff00000000ull) | (uint32_t)((uint32_t)d + o); }
__device__ __forceinline__ void mbar_init(uint32_t b, uint32_t c) { asm volatile("mbarrier.init.shared.b64 [%0], %1;" ::"r"(b), "r"(c) : "memory"); }
__device__ __forceinline__ void mbar_expect(uint32_t b, uint32_t tx) { asm volatile("mbarrier.arrive.expect_tx.shared.b64 _, [%0], %1;" ::"r"(b), "r"(tx) : "memory"); }
__device__ __forceinline__ void mbar_arrive(uint32_t b) { asm volatile("mbarrier.arrive.shared.b64 _, [%0];" ::"r"(b) : "memory"); }
__device__ __forceinline__ void mbar_arrive_cluster(uint32_t b, uint32_t cta) {
    asm volatile("{.reg .b32 r; mapa.shared::cluster.u32 r, %0, %1; mbarrier.arrive.shared::cluster.b64 _, [r];}" ::"r"(b), "r"(cta) : "memory");
}
__device__ __forceinline__ bool mbar_try(uint32_t b, uint32_t par) {
    uint32_t ok;
    asm volatile("{.reg .pred p; mbarrier.try_wait.parity.shared.b64 p, [%1], %2; selp.u32 %0, 1, 0, p;}" : "=r"(ok) : "r"(b), "r"(par) : "memory");
    return ok;
}
__device__ __forceinline__ void mbar_wait(uint32_t b, uint32_t par) {
    int it = 0;
#pragma unroll 1
    while (!mbar_try(b, par)) { spin_guard(++it); }
}
__device__ __forceinline__ void mbar_wait_w(uint32_t b, uint32_t par) {
    int it = 0;
    bool ok;
#pragma unroll 1
    do { ok = __all_sync(~0u, mbar_try(b, par)); spin_guard(++it); } while (!ok);
}
__device__ __forceinline__ void mbar_wait_cluster(uint32_t b, uint32_t par) {
    int it = 0;
    while (true) {
        uint32_t ok;
        asm volatile("{.reg .pred p; mbarrier.try_wait.parity.acquire.cluster.shared::cta.b64 p, [%1], %2; selp.u32 %0, 1, 0, p;}" : "=r"(ok) : "r"(b), "r"(par) : "memory");
        if (ok) break;
        spin_guard(++it);
    }
}
__device__ __forceinline__ void tma2d(uint32_t dst, const CUtensorMap* m, int c0, int c1, uint32_t bar) {
    asm volatile("cp.async.bulk.tensor.2d.shared::cluster.global.mbarrier::complete_tx::bytes [%0], [%1, {%3, %4}], [%2];" ::"r"(dst), "l"(m), "r"(bar), "r"(c0), "r"(c1) : "memory");
}
constexpr uint64_t EVICT_FIRST = 0x12F0000000000000ull, EVICT_NORMAL = 0x1000000000000000ull;
__device__ __forceinline__ void tma2d_mc(uint32_t dst, const CUtensorMap* m, int c0, int c1, uint32_t bar, uint16_t mask) {
    asm volatile("cp.async.bulk.tensor.2d.shared::cluster.global.mbarrier::complete_tx::bytes.multicast::cluster [%0], [%1, {%3, %4}], [%2], %5;" ::"r"(dst), "l"(m), "r"(bar), "r"(c0), "r"(c1), "h"(mask) : "memory");
}
__device__ __forceinline__ void bulk_g2s(uint32_t dst, const void* src, uint32_t bytes, uint32_t bar) {
    asm volatile("cp.async.bulk.shared::cluster.global.mbarrier::complete_tx::bytes [%0], [%1], %2, [%3];" ::"r"(dst), "l"(src), "r"(bytes), "r"(bar) : "memory");
}
__device__ __forceinline__ void bar_sync(int id, int n) { asm volatile("bar.sync %0, %1;" ::"r"(id), "r"(n) : "memory"); }
__device__ __forceinline__ void bar_arrive(int id, int n) { asm volatile("bar.arrive %0, %1;" ::"r"(id), "r"(n) : "memory"); }
__device__ __forceinline__ void cluster_sync_all() { asm volatile("barrier.cluster.arrive.aligned; barrier.cluster.wait.aligned;" ::: "memory"); }
__device__ __forceinline__ void fence_async_smem() { asm volatile("fence.proxy.async.shared::cta;" ::: "memory"); }
__device__ __forceinline__ void ldsm4t(uint32_t* r, uint32_t a) {
    asm volatile("ldmatrix.sync.aligned.m8n8.x4.trans.shared.b16 {%0,%1,%2,%3}, [%4];" : "=r"(r[0]), "=r"(r[1]), "=r"(r[2]), "=r"(r[3]) : "r"(a) : "memory");
}
__device__ __forceinline__ void ldsm4(uint32_t* r, uint32_t a) {
    asm volatile("ldmatrix.sync.aligned.m8n8.x4.shared.b16 {%0,%1,%2,%3}, [%4];" : "=r"(r[0]), "=r"(r[1]), "=r"(r[2]), "=r"(r[3]) : "r"(a) : "memory");
}
__device__ __forceinline__ uint32_t movm(uint32_t a) {
    uint32_t d; asm volatile("movmatrix.sync.aligned.m8n8.trans.b16 %0, %1;" : "=r"(d) : "r"(a)); return d;
}
__device__ __forceinline__ void mma16816(float* d, uint32_t a0, uint32_t a1, uint32_t a2, uint32_t a3, uint32_t b0, uint32_t b1) {
    asm volatile("mma.sync.aligned.m16n8k16.row.col.f32.bf16.bf16.f32 {%0,%1,%2,%3},{%4,%5,%6,%7},{%8,%9},{%0,%1,%2,%3};"
                 : "+f"(d[0]), "+f"(d[1]), "+f"(d[2]), "+f"(d[3]) : "r"(a0), "r"(a1), "r"(a2), "r"(a3), "r"(b0), "r"(b1));
}
__device__ __forceinline__ void mma16816z(float* d, const uint32_t* a, uint32_t b0, uint32_t b1) {
    asm volatile("mma.sync.aligned.m16n8k16.row.col.f32.bf16.bf16.f32 {%0,%1,%2,%3},{%4,%5,%6,%7},{%8,%9},{%10,%10,%10,%10};"
                 : "=f"(d[0]), "=f"(d[1]), "=f"(d[2]), "=f"(d[3]) : "r"(a[0]), "r"(a[1]), "r"(a[2]), "r"(a[3]), "r"(b0), "r"(b1), "f"(0.f));
}
__device__ __forceinline__ void mma1688(float* d, uint32_t a0, uint32_t a1, uint32_t b0) {
    asm volatile("mma.sync.aligned.m16n8k8.row.col.f32.bf16.bf16.f32 {%0,%1,%2,%3},{%4,%5},{%6},{%0,%1,%2,%3};"
                 : "+f"(d[0]), "+f"(d[1]), "+f"(d[2]), "+f"(d[3]) : "r"(a0), "r"(a1), "r"(b0));
}
__device__ __forceinline__ uint32_t pack2(float lo, float hi) {
    uint32_t r; asm("cvt.rn.bf16x2.f32 %0, %1, %2;" : "=r"(r) : "f"(hi), "f"(lo)); return r;
}
__device__ __forceinline__ uint32_t hadd2(uint32_t a, uint32_t b) {
    uint32_t r; asm("add.rn.bf16x2 %0, %1, %2;" : "=r"(r) : "r"(a), "r"(b)); return r;
}
__device__ __forceinline__ float bflo(uint32_t u) { return __uint_as_float(u << 16); }
__device__ __forceinline__ float bfhi(uint32_t u) { return __uint_as_float(u & 0xffff0000u); }
__device__ __forceinline__ float ex2(float x) { float r; asm("ex2.approx.ftz.f32 %0, %1;" : "=f"(r) : "f"(x)); return r; }
__device__ __forceinline__ uint4 ldg_rlx4(const void* p) {
    uint4 v; asm volatile("ld.relaxed.gpu.global.v4.u32 {%0,%1,%2,%3}, [%4];" : "=r"(v.x), "=r"(v.y), "=r"(v.z), "=r"(v.w) : "l"(p) : "memory"); return v;
}
__device__ __forceinline__ uint2 ldg_rlx2(const void* p) {
    unsigned long long v; asm volatile("ld.relaxed.gpu.global.b64 %0, [%1];" : "=l"(v) : "l"(p) : "memory");
    return make_uint2((uint32_t)v, (uint32_t)(v >> 32));
}
__device__ __forceinline__ uint32_t ldg_rlx1(const void* p) {
    uint32_t v; asm volatile("ld.relaxed.gpu.global.u32 %0, [%1];" : "=r"(v) : "l"(p) : "memory"); return v;
}
__device__ __forceinline__ void stg_rlx1(void* p, uint32_t v) { asm volatile("st.relaxed.gpu.global.u32 [%0], %1;" ::"l"(p), "r"(v) : "memory"); }
__device__ __forceinline__ void stg_rlx2(void* p, uint32_t x, uint32_t y) {
    unsigned long long v = (unsigned long long)x | ((unsigned long long)y << 32);
    asm volatile("st.relaxed.gpu.global.b64 [%0], %1;" ::"l"(p), "l"(v) : "memory");
}
__device__ __forceinline__ void stg_rlx4(void* p, uint32_t x, uint32_t y, uint32_t z, uint32_t w) {
    asm volatile("st.relaxed.gpu.global.v4.u32 [%0], {%1,%2,%3,%4};" ::"l"(p), "r"(x), "r"(y), "r"(z), "r"(w) : "memory");
}
__device__ __forceinline__ void sts4(uint32_t a, uint32_t x, uint32_t y, uint32_t z, uint32_t w) {
    asm volatile("st.shared.v4.u32 [%0], {%1,%2,%3,%4};" ::"r"(a), "r"(x), "r"(y), "r"(z), "r"(w) : "memory");
}
__device__ __forceinline__ uint4 lds4(uint32_t a) {
    uint4 v; asm volatile("ld.shared.v4.u32 {%0,%1,%2,%3}, [%4];" : "=r"(v.x), "=r"(v.y), "=r"(v.z), "=r"(v.w) : "r"(a) : "memory"); return v;
}
__device__ __forceinline__ void st_async4(uint32_t a, float x, float y, float z, float w, uint32_t bar) {
    asm volatile("st.async.shared::cluster.mbarrier::complete_tx::bytes.v4.f32 [%0], {%1,%2,%3,%4}, [%5];" ::"r"(a), "f"(x), "f"(y), "f"(z), "f"(w), "r"(bar) : "memory");
}
#define F4(d, i) "+f"(d[i]), "+f"(d[i + 1]), "+f"(d[i + 2]), "+f"(d[i + 3])
__device__ __forceinline__ void wgmma_rs32(float* d, const uint32_t* a, uint64_t b, int sc) {
    asm volatile("{.reg .pred p; setp.ne.b32 p, %21, 0;\n wgmma.mma_async.sync.aligned.m64n32k16.f32.bf16.bf16 {%0,%1,%2,%3,%4,%5,%6,%7,%8,%9,%10,%11,%12,%13,%14,%15}, {%16,%17,%18,%19}, %20, p, 1, 1, 0;}"
                 : F4(d, 0), F4(d, 4), F4(d, 8), F4(d, 12) : "r"(a[0]), "r"(a[1]), "r"(a[2]), "r"(a[3]), "l"(b), "r"(sc));
}
__device__ __forceinline__ void wgmma_ss32(float* d, uint64_t a, uint64_t b, int sc) {
    asm volatile("{.reg .pred p; setp.ne.b32 p, %18, 0;\n wgmma.mma_async.sync.aligned.m64n32k16.f32.bf16.bf16 {%0,%1,%2,%3,%4,%5,%6,%7,%8,%9,%10,%11,%12,%13,%14,%15}, %16, %17, p, 1, 1, 1, 0;}"
                 : F4(d, 0), F4(d, 4), F4(d, 8), F4(d, 12) : "l"(a), "l"(b), "r"(sc));
}
__device__ __forceinline__ void wgmma_rs40(float* d, const uint32_t* a, uint64_t b, int sc) {
    asm volatile("{.reg .pred p; setp.ne.b32 p, %25, 0;\n wgmma.mma_async.sync.aligned.m64n40k16.f32.bf16.bf16 {%0,%1,%2,%3,%4,%5,%6,%7,%8,%9,%10,%11,%12,%13,%14,%15,%16,%17,%18,%19}, {%20,%21,%22,%23}, %24, p, 1, 1, 0;}"
                 : F4(d, 0), F4(d, 4), F4(d, 8), F4(d, 12), F4(d, 16) : "r"(a[0]), "r"(a[1]), "r"(a[2]), "r"(a[3]), "l"(b), "r"(sc));
}
__device__ __forceinline__ void wgmma_ss40(float* d, uint64_t a, uint64_t b, int sc) {
    asm volatile("{.reg .pred p; setp.ne.b32 p, %22, 0;\n wgmma.mma_async.sync.aligned.m64n40k16.f32.bf16.bf16 {%0,%1,%2,%3,%4,%5,%6,%7,%8,%9,%10,%11,%12,%13,%14,%15,%16,%17,%18,%19}, %20, %21, p, 1, 1, 1, 0;}"
                 : F4(d, 0), F4(d, 4), F4(d, 8), F4(d, 12), F4(d, 16) : "l"(a), "l"(b), "r"(sc));
}
#define F16(d, i) F4(d, i), F4(d, i + 4), F4(d, i + 8), F4(d, i + 12)
template <int TA>
__device__ __forceinline__ void wgmma_ss128(float* d, uint64_t a, uint64_t b, int sc) {
    asm volatile("{.reg .pred p; setp.ne.b32 p, %66, 0;\n wgmma.mma_async.sync.aligned.m64n128k16.f32.bf16.bf16 "
                 "{%0,%1,%2,%3,%4,%5,%6,%7,%8,%9,%10,%11,%12,%13,%14,%15,%16,%17,%18,%19,%20,%21,%22,%23,%24,%25,%26,%27,%28,%29,%30,%31,"
                 "%32,%33,%34,%35,%36,%37,%38,%39,%40,%41,%42,%43,%44,%45,%46,%47,%48,%49,%50,%51,%52,%53,%54,%55,%56,%57,%58,%59,%60,%61,%62,%63}, %64, %65, p, 1, 1, %67, 1;}"
                 : F16(d, 0), F16(d, 16), F16(d, 32), F16(d, 48) : "l"(a), "l"(b), "r"(sc), "n"(TA));
}

__device__ __forceinline__ float warp_sum(float v) {
#pragma unroll
    for (int o = 16; o; o >>= 1) v += __shfl_xor_sync(~0u, v, o);
    return v;
}
__device__ __forceinline__ float bfround(float x) { return __bfloat162float(__float2bfloat16(x)); }

__device__ __forceinline__ void wait_count1(const uint32_t* p, uint32_t target) {
    int it = 0;
#pragma unroll 1
    while (true) {
        uint32_t v;
        asm volatile("ld.acquire.gpu.global.u32 %0, [%1];" : "=r"(v) : "l"(p) : "memory");
        if (v >= target) break;
        spin_guard(++it);
    }
}
__device__ __forceinline__ void red2(float* p, float a, float b) {
    asm volatile("red.relaxed.gpu.global.add.v2.f32 [%0], {%1, %2};" ::"l"(p), "f"(a), "f"(b) : "memory");
}
__device__ __forceinline__ void l2_prefetch(const void* p, uint32_t bytes) {
    asm volatile("cp.async.bulk.prefetch.L2.global [%0], %1;" ::"l"(p), "r"(bytes) : "memory");
}
__device__ __forceinline__ void signal_count(uint32_t* p) { asm volatile("red.release.gpu.global.add.u32 [%0], 1;" ::"l"(p) : "memory"); }
__device__ __forceinline__ void e_expect(uint32_t b, uint32_t tx) {
    asm volatile("{.reg .pred p; elect.sync _|p, 0xffffffff; @p mbarrier.arrive.expect_tx.shared.b64 _, [%0], %1;}" ::"r"(b), "r"(tx) : "memory");
}
__device__ __forceinline__ void e_tma2d(uint32_t dst, const CUtensorMap* m, int c0, int c1, uint32_t bar) {
    asm volatile("{.reg .pred p; elect.sync _|p, 0xffffffff;\n @p cp.async.bulk.tensor.2d.shared::cluster.global.mbarrier::complete_tx::bytes [%0], [%1, {%3, %4}], [%2];}"
                 ::"r"(dst), "l"(m), "r"(bar), "r"(c0), "r"(c1) : "memory");
}
__device__ __forceinline__ void e_tma2d_hint(uint32_t dst, const CUtensorMap* m, int c0, int c1, uint32_t bar, uint64_t pol) {
    asm volatile("{.reg .pred p; elect.sync _|p, 0xffffffff;\n @p cp.async.bulk.tensor.2d.shared::cluster.global.mbarrier::complete_tx::bytes.L2::cache_hint [%0], [%1, {%3, %4}], [%2], %5;}"
                 ::"r"(dst), "l"(m), "r"(bar), "r"(c0), "r"(c1), "l"(pol) : "memory");
}
__device__ __forceinline__ void e_tma2d_mc(uint32_t dst, const CUtensorMap* m, int c0, int c1, uint32_t bar) {
    asm volatile("{.reg .pred p; elect.sync _|p, 0xffffffff;\n @p cp.async.bulk.tensor.2d.shared::cluster.global.mbarrier::complete_tx::bytes.multicast::cluster [%0], [%1, {%3, %4}], [%2], %5;}"
                 ::"r"(dst), "l"(m), "r"(bar), "r"(c0), "r"(c1), "h"((uint16_t)3) : "memory");
}
__device__ __forceinline__ void e_prefetch(const void* p, uint32_t bytes) {
    asm volatile("{.reg .pred p; elect.sync _|p, 0xffffffff; @p cp.async.bulk.prefetch.L2.global [%0], %1;}" ::"l"(p), "r"(bytes) : "memory");
}
__device__ __forceinline__ void wait_count_w(const uint32_t* p, uint32_t target) {
    int it = 0;
#pragma unroll 1
    while (true) {
        uint32_t v;
        asm volatile("ld.acquire.gpu.global.u32 %0, [%1];" : "=r"(v) : "l"(p) : "memory");
        if (__all_sync(~0u, v >= target) | (++it > SPIN_LIMIT)) break;
        __nanosleep(100);
    }
}

#define NL 6
constexpr uint32_t SM_HB = 16384, HBK = 5120, SM_SX = 57344, SM_OX = 122880, SM_PX = 124928, SM_PA = 126976, SM_WO = 147456,
                   SM_TAB = 212992, SM_PRE = SM_TAB + 5120, SM_BAR = 227328, SM_REC_TOTAL = 227328 + 256;
constexpr uint32_t SB0 = 1024;
constexpr int B_WO = 0, B_HE = 1, B_ROLE = 2, B_HB = 3, B_W = 5;
constexpr int NB_MEM = 1, NB_QK = 2, NB_X1 = 3, NB_X2 = 4, NB_WIN = 5, NB_WG = 6, NB_KDONE = 7, NB_FIN0 = 8, NB_P = 9, NB_PX = 10, NB_G = 11, NB_A = 12, NB_B = 13, NB_C = 14, NB_S = 15;
#define D_TPV 100
#define V_POS 2
#define D_X2 400
#define D_TV 40
#define D_V 280
#define D_NEAR 1620
#define D_FAR (D_NEAR - 90)
#define E_MUL 28
#define D_WF 60
#define NE 0
#define D_H 0
#define D_W2 40
#define SETTLE 0
#define TV_POS 0
#define D_PA 40
#define NE1 10
#define H_POS 3
#define PA_POS 1
#define K_DLY 0
#define ST_BAR 0
#define W1_LATE 1
#define ROT 2
#define ALIGN 0
#define CNT32 1
#define O_POS 1
#define Z_POS 0
#define QF_LATE 100
#define W0_E 3
#define H_ROT 1
#define WO_LATE 1
#define QK_AT 15
#define QK_F 0
#define MAX_MMA 1
#define STS_LATE 1
#define W0_F 0
#define TAIL_F 0
#define G_AT 18
#define W0_AT 4
#define W0_RS (NL - 1)
#define P_GATE 1
#define NPF (NL + 6)

struct Delays { uint32_t near, far, x2, v, w2, pa, wf, tv; };
#define MISS(i, v)
#define MISS_INIT
#define MISS_OUT
#define HT(i)
#define PROF_INIT
#define PROF(i)
#define PROFV(i, v)
#define PROF_OUT

__device__ __forceinline__ uint32_t clk32() { uint32_t t; asm volatile("mov.u32 %0, %%clock;" : "=r"(t) :: "memory"); return t; }
__device__ __forceinline__ uint32_t smid() { uint32_t t; asm volatile("mov.u32 %0, %%smid;" : "=r"(t)); return t; }
__device__ __forceinline__ uint32_t gtime() { uint32_t t; asm volatile("mov.u32 %0, %%globaltimer_lo;" : "=r"(t) :: "memory"); return t; }
__device__ __forceinline__ void spin_until(uint32_t t0, uint32_t d) { while (clk32() - t0 < d) {} }
template <int N> __device__ __forceinline__ uint32_t delay(uint32_t zero) {
    float x = __uint_as_float(clk32());
#pragma unroll
    for (int i = 0; i < N; i++) asm volatile("ex2.approx.ftz.f32 %0, %0;" : "+f"(x));
    return __float_as_uint(x) & zero;
}
__device__ __forceinline__ uint32_t opaque(uint32_t v) { return __shfl_sync(~0u, v, threadIdx.x & 31); }
__device__ __forceinline__ uint32_t xor_or(uint32_t a, uint32_t b, uint32_t t) {
    uint32_t r; asm volatile("lop3.b32 %0, %1, %2, %3, 0x7E;" : "=r"(r) : "r"(a), "r"(b), "r"(t)); return r;
}
__device__ __forceinline__ uint32_t or3(uint32_t a, uint32_t b, uint32_t c) {
    uint32_t r; asm volatile("lop3.b32 %0, %1, %2, %3, 0xFE;" : "=r"(r) : "r"(a), "r"(b), "r"(c)); return r;
}
__device__ __forceinline__ uint32_t settag(uint32_t v, uint32_t tag) {
    uint32_t r; asm("lop3.b32 %0, %1, 1, %2, 0xB8;" : "=r"(r) : "r"(v), "r"(tag)); return r;
}
__device__ __forceinline__ void ldg4_if(uint4& v, const void* p, bool c) {
    asm volatile("{.reg .pred p; setp.ne.u32 p, %5, 0; @p ld.relaxed.gpu.global.v4.u32 {%0,%1,%2,%3}, [%4];}"
                 : "+r"(v.x), "+r"(v.y), "+r"(v.z), "+r"(v.w) : "l"(p), "r"((uint32_t)c) : "memory");
}
__device__ __forceinline__ uint4 ldg_rlx2x2(const void* p) {
    unsigned long long a, b;
    asm volatile("ld.relaxed.gpu.global.v2.b64 {%0,%1}, [%2];" : "=l"(a), "=l"(b) : "l"(p) : "memory");
    return make_uint4((uint32_t)a, (uint32_t)(a >> 32), (uint32_t)b, (uint32_t)(b >> 32));
}
__device__ __forceinline__ void stg_rlx2x2(void* p, uint32_t x, uint32_t y, uint32_t z, uint32_t w) {
    asm volatile("{.reg .b64 a, b; mov.b64 a, {%1,%2}; mov.b64 b, {%3,%4}; st.relaxed.gpu.global.v2.b64 [%0], {a, b};}" ::"l"(p), "r"(x), "r"(y), "r"(z), "r"(w) : "memory");
}
__device__ __forceinline__ void ldg1_if(uint32_t& v, const void* p, bool c) {
    asm volatile("{.reg .pred p; setp.ne.u32 p, %2, 0; @p ld.relaxed.gpu.global.u32 %0, [%1];}" : "+r"(v) : "l"(p), "r"((uint32_t)c) : "memory");
}
__device__ __forceinline__ void sts2(uint32_t a, float x, float y) { asm volatile("st.shared.v2.f32 [%0], {%1,%2};" ::"r"(a), "f"(x), "f"(y) : "memory"); }
__device__ __forceinline__ void sts4f(uint32_t a, float x, float y, float z, float w) {
    asm volatile("st.shared.v4.f32 [%0], {%1,%2,%3,%4};" ::"r"(a), "f"(x), "f"(y), "f"(z), "f"(w) : "memory");
}
__device__ __forceinline__ void sts1(uint32_t a, uint32_t x) { asm volatile("st.shared.u32 [%0], %1;" ::"r"(a), "r"(x) : "memory"); }
__device__ __forceinline__ uint32_t lds1(uint32_t a) { uint32_t v; asm volatile("ld.shared.u32 %0, [%1];" : "=r"(v) : "r"(a) : "memory"); return v; }
__device__ __forceinline__ float4 lds4f(uint32_t a) {
    float4 v; asm volatile("ld.shared.v4.f32 {%0,%1,%2,%3}, [%4];" : "=f"(v.x), "=f"(v.y), "=f"(v.z), "=f"(v.w) : "r"(a) : "memory"); return v;
}
__device__ __forceinline__ float2 lds2f(uint32_t a) {
    float2 v; asm volatile("ld.shared.v2.f32 {%0,%1}, [%2];" : "=f"(v.x), "=f"(v.y) : "r"(a) : "memory"); return v;
}
__device__ __forceinline__ bool any_bit0(uint32_t x) {
    uint32_t r;
    asm volatile("{.reg .pred p, q; .reg .b32 t; and.b32 t, %1, 1; setp.ne.u32 p, t, 0; vote.sync.any.pred q, p, 0xffffffff; selp.u32 %0, 1, 0, q;}" : "=r"(r) : "r"(x));
    return r;
}
__device__ __forceinline__ float rcp_fast(float x) { float r; asm("rcp.approx.ftz.f32 %0, %1;" : "=f"(r) : "f"(x)); return r; }
__device__ __forceinline__ void stsm4(uint32_t a, uint32_t r0, uint32_t r1, uint32_t r2, uint32_t r3) {
    asm volatile("stmatrix.sync.aligned.m8n8.x4.shared.b16 [%0], {%1,%2,%3,%4};" ::"r"(a), "r"(r0), "r"(r1), "r"(r2), "r"(r3) : "memory");
}
__device__ __forceinline__ void stsm4t(uint32_t a, uint32_t r0, uint32_t r1, uint32_t r2, uint32_t r3) {
    asm volatile("stmatrix.sync.aligned.m8n8.x4.trans.shared.b16 [%0], {%1,%2,%3,%4};" ::"r"(a), "r"(r0), "r"(r1), "r"(r2), "r"(r3) : "memory");
}
__device__ __forceinline__ uint32_t and3(uint32_t a, uint32_t b, uint32_t c) {
    uint32_t r; asm("lop3.b32 %0, %1, %2, %3, 0x80;" : "=r"(r) : "r"(a), "r"(b), "r"(c)); return r;
}
__device__ __forceinline__ void red_mem(void* p, uint32_t x, uint32_t y, uint32_t z, uint32_t w, void* q, uint32_t e, bool c) {
    asm volatile("{.reg .pred p; setp.ne.u32 p, %7, 0; red.relaxed.gpu.global.add.noftz.v4.bf16x2 [%0], {%1,%2,%3,%4}; @p red.relaxed.gpu.global.add.noftz.bf16x2 [%5], %6;}"
                 ::"l"(p), "r"(x), "r"(y), "r"(z), "r"(w), "l"(q), "r"(e), "r"((uint32_t)c) : "memory");
}
__device__ __forceinline__ void stg4_if(bool c, void* p, uint32_t x) {
    asm volatile("{.reg .pred p; setp.ne.u32 p, %2, 0; @p st.relaxed.gpu.global.v4.u32 [%0], {%1,%1,%1,%1};}" ::"l"(p), "r"(x), "r"((uint32_t)c) : "memory");
}
__device__ __forceinline__ uint32_t max3u(uint32_t a, uint32_t b, uint32_t c) { return __vimax3_u32(a, b, c); }
__device__ __forceinline__ void fence_gpu() { asm volatile("fence.acq_rel.gpu;" ::: "memory"); }

__device__ __forceinline__ void h_load(uint32_t sb, const uint8_t* hsrc, int pass, uint32_t rank, uint32_t rot) {
    const uint8_t* src = hsrc + (size_t)pass * 65536;
    const uint32_t bar = sb + SM_BAR + 8 * (B_HB + (pass & 1)), dst = sb + SM_HB + (pass & 1) * 65536 + rank * 4 * HBK;
    e_expect(bar, 32768);
#pragma unroll 1
    for (int i = 0; i < H_PIECES; i++) {
        const uint32_t o = ((i + rot) & (H_PIECES - 1)) * (16384 / H_PIECES);
        asm volatile("{.reg .pred p; elect.sync _|p, 0xffffffff;\n"
                     " @p cp.async.bulk.shared::cluster.global.mbarrier::complete_tx::bytes.multicast::cluster [%0], [%1], %4, [%2], %3;}"
                     ::"r"(dst + o + (o >> 12) * 1024), "l"(src + o), "r"(bar), "h"((uint16_t)3), "n"(16384 / H_PIECES) : "memory");
    }
}
__device__ __forceinline__ void h_piece(uint32_t sb, const uint8_t* hsrc, int pass, uint32_t rank, uint32_t i, bool first) {
    const uint32_t bar = sb + SM_BAR + 8 * (B_HB + (pass & 1));
    asm volatile("{.reg .pred p, q; elect.sync _|p, 0xffffffff; setp.le.and.s32 p, %5, 64, p; setp.ne.and.u32 q, %4, 0, p;\n"
                 " @q mbarrier.arrive.expect_tx.shared.b64 _, [%2], 32768;\n"
                 " @p cp.async.bulk.shared::cluster.global.mbarrier::complete_tx::bytes.multicast::cluster [%0], [%1], 4096, [%2], %3;}"
                 ::"r"(sb + SM_HB + (pass & 1) * 65536 + (rank * 4 + i) * HBK), "l"(hsrc + (uint32_t)(pass * 65536 + i * 4096)), "r"(bar), "h"((uint16_t)3), "r"((uint32_t)first), "r"(pass) : "memory");
}
__device__ __forceinline__ uint4 ldg_b128(const void* p) {
    uint4 v;
    asm volatile("{.reg .b128 t; .reg .b64 a, b; ld.relaxed.gpu.global.b128 t, [%4]; mov.b128 {a, b}, t; mov.b64 {%0,%1}, a; mov.b64 {%2,%3}, b;}"
                 : "=r"(v.x), "=r"(v.y), "=r"(v.z), "=r"(v.w) : "l"(p) : "memory");
    return v;
}
__device__ __forceinline__ void ldg_b128_into(uint4& v, const void* p) {
    asm volatile("{.reg .b128 t; .reg .b64 a, b; ld.relaxed.gpu.global.b128 t, [%4]; mov.b128 {a, b}, t; mov.b64 {%0,%1}, a; mov.b64 {%2,%3}, b;}"
                 : "+r"(v.x), "+r"(v.y), "+r"(v.z), "+r"(v.w) : "l"(p) : "memory");
}
__device__ __forceinline__ void stg_b128_if(bool c, void* p, uint32_t x, uint32_t y, uint32_t z, uint32_t w) {
    asm volatile("{.reg .pred p; setp.ne.u32 p, %5, 0; @p st.relaxed.gpu.global.v4.u32 [%0], {%1,%2,%3,%4};}"
                 ::"l"(p), "r"(x), "r"(y), "r"(z), "r"(w), "r"((uint32_t)c) : "memory");
}
__device__ __forceinline__ float pretag(float x, uint32_t add, uint32_t keep) { return __uint_as_float((__float_as_uint(x) + add) & keep); }

template <class F, class G>
__device__ __forceinline__ void softmax_rows(uint32_t src, uint32_t dst, uint32_t g16, int row0, F ready, G mid) {
    const uint32_t u = (g16 >> 7) & 3, e = ((g16 >> 9) << 3) | ((g16 >> 4) & 7);
    uint32_t se = src + e * 8, su = se + u * 1088, d0 = dst + e * 16 + u * 4, d1 = dst + 512 + e * 4;
    int vis = row0 + (e >> 2) - 2 * (e & 3) - 8 * u;
    asm volatile("" : "+r"(se), "+r"(su), "+r"(d0), "+r"(d1), "+r"(vis));
    ready();
    const float2 p0 = lds2f(su), p1 = lds2f(su + 256), p2 = lds2f(su + 512), p3 = lds2f(su + 768);
    const float2 m0 = lds2f(se + 4352), m1 = lds2f(se + 4352 + 256), m2 = lds2f(se + 4352 + 512), m3 = lds2f(se + 4352 + 768);
    float a0 = (p0.x + p1.x) + (p2.x + p3.x), a1 = (p0.y + p1.y) + (p2.y + p3.y);
    const float a2 = (m0.x + m1.x) + (m2.x + m3.x), a3 = (m0.y + m1.y) + (m2.y + m3.y);
    if (vis < 0) a0 = -1e9f / 0.08838834764831845f;
    if (vis < 1) a1 = -1e9f / 0.08838834764831845f;
    int k = __float_as_int(fmaxf(fmaxf(a0, a1), fmaxf(a2, a3)));
    k ^= (k >> 31) & 0x7fffffff;
    const bool hi = g16 & 64;
    const int k0 = __reduce_max_sync(~0u, hi ? INT_MIN : k), k1 = __reduce_max_sync(~0u, hi ? k : INT_MIN);
    mid();
    k = hi ? k1 : k0;
    const float m = __int_as_float(k ^ ((k >> 31) & 0x7fffffff));
    const float sl2 = 0.08838834764831845f * 1.4426950408889634f, mb = -m * sl2;
    sts1(d0, pack2(ex2(fmaf(a0, sl2, mb)), ex2(fmaf(a1, sl2, mb))));
    sts1(d1, pack2(ex2(fmaf(a2, sl2, mb)), ex2(fmaf(a3, sl2, mb))));
}

__device__ __forceinline__ uint32_t pack_h2(float lo, float hi) {
    uint32_t r; asm("cvt.rn.satfinite.f16x2.f32 %0, %1, %2;" : "=r"(r) : "f"(hi), "f"(lo)); return r;
}
__device__ __forceinline__ float2 unpack_h2(uint32_t u) {
    float2 r; asm("{.reg .b16 l, h; mov.b32 {l, h}, %2; cvt.f32.f16 %0, l; cvt.f32.f16 %1, h;}" : "=f"(r.x), "=f"(r.y) : "r"(u)); return r;
}
__device__ __forceinline__ uint32_t add_h2(uint32_t a, uint32_t b) { uint32_t r; asm("add.rn.f16x2 %0, %1, %2;" : "=r"(r) : "r"(a), "r"(b)); return r; }
__device__ __forceinline__ uint32_t max_h2(uint32_t a, uint32_t b) { uint32_t r; asm("max.f16x2 %0, %1, %2;" : "=r"(r) : "r"(a), "r"(b)); return r; }
__device__ __forceinline__ void stg2_if(bool c, void* p, uint32_t x, uint32_t y) {
    asm volatile("{.reg .pred p; .reg .b64 v; setp.ne.u32 p, %3, 0; mov.b64 v, {%1, %2}; @p st.relaxed.gpu.global.b64 [%0], v;}" ::"l"(p), "r"(x), "r"(y), "r"((uint32_t)c) : "memory");
}
__device__ __forceinline__ void stg1_if(bool c, void* p, uint32_t x) {
    asm volatile("{.reg .pred p; setp.ne.u32 p, %2, 0; @p st.relaxed.gpu.global.u32 [%0], %1;}" ::"l"(p), "r"(x), "r"((uint32_t)c) : "memory");
}
struct U2 { uint32_t x, y; };
__device__ __forceinline__ U2 ldg_u2(const void* p) {
    U2 v; asm volatile("{.reg .b64 t; ld.relaxed.gpu.global.b64 t, [%2]; mov.b64 {%0, %1}, t;}" : "=r"(v.x), "=r"(v.y) : "l"(p) : "memory"); return v;
}
constexpr int POLL_LIMIT = 1 << 16;
constexpr float SM_L2E = 0.08838834764831845f * 1.4426950408889634f;
template <int V> struct IC { static constexpr int value = V; };
typedef unsigned long long u64;
__device__ __forceinline__ uint32_t lo32(u64 v) { return (uint32_t)v; }
__device__ __forceinline__ uint32_t hi32(u64 v) { return (uint32_t)(v >> 32); }
__device__ __forceinline__ u64 ldg_u64(const void* p) { u64 v; asm volatile("ld.relaxed.gpu.global.b64 %0, [%1];" : "=l"(v) : "l"(p) : "memory"); return v; }
__device__ __forceinline__ void ldg_u64_if(u64& v, const void* p, bool c) {
    asm volatile("{.reg .pred p; setp.ne.u32 p, %2, 0; @p ld.relaxed.gpu.global.b64 %0, [%1];}" : "+l"(v) : "l"(p), "r"((uint32_t)c) : "memory");
}
__device__ __forceinline__ void rec_main(uint32_t sb, const CUtensorMap* tWo, uint8_t* arena, int role, int hinfo, int wg, uint32_t zero, const Delays& dly) {
    const int hA = hinfo & 255;
    const int tid = threadIdx.x, t = tid & 127, lane = tid & 31, wi = t >> 5;
    const uint32_t bars = sb + SM_BAR;
    const int head = role >> 2, qd = role & 3, j = blockIdx.x & 1, kh = role & 1;
    const uint32_t mypar = head >= hA;
    const uint32_t wu = __reduce_max_sync(~0u, wi);
    const bool warp0 = wu == 0, warp1 = wu == 1;
    const uint8_t* hsrc = (const uint8_t*)g_himg + kh * 32768 + j * 16384;
    auto tokbase = [&](int ty) { return ((ty + 1) << 21) + blk(lb_tok(head), mypar ^ ((hinfo >> (8 + ty)) & 1)); };
    const uint32_t tbw = tokbase(wg), tbq = tokbase(0) + (qd >> 1) * 2048 + (qd & 1) * 8;
    uint32_t w[32 - NL][4];
    const uint32_t frow = ((lane >> 4) * 8 + (lane & 7)) * 128, fx = ((lane >> 3) & 1) ^ (lane & 7);
    const uint32_t wl0 = sb + wg * 65536 + frow + ((fx ^ (2 * wi)) << 4);
    {
        if (wg > 0) wait_count_w(&g_tick[32 + (lane & 3) * 8], 1);
        if (wg == 1) asm volatile("fence.proxy.async.global;" ::: "memory");
#pragma unroll 1
        for (int i = 0; i < 4; i++) mbar_wait_w(bars + 8 * (B_W + (wg == 2 ? 8 + i : 2 * i + wg)), 0);
#pragma unroll
        for (int p = NL; p < 32; p++) ldsm4t(w[p - NL], wl0 + p * 2048);
        fence_async_smem();
        bar_sync(wg < 2 ? NB_WG : NB_X2, wg < 2 ? 256 : 128);
        if (wg == 2 && wu < 3) {
            e_expect(bars + 8 * B_WO, 16384);
            e_tma2d(sb + SM_WO + wu * 16384, tWo, (wu >> 1) * 512 + qd * 128 + (wu & 1) * 64, head * DH, bars + 8 * B_WO);
            e_tma2d(sb + SM_WO + wu * 16384 + 8192, tWo, (wu >> 1) * 512 + qd * 128 + (wu & 1) * 64, head * DH + 64, bars + 8 * B_WO);
        }
        if (wg == 1 && warp0) {
            if (lane == 0) mbar_arrive_cluster(bars + 8 * B_HE, j ^ 1);
            mbar_wait_w(bars + 8 * B_HE, 0);
#pragma unroll 1
            for (int i = 0; i < 2; i++) h_load(sb, hsrc, i, j, head);
        }
        TL(3 + wg)
    }
    uint32_t g16 = opaque(t * 16);
    auto G16 = [&]() { asm volatile("" : "+r"(g16)); return g16; };
    const uint32_t sbl = sb - wu * 512;
    const uint32_t xso = blk(lb_x2(head), mypar), cu = kh * 2048 + (2 * j + (wu >> 1)) * 512;
    const uint32_t u_xo = xso + wg * 16384 + (wu & 1) * 2048 + (cu >> 1) - wu * 256, u_to = tbw + (wu & 1) * 16384 + cu - wu * 512;
    const uint32_t mrow = wg < 2 ? mem_row(wu >> 1, wg * 2 + (wu & 1), qd) : mem_row(kh, wu, 0);
    const uint32_t u_m = mrow - wu * 512, u_e = mrow + 512 - wu * (CNT32 ? 64 : 128);
#define TAB(i) lds1(sb + SM_TAB + (i) * 512 + (G16() >> 2))
    {
        const uint32_t r8 = lane & 7;
        const uint32_t tb = sb + SM_TAB + wg * 1536 + t * 4, ma = sb + SM_HB + 4096 + r8 * 128;
        if (wg < 2) {
            sts1(tb, sb + SM_WO + wi * 16384 + frow + ((fx ^ (2 * wg)) << 4));
            sts1(tb + 512, wl0);
            sts1(tb + 1024, ma + (((lane >> 3) ^ r8) << 4));
        } else {
            sts1(tb, ma + (wi & 1) * HBK + ((((wi & 2) + (lane >> 4) * 4 + ((lane >> 3) & 1)) ^ r8) << 4));
            sts1(tb + 512, ((((wi & 2) + 5) ^ r8) << 4) + ((CNT32 ? (lane & 3) == 3 : lane & 1) ? ma + ((wi & 1) + (lane >> 3) * 2) * HBK : sb + SM_HB - 128));
            sts1(tb + 1024, mem_row(role >> 6, (role >> 4) & 3, (role >> 2) & 3) + (lane < 8 ? qd * 128 + lane * 16 : 512 + qd * 32 + (lane & 1) * 16));
        }
    }
    PROF_INIT
    MISS_INIT
#define HB(ks) dadd(mkdesc(SB0 + SM_HB + ((ks) >> 2) * HBK + ((ks) & 3) * 32, 16, 1024, 1), hbo)
#define STEP_CONSTS                                                                                  \
    const uint32_t tag = (s & 1) ^ 1, ttag = ((s >> 1) & 1) ^ 1, tso = (s & 1) * 32768;              \
    G16();                            \
    const int p = s + 2, b = p & 1;                                                                  \
    uint32_t hbo = b * 4096, fz[6] = {0, 0, 0, 0, 0, 0};                                                \
    const uint32_t ftag = (((p - 1) >> 1) & 1) ^ 1, ptag = ((p >> 1) & 1) ^ 1;                       \
    const uint32_t pso = tbw + (1 << 20) + (b ^ 1) * 32768 + j * 16384 + kh * 2048;
#define SCHED_FENCE(i) fz[i] = clk32();
#define FZ ((fz[0] | fz[1] | fz[2] | fz[3] | fz[4] | fz[5]) & zero)
#define BLOCK_FENCE asm volatile("pmevent 0;" ::: "memory");
    constexpr int GAP = 32 / NL;
#define l16 (sbl + g16)
#define g8 (g16 >> 1)
    uint4 u, v;
    uint8_t *pdst, *fdst;
    auto tok_pack = [&](int ty, const float* acc, uint32_t ftag, uint32_t ptag, uint32_t* later = nullptr) {
        const bool tg = ty == 2 || !(g16 & 64);
        const uint32_t add = tg ? (ftag ^ 1) << 16 : 0u, keep = tg ? 0xfffe0000u : ~0u;
        const uint32_t add1 = ty == 2 ? 0u : add, keep1 = ty == 2 ? ~0u : keep;
        const uint32_t add2 = ty == 0 ? add : 0u, keep2 = ty == 0 ? keep : ~0u;
        v = {pack2(pretag(acc[0], add, keep), pretag(acc[1], add1, keep1)), pack2(acc[2], acc[3]),
             pack2(pretag(acc[4], add2, keep2), pretag(acc[5], add2, keep2)), pack2(acc[6], acc[7])};
        if (ty < 2) { v.x = movm(v.x); v.z = movm(v.z); v.y = movm(v.y); v.w = movm(v.w); }
        if (later && TAIL_F) *later = clk32();
        u = {pack2(pretag(acc[8], (ptag ^ 1) << 16, 0xfffe0000u), acc[9]) | ptag, pack2(acc[10], acc[11]), pack2(acc[12], acc[13]), pack2(acc[14], acc[15])};
        if (later) return;
        v.x = settag(v.x, ftag);
        if (ty == 0) v.z = settag(v.z, ftag);
    };

#pragma unroll 1
    for (int s = -2; s < 0; s++) {
        STEP_CONSTS
        (void)tag; (void)ttag; (void)tso; (void)fz;
        float acc[16];
        mbar_wait_w(bars + 8 * (B_HB + b), 0);
        wg_fence();
#pragma unroll
        for (int i = 0; i < 32; i++) {
            if (i < NL) wgmma_ss32(acc, dadd(mkdesc(SB0 + i * 2048, 8192, 1024, 1), wg * 4096), HB(i), i != 0);
            else wgmma_rs32(acc, w[i < NL ? 0 : i - NL], HB(i), 1);
        }
        wg_commit();
        uint4 pa = {0, 0, 0, 0};
        int it = 0;
#pragma unroll 1
        while ((p > 0) & any_bit0(pa.x ^ ftag) & (++it < POLL_LIMIT)) pa = ldg_b128(arena + (pso + g16));
        pdst = arena + ((pso ^ (32768 + 2048)) + G16());
        fdst = arena + ((b ^ 1) * 32768 + u_to + g16);
        wg_wait<0>();
#pragma unroll
        for (int k = 0; k < 4; k++) { acc[2 * k] += bflo((&pa.x)[k]); acc[2 * k + 1] += bfhi((&pa.x)[k]); }
        tok_pack(wg, acc, ftag, ptag);
        stg_b128_if(true, pdst, u.x, u.y, u.z, u.w);
        stg_b128_if(p > 0, fdst, v.x, v.y, v.z, v.w);
        if (p == 0) {
            TL(2)
            if (wg != 1) bar_arrive(NB_C, 288);
        }
    }
    if (wg == 1 && warp0) {
        wait_count_w(&g_tick[32 + (lane & 3) * 8], 2);
        asm volatile("fence.proxy.async.global;" ::: "memory");
        bar_sync(NB_C, 288);
        if (g16 == 0) mbar_arrive_cluster(bars + 8 * B_HE, j ^ 1);
        mbar_wait_w(bars + 8 * B_HE, 1);
        h_load(sb, hsrc, 2, j, head);
    }

    auto qk_loop = [&](auto wgc) {
        constexpr int WG = decltype(wgc)::value;
        uint32_t w0[NL][4], lm0;
        auto w0_load = [&]() {
            const uint32_t wl = TAB(WG * 3 + 1);
            lm0 = TAB(WG * 3 + 2);
#pragma unroll
            for (int k = 0; k < NL; k++) ldsm4t(w0[k], wl + k * 2048);
        };
        const uint32_t wlo = WG * 65536 - SM_WO - wu * 16384, wlx = __reduce_max_sync(~0u, (wi ^ WG) << 5);
        uint32_t tq0, lm, lm1;
        auto proj_pre = [&](int s) {
            uint32_t wz0 = zero;
#pragma unroll
            for (int k = 0; k < NL; k += 2) wz0 = and3(wz0, w0[k][0], w0[k + 1 < NL ? k + 1 : k][0]);
            lm = lm0 + (s & 1) * 65536 + wz0; lm1 = lm ^ 64;
            asm volatile("" : "+r"(lm), "+r"(lm1));
        };
        auto proj = [&](int s, auto mid) {
            bar_sync(NB_MEM, 384);
            float c[4][4];
            uint32_t bf[16][4], tq1 = 0, tq2 = 0;
#pragma unroll
            for (int it = 0; it < 3; it++) ldsm4(bf[it], (it & 1 ? lm1 : lm) + (it >> 1) * HBK);
            mid(-1);
#pragma unroll
            for (int it = 0; it < 16; it++) {
                const uint32_t* bfr = bf[it];
                if (it + 3 < 16) ldsm4(bf[it + 3 < 16 ? it + 3 : 0], (it & 1 ? lm : lm1) + ((it + 3) >> 1) * HBK);
                const uint32_t* wa = 2 * it < NL ? w0[2 * it < NL ? 2 * it : 0] : w[2 * it < NL ? 0 : 2 * it - NL];
                const uint32_t* wb = 2 * it + 1 < NL ? w0[2 * it + 1 < NL ? 2 * it + 1 : 0] : w[2 * it + 1 < NL ? 0 : 2 * it + 1 - NL];
                float *ca = c[(2 * it) & 3], *cb = c[(2 * it + 1) & 3];
                if (it < 2) { mma16816z(ca, wa, bfr[0], bfr[1]); mma16816z(cb, wb, bfr[2], bfr[3]); }
                else { mma16816(ca, wa[0], wa[1], wa[2], wa[3], bfr[0], bfr[1]); mma16816(cb, wb[0], wb[1], wb[2], wb[3], bfr[2], bfr[3]); }
                mid(it);
                if (it == QK_AT) { tq1 = clk32(); bar_arrive(NB_QK, 384); if (QK_F) tq2 = clk32(); }
            }
            const uint32_t xo = u_xo + (G16() >> 1);
            float r[4];
#pragma unroll
            for (int e = 0; e < 4; e++) {
                constexpr float SH = SM_L2E / 64;
                r[e] = WG ? (c[0][e] + c[1][e]) + (c[2][e] + c[3][e]) : fmaf(c[2][e] + c[3][e], SH, (c[0][e] + c[1][e]) * SH);
            }
            const uint32_t r0 = pack2(r[0], r[1]), r1 = pack2(r[2], r[3]);
            const uint32_t m0 = movm(r0), m1 = movm(r1);
            tq0 = clk32();
            if (QK_AT > 15) bar_arrive(NB_QK, 384);
            stg_rlx2(arena + xo, settag(m0, (s & 1) ^ 1), m1);
            tq0 += (tq1 | tq2) & zero;
        };
        w0_load();
        proj_pre(0);
        if (WG == 1 || !ROT) bar_sync(NB_P, ROT ? 256 : 384);
        proj(0, [](int) {});
        if (WO_LATE && WG == 0) mbar_wait_w(bars + 8 * B_WO, 0);
#pragma unroll 1
        for (int s = 0;; s++) {
            STEP_CONSTS
            uint4 pa;
            float acc[16];
            auto acc_init = [&]() {
#pragma unroll
                for (int k = 0; k < 4; k++) { acc[2 * k] = bflo((&pa.x)[k]); acc[2 * k + 1] = bfhi((&pa.x)[k]); acc[8 + 2 * k] = __uint_as_float((&pa.x)[k] & zero); acc[9 + 2 * k] = __uint_as_float(~(&pa.x)[k] & zero); }
            };
            uint32_t wf[NPF][4], a3;
#define WF(f) ((a3 ^ (((f) & 1) * 64)) + ((f) >> 1) * 2048)
            if (WG == 1) {
                float sc[5][4];
                uint32_t sx0 = sb + SM_SX - wu * (2560 - 16) + G16() * 5;
                asm volatile("" : "+r"(sx0));
                int it = 0;
                bool bad;
#pragma unroll 1
                do {
                    uint4 kf[2][2];
                    U2 qf[2], x[8];
                    const uint32_t gz = g16 | (it & zero);
                    const uint8_t *ts = arena + (tso + tbw + gz), *tq = arena + (tso + tbq + gz), *xp = arena + (xso + (gz >> 1));
#pragma unroll
                    for (int a = 0; a < 4; a++) kf[a >> 1][a & 1] = ldg_b128(ts + (a >> 1) * 16384 + (a & 1) * 2048);
                    if (QF_LATE) spin_until(tq0, dly.x2 - QF_LATE);
#pragma unroll
                    for (int a = 0; a < 2; a++) qf[a] = ldg_u2(tq + a * 16384);
                    spin_until(tq0, dly.x2);
#pragma unroll
                    for (int i = 0; i < 8; i++) x[i] = ldg_u2(xp + (i >> 2) * 16384 + (i & 3) * 1024);
                    PROF(8)
                    const uint32_t q0[4] = {hadd2(x[0].x, x[1].x), qf[0].x, hadd2(x[0].y, x[1].y), qf[0].y};
                    const uint32_t q1[4] = {hadd2(x[2].x, x[3].x), qf[1].x, hadd2(x[2].y, x[3].y), qf[1].y};
                    PROFV(7, clk32() + (q0[0] & zero))
                    const uint32_t bt = ((qf[0].x ^ ttag) | (qf[1].x ^ ttag)) | ((kf[0][0].x ^ ttag) | (kf[0][1].x ^ ttag)) | ((kf[1][0].x ^ ttag) | (kf[1][1].x ^ ttag));
                    uint32_t bx = 0;
#pragma unroll
                    for (int i = 0; i < 8; i += 2) bx |= (x[i].x ^ tag) | (x[i + 1].x ^ tag);
                    mma16816z(sc[0], q0, kf[0][0].x, kf[0][0].y);
                    mma16816z(sc[1], q0, kf[0][0].z, kf[0][0].w);
                    mma16816z(sc[2], q0, kf[0][1].x, kf[0][1].y);
                    mma16816z(sc[3], q0, kf[0][1].z, kf[0][1].w);
                    mma16816z(sc[4], q0, hadd2(x[4].x, x[5].x), hadd2(x[4].y, x[5].y));
                    bad = any_bit0((XP & 8 ? bt & zero : bt) | bx) & (++it < POLL_LIMIT);
                    mma16816(sc[0], q1[0], q1[1], q1[2], q1[3], kf[1][0].x, kf[1][0].y);
                    mma16816(sc[1], q1[0], q1[1], q1[2], q1[3], kf[1][0].z, kf[1][0].w);
                    mma16816(sc[2], q1[0], q1[1], q1[2], q1[3], kf[1][1].x, kf[1][1].y);
                    mma16816(sc[3], q1[0], q1[1], q1[2], q1[3], kf[1][1].z, kf[1][1].w);
                    mma16816(sc[4], q1[0], q1[1], q1[2], q1[3], hadd2(x[6].x, x[7].x), hadd2(x[6].y, x[7].y));
                } while (bad);
                PROFV(13, it - 1) MISS(1, it - 1)
                sts4(sx0, pack_h2(sc[0][0], sc[0][1]), pack_h2(sc[1][0], sc[1][1]), pack_h2(sc[2][0], sc[2][1]), pack_h2(sc[3][0], sc[3][1]));
                sts1(sx0 + 64 - wu * 12, pack_h2(sc[4][0], sc[4][1]));
                bar_arrive(NB_X1, 384);
                auto tok_sts = [&]() {
#pragma unroll
                    for (int n = 0; n < 5; n++) sts2(sb + SM_SX + 2560 + g8 + n * 1088, sc[n][2], sc[n][3]);
                };
                if (!STS_LATE) tok_sts();
                PROF(3)
                a3 = TAB(WG * 3);
                if (WO_LATE && s == 0) mbar_wait_w(bars + 8 * B_WO, 0);
                softmax_rows(sb + SM_SX + 2560, sb + SM_PX + 1024, g16 | (clk32() & zero), qd * 8, [&]() { BLOCK_FENCE if (STS_LATE) tok_sts(); bar_sync(NB_PX, 128); }, [&]() {
                    BLOCK_FENCE
#pragma unroll
                    for (int f = 0; f < NE1; f++) ldsm4t(wf[f], WF(f));
                    BLOCK_FENCE
                });
                PROF(4)
            } else {
                a3 = TAB(WG * 3);
                if (warp1 && (s & 3) == 1) asm volatile("fence.proxy.async.global;" ::: "memory");
                spin_until(tq0, dly.pa);
                uint4 x, y;
                int it = 0;
#pragma unroll 1
                do { x = ldg_b128(arena + (pso + g16)); y = ldg_b128(arena + (pso + tokbase(1) - tokbase(0) + g16)); }
                while (!(XP & 8) & (p <= NSEG) & any_bit0(xor_or(x.x, y.x, ftag)) & (++it < POLL_LIMIT));
                sts4(sb + SM_PA + g16, x.x, x.y, x.z, x.w);
                sts4(sb + SM_PA + 2048 + g16, y.x, y.y, y.z, y.w);
                if (NE) spin_until(tq0, dly.wf);
#pragma unroll
                for (int f = 0; f < NE; f++) ldsm4t(wf[f], WF(f));
                bar_sync(NB_X1, 384);
                if (E_MUL && g16 < 32) asm volatile("red.relaxed.gpu.global.max.u32 [%0], %1; red.relaxed.gpu.global.add.u32 [%0+4], 1;"
                                                    ::"l"(arena + ((blk(LB_TIME, 0) ^ (g16 << 8)) + qd * 1024 + (tq0 & zero))), "r"(gtime()) : "memory");
                __syncwarp();
                const uint32_t tx = clk32();
                if (H_POS == 2 && !(XP & 1) && warp1 && s + 3 <= NSEG) h_load(sb, hsrc, s + 3, j, H_ROT ? head : 0);
                spin_until(tx, dly.w2);
            }
#pragma unroll
            for (int f = WG ? NE1 : NE; f < NPF; f++) ldsm4t(wf[f], WF(f));
            PROF(5)
            if (s + 1 == NSEG) { bar_arrive(NB_X2, 384); break; }
            const uint32_t oa = l16 + SM_OX, slot = mem_slot(s + 1);
            float c[4][4];
            uint32_t ob[4][4];
            uint32_t wz = zero;
#pragma unroll
            for (int f = 0; f < NPF; f += 2) wz = and3(wz, wf[f][0], wf[f + 1 < NPF ? f + 1 : f][0]);
            BLOCK_FENCE
            bar_sync(NB_X2 + (SETTLE ? wz : 0), 384);
            ldsm4t(ob[0], oa);
            ldsm4t(ob[1], oa + 512);
            SCHED_FENCE(0)
#pragma unroll
            for (int f = 0; f < 16; f++) {
                const uint32_t *a = wf[f % NPF], *o = ob[f >> 2] + (f & 2);
                if (f < 4) mma16816z(c[f], a, o[0], o[1]);
                else mma16816(c[f & 3], a[0], a[1], a[2], a[3], o[0], o[1]);
                if (f == 3) ldsm4t(ob[2], oa + 1024);
                if (f == 5) { ldsm4t(ob[3], oa + 1536); if (NPF < 16) ldsm4t(wf[0], WF(NPF)); }
                if (f == 7) {
#pragma unroll
                    for (int k = NPF + 1; k < 16; k++) ldsm4t(wf[k - NPF], WF(k));
                }
                if (f == 3 || f == 5 || f == 7) SCHED_FENCE(f / 2)
                if (f == 11) {
                    if (W0_F) SCHED_FENCE(5)
#pragma unroll
                    for (int k = NL - W0_E; k < NL; k++) ldsm4t(w0[k], (a3 ^ wlx) + wlo + k * 2048);
                    SCHED_FENCE(4)
                }
            }
            const float last = c[1][3] + c[3][3], one = __uint_as_float(CNT1 << 16);
            red_mem(arena + (u_m + slot + G16()), pack2(c[0][0] + c[2][0], c[0][1] + c[2][1]), pack2(c[0][2] + c[2][2], c[0][3] + c[2][3]),
                    pack2(c[1][0] + c[3][0], c[1][1] + c[3][1]), pack2(c[1][2] + c[3][2], CNT32 && !(g16 & 16) ? last : one),
                    arena + (u_e + slot + (CNT32 ? (g16 >> 3) & ~3u : g16 >> 2)), pack2(one, last), !CNT32 || (g16 & 16));
            hbo += FZ;
            PROF(6)
            constexpr int NS = NL - W0_RS, GS = (32 - NL + NS) / NS;
            auto w0_rest = [&]() {
#pragma unroll
                for (int k = NL - W0_E - 1; k >= 0; k--) ldsm4t(w0[k], (a3 ^ wlx) + wlo + k * 2048);
                lm0 = TAB(WG * 3 + 2);
                if (WG == 1) pa = lds4(sb + SM_PA + 2048 + g16);
            };
            if (WG == 0 ? W1_LATE < 3 : W1_LATE < 2) { BLOCK_FENCE w0_rest(); }
            if (WG == 0) {
                bar_arrive(NB_WIN, 384);
                if (W1_LATE == 3) w0_rest();
                pa = lds4(sb + SM_PA + g16);
                acc_init();
                asm volatile("" : F16(acc, 0));
                BLOCK_FENCE
            }
            wg_fence();
            bar_sync(WG ? NB_WIN : NB_B, WG ? 384 : 256);
            if (WG == 1 && W1_LATE >= 2) w0_rest();
#pragma unroll
            for (int i = 0; i < 32; i++) {
                const int k = i / GS;
                if (i >= 32 - NL + NS) wgmma_rs32(acc, w0[i < 32 - NL + NS ? 0 : i - 32 + NL], HB(i - 32 + NL), 1);
                else if (i % GS == GS - 1 && k < NS) wgmma_ss32(acc, mkdesc(SB0 + WG * 65536 + k * 2048, 8192, 1024, 1), HB(k), 1);
                else wgmma_rs32(acc, w[i - (k < NS ? k : NS)], HB(NL + i - (k < NS ? k : NS)), WG == 0 || i);
                if (WG == 1 && i == G_AT) bar_arrive(NB_B, 256);
                if (WG == 1 && W1_LATE && i == 31 - NL + NS) wg_fence();
            }
            wg_commit();
            BLOCK_FENCE
            if (WG == 1 && warp0 && !(s & 3)) wait_count_w(&g_tick[32 + ((G16() >> 4) & 3) * 8], min((s + 1) / 4 + 3, 17));
            auto tok_store = [&](int m) {
                if (m & 1) stg_b128_if(XP & 8 ? s == 99 : true, arena + ((b ^ 1) * 32768 + u_to + G16()), v.x, v.y, v.z, v.w);
                if (m & 2) stg_b128_if(XP & 8 ? s == 99 : p < NSEG, arena + ((pso ^ (32768 + 2048)) + G16()), u.x, u.y, u.z, u.w);
            };
            if (WG == 0) proj_pre(s + 1);
            BLOCK_FENCE
            wg_wait<0>();
            if (WG == 0 && ROT) {
                asm volatile("" : F16(acc, 0));
                proj(s + 1, [&](int it) {
                    if (it < 0) {
                        SCHED_FENCE(0)
                        asm volatile("" : F16(acc, 0));
                        tok_pack(WG, acc, ftag, ptag, fz + 4);
                        tok_store(2);
                        SCHED_FENCE(1)
                    }
                    if (it == ROT) { SCHED_FENCE(2) v.x = settag(v.x, ftag); v.z = settag(v.z, ftag); tok_store(1); SCHED_FENCE(3) }
                });
                tq0 += (fz[0] | fz[1] | fz[2] | fz[3] | (TAIL_F ? fz[4] : 0)) & zero;
            } else {
                if (WG == 1) {
#pragma unroll
                    for (int k = 0; k < 4; k++) { acc[2 * k] += bflo((&pa.x)[k]); acc[2 * k + 1] += bfhi((&pa.x)[k]); }
                }
                tok_pack(WG, acc, ftag, ptag);
                if (WG == 1) proj_pre(s + 1);
                asm volatile("" : "+r"(u.x), "+r"(u.y), "+r"(u.z), "+r"(u.w), "+r"(v.x), "+r"(v.y), "+r"(v.z), "+r"(v.w));
                BLOCK_FENCE
                bar_sync(NB_P, ROT ? 256 : 384);
                tok_store(3);
                proj(s + 1, [](int) {});
            }
        }
    };
    if (wg == 0) {
        qk_loop(IC<0>());
    } else if (wg == 1) {
        qk_loop(IC<1>());
    } else {
        const uint32_t ONES = 0x3f803f80u, u_o = qd * 65536 + head * 2048 + wu * 384;
        uint32_t tw = 0, dl = 0, dbase = kh == mypar ? dly.near : dly.far, dst0, dx0;
        dst0 = TAB(6); dx0 = TAB(7);
        uint32_t ov[4] = {0, 0, 0, 0};
        auto o_store = [&](int s) {
            uint8_t* od = (uint8_t*)g_O + (uint32_t)(s * (32 * NH * DH * 2) + u_o + (G16() >> 2));
#pragma unroll
            for (int a = 0; a < 4; a++) stg_rlx1(od + a * 128, ov[a]);
        };
        uint4 vf[2][2], pa;
        auto vf_fetch = [&](int s) {
            const uint8_t* ts = arena + ((s & 1) * 32768 + tbw + g16);
#pragma unroll
            for (int a = 0; a < 4; a++) vf[a >> 1][a & 1] = ldg_b128(ts + (a >> 1) * 16384 + (a & 1) * 2048);
        };
        auto tok_fetch = [&](int s) {
            if (TV_POS != 1) vf_fetch(s);
            pa = ldg_b128(arena + (tbw + (1 << 20) + (~s & 1) * 32768 + j * 16384 + kh * 2048 + g16));
        };
        if (PA_POS) tok_fetch(0);
        TL(9)
        if (!WO_LATE) mbar_wait_w(bars + 8 * B_WO, 0);
        TL(6)
#pragma unroll 1
        for (int s = 0; s < NSEG; s++) {
            STEP_CONSTS
#define VFBAD ((vf[0][0].x ^ ttag) | (vf[0][1].x ^ ttag) | (vf[1][0].x ^ ttag) | (vf[1][1].x ^ ttag))
#define TOKBAD ((TV_POS == 1 ? 0 : VFBAD) | (p <= NSEG ? pa.x ^ ftag : 0))
            {
                const uint32_t dst = dst0 + b * 65536, dx = dx0 + b * 65536;
                const uint8_t *ms = arena + (u_m + mem_slot(s) + g16), *me = arena + (u_e + mem_slot(s) + (CNT32 ? (g16 >> 3) & ~3u : g16 >> 2));
                const uint32_t em = CNT32 && !(g16 & 16) ? ~0u : 0u;
                asm volatile("" : "+l"(ms), "+l"(me));
                spin_until(tw, dl);
                PROF(11)
                int it = 0;
                bool bad;
#pragma unroll 1
                do {
                    uint4 m[4];
                    uint32_t x[4];
#pragma unroll
                    for (int i = 0; i < 4; i++) m[i] = ldg_rlx4(ms + i * 1024);
#pragma unroll
                    for (int i = 0; i < 4; i++) x[i] = ldg_rlx1(me + i * 1024);
#pragma unroll
                    for (int i = 0; i < 3; i++) {
                        stsm4t(dst + i * 2 * HBK, m[i].x, m[i].y, m[i].z, m[i].w);
                        if (i == P_GATE) asm volatile("{.reg .pred p; setp.eq.s32 p, %0, 0; @p bar.arrive %1, %2;}" ::"r"(it), "n"(NB_P), "n"(ROT ? 256 : 384) : "memory");
                    }
                    uint32_t c = and3(m[0].w, m[1].w, m[2].w);
                    SCHED_FENCE(1)
                    stsm4t(dst + 6 * HBK, m[3].x, m[3].y, m[3].z, m[3].w);
                    stsm4t(dx, x[0], x[1], x[2], x[3]);
                    asm volatile("" : "+r"(c));
                    c = and3(and3(((c & m[3].w) | em) >> 16, x[0], x[1]), x[2], x[3]);
                    bad = __any_sync(~0u, !(c & CNT_ALL)) & (++it < POLL_LIMIT);
                    asm volatile("{.reg .pred p; setp.eq.u32 p, %0, 0; @p bar.arrive %1, 384;}" ::"r"((uint32_t)bad), "n"(NB_MEM) : "memory");
                } while (bad);
                if (it > 1 && s > 1) dbase += dly.tv;
                PROFV(12, it - 1)
                MISS(0, it - 1) HT(5)
                PROF(8)
            }
            if (s == 1) { TL(7) TLC(0) }
            if (s == 63) TLC(1)
            if (s == 0) TL(13)
            if (O_POS == 1) o_store(max(s - 1, 0));
            if (Z_POS && warp1) stg4_if(g16 < 512 + 160, arena + (TAB(8) + mem_slot(s + 3)), 0);
            fence_async_smem();
            hbo += fz[1] & zero;
            int it = 0;
            if (!PA_POS) tok_fetch(s);
#pragma unroll 1
            while (!(XP & 8) & any_bit0(TOKBAD) & (++it < POLL_LIMIT)) tok_fetch(s + (it & zero));
            float acc[20];
#pragma unroll
            for (int k = 0; k < 4; k++) { acc[2 * k] = bflo((&pa.x)[k]); acc[2 * k + 1] = bfhi((&pa.x)[k]); acc[8 + 2 * k] = acc[9 + 2 * k] = acc[16 + k] = __uint_as_float(pa.x & zero); }
            if (XP & 1 ? s < 1 : p <= NSEG) mbar_wait_w(bars + 8 * (B_HB + b), (p >> 1) & 1);
            asm volatile("" : F16(acc, 0), F4(acc, 16));
            BLOCK_FENCE
            wg_fence();
            bar_sync(NB_QK, 384);
#pragma unroll
            for (int i = 0; i < 32; i++) {
                const int k = i / GAP;
                if (i % GAP == GAP - 1 && k < NL) wgmma_ss40(acc, mkdesc(SB0 + 131072 + k * 2048, 8192, 1024, 1), HB(k), 1);
                else wgmma_rs40(acc, w[i - (k < NL ? k : NL)], HB(NL + i - (k < NL ? k : NL)), 1);
            }
            wg_commit();
            uint8_t* vo = arena + (u_xo + (G16() >> 1));
            pdst = arena + ((pso ^ (32768 + 2048)) + G16());
            fdst = arena + ((b ^ 1) * 32768 + u_to + g16);
            BLOCK_FENCE
            wg_wait<0>();
            PROF(9)
            stg_rlx2(vo, settag(pack2(acc[16], acc[17]), tag), pack2(acc[18], acc[19]));
            const uint32_t tv = clk32();
            if (TV_POS == 1) vf_fetch(s);
            tok_pack(2, acc, ftag, ptag);
            stg_b128_if(XP & 8 ? s == 99 : p <= NSEG, fdst, v.x, v.y, v.z, v.w);
            stg_b128_if(XP & 8 ? s == 99 : p < NSEG, pdst, u.x, u.y, u.z, u.w);
            if (O_POS == 2) o_store(max(s - 1, 0));
            if (ST_BAR) bar_sync(NB_WG, 128);
            PROF(10)
            const uint8_t* xp = arena + (xso + 32768 + (G16() >> 1));
            const uint32_t sxa = sb + SM_SX - wu * 2560 + G16() * 5;
            uint32_t sel[2];
            {
                const uint32_t q = (G16() >> 4 ^ g16 >> 6 & 1) & 3;
                sel[0] = q == 0 ? 0x3c00 : 0; sel[1] = q == 2 ? 0x3c00 : 0;
                asm volatile("" : "+r"(sel[0]), "+r"(sel[1]));
            }
            uint32_t xv[4], gt = 0;
            auto pv = [&](uint32_t p0, uint32_t p1, uint32_t p2, uint32_t p3, uint32_t p4, auto getv, auto done) {
                float oc[2][4], lc[4] = {0.f, 0.f, 0.f, 0.f};
                mma16816(lc, ONES, ONES, ONES, ONES, p0, p1);
                mma16816z(oc[0], &vf[0][0].x, p0, p1);
                mma16816z(oc[1], &vf[1][0].x, p0, p1);
                mma16816(lc, ONES, ONES, ONES, ONES, p2, p3);
                mma16816(oc[0], vf[0][1].x, vf[0][1].y, vf[0][1].z, vf[0][1].w, p2, p3);
                mma16816(oc[1], vf[1][1].x, vf[1][1].y, vf[1][1].z, vf[1][1].w, p2, p3);
                mma1688(lc, ONES, ONES, p4);
                getv();
                mma1688(oc[0], xv[0], xv[1], p4);
                mma1688(oc[1], xv[2], xv[3], p4);
                done(__float_as_uint(oc[0][0]) | __float_as_uint(oc[1][0]) | __float_as_uint(lc[0]));
                const float r0 = rcp_fast(lc[0]), r1 = rcp_fast(lc[1]);
                ov[0] = pack2(oc[0][0] * r0, oc[0][1] * r1); ov[1] = pack2(oc[0][2] * r0, oc[0][3] * r1);
                ov[2] = pack2(oc[1][0] * r0, oc[1][1] * r1); ov[3] = pack2(oc[1][2] * r0, oc[1][3] * r1);
            };
            bool bad;
            it = 0;
#pragma unroll 1
            do {
                U2 xr[4];
                auto load_v = [&]() {
                    if (V_POS < 3) spin_until(tv, dly.v);
#pragma unroll
                    for (int i = 0; i < 4; i++) xr[i] = ldg_u2(xp + i * 1024);
                };
                if (TV_POS == 1 && it) {
                    const uint8_t* tz = arena + (tso + tbw + (g16 | (it & zero)));
#pragma unroll
                    for (int a = 0; a < 4; a++) ldg_b128_into(vf[a >> 1][a & 1], tz + (a >> 1) * 16384 + (a & 1) * 2048);
                }
                if (!V_POS) load_v();
                if (V_POS >= 3) spin_until(tv, dly.v);
                PROF(3)
                asm volatile("{.reg .pred p; setp.eq.s32 p, %0, 0; @p bar.sync %1, 384;}" ::"r"(it), "n"(NB_X1) : "memory");
                uint4 sx[5];
                if (V_POS == 3) load_v();
#pragma unroll
                for (int i = 0; i < 5; i++) sx[i] = lds4(sxa + i * 16);
                if (V_POS == 4) load_v();
                if (it == 0) { gt = gtime(); tw = clk32(); }
                if (V_POS == 2) load_v();
                uint32_t h[5], h0[4];
#pragma unroll
                for (int n = 0; n < 4; n++) h0[n] = add_h2((&sx[0].x)[n], (&sx[1].x)[n]);
                if (V_POS == 5) { SCHED_FENCE(2) load_v(); SCHED_FENCE(3) }
#pragma unroll
                for (int n = 0; n < 4; n++) h[n] = add_h2(h0[n], add_h2((&sx[2].x)[n], (&sx[3].x)[n]));
                h[4] = add_h2(add_h2(sx[4].x, sx[4].y), add_h2(sx[4].z, sx[4].w));
                uint32_t hm = max_h2(max_h2(max_h2(h[0], h[1]), h[2]), max_h2(h[3], h[4]));
                float2 a[5];
                float mb;
                if (MAX_MMA) {
                    float d[2][4];
                    const uint32_t hs = __byte_perm(hm, hm, 0x1032);
#pragma unroll
                    for (int k = 0; k < 2; k++)
                        asm volatile("mma.sync.aligned.m16n8k8.row.col.f32.f16.f16.f32 {%0,%1,%2,%3},{%4,%5},{%6},{%7,%7,%7,%7};"
                                     : "=f"(d[k][0]), "=f"(d[k][1]), "=f"(d[k][2]), "=f"(d[k][3]) : "r"(hm), "r"(hs), "r"(sel[k]), "f"(0.f));
#pragma unroll
                    for (int n = 0; n < 5; n++) a[n] = unpack_h2(h[n]);
                    mb = -64.0f * fmaxf(fmaxf(fmaxf(d[0][0], d[0][1]), fmaxf(d[0][2], d[0][3])), fmaxf(fmaxf(d[1][0], d[1][1]), fmaxf(d[1][2], d[1][3])));
                } else {
                    hm = max_h2(hm, __byte_perm(hm, hm, 0x1032));
                    const uint32_t m1 = __shfl_xor_sync(~0u, hm, 1), m2 = __shfl_xor_sync(~0u, hm, 2), m3 = __shfl_xor_sync(~0u, hm, 3);
#pragma unroll
                    for (int n = 0; n < 5; n++) a[n] = unpack_h2(h[n]);
                    if (V_POS == 1) load_v(); else SCHED_FENCE(0)
                    mb = -64.0f * unpack_h2(max_h2(max_h2(hm, m1), max_h2(m2, m3))).x;
                }
                uint32_t pm[5];
#pragma unroll
                for (int n = 0; n < 5; n++) pm[n] = pack2(ex2(fmaf(a[n].x, 64.0f, mb)), ex2(fmaf(a[n].y, 64.0f, mb)));
                pv(pm[0], pm[1], pm[2], pm[3], pm[4], [&]() {
                    xv[0] = hadd2(xr[0].x, xr[1].x); xv[1] = hadd2(xr[0].y, xr[1].y);
                    xv[2] = hadd2(xr[2].x, xr[3].x); xv[3] = hadd2(xr[2].y, xr[3].y);
                }, [](uint32_t) {});
                bad = any_bit0((TV_POS == 1 && !(XP & 8) ? VFBAD : 0) | (xr[0].x ^ tag) | (xr[1].x ^ tag) | (xr[2].x ^ tag) | (xr[3].x ^ tag)) & (++it < POLL_LIMIT);
                stsm4(sb + SM_OX + g16, ov[0], ov[1], ov[2], ov[3]);
            } while (bad);
            PROFV(14, it - 1) MISS(2, it - 1)
            PROF(5)
            bar_sync(NB_X2, 384);
            BLOCK_FENCE
            U2 tv2 = {0, 0};
            const uint8_t* tp = arena + (blk(LB_TIME, mypar) + ((G16() << 6) & 0xc00));
            {
                const uint4 pp = lds4(l16 + SM_PX + 1024);
                const uint32_t p4 = lds1(sb + SM_PX + 512 + 1024 - wu * 128 + (G16() >> 2));
                if (E_MUL) tv2 = ldg_u2(tp);
                if (H_POS == 3 && !(XP & 1) && warp0 && s + 3 <= NSEG) h_load(sb, hsrc, s + 3, j, H_ROT ? head : 0);
                if (H_POS == 0 && !(XP & 1)) h_piece(sb, hsrc, s + 3, j, (wu + (H_ROT ? head : 0)) & 3, wu == 0);
                pv(pp.x, pp.y, pp.z, pp.w, p4, []() {}, [&](uint32_t r) { bar_arrive(NB_WIN + ((r | fz[0] | fz[2] | fz[3]) & zero), 384); });
            }
            dst0 = TAB(6); dx0 = TAB(7);
            const uint32_t zo = Z_POS ? 0 : TAB(8);
            PROF(6) HT(7)
            BLOCK_FENCE
            if (H_POS == 1 && !(XP & 1)) h_piece(sb, hsrc, s + 3, j, (wu + (H_ROT ? head : 0)) & 3, wu == 0);
            asm volatile("" : "+r"(tv2.y));
            it = 0;
#pragma unroll 1
            while (E_MUL && __any_sync(~0u, tv2.y < 32 * (s + 1)) & (++it < 16)) tv2 = ldg_u2(tp);
            const uint32_t e = __reduce_max_sync(~0u, tv2.x) - gt;
            MISS(3, it - 1) MISS(4, gt)
            if (PA_POS) tok_fetch(s + 1);
            if (O_POS == 0) o_store(s);
            if (!Z_POS) stg4_if(g16 < 160, arena + (zo + mem_slot(s + 3)), 0);
            dl = dbase + (e > 4096 ? 0 : e * E_MUL >> 4);
        }
        if (O_POS) o_store(NSEG - 1);
        TL(8)
    }
    PROF_OUT
    MISS_OUT
}

struct RecMaps { CUtensorMap wq, wk, wv, wo, wmod, w3, w1; };
struct RecPtrs { const bf16 *x, *mem0, *c, *wmod, *w1, *w3; uint8_t* arena; uint32_t zero; const bf16 *w2, *w4, *wo; Delays dly; };

__device__ __forceinline__ float silu_bf(const bf16* c, int i) {
    const float v = __bfloat162float(c[i]);
    return bfround(__fdividef(v, 1.0f + __expf(-v)));
}
#define LN_SEQ 0xcba6420987531ull
#define W_LATE 1000
#define W_OPEN 1400
__device__ __noinline__ uint32_t side_window_(const uint8_t* arena, uint32_t n) {
    U2 v;
    int it = 0;
#pragma unroll 1
    while (v = ldg_u2(arena + (LB_TIME << 13)), ((v.y >> 5) == n || gtime() - v.x > W_OPEN + W_LATE) && v.y < 32 * NSEG && ++it < 64) __nanosleep(100);
    it = 0;
#pragma unroll 1
    while ((int)(gtime() - v.x - W_OPEN) < 0 && ++it < 256) {}
    return v.y >> 5;
}
#define side_window(arena, n) n = side_window_(arena, n)
__device__ __noinline__ void rec_ln(uint32_t sb, const bf16* x, const uint8_t* arena, int id, int r0) {
    int r1 = 32;
    uint32_t n = 0;
    const int tid = threadIdx.x, lane = tid & 31, wid = __reduce_max_sync(~0u, tid >> 5);
    const uint32_t ring = sb + wid * 8192 + lane * 16, coef = sb + SM_PRE;
    x += (id * 8 + wid) * 2 * DM + lane * 8;
#pragma unroll 1
    for (int r = r0 - 1; r < r1; r++) {
        if (r > 3) side_window(arena, n);
        if (r + 1 < r1) {
#pragma unroll
            for (int i = 0; i < 8; i++)
                asm volatile("cp.async.cg.shared.global [%0], [%1], 16;" ::"r"(ring + (~r & 1) * 4096 + i * 512), "l"(x + (r + 1) * 64 * DM + i * 256) : "memory");
        }
        asm volatile("cp.async.commit_group; cp.async.wait_group 1;" ::: "memory");
        if (r < r0) continue;
        const uint32_t src = ring + (r & 1) * 4096;
        float m[2] = {0.f, 0.f}, rs[2];
#pragma unroll 1
        for (int ps = 0; ps < 2; ps++) {
            float t[2][2] = {{0.f, 0.f}, {0.f, 0.f}};
#pragma unroll 1
            for (int i = 0; i < 2048; i += 512) {
#pragma unroll
                for (int h = 0; h < 2; h++) {
                    const uint4 u = lds4(src + h * 2048 + i);
#pragma unroll
                    for (int e = 0; e < 4; e++) {
                        const float a = bflo((&u.x)[e]) - m[h], c = bfhi((&u.x)[e]) - m[h];
                        t[h][0] = fmaf(a, ps ? a : 1.0f, t[h][0]); t[h][1] = fmaf(c, ps ? c : 1.0f, t[h][1]);
                    }
                }
            }
            rs[0] = t[0][0] + t[0][1]; rs[1] = t[1][0] + t[1][1];
#pragma unroll 1
            for (int o = 16; o; o >>= 1) { rs[0] += __shfl_xor_sync(~0u, rs[0], o); rs[1] += __shfl_xor_sync(~0u, rs[1], o); }
            if (!ps) { m[0] = rs[0] * (1.0f / DM); m[1] = rs[1] * (1.0f / DM); }
        }
        rs[0] = rsqrtf(rs[0] * (1.0f / DM) + 1e-5f); rs[1] = rsqrtf(rs[1] * (1.0f / DM) + 1e-5f);
        if (r == r0) {
#pragma unroll 1
            for (int i = tid; i < 2 * DM / 4; i += 256) {
                float t[4];
                int it = 0;
                uint32_t ok;
#pragma unroll 1
                do {
                    uint4 u[8];
#pragma unroll
                    for (int k = 0; k < 8; k++) u[k] = ldg_rlx4(g_modp + k * 2 * DM + i * 4);
                    ok = 1;
#pragma unroll
                    for (int k = 0; k < 32; k++) { const uint32_t w = (&u[k >> 2].x)[k & 3]; ok &= w; t[k & 3] = k < 4 ? __uint_as_float(w) : t[k & 3] + __uint_as_float(w); }
                } while (!__all_sync(~0u, ok) & (++it < SPIN_LIMIT));
                const float o = i >> 8;
                const uint32_t lo = pack2(t[0], t[1]), hi = pack2(t[2], t[3]);
                sts4f(coef + (i >> 8) * 4096 + (i & 1) * 2048 + ((i & 255) >> 1) * 16, bflo(lo) + o, bfhi(lo) + o, bflo(hi) + o, bfhi(hi) + o);
            }
            bar_sync(NB_FIN0, 256);
            if (tid == 0 && r0 == 0) TL(2)
        }
        uint8_t* dst = (uint8_t*)g_himg + (r * 2 + (id >> 1)) * 65536 + (lane >> 3) * 4096 + wid * 256;
#pragma unroll 1
        for (int i = 0; i < 4; i++) {
            const uint32_t ca = coef + i * 512 + lane * 16;
            const float4 s0 = lds4f(ca), s1 = lds4f(ca + 2048), c0 = lds4f(ca + 4096), c1 = lds4f(ca + 6144);
            const float sh[8] = {s0.x, s0.y, s0.z, s0.w, s1.x, s1.y, s1.z, s1.w}, sc[8] = {c0.x, c0.y, c0.z, c0.w, c1.x, c1.y, c1.z, c1.w};
#pragma unroll
            for (int h = 0; h < 2; h++) {
                uint4 u = lds4(src + h * 2048 + i * 512);
#pragma unroll
                for (int e = 0; e < 4; e++) {
                    uint32_t& w = (&u.x)[e];
                    w = pack2(fmaf((bflo(w) - m[h]) * rs[h], sc[2 * e], sh[2 * e]), fmaf((bfhi(w) - m[h]) * rs[h], sc[2 * e + 1], sh[2 * e + 1]));
                }
                *(uint4*)(dst + i * 16384 + ((id & 1) == (i >> 1) ? 65536 : 2048) + h * 128 + (((lane ^ (2 * wid + h)) & 7) << 4)) = u;
            }
        }
        if (r == 0) {
            if (tid == 0) TLX(10)
            int ro, it = 0;
#pragma unroll 1
            do asm volatile("ld.volatile.shared.u32 %0, [%1];" : "=r"(ro) : "r"(sb + SM_BAR + 192) : "memory"); while ((ro == INT_MIN) & (++it < SPIN_LIMIT));
            if (ro >= 0) r1 = 2;
        }
        if (r && !(r & 1)) continue;
        bar_sync(r ? NB_FIN0 : NB_C, r ? 256 : 320);
        if (tid == 0 && r == 0) TLX(11)
        if (wid == (r >> 1 & 7)) {
            if (r == 1) bar_arrive(NB_B, 64);
            if (r == 3) wait_count_w(&g_tick[32 + id * 8], 2);
            if (lane == 0) { signal_count(&g_tick[32 + id * 8]); if (r == 0) TLX(12) }
            __syncwarp();
        }
    }
}
#define SIDE_T 300
template <int NQ>
__device__ __forceinline__ void side_gemv(const CUtensorMap* tm, int c0, int k0, int k1, uint32_t cs, uint32_t sb, const uint8_t* arena, uint32_t& n, uint32_t& ph, float (*acc)[8], bool once = false) {
    const uint32_t w = __reduce_max_sync(~0u, threadIdx.x >> 5 & 3), ring = sb + 65536 + w * 24576, bars = sb + SM_BAR + 8 * B_W + w * 24;
#pragma unroll
    for (int q = 0; q < NQ; q++)
#pragma unroll
        for (int j = 0; j < 8; j++) acc[q][j] = 0.f;
#pragma unroll 1
    for (; k0 < k1; k0 += 48, ph ^= 1) {
        const int nr = min(48, k1 - k0);
        side_window(arena, n);
        const uint32_t t0 = clk32();
#pragma unroll 1
        for (int g = 0; g < 3; g++) {
            spin_until(t0, (g * 4 + w) * (SIDE_T / 4));
            e_expect(bars + 8 * g, g * 16 < nr ? 8192 : 0);
            if (g * 16 < nr) e_tma2d_hint(ring + g * 8192, tm, c0, k0 + g * 16, bars + 8 * g, once ? EVICT_FIRST : EVICT_NORMAL);
        }
#pragma unroll 1
        for (int r = 0; r < nr; r += 16) {
            mbar_wait_w(bars + (r >> 1), ph);
            uint4 v[16];
#pragma unroll
            for (int h = 0; h < 16; h++) v[h] = lds4(ring + (r + h) * 512 + (threadIdx.x & 31) * 16);
            float4 cf[NQ][4];
#pragma unroll
            for (int q = 0; q < NQ * 4; q++) cf[q >> 2][q & 3] = lds4f(cs + ((q >> 2) * DM + k0 + r + (q & 3) * 4) * 4);
#pragma unroll
            for (int h = 0; h < 16; h++) {
                const float f[8] = {bflo(v[h].x), bfhi(v[h].x), bflo(v[h].y), bfhi(v[h].y), bflo(v[h].z), bfhi(v[h].z), bflo(v[h].w), bfhi(v[h].w)};
#pragma unroll
                for (int q = 0; q < NQ; q++)
#pragma unroll
                    for (int j = 0; j < 8; j++) acc[q][j] = fmaf((&cf[q][h >> 2].x)[h & 3], f[j], acc[q][j]);
            }
        }
        fence_async_smem();
        __syncwarp();
    }
}
__device__ __noinline__ void rec_side(float* sm, const RecMaps& mp, const RecPtrs& p, int id) {
    const int tid = threadIdx.x;
    if (tid < 256) {
        if (blockIdx.x < 128) rec_ln(smem_u32(sm), p.x, p.arena, id, 2);
        if (tid == 0) TL(14)
        for (int i = tid; i < 2 * S_; i += 256) g_st[id * 2 * S_ + i] = 0.f;
        if (id == 0 && tid < 64) g_pcnt[tid * 8] = 0;
        if (id == 1) for (int i = tid; i < 6 * 256; i += 256) g_pflag[i] = 0;
        if (id == 2 && tid == 0) g_pt = 0;
        bar_sync(NB_FIN0, 256);
        if (PDL && tid == 0) asm volatile("fence.acq_rel.gpu; griddepcontrol.launch_dependents;" ::: "memory");
        return;
    }
    const int t = tid - 256;
    float *coef = sm + 40960, *red = coef + 3 * DM;
    const uint32_t sb = smem_u32(sm), cs = smem_u32(coef);
    uint32_t n = 0, ph = 0;
    for (int i = t; i < DM; i += 128) { coef[i] = silu_bf(p.c, i); coef[2 * DM + i] = 1.0f; }
    if (t == 0) wait_count1(&g_tick[32], 1);
    bar_sync(NB_G, 128);
    const int w = __reduce_max_sync(~0u, t >> 5);
    float acc[3][8];
    side_gemv<1>(&mp.wmod, (2 + id) * DM + w * 256, 0, DM, cs, sb, p.arena, n, ph, acc, true);
#pragma unroll
    for (int j = 0; j < 8; j++) g_mod[(2 + id) * DM + t * 8 + j] = bfround(acc[0][j]);
    bar_sync(NB_G, 128);
    if (t == 0) signal_count(&g_tick[8]);
    side_gemv<1>(&mp.w3, id * (FF / 4) + w * 256, 0, DM, cs + 8 * DM, sb, p.arena, n, ph, acc);
    if (t < FF / 32) {
#pragma unroll
        for (int j = 0; j < 8; j++) g_vec[3 * DM + id * (FF / 4) + t * 8 + j] = acc[0][j];
    }
    if (t == 0) wait_count1(&g_tick[8], 4);
    bar_sync(NB_G, 128);
    for (int i = t; i < DM; i += 128) { coef[i] = 1.0f + __ldcg(g_mod + 4 * DM + i); coef[DM + i] = __ldcg(g_mod + 3 * DM + i); }
    bar_sync(NB_G, 128);
    if (id == 1 && t < 32) {
        float u[5] = {0, 0, 0, 0, 0};
        for (int i = t; i < DM; i += 32) {
            const float a = coef[i], b = coef[DM + i];
            u[0] += a; u[1] += a * a; u[2] += a * b; u[3] += b; u[4] += b * b;
        }
#pragma unroll
        for (int q = 0; q < 5; q++) { const float r = warp_sum(u[q]); if (t == 0) g_cst[q] = r * (1.0f / DM); }
    }
    side_gemv<3>(&mp.w1, id * 256, w * 256, w * 256 + 256, cs, sb, p.arena, n, ph, acc);
#pragma unroll
    for (int q = 0; q < 3; q++)
#pragma unroll
        for (int j = 0; j < 8; j++) red[((t >> 5) * 3 + q) * 256 + (t & 31) * 8 + j] = acc[q][j];
    bar_sync(NB_G, 128);
    for (int i = t; i < 768; i += 128) g_vec[(i >> 8) * DM + id * 256 + (i & 255)] = (red[i] + red[768 + i]) + (red[1536 + i] + red[2304 + i]);
    if (t == 0) TL(9)
}

__global__ void __cluster_dims__(2, 1, 1) __launch_bounds__(384, 1)
k_rec(const __grid_constant__ RecMaps mp, const __grid_constant__ RecPtrs p) {
    extern __shared__ uint8_t smraw[];
    const uint32_t sb = smem_u32(smraw);
    if ((sb & 0x3FFFF) != SB0) __trap();
    const uint32_t bars = sb + SM_BAR;
    const int tid = threadIdx.x, lane = tid & 31, b = blockIdx.x;
    const int wid = __reduce_max_sync(~0u, tid >> 5);
    const uint32_t rank = b & 1;
    uint8_t* arena = p.arena;
    volatile int* sinfo = (volatile int*)(smraw + SM_BAR + 192);
    if (tid == 0) TL(0)
    if (tid == 0) sinfo[0] = INT_MIN;
    if (tid == 352) {
        for (int i = 0; i < 17; i++) mbar_init(bars + 8 * i, i == B_WO ? 4 : 1);
        asm volatile("fence.mbarrier_init.release.cluster;" ::: "memory");
    }
    __syncwarp();
    asm volatile("barrier.cluster.arrive.relaxed.aligned;" ::: "memory");
    int pr = 0, hA = 0;
    if (wid < 8) {
        if (b < 128) {
            const int cb = (b & 15) * 128, k0 = (b >> 4) * 128 + (tid >> 4);
            uint4 v[8];
#pragma unroll
            for (int i = 0; i < 8; i++) v[i] = __ldg((const uint4*)(p.wmod + (size_t)(k0 + 16 * i) * (6 * DM) + cb + (tid & 15) * 8));
            float acc[8] = {0, 0, 0, 0, 0, 0, 0, 0};
            const float s8 = silu_bf(p.c, k0 + 16 * (lane & 7));
#pragma unroll
            for (int i = 0; i < 8; i++) {
                const float sv = __shfl_sync(~0u, s8, i, 16);
                acc[0] += sv * bflo(v[i].x); acc[1] += sv * bfhi(v[i].x); acc[2] += sv * bflo(v[i].y); acc[3] += sv * bfhi(v[i].y);
                acc[4] += sv * bflo(v[i].z); acc[5] += sv * bfhi(v[i].z); acc[6] += sv * bflo(v[i].w); acc[7] += sv * bfhi(v[i].w);
            }
            float* red = (float*)(smraw + SM_PRE);
            *(float4*)(red + (tid >> 4) * 128 + (tid & 15) * 8) = make_float4(acc[0], acc[1], acc[2], acc[3]);
            *(float4*)(red + (tid >> 4) * 128 + (tid & 15) * 8 + 4) = make_float4(acc[4], acc[5], acc[6], acc[7]);
            bar_sync(NB_FIN0, 256);
            if (wid < 4) {
                float t = 0;
#pragma unroll
                for (int i = 0; i < 16; i++) t += red[i * 128 + tid];
                stg_rlx1(&g_modp[(b >> 4) * 2 * DM + cb + tid], __float_as_uint(t) | 1u);
                TLX(14)
            }
        } else {
            rec_ln(sb, p.x, p.arena, b - 128, 0);
        }
    } else if (wid >= 10 && b >= 128) {
        {
            const int w = (b - 128) * 2 + wid - 10;
            const uint16_t* src = (const uint16_t*)p.mem0 + (lane & 3) * 2 * DM + (w >> 2) * 512 + (w & 1) * 64 + (w & 2) * 8 + (lane >> 2);
            uint32_t v[4][4];
#pragma unroll
            for (int i = 0; i < 16; i++) v[i >> 2][i & 3] = src[(i >> 2) * 128 + (i & 2) * 16 + (i & 1) * 8] | ((uint32_t)src[DM + (i >> 2) * 128 + (i & 2) * 16 + (i & 1) * 8] << 16);
            uint8_t* d = arena + mem_row(w >> 2, w & 3, 0);
            uint8_t* e = d + 512 + (CNT32 ? lane >> 1 : lane) * 4;
            d += lane * 16;
#pragma unroll
            for (int i = 0; i < 4; i++, d += 1024, e += 1024) {
                stg_rlx4(d, v[i][0], v[i][1], v[i][2], CNT32 && !(lane & 1) ? v[i][3] : (v[i][3] & 0xffff) | CNT_ALL << 16);
                stg_rlx4(d + mem_slot(1), 0, 0, 0, 0);
                stg_rlx4(d + mem_slot(2), 0, 0, 0, 0);
                if (!CNT32 || (lane & 1)) { stg_rlx1(e, (v[i][3] & 0xffff0000u) | CNT_ALL); stg_rlx1(e + mem_slot(1), 0); stg_rlx1(e + mem_slot(2), 0); }
            }
            if (w == 0 && lane < 8) stg_rlx2(arena + (LB_TIME << 13) + lane * 1024, 0, 0);
            bar_arrive(NB_C, 320);
        }
    } else if (rank == 0) {
        uint32_t best = ~0u;
        const int pg = wid < 10 ? 0 : 1 + (b >> 1) / 22;
        uint32_t* q = (uint32_t*)(arena + (pg << 21) + (pg ? blk(b >> 1, wid & 1) : blk(LB_PROBE, wid & 1) + b * 16));
        if (lane < 8) stg_rlx1(q + lane, 0);
        __syncwarp();
        if (lane == 0) {
            q += 3;
            uint32_t v = atomicAdd(q, 1u);
#pragma unroll 1
            for (int r = 0; r < NPROBE; r++) {
                const uint32_t t0 = clk32() + (v >> 8);
                v = atomicAdd(q + (v >> 8), 1u);
                uint32_t t1;
                asm volatile("{.reg .pred p; setp.eq.u32 p, %1, 0xffffffff; @p exit; mov.u32 %0, %%clock;}" : "=r"(t1) : "r"(v) : "memory");
                best = min(best, t1 - t0);
            }
            sinfo[wid - 6] = best;
        }
        bar_sync(NB_KDONE, b < 128 ? 128 : 64);
        if (tid == 256) {
            const uint32_t par = sinfo[2] > sinfo[3], vote = b < 128 && (sinfo[4] > sinfo[5]) != par;
            stg_rlx2(&g_clk[b >> 1], ((clk32() - 2 * gtime()) & ~127u) | b >> 1, 1 + 2 * par + 4 * vote);
        }
    }
    if (wid == 8) {
        U2 v[3], my;
        uint32_t c0;
        const int me = b >> 1;
        int it = 0;
        __syncwarp();
#pragma unroll 1
        do {
            my = ldg_u2(&g_clk[me]);
#pragma unroll
            for (int k = 0; k < 3; k++) v[k] = ldg_u2(&g_clk[k * 22 + min(lane, 21)]);
        } while (!__all_sync(~0u, my.y & v[0].y & v[1].y & v[2].y & 1) & (++it < SPIN_LIMIT));
        TLX(15)
        c0 = __reduce_min_sync(~0u, lane ? ~0u : v[0].x) - 4096;
        const uint32_t mc = me >= 64 ? ~0u : my.x - c0;
        const int par = my.y >> 1 & 1;
        uint32_t cnt = 0, flip = 0;
#pragma unroll
        for (int k = 0; k < 3; k++) {
            const uint32_t c = v[k].x - c0, o = v[k].y >> 1 & 1;
            const bool ln = k == 2 && lane >= 20;
            cnt += o + (o == par ? (ln ? 44 + lane < me : c < mc) * 256 + (c < my.x - c0) * 65536 : 0);
            flip |= __popc(__ballot_sync(~0u, v[k].y & 4) & 0x3fffff) > 10 ? 256 << k : 0;
        }
        cnt = __reduce_add_sync(~0u, lane < 22 ? cnt : 0);
        const int n1 = cnt & 255, n0 = 66 - n1, tk = cnt >> 8 & 255;
        if (lane == 0) g_cls[smid() & 255] = cnt < 32 << 16 ? par * 4 + (cnt >> 19) : 8;
        hA = min(n0 >> 1, NH);
        const int q0 = 2 * hA, q1 = 2 * NH - q0;
        const int over = tk - (par ? q1 : q0), lack = max(par ? q0 - n0 : q1 - n1, 0);
        if (over < 0) pr = par ? q0 + tk : tk;
        else if (over < lack) pr = (par ? n0 : q0 + n1) + over;
        else pr = -1 - (over - lack + (par ? max(n0 - q0, 0) : 0));
        hA |= flip;
        if (lane == 0) {
            sinfo[1] = hA; sinfo[0] = pr;
            if (b >= 128 && rank == 0) atomicOr(&g_tick[6], (pr < 0 ? 4u : 1u) << ((b - 128) >> 1));
        }
    }
    asm volatile("barrier.cluster.wait.aligned;" ::: "memory");
    if (wid == 8) {
        TL(1)
        __syncwarp();
        bar_arrive(NB_A, 288);
        bar_arrive(NB_S, 128);
        if (b >= 128 && pr < 0) bar_sync(NB_B, 64);
        if (pr >= 0) {
            const int pu = __reduce_max_sync(~0u, pr), c0 = (pu >> 1) * 128 + rank * 64, r0 = (pu & 1) * 512;
#pragma unroll 1
            for (int n = 0; n < 13; n++) {
                const u64 seq = b >= 128 ? LN_SEQ : 0xcba9876543210ull;
                const int i = seq >> (4 * n) & 15;
                if (b >= 128 && i == 0) bar_sync(NB_B, 64);
                if (n >= W_INFL) mbar_wait_w(bars + 8 * (B_W + (seq >> (4 * (n - W_INFL)) & 15)), 0);
                const int m = i < 8 ? i & 1 : i >> 2, k = i < 8 ? i >> 1 : i & 3;
                const uint32_t dst = sb + m * 65536 + k * 16384, br = bars + 8 * (m < 3 ? B_W + i : B_WO);
                const int c = m < 3 ? c0 : 576 + rank * 256 + (pu & 1) * 128, r = m < 3 ? r0 + k * 128 : (pu >> 1) * DH;
                const uint64_t pol = m < 3 ? EVICT_FIRST : EVICT_NORMAL;
                e_expect(br, 16384);
                e_tma2d_hint(dst, &mp.wq + m, c, r, br, pol);
                e_tma2d_hint(dst + 8192, &mp.wq + m, c, r + 64, br, pol);
            }
        }
    } else {
        bar_sync(wid < 8 ? NB_A : NB_S, wid < 8 ? 288 : 128);
    }
    const int prr = __reduce_max_sync(~0u, sinfo[0]);
    hA = __reduce_max_sync(~0u, sinfo[1]);
    if (prr < 0) {
        int j = (b - 128) >> 1;
        if (b < 128) {
            uint32_t v;
            int it = 0;
#pragma unroll 1
            do { v = __reduce_max_sync(~0u, ldg_rlx1(&g_tick[6])); spin_guard(++it); } while (__popc(v) < 2);
            j = v == 3 ? -1 - prr : (v & 1) ^ 1;
        }
        rec_side((float*)smraw, mp, p, j * 2 + rank);
        return;
    }
    if (PDL) asm volatile("griddepcontrol.launch_dependents;" ::: "memory");
    const int role = (prr >> 1) * 4 + rank * 2 + (prr & 1);
    rec_main(sb, &mp.wo, arena, role, hA, wid >> 2, p.zero, p.dly);
}

__device__ __forceinline__ void wgmma_ss192(float* d, uint64_t a, uint64_t b, int sc) {
    asm volatile("{.reg .pred p; setp.ne.b32 p, %98, 0;\n wgmma.mma_async.sync.aligned.m64n192k16.f32.bf16.bf16 "
                 "{%0,%1,%2,%3,%4,%5,%6,%7,%8,%9,%10,%11,%12,%13,%14,%15,%16,%17,%18,%19,%20,%21,%22,%23,%24,%25,%26,%27,%28,%29,%30,%31,%32,%33,%34,%35,%36,%37,%38,%39,%40,%41,%42,%43,%44,%45,%46,%47,%48,%49,%50,%51,%52,%53,%54,%55,%56,%57,%58,%59,%60,%61,%62,%63,%64,%65,%66,%67,%68,%69,%70,%71,%72,%73,%74,%75,%76,%77,%78,%79,%80,%81,%82,%83,%84,%85,%86,%87,%88,%89,%90,%91,%92,%93,%94,%95}, %96, %97, p, 1, 1, 0, 1;}"
                 : F16(d, 0), F16(d, 16), F16(d, 32), F16(d, 48), F16(d, 64), F16(d, 80) : "l"(a), "l"(b), "r"(sc));
}

constexpr uint32_t P_B = 81920, P_PL = 40960, P_OUT = 180224, P_VEC = 212992, P_ROW = P_VEC + 6144, P_BAR = P_ROW + 4096, P_SMEM = P_BAR + 256;
#define PPH 1
#define FLAG_ST "st.release.gpu.global.u32"
#define FLAG_LD "ld.acquire.gpu.global.u32"
#define PX 0
#define MIDF 0
#define END_FAST 1
#define DS_AT 3
constexpr int ST = 5;
constexpr int PB_F = 0, PB_E = 5, PB_R = 10, PB_OUT = 16;
enum { C_Y = 0, C_G = 1, C_X1 = 2, C_U = 3, C_S1 = 8, C_S3 = 9 };
enum { V_GA = 0, V_A = 1, V_B = 2, V_GB = 3, V_VA = 4, V_VB = 5, V_VC = 6, V_C3 = 7 };
struct PostMaps { CUtensorMap o, wo, y, w1, g, w2, x1, w3, u, w4, out; };
struct PostPtrs { const bf16* x; };

struct GeluK { float k0, k1, kh; };
__device__ __forceinline__ GeluK gelu_k(float c) { return {0.7978845608028654f * c, 0.7978845608028654f * 0.044715f * c * c * c, 0.5f * c}; }
__device__ __forceinline__ float gelu_s(float t, const GeluK& k) {
    const float u = t * fmaf(t * t, k.k1, k.k0);
    float th; asm("tanh.approx.f32 %0, %1;" : "=f"(th) : "f"(u));
    const float hx = k.kh * t;
    return fmaf(hx, th, hx);
}
__device__ __forceinline__ float2 ldsv(uint32_t a) {
    float2 v; asm("ld.shared.v2.f32 {%0,%1}, [%2];" : "=f"(v.x), "=f"(v.y) : "r"(a)); return v;
}
__device__ __forceinline__ void wait_smem(uint32_t a, int target) {
    int it = 0;
#pragma unroll 1
    while (true) {
        int v;
        asm volatile("ld.acquire.cta.shared.u32 %0, [%1];" : "=r"(v) : "r"(a) : "memory");
        if (__all_sync(~0u, v >= target) | (++it > SPIN_LIMIT)) break;
    }
}

#define PP(i)
#define PH_(c, w, i)
__device__ __forceinline__ void mbar_wait_b(uint32_t b, uint32_t par) {
    int it = 0;
#pragma unroll 1
    while (!__all_sync(~0u, mbar_try(b, par)) & (++it < SPIN_LIMIT)) {}
}
__device__ __forceinline__ void release(uint32_t rel, int st, bool c) {
    asm volatile("{.reg .pred p; setp.ne.u32 p, %1, 0; setp.ne.and.u32 p, %2, 0, p; @p mbarrier.arrive.shared::cluster.b64 _, [%0];}"
                 ::"r"(rel + 8 * (st ? st - 1 : ST - 1)), "r"(rel), "r"((uint32_t)c) : "memory");
}
struct Pipe { int st, ph; uint32_t rel; };
__device__ __forceinline__ void adv(Pipe& p) { if (++p.st == ST) { p.st = 0; p.ph ^= 1; } }

__device__ __forceinline__ void post_weights(uint32_t sb, const PostMaps& mp, int nb, int rank) {
    const uint32_t full = sb + P_BAR + 8 * PB_F, empty = sb + P_BAR + 8 * PB_E;
    int st = 0, pp = 1;
#pragma unroll 1
    for (int ph = 0; ph < 7; ph++) {
        const int NK = ph == 0 ? 64 : ph == 6 ? 56 : 16, km = NK == 16 ? 15 : 63;
        const CUtensorMap* tb = &mp.wo + 2 * (ph < 3 ? ph : ph < 6 ? 3 : 4);
        const bool w3 = ph >= 3 && ph < 6;
        const int n0 = w3 ? nb * 64 + (ph == 4 ? 1536 : ph == 5 ? 2560 : 0) : nb * 128, dn = w3 ? 512 : 64;
        const int rot = NK == 16 ? 2 * (nb & 6) : 0, sw = ph == 1 || ph == 3 ? 2 * rank : 0;
#pragma unroll 1
        for (int i = 0; i < NK; i++) {
            const int k0 = (((i < 4 ? i ^ sw : i) + rot) & km) * 64;
            const uint32_t a = sb + P_B + st * 8192, f = full + 8 * st;
            mbar_wait_b(empty + 8 * st, pp);
            e_expect(f, ph == 3 ? 40960 : 32768);
            e_tma2d(a, tb, n0, k0, f);
            e_tma2d(a + P_PL, tb, n0 + dn, k0, f);
            if (ph == 3) e_tma2d(a + 2 * P_PL, tb, n0 + 1024, k0, f);
            if (++st == ST) { st = 0; pp ^= 1; }
        }
    }
#pragma unroll 1
    for (int i = 0; i < ST; i++) mbar_wait_b(empty + 8 * i, pp ^ (i < st));
}
__device__ __forceinline__ void post_acts(uint32_t sb, const PostMaps& mp, int mb, int nb, int rank) {
    const int rh = 2 * mb + rank, lane = threadIdx.x & 31;
    const uint32_t full = sb + P_BAR + 8 * PB_F, empty = sb + P_BAR + 8 * PB_E;
    int st = 0, pp = 1;
#pragma unroll 1
    for (int ph = 0; ph < 7; ph++) {
        const int NK = ph == 0 ? 64 : ph == 6 ? 56 : 16, km = NK == 16 ? 15 : 63;
        const CUtensorMap* ta = &mp.o + 2 * (ph < 3 ? ph : ph < 6 ? 3 : 4);
        const int amul = ph == 0 ? 256 : 64, arow = ph == 0 ? rh * 8 : rh * 64;
        const int rot = NK == 16 ? 2 * (nb & 6) : 0, own = ph == 1 || ph == 3 ? 4 : 0;
        const uint32_t shifts = ph == 2 ? 0x04000301u : 0x02020202u;
        const uint32_t* fl = &g_pflag[(ph == 6 ? C_U : min(ph - 1, 2)) * 256 + (ph == 2 ? min(max(rh + min(lane >> 3, 2) - 1, 0), 31) : rh) * 8 + (lane & 7)];
        uint32_t have = ph == 0 || ph == 5;
        if (own) { if (st) { st--; pp ^= 1; } else st = 4; }
#pragma unroll 1
        for (int i = own; i < NK; i++) {
            const int kb = (i + rot) & km;
            const uint32_t need = ph == 6 ? 255u : (ph == 2 ? 0x10101u : 1u) << ((kb >> 1) & 7), lvl = ph == 6 ? i >> 3 : 0;
            PH_(ph == PPH && i == own, 0, 27) PH_(ph == PPH && i == own, 1, 27)
            if ((__ballot_sync(~0u, have > lvl) & need) != need) {
                int it = 0;
#pragma unroll 1
                do asm volatile(FLAG_LD " %0, [%1];" : "=r"(have) : "l"(fl) : "memory");
                while (((__ballot_sync(~0u, have > lvl) & need) != need) & (++it < SPIN_LIMIT));
                PH_(ph == PPH && i == own, 0, 23) PH_(ph == PPH, 0, 24) PH_(ph == PPH && i == own, 1, 23) PH_(ph == PPH, 1, 24)
                asm volatile("fence.proxy.async.global;" ::: "memory");
            }
            const int d = own && (i == 5 || i == 6) ? 2 : 0, s2 = st + d < ST ? st + d : st + d - ST;
            mbar_wait_b(empty + 8 * s2, pp ^ (s2 < st));
            e_tma2d_mc(sb + st * 16384 + rank * 8192, ta, kb * amul, arow + (int)((shifts >> ((kb & 12) * 2)) & 7) - 2, full + 8 * st);
            if (++st == ST) { st = 0; pp ^= 1; }
        }
    }
}

template <int PH, bool EARLY = false, class F>
__device__ __forceinline__ void post_kb(uint32_t sb, float* acc, Pipe& p, int wg, bool lead, bool first, F mid) {
    constexpr uint64_t DA = PH == 0 ? mkdesc(SB0, 128, 1024, 0) : mkdesc(SB0, 16, 1024, 1);
    constexpr uint64_t DB = mkdesc(SB0 + P_B, P_PL, 1024, 1);
    mbar_wait_b(sb + P_BAR + 8 * PB_F + 8 * p.st, p.ph);
    const uint32_t a = (uint32_t)DA + p.st * 1024 + wg * 512, b = (uint32_t)DB + p.st * 512;
    wg_fence();
#pragma unroll
    for (int k = 0; k < 4; k++) {
        const uint64_t da = (DA & 0xffffffff00000000ull) | (a + k * (PH == 0 ? 16 : 2)), db = (DB & 0xffffffff00000000ull) | (b + k * 128);
        if (PH == 3) wgmma_ss192(acc, da, db, k || !first);
        else wgmma_ss128<PH == 0>(acc, da, db, k || !first);
    }
    wg_commit();
    if (EARLY) mid();
    wg_wait<1>();
    release(p.rel, p.st, !first);
    if (!EARLY) mid();
    adv(p);
}
__device__ __forceinline__ void post_end(uint32_t sb, Pipe& p, bool lead) {
    wg_wait<0>();
    release(p.rel, p.st, true);
}
template <int PH>
__device__ __forceinline__ void post_mma(uint32_t sb, float* acc, Pipe& p, int wg, bool lead, int nout, int pi, int mb, int nb) {
#pragma unroll 1
    for (int kb = 0; kb < 16; kb++)
        post_kb<PH>(sb, acc, p, wg, lead, kb == 0, [&]() {
            if (kb == 0) { PP(pi) }
            if (nout && kb == 0) wait_smem(sb + P_BAR + 8 * (PB_OUT + wg), nout);
        });
    post_end(sb, p, lead);
    PP(pi + 1)
}

__global__ void __cluster_dims__(2, 1, 1) __launch_bounds__(384, 1)
k_post(const __grid_constant__ PostMaps mp, const __grid_constant__ PostPtrs pp) {
    extern __shared__ uint8_t smraw[];
    const uint32_t sb = smem_u32(smraw);
    if ((sb & 0x3FFFF) != SB0) __trap();
    const int tid = threadIdx.x, lane = tid & 31;
    const int rank = blockIdx.x & 1;
    const uint32_t bars = sb + P_BAR;
    int c = 0;
    unsigned long long v = 0;
    const int wid = __reduce_max_sync(~0u, tid >> 5);
    const bool draw = tid == 352 && rank == 0;
    if (draw) {
        c = min(ldg_rlx1(&g_cls[smid() & 255]), 8u);
        asm volatile("{.reg .b64 a; cvt.u64.u32 a, %%laneid; add.u64 a, a, %1; atom.relaxed.gpu.global.add.u64 %0, [a], %2;}" : "=l"(v) : "l"(&g_pt), "l"(1ull << (7 * c)) : "memory");
    }
    if (wid < 11) {
        asm volatile("{.reg .pred p; elect.sync _|p, 0xffffffff; @p mbarrier.init.shared.b64 [%0], %1; @p prefetch.tensormap [%2]; fence.mbarrier_init.release.cluster;}"
                     ::"r"(bars + 8 * wid), "r"(wid >= PB_E && wid < PB_R ? 4 : 1), "l"(&mp.o + wid) : "memory");
        if (wid == PB_R) { sts4(bars + 8 * PB_OUT, 0, 0, 0, 0); e_expect(bars + 8 * PB_R, 4); }
    }
    __syncwarp();
    asm volatile("barrier.cluster.arrive.relaxed.aligned; barrier.cluster.wait.aligned;" ::: "memory");
    if (draw) {
        int r = (v >> (7 * c)) & 127, role = c * 8 + r;
        if (c == 8 || r >= 8) {
            int n, x, it = 0;
#pragma unroll 1
            do {
                __nanosleep(200);
                v = ldg_u64(&g_pt); n = 0; x = c < 8 ? r - 8 : r;
#pragma unroll 1
                for (int i = 0; i < 63; i += 7) { const int m = v >> i & 127; n += m; if (i < 7 * c) x += max(m - 8, 0); }
            } while (n < gridDim.x / 2 && ++it < SPIN_LIMIT);
            role = -1;
#pragma unroll 1
            for (int i = 0; i < 64; i += 8, v >>= 7) {
                n = v & 127;
                if (x >= 0 && n + x < 8) role = i + n + x;
                x -= max(8 - n, 0);
            }
        }
#pragma unroll
        for (int i = 0; i < 2; i++)
            asm volatile("{.reg .b32 d; mapa.shared::cluster.u32 d, %0, %2; st.async.shared::cluster.mbarrier::complete_tx::bytes.u32 [d+8], %1, [d];}"
                         ::"r"(bars + 8 * PB_R), "r"(role), "r"(i) : "memory");
    }
    __syncwarp();
    mbar_wait_b(bars + 8 * PB_R, 0);
    const int pr = __reduce_max_sync(~0u, (int)lds1(bars + 8 * PB_R + 8));
    if (pr < 0) return;
    const int mb = (pr >> 5) * 8 + (pr & 7), nb = (pr >> 2 & 6) + rank, cta = pr * 2 + rank;
    if (wid >= 8) {
        asm volatile("setmaxnreg.dec.sync.aligned.u32 40;");
        const int w = wid - 8;
        if (w == 0) {
            post_weights(sb, mp, nb, rank);
        } else if (w == 3) {
            asm volatile("griddepcontrol.wait;" ::: "memory");
            TLP(15)
            post_acts(sb, mp, mb, nb, rank);
        } else {
            const int wg = w - 1, rh = 2 * mb + wg;
            float* rowc = (float*)(smraw + P_ROW) + (wg * 64 + lane * 2) * 8;
            int nout = 0, sig = 0;
#pragma unroll 1
            for (int i = 0; i < 13; i++) {
                const int cnt = (0x4333333392180ull >> (4 * i)) & 15;
                if (cnt < C_S1) {
                    const int ng = cnt == C_U ? 1 : 2, c0 = cnt == C_U ? (i - 5) * 512 + nb * 64 : nb * 128;
                    const bool fast = (cnt == C_Y || cnt == C_X1);
#pragma unroll 1
                    for (int j = 0; j < ng; j++) {
                        const uint32_t st = j ? cnt : cnt ? 1 : 4;
                        const uint32_t src = sb + (fast ? st * 16384 + wg * 8192 : P_OUT + wg * 16384 + ((nout + j) & 1) * 8192);
                        bar_sync(4 + 4 * wg + (sig++ & 3), 160);
                        if (lane == 0) {
                            PH_(cnt == PPH - 1, wg, 20)
                            if (fast) asm volatile("mbarrier.complete_tx.relaxed.cta.shared::cta.b64 [%0], 8192;" ::"r"(bars + 8 * (PB_F + st)) : "memory");
                            asm volatile("cp.async.bulk.tensor.2d.global.shared::cta.bulk_group [%0, {%2, %3}], [%1]; cp.async.bulk.commit_group;"
                                         ::"l"(&mp.y + 2 * cnt), "r"(src), "r"(c0 + j * 64), "r"(rh * 64) : "memory");
                        }
                        __syncwarp();
                    }
                    if (lane == 0) {
                        auto to_peer = [&]() {
                            const uint32_t n = cnt ? 1 : 4;
                            mbar_wait(bars + 8 * (PB_E + (cnt ? 4 : 2)), 0);
#pragma unroll
                            for (int i = 0; i < 2; i++)
                                asm volatile("{.reg .b32 d, m; mapa.shared::cluster.u32 d, %0, %3; mapa.shared::cluster.u32 m, %2, %3;\n"
                                             " cp.async.bulk.shared::cluster.shared::cta.mbarrier::complete_tx::bytes [d], [%1], 8192, [m];}"
                                             ::"r"(sb + (cnt + 1 + i) * 16384 + wg * 8192), "r"(sb + (i ? cnt : n) * 16384 + wg * 8192), "r"(bars + 8 * (PB_F + cnt + 1 + i)), "r"(rank ^ 1) : "memory");
                        };
                        if (DS_AT == 1 && fast) to_peer();
                        asm volatile("cp.async.bulk.wait_group 0; fence.proxy.async.global;" ::: "memory");
                        asm volatile("st.release.cta.shared.u32 [%0], %1;" ::"r"(bars + 8 * (PB_OUT + wg)), "r"(nout + ng) : "memory");
                        PH_(cnt == PPH - 1, wg, 21)
                        if (DS_AT == 2 && fast) to_peer();
                        if (i < 12 || !END_FAST) asm volatile(FLAG_ST " [%0], %1;" ::"l"(&g_pflag[cnt * 256 + rh * 8 + nb]), "r"(max(i - 4, 1)) : "memory");
                        PH_(cnt == PPH - 1, wg, 22)
                        if (DS_AT == 3 && fast) to_peer();
                    }
                    nout += ng;
                    __syncwarp();
                    continue;
                }
                bar_sync(4 + 4 * wg + (sig++ & 3), 160);
                uint32_t* c = &g_pcnt[(cnt - C_S1) * 256 + rh * 8];
                if (lane == 0) { signal_count(c); wait_count1(c, 8); }
                __syncwarp();
                const float4* sp = (const float4*)g_st + rh * 32 + lane;
                float4 u[3] = {__ldcg(sp + (cnt == C_S1 ? 0 : 3) * (S_ / 2)), __ldcg(sp + S_ / 2), __ldcg(sp + S_)};
#pragma unroll 1
                for (int h = 0; h < 2; h++) {
                    const float id = 1.0f / DM;
                    const float m = u[0].x * id, var = fmaxf(u[0].y * id - m * m, 0.f) + 1e-5f, r = rsqrtf(var);
                    float sc = r, m2 = 0.f;
                    if (cnt == C_S1) {
                        m2 = r * (u[1].x * id - m * g_cst[0]) + g_cst[3];
                        const float e2 = r * r * (u[2].x * id - 2.0f * m * u[1].y * id + m * m * g_cst[1]) + 2.0f * r * (u[2].y * id - m * g_cst[2]) + g_cst[4];
                        sc = r * rsqrtf(fmaxf(e2 - m2 * m2, 0.f) + 1e-5f);
                    }
                    const GeluK k = gelu_k(sc);
                    *(float4*)(rowc + h * 8) = make_float4(k.k0, k.k1, k.kh, -m);
                    *(float4*)(rowc + h * 8 + 4) = make_float4(var * r, -m2 * var * r, r, -m * r);
#pragma unroll
                    for (int q = 0; q < 3; q++) { u[q].x = u[q].z; u[q].y = u[q].w; }
                }
                bar_arrive(1 + wg, 160);
            }
        }
    } else {
        asm volatile("setmaxnreg.inc.sync.aligned.u32 232;");
        const bf16* xin = pp.x;
        const int wg = wid >> 2, wi = (tid >> 5) & 3, g = lane >> 2, tq = lane & 3;
        const int rh = 2 * mb + wg, row = rh * 64 + wi * 16 + g;
        const bool lead = (tid & 127) == 0;
        PP(0)
        if (tid == 0) TLP(10)
        uint32_t keep[32];
#pragma unroll
        for (int i = 0; i < 8; i++)
            *(uint4*)(keep + 4 * i) = __ldg((const uint4*)(xin + (size_t)(rh * 64 + wi * 16 + (i & 3) * 4 + (lane >> 3)) * DM + nb * 128 + (i >> 2) * 64 + (lane & 7) * 8));
        asm volatile("griddepcontrol.wait;" ::: "memory");
        if (cta < 64) g_modp[cta * 256 + tid] = 0;
        if (cta == 64 && tid < 196) g_tick[tid] = 0;
        const float* src = wg ? g_vec + nb * 128 + tid - 128 : g_mod + 2 * DM + nb * 128 + tid;
        const float* c3 = &g_vec[3 * DM + (tid >> 6) * 512 + nb * 64 + (tid & 63)];
        const float cv[6] = {__ldcg(src), __ldcg(src + (wg ? 1 : 2) * DM), __ldcg(src + (wg ? 2 : 1) * DM), __ldcg(src + 3 * DM), __ldcg(c3), __ldcg(c3 + (tid < 192 ? 2048 : 0))};
        uint32_t vec = sb + P_VEC + tq * 8;
        const uint32_t stw = sb + (wi * 16 + ((lane >> 3) & 1) * 8 + (lane & 7)) * 128 + (((lane >> 4) ^ (lane & 7)) << 4);
        int sig = 0;
        auto signal = [&]() { bar_arrive(4 + 4 * wg + (sig++ & 3), 160); };
        auto put64 = [&](uint32_t o, const float* v) {
#pragma unroll
            for (int jj = 0; jj < 4; jj++, v += 8) stsm4((stw + o) ^ (jj << 5), pack2(v[0], v[1]), pack2(v[2], v[3]), pack2(v[4], v[5]), pack2(v[6], v[7]));
            fence_async_smem();
            signal();
        };
        auto slot = [&](int n) {
            mbar_wait_b(bars + 8 * (PB_E + n % 5), ((n / 5) & 1) ^ 1);
            return (n % 5) * 16384 + wg * 8192;
        };
        const uint32_t rowc = sb + P_ROW + (wg * 64 + wi * 16 + g) * 32, o128 = P_OUT + wg * 16384;
        Pipe pa = {0, 0, 0};
        asm("mapa.shared::cluster.u32 %0, %1, %2;" : "=r"(pa.rel) : "r"(bars + 8 * PB_E), "r"(tid & 1));
        if (tid & 126) pa.rel = 0;
#define KEEP(jn, e) (((e) & 1) ? bfhi(keep[2 * (jn) + ((e) >> 1)]) : bflo(keep[2 * (jn) + ((e) >> 1)]))
        float mu1[2], r1[2];
        {
            float acc[64];
#pragma unroll 1
            for (int kb = 0; kb < 64; kb++) {
                post_kb<0>(sb, acc, pa, wg, lead, kb == 0, []() {});
                if (kb == 0) { PP(1) if (wg == 0) TLP(11) }
                if (kb == 24) bar_sync(3, 256);
                if (kb != 8 + 8 * wg) continue;
                float* sv = (float*)(smraw + P_VEC) + tid;
                const uint32_t xo = sb + o128 + wi * 2048 + (lane >> 3) * 128;
#pragma unroll
                for (int i = 0; i < 8; i++) sts4(xo + (i >> 2) * 8192 + (i & 3) * 512 + (((lane & 7) ^ ((i & 1) * 4 + (lane >> 3))) << 4), keep[4 * i], keep[4 * i + 1], keep[4 * i + 2], keep[4 * i + 3]);
                __syncwarp();
#pragma unroll
                for (int jj = 0; jj < 8; jj++) ldsm4(keep + jj * 4, (stw + o128 + (jj >> 2) * 8192) ^ ((jj & 3) << 5));
                sv[wg * 384] = cv[0]; sv[wg * 384 + 128] = cv[1] + (wg ? 0.0f : 1.0f); sv[wg * 384 + 256] = cv[2];
                if (!wg) sv[384] = cv[3];
                sv[V_C3 * 128] = cv[4]; sv[V_C3 * 128 + 256] = cv[5];
            }
            post_end(sb, pa, lead);
            PP(2)
            asm volatile("" : "+r"(vec) :: "memory");
            float st[2][6];
#pragma unroll
            for (int q = 0; q < 6; q++) st[0][q] = st[1][q] = 0.f;
#pragma unroll
            for (int jn = 0; jn < 16; jn++) {
                const float2 ga = ldsv(vec + V_GA * 512 + jn * 32), a = ldsv(vec + V_A * 512 + jn * 32);
                float xa[4];
#pragma unroll
                for (int e = 0; e < 4; e++) {
                    xa[e] = fmaf((e & 1) ? ga.y : ga.x, acc[4 * jn + e], KEEP(jn, e));
                    st[e >> 1][0] += xa[e]; st[e >> 1][1] = fmaf(xa[e], xa[e], st[e >> 1][1]);
                    acc[4 * jn + e] = ((e & 1) ? a.y : a.x) * xa[e];
                }
                keep[2 * jn] = pack2(xa[0], xa[1]); keep[2 * jn + 1] = pack2(xa[2], xa[3]);
                if ((jn & 7) == 7) put64(slot(64 + (jn >> 3)), acc + 4 * jn - 28);
            }
            PP(3)
#pragma unroll
            for (int jn = 0; jn < 16; jn++) {
                const float2 a = ldsv(vec + V_A * 512 + jn * 32), b = ldsv(vec + V_B * 512 + jn * 32);
#pragma unroll
                for (int e = 0; e < 4; e++) {
                    const float y = acc[4 * jn + e], aa = (e & 1) ? a.y : a.x, bb = (e & 1) ? b.y : b.x;
                    float* s = st[e >> 1];
                    s[2] += y; s[3] = fmaf(aa, y, s[3]); s[4] = fmaf(y, y, s[4]); s[5] = fmaf(bb, y, s[5]);
                }
            }
#pragma unroll
            for (int h = 0; h < 2; h++)
#pragma unroll
                for (int q = 0; q < 6; q++) { st[h][q] += __shfl_xor_sync(~0u, st[h][q], 1); st[h][q] += __shfl_xor_sync(~0u, st[h][q], 2); }
            if (tq < 3 && !(PX & 1)) {
#pragma unroll
                for (int h = 0; h < 2; h++)
                    red2(g_st + (tq * S_ + row + h * 8) * 2, tq == 0 ? st[h][0] : tq == 1 ? st[h][2] : st[h][4], tq == 0 ? st[h][1] : tq == 1 ? st[h][3] : st[h][5]);
            }
            signal();
            PP(29)
        }
        {
            float acc[64];
            post_mma<1>(sb, acc, pa, wg, lead, 2, 4, mb, nb);
            float c1[2], c2[2], c3[2];
            GeluK gk[2];
            bar_sync(1 + wg, 160);
#pragma unroll
            for (int h = 0; h < 2; h++) {
                const float4 a = lds4f(rowc + h * 256), b = lds4f(rowc + h * 256 + 16);
                gk[h] = {a.x, a.y, a.z}; c1[h] = a.w; c2[h] = b.x; c3[h] = b.y; mu1[h] = b.w; r1[h] = b.z;
            }
#pragma unroll
            for (int jn = 0; jn < 16; jn++) {
                const float2 va = ldsv(vec + V_VA * 512 + jn * 32), vb = ldsv(vec + V_VB * 512 + jn * 32), vc = ldsv(vec + V_VC * 512 + jn * 32);
#pragma unroll
                for (int e = 0; e < 4; e++) {
                    const int h = e >> 1;
                    const float t = fmaf(c1[h], (e & 1) ? va.y : va.x, fmaf(c2[h], (e & 1) ? vb.y : vb.x, fmaf(c3[h], (e & 1) ? vc.y : vc.x, acc[4 * jn + e])));
                    acc[4 * jn + e] = gelu_s(t, gk[h]);
                }
                if ((jn & 7) == 7) put64(o128 + (jn >> 3) * 8192, acc + 4 * jn - 28);
            }
            PP(6)
        }
        {
            float acc[64];
            post_mma<2>(sb, acc, pa, wg, lead, 0, 7, mb, nb);
#pragma unroll
            for (int jn = 0; jn < 16; jn++) {
                const float2 a = ldsv(vec + V_A * 512 + jn * 32), b = ldsv(vec + V_B * 512 + jn * 32);
#pragma unroll
                for (int e = 0; e < 4; e++) {
                    const int h = e >> 1;
                    acc[4 * jn + e] += fmaf(fmaf(KEEP(jn, e), r1[h], mu1[h]), (e & 1) ? a.y : a.x, (e & 1) ? b.y : b.x);
                }
                if ((jn & 7) == 7) put64(slot(96 + (jn >> 3)), acc + 4 * jn - 28);
            }
            BLOCK_FENCE
#pragma unroll
            for (int i = 0; i < 64; i += 16) asm volatile("" : F16(acc, i));
            PP(9)
            float st[2][2] = {{0.f, 0.f}, {0.f, 0.f}};
#pragma unroll
            for (int jn = 0; jn < 16; jn++) {
                const float2 gb = ldsv(vec + V_GB * 512 + jn * 32);
                float z[4];
#pragma unroll
                for (int e = 0; e < 4; e++) {
                    const float x1 = acc[4 * jn + e];
                    st[e >> 1][0] += x1; st[e >> 1][1] = fmaf(x1, x1, st[e >> 1][1]);
                    z[e] = fmaf((e & 1) ? gb.y : gb.x, x1, KEEP(jn, e));
                }
                keep[2 * jn] = pack2(z[0], z[1]); keep[2 * jn + 1] = pack2(z[2], z[3]);
            }
#pragma unroll
            for (int h = 0; h < 2; h++)
#pragma unroll
                for (int q = 0; q < 2; q++) { st[h][q] += __shfl_xor_sync(~0u, st[h][q], 1); st[h][q] += __shfl_xor_sync(~0u, st[h][q], 2); }
            if (tq < 2) red2(g_st + (3 * S_ + row + tq * 8) * 2, tq ? st[1][0] : st[0][0], tq ? st[1][1] : st[0][1]);
            signal();
            PP(30)
        }
        {
            float old[96], acc[64];
            post_mma<3>(sb, old, pa, wg, lead, 6, 10, mb, nb);
#pragma unroll
            for (int i = 0; i < 96; i += 16) asm volatile("" : F16(old, i));
            uint32_t v3 = vec + V_C3 * 512;
            bar_sync(1 + wg, 160);
            const float4 rc[2] = {lds4f(rowc), lds4f(rowc + 256)};
            float2 vc[2] = {lds2f(v3), lds2f(v3 + 32)};
            bar_sync(3, 256);
#pragma unroll 1
            for (int blk = 0; blk < 11; blk++) {
                const uint32_t o = stw + o128 + (blk & 1) * 8192;
                const int turn = blk < 7 ? wg : 2;
#pragma unroll
                for (int q = 0; q < 4; q++) {
#pragma unroll 1
                    for (int rep = 0; rep < 2; rep++) {
                        post_kb<1, MIDF>(sb, acc, pa, wg, lead, q == 0 && rep == 0 && blk < 6 && !(blk & 1), [&]() {
                        if (rep != turn) return;
                        asm volatile("" : F4(old, 8 * q), F4(old, 8 * q + 4));
                        const float2 vn[2] = {lds2f(v3 + q * 64 + 64), lds2f(v3 + q * 64 + 96)};
                        float t[8];
#pragma unroll
                        for (int i = 0; i < 8; i++) {
                            const float4& c = rc[(i >> 1) & 1];
                            t[i] = gelu_s(fmaf(c.w, (i & 1) ? vc[i >> 2].y : vc[i >> 2].x, old[8 * q + i]), GeluK{c.x, c.y, c.z});
                            old[8 * q + i] = old[32 + 8 * q + i];
                            old[32 + 8 * q + i] = old[64 + 8 * q + i];
                        }
                        stsm4(o ^ (q << 5), pack2(t[0], t[1]), pack2(t[2], t[3]), pack2(t[4], t[5]), pack2(t[6], t[7]));
                        vc[0] = vn[0]; vc[1] = vn[1];
                        if (q == 2) wait_smem(bars + 8 * (PB_OUT + wg), 6 + blk);
                        if (q == 3) { fence_async_smem(); signal(); }
                        });
                    }
                }
                v3 += 256;
                if (blk != 1 && blk != 3) continue;
                post_end(sb, pa, lead);
                PP(12 + blk)
                asm volatile("" : F16(acc, 0), F4(acc, 16), F4(acc, 20), F4(acc, 24));
                asm volatile("" : F16(acc, 28), F4(acc, 44), F4(acc, 48), F4(acc, 52));
                asm volatile("" : F4(acc, 56), F4(acc, 60));
#pragma unroll
                for (int i = 0; i < 64; i++) old[32 + i] = acc[i];
            }
            post_end(sb, pa, lead);
            PP(17)
#pragma unroll
            for (int jn = 0; jn < 16; jn++) {
                const float2 gb = ldsv(vec + V_GB * 512 + jn * 32);
#pragma unroll
                for (int e = 0; e < 4; e++) acc[4 * jn + e] = fmaf((e & 1) ? gb.y : gb.x, acc[4 * jn + e], KEEP(jn, e));
                if ((jn & 7) == 7) put64(o128 + ((jn >> 3) ^ 1) * 8192, acc + 4 * jn - 28);
            }
            PP(18)
            if (tid == 0) TLP(12)
        }
    }
}

typedef CUresult (*EncFn)(CUtensorMap*, CUtensorMapDataType, cuuint32_t, void*, const cuuint64_t*, const cuuint64_t*, const cuuint32_t*,
                          const cuuint32_t*, CUtensorMapInterleave, CUtensorMapSwizzle, CUtensorMapL2promotion, CUtensorMapFloatOOBfill);

static CUtensorMap make_map(EncFn enc, const void* p, uint64_t inner, uint64_t outer, uint32_t bi = 64) {
    CUtensorMap m;
    cuuint64_t dims[2] = {inner, outer};
    cuuint64_t str[1] = {inner * 2};
    cuuint32_t box[2] = {bi, bi == 64 ? 64u : 16u};
    cuuint32_t es[2] = {1, 1};
    enc(&m, CU_TENSOR_MAP_DATA_TYPE_BFLOAT16, 2, (void*)p, dims, str, box, es, CU_TENSOR_MAP_INTERLEAVE_NONE,
        bi == 64 ? CU_TENSOR_MAP_SWIZZLE_128B : CU_TENSOR_MAP_SWIZZLE_NONE, CU_TENSOR_MAP_L2_PROMOTION_L2_256B, CU_TENSOR_MAP_FLOAT_OOB_FILL_NONE);
    return m;
}
static CUtensorMap make_map_o(EncFn enc, const void* p) {
    CUtensorMap m;
    cuuint64_t dims[2] = {16384, 256};
    cuuint64_t str[1] = {65536};
    cuuint32_t box[2] = {256, 8};
    cuuint32_t es[2] = {1, 1};
    enc(&m, CU_TENSOR_MAP_DATA_TYPE_UINT32, 2, (void*)p, dims, str, box, es, CU_TENSOR_MAP_INTERLEAVE_NONE, CU_TENSOR_MAP_SWIZZLE_NONE,
        CU_TENSOR_MAP_L2_PROMOTION_L2_256B, CU_TENSOR_MAP_FLOAT_OOB_FILL_NONE);
    return m;
}
template <class T> static T* sym(T& s) { void* p = nullptr; cudaGetSymbolAddress(&p, s); return (T*)p; }

static const Delays h_dly = {D_NEAR, D_FAR, D_X2, D_V, D_W2, D_PA, D_WF, D_TV};
extern "C" void kernel_launch(void* const* d_in, const int* in_sizes, int n_in, void* d_out, int out_size) {
    const bf16* x = (const bf16*)d_in[0];
    const bf16* mem0 = (const bf16*)d_in[1];
    const bf16 *Wq = (const bf16*)d_in[2], *Wk = (const bf16*)d_in[3], *Wv = (const bf16*)d_in[4], *Wo = (const bf16*)d_in[5];
    const bf16 *w1 = (const bf16*)d_in[8], *w2 = (const bf16*)d_in[9], *w3 = (const bf16*)d_in[10], *w4 = (const bf16*)d_in[11];
    const bf16 *c = (const bf16*)d_in[12], *wmod = (const bf16*)d_in[13];
    bf16* out = (bf16*)d_out;

    EncFn enc = nullptr;
    cudaDriverEntryPointQueryResult qr;
    cudaGetDriverEntryPoint("cuTensorMapEncodeTiled", (void**)&enc, cudaEnableDefault, &qr);
    CUtensorMap tWq = make_map(enc, Wq, NH * DH, DM), tWk = make_map(enc, Wk, NH * DH, DM), tWv = make_map(enc, Wv, NH * DH, DM);
    PostMaps mp;
    mp.o = make_map_o(enc, sym(g_O)); mp.wo = make_map(enc, Wo, DM, NH * DH);
    mp.y = make_map(enc, sym(g_y), DM, S_); mp.w1 = make_map(enc, w1, DM, DM);
    mp.g = make_map(enc, sym(g_g), DM, S_); mp.w2 = make_map(enc, w2, DM, DM);
    mp.x1 = make_map(enc, sym(g_x1), DM, S_); mp.w3 = make_map(enc, w3, FF, DM);
    mp.u = make_map(enc, sym(g_u), FF, S_); mp.w4 = make_map(enc, w4, DM, FF);
    mp.out = make_map(enc, out, DM, S_);
    cudaFuncSetAttribute(k_rec, cudaFuncAttributeMaxDynamicSharedMemorySize, SM_REC_TOTAL + 2048);
    cudaFuncSetAttribute(k_post, cudaFuncAttributeMaxDynamicSharedMemorySize, P_SMEM);

    uint8_t* arena = (uint8_t*)(((uintptr_t)sym(g_arena) + (2u << 20) - 1) & ~(uintptr_t)((2u << 20) - 1));
    const PostPtrs pp = {x};
    const RecPtrs rp = {x, mem0, c, wmod, w1, w3, arena, 0u, w2, w4, Wo, h_dly};
    const RecMaps rm = {tWq, tWk, tWv, mp.wo, make_map(enc, wmod, 6 * DM, DM, 256), make_map(enc, w3, FF, DM, 256), make_map(enc, w1, DM, DM, 256)};
    k_rec<<<132, 384, SM_REC_TOTAL + 2048>>>(rm, rp);
    cudaLaunchConfig_t cfg = {};
    cfg.gridDim = dim3(132); cfg.blockDim = dim3(384); cfg.dynamicSmemBytes = P_SMEM; cfg.stream = cudaStreamPerThread;
    cudaLaunchAttribute at[1];
    at[0].id = cudaLaunchAttributeProgrammaticStreamSerialization; at[0].val.programmaticStreamSerializationAllowed = PDL;
    cfg.attrs = at; cfg.numAttrs = 1;
    cudaLaunchKernelEx(&cfg, k_post, mp, pp);
}
```

```cpp
#include <cuda_runtime.h>
#include <cuda.h>
#include <cuda_bf16.h>
#include <stdint.h>
#include <limits.h>

typedef __nv_bfloat16 bf16;

constexpr int S_ = 2048, DM = 1024, NH = 32, DH = 128, NSEG = 64, FF = 3584;
constexpr int SPIN_LIMIT = 1 << 22;
#define W_INFL 2
#define H_PIECES 4
#define PDL 1
#define NPROBE 3

__device__ uint8_t g_arena[10 << 20];
__device__ __align__(128) uint32_t g_tick[64 + 132];
#define g_clk ((uint2*)(g_tick + 64))
__device__ uint32_t g_cls[256];
__device__ unsigned long long g_pt;
__device__ __align__(16) uint32_t g_modp[8 * 2 * DM];
__host__ __device__ constexpr uint32_t blk(uint32_t lb, uint32_t par) {
    return (lb << 13) | ((((lb) ^ (lb >> 3) ^ (lb >> 4) ^ (lb >> 6) ^ par) & 1) << 12);
}
__host__ __device__ constexpr uint32_t lb_x2(uint32_t h) { return (h & 1) | ((h >> 1) << 3); }
__host__ __device__ constexpr uint32_t mem_row(uint32_t kh, uint32_t b, uint32_t r) { return blk(128 | b, kh) + r * 1024; }
__device__ __forceinline__ uint32_t mem_slot(uint32_t s) { return ((s & 1) << 15) | ((s & 2) << 17); }
constexpr uint32_t CNT1 = 0x3d80, CNT_ALL = 0x4000;
constexpr uint32_t LB_PROBE = 6 | 64, LB_TIME = 6;
__host__ __device__ constexpr uint32_t lb_tok(uint32_t h) { return (h & 1) | ((h >> 1) << 3); }
__device__ float g_mod[6 * DM];
__device__ __align__(1024) bf16 g_himg[(S_ + 32) * DM];
__device__ __align__(1024) bf16 g_O[S_ * NH * DH];
__device__ __align__(1024) bf16 g_y[S_ * DM];
__device__ __align__(1024) bf16 g_g[S_ * DM];
__device__ __align__(1024) bf16 g_x1[S_ * DM];
__device__ __align__(16) float g_st[4 * S_ * 2];
__device__ float g_vec[3 * DM + FF];
__device__ float g_cst[8];
__device__ uint32_t g_pcnt[2 * 32 * 8], g_pflag[7 * 32 * 8];
__device__ __align__(1024) bf16 g_u[S_ * FF];

#define TL(i) {}
#define TLX(i) {}
#define TLP(i) TL(i)
#define TLC(i) {}
__device__ __forceinline__ uint32_t smem_u32(const void* p) { return (uint32_t)__cvta_generic_to_shared(p); }
__device__ __forceinline__ void spin_guard(int it) {
    asm volatile("{.reg .pred p; setp.gt.s32 p, %0, %1; @p st.global.u32 [%2], %0;}" ::"r"(it), "n"(SPIN_LIMIT), "l"(1ull));
}
__device__ __forceinline__ void wg_fence() { asm volatile("wgmma.fence.sync.aligned;" ::: "memory"); }
__device__ __forceinline__ void wg_commit() { asm volatile("wgmma.commit_group.sync.aligned;" ::: "memory"); }
template <int N> __device__ __forceinline__ void wg_wait() { asm volatile("wgmma.wait_group.sync.aligned %0;" ::"n"(N) : "memory"); }
__host__ __device__ constexpr uint64_t mkdesc(uint32_t addr, uint32_t lbo, uint32_t sbo, uint32_t swz) {
    return (uint64_t)((addr & 0x3FFFF) >> 4) | ((uint64_t)(lbo >> 4) << 16) | ((uint64_t)(sbo >> 4) << 32) | ((uint64_t)swz << 62);
}
__device__ __forceinline__ uint64_t dadd(uint64_t d, uint32_t o) { return (d & 0xffffffff00000000ull) | (uint32_t)((uint32_t)d + o); }
__device__ __forceinline__ void mbar_init(uint32_t b, uint32_t c) { asm volatile("mbarrier.init.shared.b64 [%0], %1;" ::"r"(b), "r"(c) : "memory"); }
__device__ __forceinline__ void mbar_arrive_cluster(uint32_t b, uint32_t cta) {
    asm volatile("{.reg .b32 r; mapa.shared::cluster.u32 r, %0, %1; mbarrier.arrive.shared::cluster.b64 _, [r];}" ::"r"(b), "r"(cta) : "memory");
}
__device__ __forceinline__ bool mbar_try(uint32_t b, uint32_t par) {
    uint32_t ok;
    asm volatile("{.reg .pred p; mbarrier.try_wait.parity.shared.b64 p, [%1], %2; selp.u32 %0, 1, 0, p;}" : "=r"(ok) : "r"(b), "r"(par) : "memory");
    return ok;
}
__device__ __forceinline__ void mbar_wait(uint32_t b, uint32_t par) {
    int it = 0;
#pragma unroll 1
    while (!mbar_try(b, par) & (++it < SPIN_LIMIT)) {}
}
__device__ __forceinline__ void mbar_wait_w(uint32_t b, uint32_t par) {
    int it = 0;
#pragma unroll 1
    while (!__all_sync(~0u, mbar_try(b, par)) & (++it < SPIN_LIMIT)) {}
}
constexpr uint64_t EVICT_FIRST = 0x12F0000000000000ull, EVICT_NORMAL = 0x1000000000000000ull;   __device__ __forceinline__ void bar_sync(int id, int n) { asm volatile("bar.sync %0, %1;" ::"r"(id), "r"(n) : "memory"); }
__device__ __forceinline__ void bar_arrive(int id, int n) { asm volatile("bar.arrive %0, %1;" ::"r"(id), "r"(n) : "memory"); }
__device__ __forceinline__ void fence_async_smem() { asm volatile("fence.proxy.async.shared::cta;" ::: "memory"); }
__device__ __forceinline__ void ldsm4t(uint32_t* r, uint32_t a) {
    asm volatile("ldmatrix.sync.aligned.m8n8.x4.trans.shared.b16 {%0,%1,%2,%3}, [%4];" : "=r"(r[0]), "=r"(r[1]), "=r"(r[2]), "=r"(r[3]) : "r"(a) : "memory");
}
__device__ __forceinline__ void ldsm4(uint32_t* r, uint32_t a) {
    asm volatile("ldmatrix.sync.aligned.m8n8.x4.shared.b16 {%0,%1,%2,%3}, [%4];" : "=r"(r[0]), "=r"(r[1]), "=r"(r[2]), "=r"(r[3]) : "r"(a) : "memory");
}
__device__ __forceinline__ uint32_t movm(uint32_t a) {
    uint32_t d; asm volatile("movmatrix.sync.aligned.m8n8.trans.b16 %0, %1;" : "=r"(d) : "r"(a)); return d;
}
__device__ __forceinline__ void mma16816(float* d, uint32_t a0, uint32_t a1, uint32_t a2, uint32_t a3, uint32_t b0, uint32_t b1) {
    asm volatile("mma.sync.aligned.m16n8k16.row.col.f32.bf16.bf16.f32 {%0,%1,%2,%3},{%4,%5,%6,%7},{%8,%9},{%0,%1,%2,%3};"
                 : "+f"(d[0]), "+f"(d[1]), "+f"(d[2]), "+f"(d[3]) : "r"(a0), "r"(a1), "r"(a2), "r"(a3), "r"(b0), "r"(b1));
}
__device__ __forceinline__ void mma16816z(float* d, const uint32_t* a, uint32_t b0, uint32_t b1) {
    asm volatile("mma.sync.aligned.m16n8k16.row.col.f32.bf16.bf16.f32 {%0,%1,%2,%3},{%4,%5,%6,%7},{%8,%9},{%10,%10,%10,%10};"
                 : "=f"(d[0]), "=f"(d[1]), "=f"(d[2]), "=f"(d[3]) : "r"(a[0]), "r"(a[1]), "r"(a[2]), "r"(a[3]), "r"(b0), "r"(b1), "f"(0.f));
}
__device__ __forceinline__ void mma1688(float* d, uint32_t a0, uint32_t a1, uint32_t b0) {
    asm volatile("mma.sync.aligned.m16n8k8.row.col.f32.bf16.bf16.f32 {%0,%1,%2,%3},{%4,%5},{%6},{%0,%1,%2,%3};"
                 : "+f"(d[0]), "+f"(d[1]), "+f"(d[2]), "+f"(d[3]) : "r"(a0), "r"(a1), "r"(b0));
}
__device__ __forceinline__ uint32_t pack2(float lo, float hi) {
    uint32_t r; asm("cvt.rn.bf16x2.f32 %0, %1, %2;" : "=r"(r) : "f"(hi), "f"(lo)); return r;
}
__device__ __forceinline__ uint32_t hadd2(uint32_t a, uint32_t b) {
    uint32_t r; asm("add.rn.bf16x2 %0, %1, %2;" : "=r"(r) : "r"(a), "r"(b)); return r;
}
__device__ __forceinline__ float bflo(uint32_t u) { return __uint_as_float(u << 16); }
__device__ __forceinline__ float bfhi(uint32_t u) { return __uint_as_float(u & 0xffff0000u); }
__device__ __forceinline__ float ex2(float x) { float r; asm("ex2.approx.ftz.f32 %0, %1;" : "=f"(r) : "f"(x)); return r; }
__device__ __forceinline__ uint4 ldg_rlx4(const void* p) {
    uint4 v; asm volatile("ld.relaxed.gpu.global.v4.u32 {%0,%1,%2,%3}, [%4];" : "=r"(v.x), "=r"(v.y), "=r"(v.z), "=r"(v.w) : "l"(p) : "memory"); return v;
}
__device__ __forceinline__ uint32_t ldg_rlx1(const void* p) {
    uint32_t v; asm volatile("ld.relaxed.gpu.global.u32 %0, [%1];" : "=r"(v) : "l"(p) : "memory"); return v;
}
__device__ __forceinline__ void stg_rlx1(void* p, uint32_t v) { asm volatile("st.relaxed.gpu.global.u32 [%0], %1;" ::"l"(p), "r"(v) : "memory"); }
__device__ __forceinline__ void stg_rlx2(void* p, uint32_t x, uint32_t y) {
    unsigned long long v = (unsigned long long)x | ((unsigned long long)y << 32);
    asm volatile("st.relaxed.gpu.global.b64 [%0], %1;" ::"l"(p), "l"(v) : "memory");
}
__device__ __forceinline__ void stg_rlx4(void* p, uint32_t x, uint32_t y, uint32_t z, uint32_t w) {
    asm volatile("st.relaxed.gpu.global.v4.u32 [%0], {%1,%2,%3,%4};" ::"l"(p), "r"(x), "r"(y), "r"(z), "r"(w) : "memory");
}
__device__ __forceinline__ void sts4(uint32_t a, uint32_t x, uint32_t y, uint32_t z, uint32_t w) {
    asm volatile("st.shared.v4.u32 [%0], {%1,%2,%3,%4};" ::"r"(a), "r"(x), "r"(y), "r"(z), "r"(w) : "memory");
}
__device__ __forceinline__ uint4 lds4(uint32_t a) {
    uint4 v; asm volatile("ld.shared.v4.u32 {%0,%1,%2,%3}, [%4];" : "=r"(v.x), "=r"(v.y), "=r"(v.z), "=r"(v.w) : "r"(a) : "memory"); return v;
}
#define F4(d, i) "+f"(d[i]), "+f"(d[i + 1]), "+f"(d[i + 2]), "+f"(d[i + 3])
__device__ __forceinline__ void wgmma_rs32(float* d, const uint32_t* a, uint64_t b, int sc) {
    asm volatile("{.reg .pred p; setp.ne.b32 p, %21, 0;\n wgmma.mma_async.sync.aligned.m64n32k16.f32.bf16.bf16 {%0,%1,%2,%3,%4,%5,%6,%7,%8,%9,%10,%11,%12,%13,%14,%15}, {%16,%17,%18,%19}, %20, p, 1, 1, 0;}"
                 : F4(d, 0), F4(d, 4), F4(d, 8), F4(d, 12) : "r"(a[0]), "r"(a[1]), "r"(a[2]), "r"(a[3]), "l"(b), "r"(sc));
}
__device__ __forceinline__ void wgmma_ss32(float* d, uint64_t a, uint64_t b, int sc) {
    asm volatile("{.reg .pred p; setp.ne.b32 p, %18, 0;\n wgmma.mma_async.sync.aligned.m64n32k16.f32.bf16.bf16 {%0,%1,%2,%3,%4,%5,%6,%7,%8,%9,%10,%11,%12,%13,%14,%15}, %16, %17, p, 1, 1, 1, 0;}"
                 : F4(d, 0), F4(d, 4), F4(d, 8), F4(d, 12) : "l"(a), "l"(b), "r"(sc));
}
__device__ __forceinline__ void wgmma_rs40(float* d, const uint32_t* a, uint64_t b, int sc) {
    asm volatile("{.reg .pred p; setp.ne.b32 p, %25, 0;\n wgmma.mma_async.sync.aligned.m64n40k16.f32.bf16.bf16 {%0,%1,%2,%3,%4,%5,%6,%7,%8,%9,%10,%11,%12,%13,%14,%15,%16,%17,%18,%19}, {%20,%21,%22,%23}, %24, p, 1, 1, 0;}"
                 : F4(d, 0), F4(d, 4), F4(d, 8), F4(d, 12), F4(d, 16) : "r"(a[0]), "r"(a[1]), "r"(a[2]), "r"(a[3]), "l"(b), "r"(sc));
}
__device__ __forceinline__ void wgmma_ss40(float* d, uint64_t a, uint64_t b, int sc) {
    asm volatile("{.reg .pred p; setp.ne.b32 p, %22, 0;\n wgmma.mma_async.sync.aligned.m64n40k16.f32.bf16.bf16 {%0,%1,%2,%3,%4,%5,%6,%7,%8,%9,%10,%11,%12,%13,%14,%15,%16,%17,%18,%19}, %20, %21, p, 1, 1, 1, 0;}"
                 : F4(d, 0), F4(d, 4), F4(d, 8), F4(d, 12), F4(d, 16) : "l"(a), "l"(b), "r"(sc));
}
#define F16(d, i) F4(d, i), F4(d, i + 4), F4(d, i + 8), F4(d, i + 12)
template <int TA>
__device__ __forceinline__ void wgmma_ss128(float* d, uint64_t a, uint64_t b, int sc) {
    asm volatile("{.reg .pred p; setp.ne.b32 p, %66, 0;\n wgmma.mma_async.sync.aligned.m64n128k16.f32.bf16.bf16 "
                 "{%0,%1,%2,%3,%4,%5,%6,%7,%8,%9,%10,%11,%12,%13,%14,%15,%16,%17,%18,%19,%20,%21,%22,%23,%24,%25,%26,%27,%28,%29,%30,%31,"
                 "%32,%33,%34,%35,%36,%37,%38,%39,%40,%41,%42,%43,%44,%45,%46,%47,%48,%49,%50,%51,%52,%53,%54,%55,%56,%57,%58,%59,%60,%61,%62,%63}, %64, %65, p, 1, 1, %67, 1;}"
                 : F16(d, 0), F16(d, 16), F16(d, 32), F16(d, 48) : "l"(a), "l"(b), "r"(sc), "n"(TA));
}

__device__ __forceinline__ float warp_sum(float v) {
#pragma unroll
    for (int o = 16; o; o >>= 1) v += __shfl_xor_sync(~0u, v, o);
    return v;
}
__device__ __forceinline__ float bfround(float x) { return __bfloat162float(__float2bfloat16(x)); }

__device__ __forceinline__ void wait_count1(const uint32_t* p, uint32_t target) {
    int it = 0;
#pragma unroll 1
    while (true) {
        uint32_t v;
        asm volatile("ld.acquire.gpu.global.u32 %0, [%1];" : "=r"(v) : "l"(p) : "memory");
        if (v >= target) break;
        spin_guard(++it);
    }
}
__device__ __forceinline__ void red2(float* p, float a, float b) {
    asm volatile("red.relaxed.gpu.global.add.v2.f32 [%0], {%1, %2};" ::"l"(p), "f"(a), "f"(b) : "memory");
}
__device__ __forceinline__ void signal_count(uint32_t* p) { asm volatile("red.release.gpu.global.add.u32 [%0], 1;" ::"l"(p) : "memory"); }
__device__ __forceinline__ void e_expect(uint32_t b, uint32_t tx) {
    asm volatile("{.reg .pred p; elect.sync _|p, 0xffffffff; @p mbarrier.arrive.expect_tx.shared.b64 _, [%0], %1;}" ::"r"(b), "r"(tx) : "memory");
}
__device__ __forceinline__ void e_tma2d(uint32_t dst, const CUtensorMap* m, int c0, int c1, uint32_t bar) {
    asm volatile("{.reg .pred p; elect.sync _|p, 0xffffffff;\n @p cp.async.bulk.tensor.2d.shared::cluster.global.mbarrier::complete_tx::bytes [%0], [%1, {%3, %4}], [%2];}"
                 ::"r"(dst), "l"(m), "r"(bar), "r"(c0), "r"(c1) : "memory");
}
__device__ __forceinline__ void e_tma2d_hint(uint32_t dst, const CUtensorMap* m, int c0, int c1, uint32_t bar, uint64_t pol) {
    asm volatile("{.reg .pred p; elect.sync _|p, 0xffffffff;\n @p cp.async.bulk.tensor.2d.shared::cluster.global.mbarrier::complete_tx::bytes.L2::cache_hint [%0], [%1, {%3, %4}], [%2], %5;}"
                 ::"r"(dst), "l"(m), "r"(bar), "r"(c0), "r"(c1), "l"(pol) : "memory");
}
__device__ __forceinline__ void e_tma2d_mc(uint32_t dst, const CUtensorMap* m, int c0, int c1, uint32_t bar) {
    asm volatile("{.reg .pred p; elect.sync _|p, 0xffffffff;\n @p cp.async.bulk.tensor.2d.shared::cluster.global.mbarrier::complete_tx::bytes.multicast::cluster [%0], [%1, {%3, %4}], [%2], %5;}"
                 ::"r"(dst), "l"(m), "r"(bar), "r"(c0), "r"(c1), "h"((uint16_t)3) : "memory");
}
__device__ __forceinline__ void wait_count_w(const uint32_t* p, uint32_t target) {
    int it = 0;
#pragma unroll 1
    while (true) {
        uint32_t v;
        asm volatile("ld.acquire.gpu.global.u32 %0, [%1];" : "=r"(v) : "l"(p) : "memory");
        if (__all_sync(~0u, v >= target) | (++it > SPIN_LIMIT)) break;
        __nanosleep(100);
    }
}

#define NL 6
constexpr uint32_t SM_HB = 16384, HBK = 5120, SM_SX = 57344, SM_OX = 122880, SM_PX = 124928, SM_PA = 126976, SM_WO = 147456,
                   SM_TAB = 212992, SM_PRE = SM_TAB + 5120, SM_BAR = 227328, SM_REC_TOTAL = 227328 + 256;
constexpr uint32_t SB0 = 1024;
constexpr int B_WO = 0, B_HE = 1, B_HB = 3, B_W = 5;
constexpr int NB_MEM = 1, NB_QK = 2, NB_X1 = 3, NB_X2 = 4, NB_WIN = 5, NB_WG = 6, NB_KDONE = 7, NB_FIN0 = 8, NB_P = 9, NB_PX = 10, NB_G = 11, NB_A = 12, NB_B = 13, NB_C = 14, NB_S = 15;
#define D_NEAR 1620
#define D_FAR (D_NEAR - 90)
#define D_X2 400
#define D_V 280
#define D_W2 40
#define D_PA 40
#define D_MORE 40
constexpr int E_MUL = 28;
constexpr int NPF = NL + 6, NE1 = 10;
constexpr int W0_E = 3, W0_RS = NL - 1, G_AT = 18;
struct Delays { uint32_t near, far, x2, v, w2, pa, spare, more; };
#define MISS(i, v)
#define MISS_INIT
#define MISS_OUT
#define HT(i)

__device__ __forceinline__ uint32_t clk32() { uint32_t t; asm volatile("mov.u32 %0, %%clock;" : "=r"(t) :: "memory"); return t; }
__device__ __forceinline__ uint32_t smid() { uint32_t t; asm volatile("mov.u32 %0, %%smid;" : "=r"(t)); return t; }
__device__ __forceinline__ uint32_t gtime() { uint32_t t; asm volatile("mov.u32 %0, %%globaltimer_lo;" : "=r"(t) :: "memory"); return t; }
__device__ __forceinline__ void spin_until(uint32_t t0, uint32_t d) { while (clk32() - t0 < d) {} }
template <int N> __device__ __forceinline__ uint32_t delay(uint32_t zero) {
    float x = __uint_as_float(clk32());
#pragma unroll
    for (int i = 0; i < N; i++) asm volatile("ex2.approx.ftz.f32 %0, %0;" : "+f"(x));
    return __float_as_uint(x) & zero;
}
__device__ __forceinline__ uint32_t opaque(uint32_t v) { return __shfl_sync(~0u, v, threadIdx.x & 31); }
__device__ __forceinline__ uint32_t xor_or(uint32_t a, uint32_t b, uint32_t t) {
    uint32_t r; asm volatile("lop3.b32 %0, %1, %2, %3, 0x7E;" : "=r"(r) : "r"(a), "r"(b), "r"(t)); return r;
}
__device__ __forceinline__ uint32_t settag(uint32_t v, uint32_t tag) {
    uint32_t r; asm("lop3.b32 %0, %1, 1, %2, 0xB8;" : "=r"(r) : "r"(v), "r"(tag)); return r;
}
__device__ __forceinline__ void sts2(uint32_t a, float x, float y) { asm volatile("st.shared.v2.f32 [%0], {%1,%2};" ::"r"(a), "f"(x), "f"(y) : "memory"); }
__device__ __forceinline__ void sts4f(uint32_t a, float x, float y, float z, float w) {
    asm volatile("st.shared.v4.f32 [%0], {%1,%2,%3,%4};" ::"r"(a), "f"(x), "f"(y), "f"(z), "f"(w) : "memory");
}
__device__ __forceinline__ void sts1(uint32_t a, uint32_t x) { asm volatile("st.shared.u32 [%0], %1;" ::"r"(a), "r"(x) : "memory"); }
__device__ __forceinline__ uint32_t lds1(uint32_t a) { uint32_t v; asm volatile("ld.shared.u32 %0, [%1];" : "=r"(v) : "r"(a) : "memory"); return v; }
__device__ __forceinline__ float4 lds4f(uint32_t a) {
    float4 v; asm volatile("ld.shared.v4.f32 {%0,%1,%2,%3}, [%4];" : "=f"(v.x), "=f"(v.y), "=f"(v.z), "=f"(v.w) : "r"(a) : "memory"); return v;
}
__device__ __forceinline__ float2 lds2f(uint32_t a) {
    float2 v; asm volatile("ld.shared.v2.f32 {%0,%1}, [%2];" : "=f"(v.x), "=f"(v.y) : "r"(a) : "memory"); return v;
}
__device__ __forceinline__ bool any_bit0(uint32_t x) {
    uint32_t r;
    asm volatile("{.reg .pred p, q; .reg .b32 t; and.b32 t, %1, 1; setp.ne.u32 p, t, 0; vote.sync.any.pred q, p, 0xffffffff; selp.u32 %0, 1, 0, q;}" : "=r"(r) : "r"(x));
    return r;
}
__device__ __forceinline__ float rcp_fast(float x) { float r; asm("rcp.approx.ftz.f32 %0, %1;" : "=f"(r) : "f"(x)); return r; }
__device__ __forceinline__ void stsm4(uint32_t a, uint32_t r0, uint32_t r1, uint32_t r2, uint32_t r3) {
    asm volatile("stmatrix.sync.aligned.m8n8.x4.shared.b16 [%0], {%1,%2,%3,%4};" ::"r"(a), "r"(r0), "r"(r1), "r"(r2), "r"(r3) : "memory");
}
__device__ __forceinline__ void stsm4t(uint32_t a, uint32_t r0, uint32_t r1, uint32_t r2, uint32_t r3) {
    asm volatile("stmatrix.sync.aligned.m8n8.x4.trans.shared.b16 [%0], {%1,%2,%3,%4};" ::"r"(a), "r"(r0), "r"(r1), "r"(r2), "r"(r3) : "memory");
}
__device__ __forceinline__ uint32_t and3(uint32_t a, uint32_t b, uint32_t c) {
    uint32_t r; asm("lop3.b32 %0, %1, %2, %3, 0x80;" : "=r"(r) : "r"(a), "r"(b), "r"(c)); return r;
}
__device__ __forceinline__ void red_mem(void* p, uint32_t x, uint32_t y, uint32_t z, uint32_t w, void* q, uint32_t e, bool c) {
    asm volatile("{.reg .pred p; setp.ne.u32 p, %7, 0; red.relaxed.gpu.global.add.noftz.v4.bf16x2 [%0], {%1,%2,%3,%4}; @p red.relaxed.gpu.global.add.noftz.bf16x2 [%5], %6;}"
                 ::"l"(p), "r"(x), "r"(y), "r"(z), "r"(w), "l"(q), "r"(e), "r"((uint32_t)c) : "memory");
}
__device__ __forceinline__ void stg4_if(bool c, void* p, uint32_t x) {
    asm volatile("{.reg .pred p; setp.ne.u32 p, %2, 0; @p st.relaxed.gpu.global.v4.u32 [%0], {%1,%1,%1,%1};}" ::"l"(p), "r"(x), "r"((uint32_t)c) : "memory");
}

__device__ __forceinline__ void h_load(uint32_t sb, const uint8_t* hsrc, int pass, uint32_t rank, uint32_t rot) {
    const uint8_t* src = hsrc + (size_t)pass * 65536;
    const uint32_t bar = sb + SM_BAR + 8 * (B_HB + (pass & 1)), dst = sb + SM_HB + (pass & 1) * 65536 + rank * 4 * HBK;
    e_expect(bar, 32768);
#pragma unroll 1
    for (int i = 0; i < H_PIECES; i++) {
        const uint32_t o = ((i + rot) & (H_PIECES - 1)) * (16384 / H_PIECES);
        asm volatile("{.reg .pred p; elect.sync _|p, 0xffffffff;\n"
                     " @p cp.async.bulk.shared::cluster.global.mbarrier::complete_tx::bytes.multicast::cluster [%0], [%1], %4, [%2], %3;}"
                     ::"r"(dst + o + (o >> 12) * 1024), "l"(src + o), "r"(bar), "h"((uint16_t)3), "n"(16384 / H_PIECES) : "memory");
    }
}
__device__ __forceinline__ uint4 ldg_b128(const void* p) {
    uint4 v;
    asm volatile("{.reg .b128 t; .reg .b64 a, b; ld.relaxed.gpu.global.b128 t, [%4]; mov.b128 {a, b}, t; mov.b64 {%0,%1}, a; mov.b64 {%2,%3}, b;}"
                 : "=r"(v.x), "=r"(v.y), "=r"(v.z), "=r"(v.w) : "l"(p) : "memory");
    return v;
}
__device__ __forceinline__ void stg_b128_if(bool c, void* p, uint32_t x, uint32_t y, uint32_t z, uint32_t w) {
    asm volatile("{.reg .pred p; setp.ne.u32 p, %5, 0; @p st.relaxed.gpu.global.v4.u32 [%0], {%1,%2,%3,%4};}"
                 ::"l"(p), "r"(x), "r"(y), "r"(z), "r"(w), "r"((uint32_t)c) : "memory");
}
__device__ __forceinline__ float pretag(float x, uint32_t add, uint32_t keep) { return __uint_as_float((__float_as_uint(x) + add) & keep); }

template <class F, class G>
__device__ __forceinline__ void softmax_rows(uint32_t src, uint32_t dst, uint32_t g16, int row0, F ready, G mid) {
    const uint32_t u = (g16 >> 7) & 3, e = ((g16 >> 9) << 3) | ((g16 >> 4) & 7);
    uint32_t se = src + e * 8, su = se + u * 1088, d0 = dst + e * 16 + u * 4, d1 = dst + 512 + e * 4;
    int vis = row0 + (e >> 2) - 2 * (e & 3) - 8 * u;
    asm volatile("" : "+r"(se), "+r"(su), "+r"(d0), "+r"(d1), "+r"(vis));
    ready();
    const float2 p0 = lds2f(su), p1 = lds2f(su + 256), p2 = lds2f(su + 512), p3 = lds2f(su + 768);
    const float2 m0 = lds2f(se + 4352), m1 = lds2f(se + 4352 + 256), m2 = lds2f(se + 4352 + 512), m3 = lds2f(se + 4352 + 768);
    float a0 = (p0.x + p1.x) + (p2.x + p3.x), a1 = (p0.y + p1.y) + (p2.y + p3.y);
    const float a2 = (m0.x + m1.x) + (m2.x + m3.x), a3 = (m0.y + m1.y) + (m2.y + m3.y);
    if (vis < 0) a0 = -1e9f / 0.08838834764831845f;
    if (vis < 1) a1 = -1e9f / 0.08838834764831845f;
    int k = __float_as_int(fmaxf(fmaxf(a0, a1), fmaxf(a2, a3)));
    k ^= (k >> 31) & 0x7fffffff;
    const bool hi = g16 & 64;
    const int k0 = __reduce_max_sync(~0u, hi ? INT_MIN : k), k1 = __reduce_max_sync(~0u, hi ? k : INT_MIN);
    mid();
    k = hi ? k1 : k0;
    const float m = __int_as_float(k ^ ((k >> 31) & 0x7fffffff));
    const float sl2 = 0.08838834764831845f * 1.4426950408889634f, mb = -m * sl2;
    sts1(d0, pack2(ex2(fmaf(a0, sl2, mb)), ex2(fmaf(a1, sl2, mb))));
    sts1(d1, pack2(ex2(fmaf(a2, sl2, mb)), ex2(fmaf(a3, sl2, mb))));
}

__device__ __forceinline__ uint32_t pack_h2(float lo, float hi) {
    uint32_t r; asm("cvt.rn.satfinite.f16x2.f32 %0, %1, %2;" : "=r"(r) : "f"(hi), "f"(lo)); return r;
}
__device__ __forceinline__ float2 unpack_h2(uint32_t u) {
    float2 r; asm("{.reg .b16 l, h; mov.b32 {l, h}, %2; cvt.f32.f16 %0, l; cvt.f32.f16 %1, h;}" : "=f"(r.x), "=f"(r.y) : "r"(u)); return r;
}
__device__ __forceinline__ uint32_t add_h2(uint32_t a, uint32_t b) { uint32_t r; asm("add.rn.f16x2 %0, %1, %2;" : "=r"(r) : "r"(a), "r"(b)); return r; }
__device__ __forceinline__ uint32_t max_h2(uint32_t a, uint32_t b) { uint32_t r; asm("max.f16x2 %0, %1, %2;" : "=r"(r) : "r"(a), "r"(b)); return r; }
struct U2 { uint32_t x, y; };
__device__ __forceinline__ U2 ldg_u2(const void* p) {
    U2 v; asm volatile("{.reg .b64 t; ld.relaxed.gpu.global.b64 t, [%2]; mov.b64 {%0, %1}, t;}" : "=r"(v.x), "=r"(v.y) : "l"(p) : "memory"); return v;
}
constexpr int POLL_LIMIT = 1 << 16;
constexpr float SM_L2E = 0.08838834764831845f * 1.4426950408889634f;
template <int V> struct IC { static constexpr int value = V; };
typedef unsigned long long u64;
__device__ __forceinline__ u64 ldg_u64(const void* p) { u64 v; asm volatile("ld.relaxed.gpu.global.b64 %0, [%1];" : "=l"(v) : "l"(p) : "memory"); return v; }
__device__ __forceinline__ void rec_main(uint32_t sb, const CUtensorMap* tWo, uint8_t* arena, int role, int hinfo, int wg, uint32_t zero, const Delays& dly) {
    const int hA = hinfo & 255;
    const int tid = threadIdx.x, t = tid & 127, lane = tid & 31, wi = t >> 5;
    const uint32_t bars = sb + SM_BAR;
    const int head = role >> 2, qd = role & 3, j = blockIdx.x & 1, kh = role & 1;
    const uint32_t mypar = head >= hA;
    const uint32_t wu = __reduce_max_sync(~0u, wi);
    const bool warp0 = wu == 0, warp1 = wu == 1;
    const uint8_t* hsrc = (const uint8_t*)g_himg + kh * 32768 + j * 16384;
    auto tokbase = [&](int ty) { return ((ty + 1) << 21) + blk(lb_tok(head), mypar ^ ((hinfo >> (8 + ty)) & 1)); };
    const uint32_t tbw = tokbase(wg), tbq = tokbase(0) + (qd >> 1) * 2048 + (qd & 1) * 8;
    uint32_t w[32 - NL][4];
    const uint32_t frow = ((lane >> 4) * 8 + (lane & 7)) * 128, fx = ((lane >> 3) & 1) ^ (lane & 7);
    const uint32_t wl0 = sb + wg * 65536 + frow + ((fx ^ (2 * wi)) << 4);
    uint32_t g16 = opaque(t * 16);
    auto G16 = [&]() { asm volatile("" : "+r"(g16)); return g16; };
    const uint32_t sbl = sb - wu * 512;
    const uint32_t xso = blk(lb_x2(head), mypar), cu = kh * 2048 + (2 * j + (wu >> 1)) * 512;
    const uint32_t u_xo = xso + wg * 16384 + (wu & 1) * 2048 + (cu >> 1) - wu * 256, u_to = tbw + (wu & 1) * 16384 + cu - wu * 512;
    {
        uint8_t* pp = arena + (tbw + (1 << 20) + j * 16384 + (kh ^ 1) * 2048 + g16);
        stg_rlx4(pp, 0, 0, 0, 0);
        stg_rlx4(pp + 32768, 0, 0, 0, 0);
        stg_rlx4(arena + (u_to + g16), 0, 0, 0, 0);
        stg_rlx2(arena + (u_xo + (g16 >> 1)), 0, 0);
    }
    {
        if (wg > 0) wait_count_w(&g_tick[32 + (lane & 3) * 8], 1);
        if (wg == 1) asm volatile("fence.proxy.async.global;" ::: "memory");
#pragma unroll 1
        for (int i = 0; i < 4; i++) mbar_wait_w(bars + 8 * (B_W + (wg == 2 ? 8 + i : 2 * i + wg)), 0);
#pragma unroll
        for (int p = NL; p < 32; p++) ldsm4t(w[p - NL], wl0 + p * 2048);
        fence_async_smem();
        bar_sync(wg < 2 ? NB_WG : NB_X2, wg < 2 ? 256 : 128);
        if (wg == 2 && wu < 3) {
            e_expect(bars + 8 * B_WO, 16384);
            e_tma2d(sb + SM_WO + wu * 16384, tWo, (wu >> 1) * 512 + qd * 128 + (wu & 1) * 64, head * DH, bars + 8 * B_WO);
            e_tma2d(sb + SM_WO + wu * 16384 + 8192, tWo, (wu >> 1) * 512 + qd * 128 + (wu & 1) * 64, head * DH + 64, bars + 8 * B_WO);
        }
        if (wg == 1 && warp0) {
            if (lane == 0) mbar_arrive_cluster(bars + 8 * B_HE, j ^ 1);
            mbar_wait_w(bars + 8 * B_HE, 0);
#pragma unroll 1
            for (int i = 0; i < 2; i++) h_load(sb, hsrc, i, j, head);
        }
        TL(3 + wg)
    }
    const uint32_t mrow = wg < 2 ? mem_row(wu >> 1, wg * 2 + (wu & 1), qd) : mem_row(kh, wu, 0);
    const uint32_t u_m = mrow - wu * 512, u_e = mrow + 512 - wu * 64;
#define TAB(i) lds1(sb + SM_TAB + (i) * 512 + (G16() >> 2))
    {
        const uint32_t r8 = lane & 7;
        const uint32_t tb = sb + SM_TAB + wg * 1536 + t * 4, ma = sb + SM_HB + 4096 + r8 * 128;
        if (wg < 2) {
            sts1(tb, sb + SM_WO + wi * 16384 + frow + ((fx ^ (2 * wg)) << 4));
            sts1(tb + 512, wl0);
            sts1(tb + 1024, ma + (((lane >> 3) ^ r8) << 4));
        } else {
            sts1(tb, ma + (wi & 1) * HBK + ((((wi & 2) + (lane >> 4) * 4 + ((lane >> 3) & 1)) ^ r8) << 4));
            sts1(tb + 512, ((((wi & 2) + 5) ^ r8) << 4) + ((lane & 3) == 3 ? ma + ((wi & 1) + (lane >> 3) * 2) * HBK : sb + SM_HB - 128));
            sts1(tb + 1024, mem_row(role >> 6, (role >> 4) & 3, (role >> 2) & 3) + (lane < 8 ? qd * 128 + lane * 16 : 512 + qd * 32 + (lane & 1) * 16));
        }
    }
    MISS_INIT
#define HB(ks) dadd(mkdesc(SB0 + SM_HB + ((ks) >> 2) * HBK + ((ks) & 3) * 32, 16, 1024, 1), hbo)
#define STEP_CONSTS                                                                                  \
    const uint32_t tag = (s & 1) ^ 1, ttag = ((s >> 1) & 1) ^ 1, tso = (s & 1) * 32768;              \
    G16();                            \
    const int p = s + 2, b = p & 1;                                                                  \
    uint32_t hbo = b * 4096, fz[5] = {0, 0, 0, 0, 0};                                                   \
    const uint32_t ftag = (((p - 1) >> 1) & 1) ^ 1, ptag = ((p >> 1) & 1) ^ 1;                       \
    const uint32_t pso = tbw + (1 << 20) + (b ^ 1) * 32768 + j * 16384 + kh * 2048;
#define SCHED_FENCE(i) fz[i] = clk32();
#define FZ ((fz[0] | fz[1] | fz[2] | fz[3] | fz[4]) & zero)
#define BLOCK_FENCE asm volatile("pmevent 0;" ::: "memory");
    constexpr int GAP = 32 / NL;
#define l16 (sbl + g16)
#define g8 (g16 >> 1)
    uint4 u, v;
    uint8_t *pdst, *fdst;
    auto tok_pack = [&](int ty, const float* acc, uint32_t ftag, uint32_t ptag, bool later = false) {
        const bool tg = ty == 2 || !(g16 & 64);
        const uint32_t add = tg ? (ftag ^ 1) << 16 : 0u, keep = tg ? 0xfffe0000u : ~0u;
        const uint32_t add1 = ty == 2 ? 0u : add, keep1 = ty == 2 ? ~0u : keep;
        const uint32_t add2 = ty == 0 ? add : 0u, keep2 = ty == 0 ? keep : ~0u;
        v = {pack2(pretag(acc[0], add, keep), pretag(acc[1], add1, keep1)), pack2(acc[2], acc[3]),
             pack2(pretag(acc[4], add2, keep2), pretag(acc[5], add2, keep2)), pack2(acc[6], acc[7])};
        if (ty < 2) { v.x = movm(v.x); v.z = movm(v.z); v.y = movm(v.y); v.w = movm(v.w); }
        u = {pack2(pretag(acc[8], (ptag ^ 1) << 16, 0xfffe0000u), acc[9]) | ptag, pack2(acc[10], acc[11]), pack2(acc[12], acc[13]), pack2(acc[14], acc[15])};
        if (later) return;
        v.x = settag(v.x, ftag);
        if (ty == 0) v.z = settag(v.z, ftag);
    };

#pragma unroll 1
    for (int s = -2; s < 0; s++) {
        STEP_CONSTS
        (void)tag; (void)ttag; (void)tso; (void)fz;
        float acc[16];
        mbar_wait_w(bars + 8 * (B_HB + b), 0);
        wg_fence();
#pragma unroll
        for (int i = 0; i < 32; i++) {
            if (i < NL) wgmma_ss32(acc, dadd(mkdesc(SB0 + i * 2048, 8192, 1024, 1), wg * 4096), HB(i), i != 0);
            else wgmma_rs32(acc, w[i < NL ? 0 : i - NL], HB(i), 1);
        }
        wg_commit();
        uint4 pa = {0, 0, 0, 0};
        int it = 0;
#pragma unroll 1
        while ((p > 0) & any_bit0(pa.x ^ ftag) & (++it < POLL_LIMIT)) pa = ldg_b128(arena + (pso + g16));
        pdst = arena + ((pso ^ (32768 + 2048)) + G16());
        fdst = arena + ((b ^ 1) * 32768 + u_to + g16);
        wg_wait<0>();
#pragma unroll
        for (int k = 0; k < 4; k++) { acc[2 * k] += bflo((&pa.x)[k]); acc[2 * k + 1] += bfhi((&pa.x)[k]); }
        tok_pack(wg, acc, ftag, ptag);
        stg_b128_if(true, pdst, u.x, u.y, u.z, u.w);
        stg_b128_if(p > 0, fdst, v.x, v.y, v.z, v.w);
        if (p == 0) {
            TL(2)
            if (wg != 1) bar_arrive(NB_C, 288);
        }
    }
    if (wg == 1 && warp0) {
        wait_count_w(&g_tick[32 + (lane & 3) * 8], 2);
        asm volatile("fence.proxy.async.global;" ::: "memory");
        bar_sync(NB_C, 288);
        if (g16 == 0) mbar_arrive_cluster(bars + 8 * B_HE, j ^ 1);
        mbar_wait_w(bars + 8 * B_HE, 1);
        h_load(sb, hsrc, 2, j, head);
    }

    auto qk_loop = [&](auto wgc) {
        constexpr int WG = decltype(wgc)::value;
        uint32_t w0[NL][4], lm0;
        auto w0_load = [&]() {
            const uint32_t wl = TAB(WG * 3 + 1);
            lm0 = TAB(WG * 3 + 2);
#pragma unroll
            for (int k = 0; k < NL; k++) ldsm4t(w0[k], wl + k * 2048);
        };
        const uint32_t wlo = WG * 65536 - SM_WO - wu * 16384, wlx = __reduce_max_sync(~0u, (wi ^ WG) << 5);
        uint32_t tq0, lm, lm1;
        auto proj_pre = [&](int s) {
            uint32_t wz0 = zero;
#pragma unroll
            for (int k = 0; k < NL; k += 2) wz0 = and3(wz0, w0[k][0], w0[k + 1 < NL ? k + 1 : k][0]);
            lm = lm0 + (s & 1) * 65536 + wz0; lm1 = lm ^ 64;
            asm volatile("" : "+r"(lm), "+r"(lm1));
        };
        auto proj = [&](int s, auto mid) {
            bar_sync(NB_MEM, 384);
            float c[4][4];
            uint32_t bf[16][4], tq1;
#pragma unroll
            for (int it = 0; it < 3; it++) ldsm4(bf[it], (it & 1 ? lm1 : lm) + (it >> 1) * HBK);
            mid(-1);
#pragma unroll
            for (int it = 0; it < 16; it++) {
                const uint32_t* bfr = bf[it];
                if (it + 3 < 16) ldsm4(bf[it + 3 < 16 ? it + 3 : 0], (it & 1 ? lm : lm1) + ((it + 3) >> 1) * HBK);
                const uint32_t* wa = 2 * it < NL ? w0[2 * it < NL ? 2 * it : 0] : w[2 * it < NL ? 0 : 2 * it - NL];
                const uint32_t* wb = 2 * it + 1 < NL ? w0[2 * it + 1 < NL ? 2 * it + 1 : 0] : w[2 * it + 1 < NL ? 0 : 2 * it + 1 - NL];
                float *ca = c[(2 * it) & 3], *cb = c[(2 * it + 1) & 3];
                if (it < 2) { mma16816z(ca, wa, bfr[0], bfr[1]); mma16816z(cb, wb, bfr[2], bfr[3]); }
                else { mma16816(ca, wa[0], wa[1], wa[2], wa[3], bfr[0], bfr[1]); mma16816(cb, wb[0], wb[1], wb[2], wb[3], bfr[2], bfr[3]); }
                mid(it);
                if (it == 15) { tq1 = clk32(); bar_arrive(NB_QK, 384); }
            }
            const uint32_t xo = u_xo + (G16() >> 1);
            float r[4];
#pragma unroll
            for (int e = 0; e < 4; e++) {
                constexpr float SH = SM_L2E / 64;
                r[e] = WG ? (c[0][e] + c[1][e]) + (c[2][e] + c[3][e]) : fmaf(c[2][e] + c[3][e], SH, (c[0][e] + c[1][e]) * SH);
            }
            const uint32_t r0 = pack2(r[0], r[1]), r1 = pack2(r[2], r[3]);
            const uint32_t m0 = movm(r0), m1 = movm(r1);
            tq0 = clk32();
            stg_rlx2(arena + xo, settag(m0, (s & 1) ^ 1), m1);
            tq0 += tq1 & zero;
        };
        w0_load();
        proj_pre(0);
        if (WG == 1) bar_sync(NB_P, 256);
        proj(0, [](int) {});
        if (WG == 0) mbar_wait_w(bars + 8 * B_WO, 0);
#pragma unroll 1
        for (int s = 0;; s++) {
            STEP_CONSTS
            uint4 pa;
            float acc[16];
            auto acc_init = [&]() {
#pragma unroll
                for (int k = 0; k < 4; k++) { acc[2 * k] = bflo((&pa.x)[k]); acc[2 * k + 1] = bfhi((&pa.x)[k]); acc[8 + 2 * k] = __uint_as_float((&pa.x)[k] & zero); acc[9 + 2 * k] = __uint_as_float(~(&pa.x)[k] & zero); }
            };
            uint32_t wf[NPF][4], a3;
#define WF(f) ((a3 ^ (((f) & 1) * 64)) + ((f) >> 1) * 2048)
            if (WG == 1) {
                float sc[5][4];
                uint32_t sx0 = sb + SM_SX - wu * (2560 - 16) + G16() * 5;
                asm volatile("" : "+r"(sx0));
                int it = 0;
                bool bad;
#pragma unroll 1
                do {
                    uint4 kf[2][2];
                    U2 qf[2], x[8];
                    const uint32_t gz = g16 | (it & zero);
                    const uint8_t *ts = arena + (tso + tbw + gz), *tq = arena + (tso + tbq + gz), *xp = arena + (xso + (gz >> 1));
#pragma unroll
                    for (int a = 0; a < 4; a++) kf[a >> 1][a & 1] = ldg_b128(ts + (a >> 1) * 16384 + (a & 1) * 2048);
                    spin_until(tq0, dly.x2 - 100);
#pragma unroll
                    for (int a = 0; a < 2; a++) qf[a] = ldg_u2(tq + a * 16384);
                    spin_until(tq0, dly.x2);
#pragma unroll
                    for (int i = 0; i < 8; i++) x[i] = ldg_u2(xp + (i >> 2) * 16384 + (i & 3) * 1024);
                    const uint32_t q0[4] = {hadd2(x[0].x, x[1].x), qf[0].x, hadd2(x[0].y, x[1].y), qf[0].y};
                    const uint32_t q1[4] = {hadd2(x[2].x, x[3].x), qf[1].x, hadd2(x[2].y, x[3].y), qf[1].y};
                    const uint32_t bt = ((qf[0].x ^ ttag) | (qf[1].x ^ ttag)) | ((kf[0][0].x ^ ttag) | (kf[0][1].x ^ ttag)) | ((kf[1][0].x ^ ttag) | (kf[1][1].x ^ ttag));
                    uint32_t bx = 0;
#pragma unroll
                    for (int i = 0; i < 8; i += 2) bx |= (x[i].x ^ tag) | (x[i + 1].x ^ tag);
                    mma16816z(sc[0], q0, kf[0][0].x, kf[0][0].y);
                    mma16816z(sc[1], q0, kf[0][0].z, kf[0][0].w);
                    mma16816z(sc[2], q0, kf[0][1].x, kf[0][1].y);
                    mma16816z(sc[3], q0, kf[0][1].z, kf[0][1].w);
                    mma16816z(sc[4], q0, hadd2(x[4].x, x[5].x), hadd2(x[4].y, x[5].y));
                    bad = any_bit0(bt | bx) & (++it < POLL_LIMIT);
                    mma16816(sc[0], q1[0], q1[1], q1[2], q1[3], kf[1][0].x, kf[1][0].y);
                    mma16816(sc[1], q1[0], q1[1], q1[2], q1[3], kf[1][0].z, kf[1][0].w);
                    mma16816(sc[2], q1[0], q1[1], q1[2], q1[3], kf[1][1].x, kf[1][1].y);
                    mma16816(sc[3], q1[0], q1[1], q1[2], q1[3], kf[1][1].z, kf[1][1].w);
                    mma16816(sc[4], q1[0], q1[1], q1[2], q1[3], hadd2(x[6].x, x[7].x), hadd2(x[6].y, x[7].y));
                } while (bad);
                MISS(1, it - 1)
                sts4(sx0, pack_h2(sc[0][0], sc[0][1]), pack_h2(sc[1][0], sc[1][1]), pack_h2(sc[2][0], sc[2][1]), pack_h2(sc[3][0], sc[3][1]));
                sts1(sx0 + 64 - wu * 12, pack_h2(sc[4][0], sc[4][1]));
                bar_arrive(NB_X1, 384);
                auto tok_sts = [&]() {
#pragma unroll
                    for (int n = 0; n < 5; n++) sts2(sb + SM_SX + 2560 + g8 + n * 1088, sc[n][2], sc[n][3]);
                };
                a3 = TAB(WG * 3);
                if (s == 0) mbar_wait_w(bars + 8 * B_WO, 0);
                softmax_rows(sb + SM_SX + 2560, sb + SM_PX + 1024, g16 | (clk32() & zero), qd * 8, [&]() { BLOCK_FENCE tok_sts(); bar_sync(NB_PX, 128); }, [&]() {
                    BLOCK_FENCE
#pragma unroll
                    for (int f = 0; f < NE1; f++) ldsm4t(wf[f], WF(f));
                    BLOCK_FENCE
                });
            } else {
                a3 = TAB(WG * 3);
                if (warp1 && (s & 3) == 1) asm volatile("fence.proxy.async.global;" ::: "memory");
                spin_until(tq0, dly.pa);
                uint4 x, y;
                int it = 0;
#pragma unroll 1
                do { x = ldg_b128(arena + (pso + g16)); y = ldg_b128(arena + (pso + tokbase(1) - tokbase(0) + g16)); }
                while ((p <= NSEG) & any_bit0(xor_or(x.x, y.x, ftag)) & (++it < POLL_LIMIT));
                sts4(sb + SM_PA + g16, x.x, x.y, x.z, x.w);
                sts4(sb + SM_PA + 2048 + g16, y.x, y.y, y.z, y.w);
                bar_sync(NB_X1, 384);
                if (g16 < 32) asm volatile("red.relaxed.gpu.global.max.u32 [%0], %1; red.relaxed.gpu.global.add.u32 [%0+4], 1;"
                                                    ::"l"(arena + ((blk(LB_TIME, 0) ^ (g16 << 8)) + qd * 1024 + (tq0 & zero))), "r"(gtime()) : "memory");
                __syncwarp();
                const uint32_t tx = clk32();
                spin_until(tx, dly.w2);
            }
#pragma unroll
            for (int f = WG ? NE1 : 0; f < NPF; f++) ldsm4t(wf[f], WF(f));
            if (s + 1 == NSEG) { bar_arrive(NB_X2, 384); break; }
            const uint32_t oa = l16 + SM_OX, slot = mem_slot(s + 1);
            float c[4][4];
            uint32_t ob[4][4];
            BLOCK_FENCE
            bar_sync(NB_X2, 384);
            ldsm4t(ob[0], oa);
            ldsm4t(ob[1], oa + 512);
            SCHED_FENCE(0)
#pragma unroll
            for (int f = 0; f < 16; f++) {
                const uint32_t *a = wf[f % NPF], *o = ob[f >> 2] + (f & 2);
                if (f < 4) mma16816z(c[f], a, o[0], o[1]);
                else mma16816(c[f & 3], a[0], a[1], a[2], a[3], o[0], o[1]);
                if (f == 3) ldsm4t(ob[2], oa + 1024);
                if (f == 5) { ldsm4t(ob[3], oa + 1536); if (NPF < 16) ldsm4t(wf[0], WF(NPF)); }
                if (f == 7) {
#pragma unroll
                    for (int k = NPF + 1; k < 16; k++) ldsm4t(wf[k - NPF], WF(k));
                }
                if (f == 3 || f == 5 || f == 7) SCHED_FENCE(f / 2)
                if (f == 11) {
#pragma unroll
                    for (int k = NL - W0_E; k < NL; k++) ldsm4t(w0[k], (a3 ^ wlx) + wlo + k * 2048);
                    SCHED_FENCE(4)
                }
            }
            const float last = c[1][3] + c[3][3], one = __uint_as_float(CNT1 << 16);
            red_mem(arena + (u_m + slot + G16()), pack2(c[0][0] + c[2][0], c[0][1] + c[2][1]), pack2(c[0][2] + c[2][2], c[0][3] + c[2][3]),
                    pack2(c[1][0] + c[3][0], c[1][1] + c[3][1]), pack2(c[1][2] + c[3][2], g16 & 16 ? one : last),
                    arena + (u_e + slot + ((g16 >> 3) & ~3u)), pack2(one, last), g16 & 16);
            hbo += FZ;
            constexpr int NS = NL - W0_RS, GS = (32 - NL + NS) / NS;
            BLOCK_FENCE
#pragma unroll
            for (int k = NL - W0_E - 1; k >= 0; k--) ldsm4t(w0[k], (a3 ^ wlx) + wlo + k * 2048);
            lm0 = TAB(WG * 3 + 2);
            if (WG == 1) pa = lds4(sb + SM_PA + 2048 + g16);
            if (WG == 0) {
                bar_arrive(NB_WIN, 384);
                pa = lds4(sb + SM_PA + g16);
                acc_init();
                asm volatile("" : F16(acc, 0));
                BLOCK_FENCE
            }
            wg_fence();
            bar_sync(WG ? NB_WIN : NB_B, WG ? 384 : 256);
#pragma unroll
            for (int i = 0; i < 32; i++) {
                const int k = i / GS;
                if (i >= 32 - NL + NS) wgmma_rs32(acc, w0[i < 32 - NL + NS ? 0 : i - 32 + NL], HB(i - 32 + NL), 1);
                else if (i % GS == GS - 1 && k < NS) wgmma_ss32(acc, mkdesc(SB0 + WG * 65536 + k * 2048, 8192, 1024, 1), HB(k), 1);
                else wgmma_rs32(acc, w[i - (k < NS ? k : NS)], HB(NL + i - (k < NS ? k : NS)), WG == 0 || i);
                if (WG == 1 && i == G_AT) bar_arrive(NB_B, 256);
                if (WG == 1 && i == 31 - NL + NS) wg_fence();
            }
            wg_commit();
            BLOCK_FENCE
            if (WG == 1 && warp0 && !(s & 3)) wait_count_w(&g_tick[32 + ((G16() >> 4) & 3) * 8], min((s + 1) / 4 + 3, 17));
            auto tok_store = [&](int m) {
                if (m & 1) stg_b128_if(true, arena + ((b ^ 1) * 32768 + u_to + G16()), v.x, v.y, v.z, v.w);
                if (m & 2) stg_b128_if(p < NSEG, arena + ((pso ^ (32768 + 2048)) + G16()), u.x, u.y, u.z, u.w);
            };
            if (WG == 0) proj_pre(s + 1);
            BLOCK_FENCE
            wg_wait<0>();
            if (WG == 0) {
                asm volatile("" : F16(acc, 0));
                proj(s + 1, [&](int it) {
                    if (it < 0) {
                        SCHED_FENCE(0)
                        asm volatile("" : F16(acc, 0));
                        tok_pack(WG, acc, ftag, ptag, true);
                        tok_store(2);
                        SCHED_FENCE(1)
                    }
                    if (it == 2) { SCHED_FENCE(2) v.x = settag(v.x, ftag); v.z = settag(v.z, ftag); tok_store(1); SCHED_FENCE(3) }
                });
                tq0 += (fz[0] | fz[1] | fz[2] | fz[3]) & zero;
            } else {
#pragma unroll
                for (int k = 0; k < 4; k++) { acc[2 * k] += bflo((&pa.x)[k]); acc[2 * k + 1] += bfhi((&pa.x)[k]); }
                tok_pack(WG, acc, ftag, ptag);
                proj_pre(s + 1);
                asm volatile("" : "+r"(u.x), "+r"(u.y), "+r"(u.z), "+r"(u.w), "+r"(v.x), "+r"(v.y), "+r"(v.z), "+r"(v.w));
                BLOCK_FENCE
                bar_sync(NB_P, 256);
                tok_store(3);
                proj(s + 1, [](int) {});
            }
        }
    };
    if (wg == 0) {
        qk_loop(IC<0>());
    } else if (wg == 1) {
        qk_loop(IC<1>());
    } else {
        const uint32_t ONES = 0x3f803f80u, u_o = qd * 65536 + head * 2048 + wu * 384;
        uint32_t tw = 0, dl = 0, dbase = kh == mypar ? dly.near : dly.far, dst0, dx0;
        dst0 = TAB(6); dx0 = TAB(7);
        uint32_t ov[4] = {0, 0, 0, 0};
        auto o_store = [&](int s) {
            uint8_t* od = (uint8_t*)g_O + (uint32_t)(s * (32 * NH * DH * 2) + u_o + (G16() >> 2));
#pragma unroll
            for (int a = 0; a < 4; a++) stg_rlx1(od + a * 128, ov[a]);
        };
        uint4 vf[2][2], pa;
        auto tok_fetch = [&](int s) {
            const uint8_t* ts = arena + ((s & 1) * 32768 + tbw + g16);
#pragma unroll
            for (int a = 0; a < 4; a++) vf[a >> 1][a & 1] = ldg_b128(ts + (a >> 1) * 16384 + (a & 1) * 2048);
            pa = ldg_b128(arena + (tbw + (1 << 20) + (~s & 1) * 32768 + j * 16384 + kh * 2048 + g16));
        };
        tok_fetch(0);
        TL(9)
        TL(6)
#pragma unroll 1
        for (int s = 0; s < NSEG; s++) {
            STEP_CONSTS
#define VFBAD ((vf[0][0].x ^ ttag) | (vf[0][1].x ^ ttag) | (vf[1][0].x ^ ttag) | (vf[1][1].x ^ ttag))
#define TOKBAD (VFBAD | (p <= NSEG ? pa.x ^ ftag : 0))
            {
                const uint32_t dst = dst0 + b * 65536, dx = dx0 + b * 65536;
                const uint8_t *ms = arena + (u_m + mem_slot(s) + g16), *me = arena + (u_e + mem_slot(s) + ((g16 >> 3) & ~3u));
                const uint32_t em = g16 & 16 ? 0u : ~0u;
                asm volatile("" : "+l"(ms), "+l"(me));
                spin_until(tw, dl);
                int it = 0;
                bool bad;
#pragma unroll 1
                do {
                    uint4 m[4];
                    uint32_t x[4];
#pragma unroll
                    for (int i = 0; i < 4; i++) m[i] = ldg_rlx4(ms + i * 1024);
#pragma unroll
                    for (int i = 0; i < 4; i++) x[i] = ldg_rlx1(me + i * 1024);
#pragma unroll
                    for (int i = 0; i < 3; i++) {
                        stsm4t(dst + i * 2 * HBK, m[i].x, m[i].y, m[i].z, m[i].w);
                        if (i == 1) asm volatile("{.reg .pred p; setp.eq.s32 p, %0, 0; @p bar.arrive %1, 256;}" ::"r"(it), "n"(NB_P) : "memory");
                    }
                    uint32_t c = and3(m[0].w, m[1].w, m[2].w);
                    SCHED_FENCE(1)
                    stsm4t(dst + 6 * HBK, m[3].x, m[3].y, m[3].z, m[3].w);
                    stsm4t(dx, x[0], x[1], x[2], x[3]);
                    asm volatile("" : "+r"(c));
                    c = and3(and3(((c & m[3].w) | em) >> 16, x[0], x[1]), x[2], x[3]);
                    bad = __any_sync(~0u, !(c & CNT_ALL)) & (++it < POLL_LIMIT);
                    asm volatile("{.reg .pred p; setp.eq.u32 p, %0, 0; @p bar.arrive %1, 384;}" ::"r"((uint32_t)bad), "n"(NB_MEM) : "memory");
                } while (bad);
                if (it > 1 && s > 1) dbase += dly.more;
                MISS(0, it - 1) HT(5)
            }
            if (s == 1) { TL(7) TLC(0) }
            if (s == 63) TLC(1)
            if (s == 0) TL(13)
            o_store(max(s - 1, 0));
            fence_async_smem();
            hbo += fz[1] & zero;
            int it = 0;
#pragma unroll 1
            while (any_bit0(TOKBAD) & (++it < POLL_LIMIT)) tok_fetch(s + (it & zero));
            float acc[20];
#pragma unroll
            for (int k = 0; k < 4; k++) { acc[2 * k] = bflo((&pa.x)[k]); acc[2 * k + 1] = bfhi((&pa.x)[k]); acc[8 + 2 * k] = acc[9 + 2 * k] = acc[16 + k] = __uint_as_float(pa.x & zero); }
            if (p <= NSEG) mbar_wait_w(bars + 8 * (B_HB + b), (p >> 1) & 1);
            asm volatile("" : F16(acc, 0), F4(acc, 16));
            BLOCK_FENCE
            wg_fence();
            bar_sync(NB_QK, 384);
#pragma unroll
            for (int i = 0; i < 32; i++) {
                const int k = i / GAP;
                if (i % GAP == GAP - 1 && k < NL) wgmma_ss40(acc, mkdesc(SB0 + 131072 + k * 2048, 8192, 1024, 1), HB(k), 1);
                else wgmma_rs40(acc, w[i - (k < NL ? k : NL)], HB(NL + i - (k < NL ? k : NL)), 1);
            }
            wg_commit();
            uint8_t* vo = arena + (u_xo + (G16() >> 1));
            pdst = arena + ((pso ^ (32768 + 2048)) + G16());
            fdst = arena + ((b ^ 1) * 32768 + u_to + g16);
            BLOCK_FENCE
            wg_wait<0>();
            stg_rlx2(vo, settag(pack2(acc[16], acc[17]), tag), pack2(acc[18], acc[19]));
            const uint32_t tv = clk32();
            tok_pack(2, acc, ftag, ptag);
            stg_b128_if(p <= NSEG, fdst, v.x, v.y, v.z, v.w);
            stg_b128_if(p < NSEG, pdst, u.x, u.y, u.z, u.w);
            const uint8_t* xp = arena + (xso + 32768 + (G16() >> 1));
            const uint32_t sxa = sb + SM_SX - wu * 2560 + G16() * 5;
            uint32_t sel[2];
            {
                const uint32_t q = (G16() >> 4 ^ g16 >> 6 & 1) & 3;
                sel[0] = q == 0 ? 0x3c00 : 0; sel[1] = q == 2 ? 0x3c00 : 0;
                asm volatile("" : "+r"(sel[0]), "+r"(sel[1]));
            }
            uint32_t xv[4], gt = 0;
            auto pv = [&](uint32_t p0, uint32_t p1, uint32_t p2, uint32_t p3, uint32_t p4, auto getv, auto done) {
                float oc[2][4], lc[4] = {0.f, 0.f, 0.f, 0.f};
                mma16816(lc, ONES, ONES, ONES, ONES, p0, p1);
                mma16816z(oc[0], &vf[0][0].x, p0, p1);
                mma16816z(oc[1], &vf[1][0].x, p0, p1);
                mma16816(lc, ONES, ONES, ONES, ONES, p2, p3);
                mma16816(oc[0], vf[0][1].x, vf[0][1].y, vf[0][1].z, vf[0][1].w, p2, p3);
                mma16816(oc[1], vf[1][1].x, vf[1][1].y, vf[1][1].z, vf[1][1].w, p2, p3);
                mma1688(lc, ONES, ONES, p4);
                getv();
                mma1688(oc[0], xv[0], xv[1], p4);
                mma1688(oc[1], xv[2], xv[3], p4);
                done(__float_as_uint(oc[0][0]) | __float_as_uint(oc[1][0]) | __float_as_uint(lc[0]));
                const float r0 = rcp_fast(lc[0]), r1 = rcp_fast(lc[1]);
                ov[0] = pack2(oc[0][0] * r0, oc[0][1] * r1); ov[1] = pack2(oc[0][2] * r0, oc[0][3] * r1);
                ov[2] = pack2(oc[1][0] * r0, oc[1][1] * r1); ov[3] = pack2(oc[1][2] * r0, oc[1][3] * r1);
            };
            bool bad;
            it = 0;
#pragma unroll 1
            do {
                U2 xr[4];
                asm volatile("{.reg .pred p; setp.eq.s32 p, %0, 0; @p bar.sync %1, 384;}" ::"r"(it), "n"(NB_X1) : "memory");
                uint4 sx[5];
#pragma unroll
                for (int i = 0; i < 5; i++) sx[i] = lds4(sxa + i * 16);
                if (it == 0) { gt = gtime(); tw = clk32(); }
                spin_until(tv, dly.v);
#pragma unroll
                for (int i = 0; i < 4; i++) xr[i] = ldg_u2(xp + i * 1024);
                uint32_t h[5], h0[4];
#pragma unroll
                for (int n = 0; n < 4; n++) h0[n] = add_h2((&sx[0].x)[n], (&sx[1].x)[n]);
#pragma unroll
                for (int n = 0; n < 4; n++) h[n] = add_h2(h0[n], add_h2((&sx[2].x)[n], (&sx[3].x)[n]));
                h[4] = add_h2(add_h2(sx[4].x, sx[4].y), add_h2(sx[4].z, sx[4].w));
                uint32_t hm = max_h2(max_h2(max_h2(h[0], h[1]), h[2]), max_h2(h[3], h[4]));
                float2 a[5];
                float mb;
                {
                    float d[2][4];
                    const uint32_t hs = __byte_perm(hm, hm, 0x1032);
#pragma unroll
                    for (int k = 0; k < 2; k++)
                        asm volatile("mma.sync.aligned.m16n8k8.row.col.f32.f16.f16.f32 {%0,%1,%2,%3},{%4,%5},{%6},{%7,%7,%7,%7};"
                                     : "=f"(d[k][0]), "=f"(d[k][1]), "=f"(d[k][2]), "=f"(d[k][3]) : "r"(hm), "r"(hs), "r"(sel[k]), "f"(0.f));
#pragma unroll
                    for (int n = 0; n < 5; n++) a[n] = unpack_h2(h[n]);
                    mb = -64.0f * fmaxf(fmaxf(fmaxf(d[0][0], d[0][1]), fmaxf(d[0][2], d[0][3])), fmaxf(fmaxf(d[1][0], d[1][1]), fmaxf(d[1][2], d[1][3])));
                }
                uint32_t pm[5];
#pragma unroll
                for (int n = 0; n < 5; n++) pm[n] = pack2(ex2(fmaf(a[n].x, 64.0f, mb)), ex2(fmaf(a[n].y, 64.0f, mb)));
                pv(pm[0], pm[1], pm[2], pm[3], pm[4], [&]() {
                    xv[0] = hadd2(xr[0].x, xr[1].x); xv[1] = hadd2(xr[0].y, xr[1].y);
                    xv[2] = hadd2(xr[2].x, xr[3].x); xv[3] = hadd2(xr[2].y, xr[3].y);
                }, [](uint32_t) {});
                bad = any_bit0((xr[0].x ^ tag) | (xr[1].x ^ tag) | (xr[2].x ^ tag) | (xr[3].x ^ tag)) & (++it < POLL_LIMIT);
                stsm4(sb + SM_OX + g16, ov[0], ov[1], ov[2], ov[3]);
            } while (bad);
                MISS(2, it - 1)
            bar_sync(NB_X2, 384);
            BLOCK_FENCE
            U2 tv2 = {0, 0};
            const uint8_t* tp = arena + (blk(LB_TIME, mypar) + ((G16() << 6) & 0xc00));
            {
                const uint4 pp = lds4(l16 + SM_PX + 1024);
                const uint32_t p4 = lds1(sb + SM_PX + 512 + 1024 - wu * 128 + (G16() >> 2));
                tv2 = ldg_u2(tp);
                if (warp0 && s + 3 <= NSEG) h_load(sb, hsrc, s + 3, j, head);
                pv(pp.x, pp.y, pp.z, pp.w, p4, []() {}, [&](uint32_t r) { bar_arrive(NB_WIN + (r & zero), 384); });
            }
            dst0 = TAB(6); dx0 = TAB(7);
            const uint32_t zo = TAB(8);
                HT(7)
            BLOCK_FENCE
            asm volatile("" : "+r"(tv2.y));
            it = 0;
#pragma unroll 1
            while (__any_sync(~0u, tv2.y < 32 * (s + 1)) & (++it < 16)) tv2 = ldg_u2(tp);
            const uint32_t e = __reduce_max_sync(~0u, tv2.x) - gt;
            MISS(3, it - 1) MISS(4, gt)
            tok_fetch(s + 1);
            stg4_if(g16 < 160, arena + (zo + mem_slot(s + 3)), 0);
            dl = dbase + (e > 4096 ? 0 : e * E_MUL >> 4);
        }
        o_store(NSEG - 1);
        TL(8)
    }
    MISS_OUT
}

struct RecMaps { CUtensorMap wq, wk, wv, wo, wmod, w3, w1; };
struct RecPtrs { const bf16 *x, *mem0, *c, *wmod, *w1, *w3; uint8_t* arena; uint32_t zero; const bf16 *w2, *w4, *wo; Delays dly; };

__device__ __forceinline__ float silu_bf(const bf16* c, int i) {
    const float v = __bfloat162float(c[i]);
    return bfround(__fdividef(v, 1.0f + __expf(-v)));
}
#define LN_SEQ 0xcba6420987531ull
#define W_LATE 1000
#define W_OPEN 1400
__device__ __noinline__ uint32_t side_window_(const uint8_t* arena, uint32_t n);
#define side_window(arena, n) n = side_window_(arena, n)
__device__ __noinline__ void rec_ln(uint32_t sb, const bf16* x, const uint8_t* arena, int id, int r0) {
    int r1 = 32;
    uint32_t n = 0;
    const int tid = threadIdx.x, lane = tid & 31, wid = __reduce_max_sync(~0u, tid >> 5);
    const uint32_t ring = sb + wid * 8192 + lane * 16, coef = sb + SM_PRE;
    x += (id * 8 + wid) * 2 * DM + lane * 8;
#pragma unroll 1
    for (int r = r0 - 1; r < r1; r++) {
        if (r > 3) side_window(arena, n);
        if (r + 1 < r1) {
#pragma unroll
            for (int i = 0; i < 8; i++)
                asm volatile("cp.async.cg.shared.global [%0], [%1], 16;" ::"r"(ring + (~r & 1) * 4096 + i * 512), "l"(x + (r + 1) * 64 * DM + i * 256) : "memory");
        }
        asm volatile("cp.async.commit_group; cp.async.wait_group 1;" ::: "memory");
        if (r < r0) continue;
        const uint32_t src = ring + (r & 1) * 4096;
        float m[2] = {0.f, 0.f}, rs[2];
#pragma unroll 1
        for (int ps = 0; ps < 2; ps++) {
            float t[2][2] = {{0.f, 0.f}, {0.f, 0.f}};
#pragma unroll 1
            for (int i = 0; i < 2048; i += 512) {
#pragma unroll
                for (int h = 0; h < 2; h++) {
                    const uint4 u = lds4(src + h * 2048 + i);
#pragma unroll
                    for (int e = 0; e < 4; e++) {
                        const float a = bflo((&u.x)[e]) - m[h], c = bfhi((&u.x)[e]) - m[h];
                        t[h][0] = fmaf(a, ps ? a : 1.0f, t[h][0]); t[h][1] = fmaf(c, ps ? c : 1.0f, t[h][1]);
                    }
                }
            }
            rs[0] = t[0][0] + t[0][1]; rs[1] = t[1][0] + t[1][1];
#pragma unroll 1
            for (int o = 16; o; o >>= 1) { rs[0] += __shfl_xor_sync(~0u, rs[0], o); rs[1] += __shfl_xor_sync(~0u, rs[1], o); }
            if (!ps) { m[0] = rs[0] * (1.0f / DM); m[1] = rs[1] * (1.0f / DM); }
        }
        rs[0] = rsqrtf(rs[0] * (1.0f / DM) + 1e-5f); rs[1] = rsqrtf(rs[1] * (1.0f / DM) + 1e-5f);
        if (r == r0) {
#pragma unroll 1
            for (int i = tid; i < 2 * DM / 4; i += 256) {
                float t[4];
                int it = 0;
                uint32_t ok;
#pragma unroll 1
                do {
                    uint4 u[8];
#pragma unroll
                    for (int k = 0; k < 8; k++) u[k] = ldg_rlx4(g_modp + k * 2 * DM + i * 4);
                    ok = 1;
#pragma unroll
                    for (int k = 0; k < 32; k++) { const uint32_t w = (&u[k >> 2].x)[k & 3]; ok &= w; t[k & 3] = k < 4 ? __uint_as_float(w) : t[k & 3] + __uint_as_float(w); }
                } while (!__all_sync(~0u, ok) & (++it < SPIN_LIMIT));
                const float o = i >> 8;
                const uint32_t lo = pack2(t[0], t[1]), hi = pack2(t[2], t[3]);
                sts4f(coef + (i >> 8) * 4096 + (i & 1) * 2048 + ((i & 255) >> 1) * 16, bflo(lo) + o, bfhi(lo) + o, bflo(hi) + o, bfhi(hi) + o);
            }
            bar_sync(NB_FIN0, 256);
            if (tid == 0 && r0 == 0) TL(2)
        }
        uint8_t* dst = (uint8_t*)g_himg + (r * 2 + (id >> 1)) * 65536 + (lane >> 3) * 4096 + wid * 256;
#pragma unroll 1
        for (int i = 0; i < 4; i++) {
            const uint32_t ca = coef + i * 512 + lane * 16;
            const float4 s0 = lds4f(ca), s1 = lds4f(ca + 2048), c0 = lds4f(ca + 4096), c1 = lds4f(ca + 6144);
            const float sh[8] = {s0.x, s0.y, s0.z, s0.w, s1.x, s1.y, s1.z, s1.w}, sc[8] = {c0.x, c0.y, c0.z, c0.w, c1.x, c1.y, c1.z, c1.w};
#pragma unroll
            for (int h = 0; h < 2; h++) {
                uint4 u = lds4(src + h * 2048 + i * 512);
#pragma unroll
                for (int e = 0; e < 4; e++) {
                    uint32_t& w = (&u.x)[e];
                    w = pack2(fmaf((bflo(w) - m[h]) * rs[h], sc[2 * e], sh[2 * e]), fmaf((bfhi(w) - m[h]) * rs[h], sc[2 * e + 1], sh[2 * e + 1]));
                }
                *(uint4*)(dst + i * 16384 + ((id & 1) == (i >> 1) ? 65536 : 2048) + h * 128 + (((lane ^ (2 * wid + h)) & 7) << 4)) = u;
            }
        }
        if (r == 0) {
            if (tid == 0) TLX(10)
            int ro, it = 0;
#pragma unroll 1
            do asm volatile("ld.volatile.shared.u32 %0, [%1];" : "=r"(ro) : "r"(sb + SM_BAR + 192) : "memory"); while ((ro == INT_MIN) & (++it < SPIN_LIMIT));
            if (ro >= 0) r1 = 2;
        }
        if (r && !(r & 1)) continue;
        bar_sync(r ? NB_FIN0 : NB_C, r ? 256 : 320);
        if (tid == 0 && r == 0) TLX(11)
        if (wid == (r >> 1 & 7)) {
            if (r == 1) bar_arrive(NB_B, 64);
            if (r == 3) wait_count_w(&g_tick[32 + id * 8], 2);
            if (lane == 0) { signal_count(&g_tick[32 + id * 8]); if (r == 0) TLX(12) }
            __syncwarp();
        }
    }
}
__device__ __noinline__ uint32_t side_window_(const uint8_t* arena, uint32_t n) {
    U2 v;
    int it = 0;
#pragma unroll 1
    while (v = ldg_u2(arena + (LB_TIME << 13)), ((v.y >> 5) == n || gtime() - v.x > W_OPEN + W_LATE) && v.y < 32 * NSEG && ++it < 64) __nanosleep(100);
    it = 0;
#pragma unroll 1
    while ((int)(gtime() - v.x - W_OPEN) < 0 && ++it < 256) {}
    return v.y >> 5;
}
#define SIDE_T 300
template <int NQ, int NB>
__device__ __forceinline__ void side_gemv(const CUtensorMap* tm, int c0, int k0, int k1, uint32_t cs, uint32_t sb, const uint8_t* arena, uint32_t& n, uint32_t& ph, float (*acc)[8], bool once = false) {
    const uint32_t w = __reduce_max_sync(~0u, threadIdx.x >> 5 & 3), ring = sb + (NB == 3 ? 65536 : 0) + w * NB * 8192;
    const uint32_t bars = sb + SM_BAR + (NB == 3 ? 8 * B_W + w * 24 : 8 + w * 8), bs = NB == 3 ? 8 : 0;
#pragma unroll
    for (int q = 0; q < NQ; q++)
#pragma unroll
        for (int j = 0; j < 8; j++) acc[q][j] = 0.f;
#pragma unroll 1
    for (; k0 < k1; k0 += NB * 16, ph ^= 1) {
        const int nr = min(NB * 16, k1 - k0);
        side_window(arena, n);
        const uint32_t t0 = clk32();
#pragma unroll 1
        for (int g = 0; g < NB; g++) {
            spin_until(t0, (g * 4 + w) * (SIDE_T / 4));
            if (bs || !g) e_expect(bars + bs * g, !bs ? NB * 8192 : g * 16 < nr ? 8192 : 0);
            if (g * 16 < nr) e_tma2d_hint(ring + g * 8192, tm, c0, k0 + g * 16, bars + bs * g, once ? EVICT_FIRST : EVICT_NORMAL);
        }
#pragma unroll 1
        for (int r = 0; r < nr; r += 16) {
            mbar_wait_w(bars + bs * (r >> 4), ph);
            uint4 v[16];
#pragma unroll
            for (int h = 0; h < 16; h++) v[h] = lds4(ring + (r + h) * 512 + (threadIdx.x & 31) * 16);
            float4 cf[NQ][4];
#pragma unroll
            for (int q = 0; q < NQ * 4; q++) cf[q >> 2][q & 3] = lds4f(cs + ((q >> 2) * DM + k0 + r + (q & 3) * 4) * 4);
#pragma unroll
            for (int h = 0; h < 16; h++) {
                const float f[8] = {bflo(v[h].x), bfhi(v[h].x), bflo(v[h].y), bfhi(v[h].y), bflo(v[h].z), bfhi(v[h].z), bflo(v[h].w), bfhi(v[h].w)};
#pragma unroll
                for (int q = 0; q < NQ; q++)
#pragma unroll
                    for (int j = 0; j < 8; j++) acc[q][j] = fmaf((&cf[q][h >> 2].x)[h & 3], f[j], acc[q][j]);
            }
        }
        fence_async_smem();
        __syncwarp();
    }
}
__device__ __noinline__ void rec_side(float* sm, const RecMaps& mp, const RecPtrs& p, int id) {
    const int tid = threadIdx.x, t = tid & 127, w = __reduce_max_sync(~0u, t >> 5);
    float* coef = sm + (tid < 256 ? 44032 : 40960);
    const uint32_t sb = smem_u32(sm), cs = smem_u32(coef);
    uint32_t n = 0, ph = 0;
    float acc[3][8];
    if (tid < 256) {
        if (blockIdx.x < 128) rec_ln(smem_u32(sm), p.x, p.arena, id, 2);
        if (tid == 0) TL(14)
        for (int i = tid; i < 2 * S_; i += 256) g_st[id * 2 * S_ + i] = 0.f;
        if (id == 0 && tid < 64) g_pcnt[tid * 8] = 0;
        if (id == 1) for (int i = tid; i < 6 * 256; i += 256) g_pflag[i] = 0;
        if (id == 2 && tid == 0) g_pt = 0;
        fence_async_smem();
        bar_sync(NB_FIN0, 256);
        if (PDL && tid == 0) asm volatile("fence.acq_rel.gpu; griddepcontrol.launch_dependents;" ::: "memory");
        if (tid >= 128) return;
        float* red = coef + 3 * DM;
        if (t == 0) wait_count1(&g_tick[8], 4);
        bar_sync(NB_S, 128);
        for (int i = t; i < DM; i += 128) { coef[i] = 1.0f + __ldcg(g_mod + 4 * DM + i); coef[DM + i] = __ldcg(g_mod + 3 * DM + i); coef[2 * DM + i] = 1.0f; }
        bar_sync(NB_S, 128);
        if (id == 1 && t < 32) {
            float u[5] = {0, 0, 0, 0, 0};
            for (int i = t; i < DM; i += 32) {
                const float a = coef[i], b = coef[DM + i];
                u[0] += a; u[1] += a * a; u[2] += a * b; u[3] += b; u[4] += b * b;
            }
#pragma unroll
            for (int q = 0; q < 5; q++) { const float r = warp_sum(u[q]); if (t == 0) g_cst[q] = r * (1.0f / DM); }
        }
        side_gemv<3, 2>(&mp.w1, id * 256, w * 256, w * 256 + 256, cs, sb, p.arena, n, ph, acc);
#pragma unroll
        for (int q = 0; q < 3; q++)
#pragma unroll
            for (int j = 0; j < 8; j++) red[((t >> 5) * 3 + q) * 256 + (t & 31) * 8 + j] = acc[q][j];
        bar_sync(NB_S, 128);
        for (int i = t; i < 768; i += 128) g_vec[(i >> 8) * DM + id * 256 + (i & 255)] = (red[i] + red[768 + i]) + (red[1536 + i] + red[2304 + i]);
        if (tid == 0) TL(6)
        return;
    }
    for (int i = t; i < DM; i += 128) { coef[i] = silu_bf(p.c, i); coef[2 * DM + i] = 1.0f; }
    if (t == 0) wait_count1(&g_tick[32], 1);
    bar_sync(NB_G, 128);
    side_gemv<1, 3>(&mp.wmod, (2 + id) * DM + w * 256, 0, DM, cs, sb, p.arena, n, ph, acc, true);
#pragma unroll
    for (int j = 0; j < 8; j++) g_mod[(2 + id) * DM + t * 8 + j] = bfround(acc[0][j]);
    bar_sync(NB_G, 128);
    if (t == 0) signal_count(&g_tick[8]);
    side_gemv<1, 3>(&mp.w3, id * (FF / 4) + w * 256, 0, DM, cs + 8 * DM, sb, p.arena, n, ph, acc);
    if (t < FF / 32) {
#pragma unroll
        for (int j = 0; j < 8; j++) g_vec[3 * DM + id * (FF / 4) + t * 8 + j] = acc[0][j];
    }
    if (t == 0) TL(9)
}

__global__ void __cluster_dims__(2, 1, 1) __launch_bounds__(384, 1)
k_rec(const __grid_constant__ RecMaps mp, const __grid_constant__ RecPtrs p) {
    extern __shared__ uint8_t smraw[];
    const uint32_t sb = smem_u32(smraw);
    if ((sb & 0x3FFFF) != SB0) __trap();
    const uint32_t bars = sb + SM_BAR;
    const int tid = threadIdx.x, lane = tid & 31, b = blockIdx.x;
    const int wid = __reduce_max_sync(~0u, tid >> 5);
    const uint32_t rank = b & 1;
    uint8_t* arena = p.arena;
    volatile int* sinfo = (volatile int*)(smraw + SM_BAR + 192);
    if (tid == 0) TL(0)
    if (tid == 0) sinfo[0] = INT_MIN;
    if (tid == 352) {
        for (int i = 0; i < 17; i++) mbar_init(bars + 8 * i, i == B_WO ? 4 : 1);
        asm volatile("fence.mbarrier_init.release.cluster;" ::: "memory");
    }
    __syncwarp();
    asm volatile("barrier.cluster.arrive.relaxed.aligned;" ::: "memory");
    int pr = 0, hA = 0;
    if (wid < 8) {
        if (b < 128) {
            const int cb = (b & 15) * 128, k0 = (b >> 4) * 128 + (tid >> 4);
            uint4 v[8];
#pragma unroll
            for (int i = 0; i < 8; i++) v[i] = __ldg((const uint4*)(p.wmod + (size_t)(k0 + 16 * i) * (6 * DM) + cb + (tid & 15) * 8));
            float acc[8] = {0, 0, 0, 0, 0, 0, 0, 0};
            const float s8 = silu_bf(p.c, k0 + 16 * (lane & 7));
#pragma unroll
            for (int i = 0; i < 8; i++) {
                const float sv = __shfl_sync(~0u, s8, i, 16);
                acc[0] += sv * bflo(v[i].x); acc[1] += sv * bfhi(v[i].x); acc[2] += sv * bflo(v[i].y); acc[3] += sv * bfhi(v[i].y);
                acc[4] += sv * bflo(v[i].z); acc[5] += sv * bfhi(v[i].z); acc[6] += sv * bflo(v[i].w); acc[7] += sv * bfhi(v[i].w);
            }
            float* red = (float*)(smraw + SM_PRE);
            *(float4*)(red + (tid >> 4) * 128 + (tid & 15) * 8) = make_float4(acc[0], acc[1], acc[2], acc[3]);
            *(float4*)(red + (tid >> 4) * 128 + (tid & 15) * 8 + 4) = make_float4(acc[4], acc[5], acc[6], acc[7]);
            bar_sync(NB_FIN0, 256);
            if (wid < 4) {
                float t = 0;
#pragma unroll
                for (int i = 0; i < 16; i++) t += red[i * 128 + tid];
                stg_rlx1(&g_modp[(b >> 4) * 2 * DM + cb + tid], __float_as_uint(t) | 1u);
                TLX(14)
            }
        } else {
            rec_ln(sb, p.x, p.arena, b - 128, 0);
        }
    } else if (wid >= 10 && b >= 128) {
        {
            const int w = (b - 128) * 2 + wid - 10;
            const uint16_t* src = (const uint16_t*)p.mem0 + (lane & 3) * 2 * DM + (w >> 2) * 512 + (w & 1) * 64 + (w & 2) * 8 + (lane >> 2);
            uint32_t v[4][4];
#pragma unroll
            for (int i = 0; i < 16; i++) v[i >> 2][i & 3] = src[(i >> 2) * 128 + (i & 2) * 16 + (i & 1) * 8] | ((uint32_t)src[DM + (i >> 2) * 128 + (i & 2) * 16 + (i & 1) * 8] << 16);
            uint8_t* d = arena + mem_row(w >> 2, w & 3, 0);
            uint8_t* e = d + 512 + (lane >> 1) * 4;
            d += lane * 16;
#pragma unroll
            for (int i = 0; i < 4; i++, d += 1024, e += 1024) {
                stg_rlx4(d, v[i][0], v[i][1], v[i][2], lane & 1 ? (v[i][3] & 0xffff) | CNT_ALL << 16 : v[i][3]);
                stg_rlx4(d + mem_slot(1), 0, 0, 0, 0);
                stg_rlx4(d + mem_slot(2), 0, 0, 0, 0);
                if (lane & 1) { stg_rlx1(e, (v[i][3] & 0xffff0000u) | CNT_ALL); stg_rlx1(e + mem_slot(1), 0); stg_rlx1(e + mem_slot(2), 0); }
            }
            if (w == 0 && lane < 8) stg_rlx2(arena + (LB_TIME << 13) + lane * 1024, 0, 0);
            bar_arrive(NB_C, 320);
        }
    } else if (rank == 0) {
        uint32_t best = ~0u;
        const int pg = wid < 10 ? 0 : 1 + (b >> 1) / 22;
        uint32_t* q = (uint32_t*)(arena + (pg << 21) + (pg ? blk(b >> 1, wid & 1) : blk(LB_PROBE, wid & 1) + b * 16));
        if (lane < 8) stg_rlx1(q + lane, 0);
        __syncwarp();
        if (lane == 0) {
            q += 3;
            uint32_t v = p.zero;
#pragma unroll 1
            for (int r = v; r <= NPROBE; r++) {
                const uint32_t t0 = clk32() + (v >> 8);
                v = atomicAdd(q + (v >> 8), 1u);
                uint32_t t1;
                asm volatile("{.reg .pred p; setp.eq.u32 p, %1, 0xffffffff; @p exit; mov.u32 %0, %%clock;}" : "=r"(t1) : "r"(v) : "memory");
                best = min(best, t1 - t0);
            }
            sinfo[wid - 6] = best;
        }
        bar_sync(NB_KDONE, b < 128 ? 128 : 64);
        if (tid == 256) {
            const uint32_t par = sinfo[2] > sinfo[3], vote = b < 128 && (sinfo[4] > sinfo[5]) != par;
            stg_rlx2(&g_clk[b >> 1], ((clk32() - 2 * gtime()) & ~127u) | b >> 1, 1 + 2 * par + 4 * vote);
        }
    }
    if (wid == 8) {
        U2 v[3], my;
        uint32_t c0;
        const int me = b >> 1;
        int it = 0;
        __syncwarp();
#pragma unroll 1
        do {
            my = ldg_u2(&g_clk[me]);
#pragma unroll
            for (int k = 0; k < 3; k++) v[k] = ldg_u2(&g_clk[k * 22 + min(lane, 21)]);
        } while (!__all_sync(~0u, my.y & v[0].y & v[1].y & v[2].y & 1) & (++it < SPIN_LIMIT));
        TLX(15)
        c0 = __reduce_min_sync(~0u, lane ? ~0u : v[0].x) - 4096;
        const uint32_t mc = me >= 64 ? ~0u : my.x - c0;
        const int par = my.y >> 1 & 1;
        uint32_t cnt = 0, flip = 0;
#pragma unroll
        for (int k = 0; k < 3; k++) {
            const uint32_t c = v[k].x - c0, o = v[k].y >> 1 & 1;
            const bool ln = k == 2 && lane >= 20;
            cnt += o + (o == par ? (ln ? 44 + lane < me : c < mc) * 256 + (c < my.x - c0) * 65536 : 0);
            flip |= __popc(__ballot_sync(~0u, v[k].y & 4) & 0x3fffff) > 10 ? 256 << k : 0;
        }
        cnt = __reduce_add_sync(~0u, lane < 22 ? cnt : 0);
        const int n1 = cnt & 255, n0 = 66 - n1, tk = cnt >> 8 & 255;
        if (lane == 0) g_cls[smid() & 255] = cnt < 32 << 16 ? par * 4 + (cnt >> 19) : 8;
        hA = min(n0 >> 1, NH);
        const int q0 = 2 * hA, q1 = 2 * NH - q0;
        const int over = tk - (par ? q1 : q0), lack = max(par ? q0 - n0 : q1 - n1, 0);
        if (over < 0) pr = par ? q0 + tk : tk;
        else if (over < lack) pr = (par ? n0 : q0 + n1) + over;
        else pr = -1 - (over - lack + (par ? max(n0 - q0, 0) : 0));
        hA |= flip;
        if (lane == 0) {
            sinfo[1] = hA; sinfo[0] = pr;
            if (b >= 128 && rank == 0) atomicOr(&g_tick[6], (pr < 0 ? 4u : 1u) << ((b - 128) >> 1));
        }
    }
    asm volatile("barrier.cluster.wait.aligned;" ::: "memory");
    if (wid == 8) {
        TL(1)
        __syncwarp();
        bar_arrive(NB_A, 288);
        bar_arrive(NB_S, 128);
        if (b >= 128 && pr < 0) bar_sync(NB_B, 64);
        if (pr >= 0) {
            const int pu = __reduce_max_sync(~0u, pr), c0 = (pu >> 1) * 128 + rank * 64, r0 = (pu & 1) * 512;
#pragma unroll 1
            for (int n = 0; n < 13; n++) {
                const u64 seq = b >= 128 ? LN_SEQ : 0xcba9876543210ull;
                const int i = seq >> (4 * n) & 15;
                if (b >= 128 && i == 0) bar_sync(NB_B, 64);
                if (n >= W_INFL) mbar_wait_w(bars + 8 * (B_W + (seq >> (4 * (n - W_INFL)) & 15)), 0);
                const int m = i < 8 ? i & 1 : i >> 2, k = i < 8 ? i >> 1 : i & 3;
                const uint32_t dst = sb + m * 65536 + k * 16384, br = bars + 8 * (m < 3 ? B_W + i : B_WO);
                const int c = m < 3 ? c0 : 576 + rank * 256 + (pu & 1) * 128, r = m < 3 ? r0 + k * 128 : (pu >> 1) * DH;
                const uint64_t pol = m < 3 ? EVICT_FIRST : EVICT_NORMAL;
                e_expect(br, 16384);
                e_tma2d_hint(dst, &mp.wq + m, c, r, br, pol);
                e_tma2d_hint(dst + 8192, &mp.wq + m, c, r + 64, br, pol);
            }
        }
    } else {
        bar_sync(wid < 8 ? NB_A : NB_S, wid < 8 ? 288 : 128);
    }
    const int prr = __reduce_max_sync(~0u, sinfo[0]);
    hA = __reduce_max_sync(~0u, sinfo[1]);
    if (prr < 0) {
        int j = (b - 128) >> 1;
        if (b < 128) {
            uint32_t v;
            int it = 0;
#pragma unroll 1
            do { v = __reduce_max_sync(~0u, ldg_rlx1(&g_tick[6])); spin_guard(++it); } while (__popc(v) < 2);
            j = v == 3 ? -1 - prr : (v & 1) ^ 1;
        }
        rec_side((float*)smraw, mp, p, j * 2 + rank);
        return;
    }
    if (PDL) asm volatile("griddepcontrol.launch_dependents;" ::: "memory");
    const int role = (prr >> 1) * 4 + rank * 2 + (prr & 1);
    rec_main(sb, &mp.wo, arena, role, hA, wid >> 2, p.zero, p.dly);
}

__device__ __forceinline__ void wgmma_ss192(float* d, uint64_t a, uint64_t b, int sc) {
    asm volatile("{.reg .pred p; setp.ne.b32 p, %98, 0;\n wgmma.mma_async.sync.aligned.m64n192k16.f32.bf16.bf16 "
                 "{%0,%1,%2,%3,%4,%5,%6,%7,%8,%9,%10,%11,%12,%13,%14,%15,%16,%17,%18,%19,%20,%21,%22,%23,%24,%25,%26,%27,%28,%29,%30,%31,%32,%33,%34,%35,%36,%37,%38,%39,%40,%41,%42,%43,%44,%45,%46,%47,%48,%49,%50,%51,%52,%53,%54,%55,%56,%57,%58,%59,%60,%61,%62,%63,%64,%65,%66,%67,%68,%69,%70,%71,%72,%73,%74,%75,%76,%77,%78,%79,%80,%81,%82,%83,%84,%85,%86,%87,%88,%89,%90,%91,%92,%93,%94,%95}, %96, %97, p, 1, 1, 0, 1;}"
                 : F16(d, 0), F16(d, 16), F16(d, 32), F16(d, 48), F16(d, 64), F16(d, 80) : "l"(a), "l"(b), "r"(sc));
}

constexpr uint32_t P_B = 81920, P_PL = 40960, P_OUT = 180224, P_VEC = 212992, P_ROW = P_VEC + 6144, P_BAR = P_ROW + 4096, P_SMEM = P_BAR + 256;
#define PPH 1
#define FLAG_ST "st.release.gpu.global.u32"
#define FLAG_LD "ld.acquire.gpu.global.u32"
constexpr int ST = 5;
constexpr int PB_F = 0, PB_E = 5, PB_R = 10, PB_OUT = 16;
enum { C_Y = 0, C_G = 1, C_X1 = 2, C_U = 3, C_S1 = 8, C_S3 = 9 };
enum { V_GA = 0, V_A = 1, V_B = 2, V_GB = 3, V_VA = 4, V_VB = 5, V_VC = 6, V_C3 = 7 };
struct PostMaps { CUtensorMap o, wo, y, w1, g, w2, x1, w3, u, w4, out; };
struct PostPtrs { const bf16* x; };

struct GeluK { float k0, k1, kh; };
__device__ __forceinline__ GeluK gelu_k(float c) { return {0.7978845608028654f * c, 0.7978845608028654f * 0.044715f * c * c * c, 0.5f * c}; }
__device__ __forceinline__ float gelu_s(float t, const GeluK& k) {
    const float u = t * fmaf(t * t, k.k1, k.k0);
    float th; asm("tanh.approx.f32 %0, %1;" : "=f"(th) : "f"(u));
    const float hx = k.kh * t;
    return fmaf(hx, th, hx);
}
__device__ __forceinline__ float2 ldsv(uint32_t a) {
    float2 v; asm("ld.shared.v2.f32 {%0,%1}, [%2];" : "=f"(v.x), "=f"(v.y) : "r"(a)); return v;
}
__device__ __forceinline__ void wait_smem(uint32_t a, int target) {
    int it = 0;
#pragma unroll 1
    while (true) {
        int v;
        asm volatile("ld.acquire.cta.shared.u32 %0, [%1];" : "=r"(v) : "r"(a) : "memory");
        if (__all_sync(~0u, v >= target) | (++it > SPIN_LIMIT)) break;
    }
}

#define PP(i)
#define PH_(c, w, i)
__device__ __forceinline__ void release(uint32_t rel, int st, bool c) {
    asm volatile("{.reg .pred p; setp.ne.u32 p, %1, 0; setp.ne.and.u32 p, %2, 0, p; @p mbarrier.arrive.shared::cluster.b64 _, [%0];}"
                 ::"r"(rel + 8 * (st ? st - 1 : ST - 1)), "r"(rel), "r"((uint32_t)c) : "memory");
}
struct Pipe { int st, ph; uint32_t rel; };
__device__ __forceinline__ void adv(Pipe& p) { if (++p.st == ST) { p.st = 0; p.ph ^= 1; } }

__device__ __forceinline__ void post_weights(uint32_t sb, const PostMaps& mp, int nb, int rank) {
    const uint32_t full = sb + P_BAR + 8 * PB_F, empty = sb + P_BAR + 8 * PB_E;
    int st = 0, pp = 1;
#pragma unroll 1
    for (int ph = 0; ph < 7; ph++) {
        const int NK = ph == 0 ? 64 : ph == 6 ? 56 : 16, km = NK == 16 ? 15 : 63;
        const CUtensorMap* tb = &mp.wo + 2 * (ph < 3 ? ph : ph < 6 ? 3 : 4);
        const bool w3 = ph >= 3 && ph < 6;
        const int n0 = w3 ? nb * 64 + (ph == 4 ? 1536 : ph == 5 ? 2560 : 0) : nb * 128, dn = w3 ? 512 : 64;
        const int rot = NK == 16 ? 2 * (nb & 6) : 0, sw = ph == 1 || ph == 3 ? 2 * rank : 0;
#pragma unroll 1
        for (int i = 0; i < NK; i++) {
            const int k0 = (((i < 4 ? i ^ sw : i) + rot) & km) * 64;
            const uint32_t a = sb + P_B + st * 8192, f = full + 8 * st;
            mbar_wait_w(empty + 8 * st, pp);
            e_expect(f, ph == 3 ? 40960 : 32768);
            e_tma2d(a, tb, n0, k0, f);
            e_tma2d(a + P_PL, tb, n0 + dn, k0, f);
            if (ph == 3) e_tma2d(a + 2 * P_PL, tb, n0 + 1024, k0, f);
            if (++st == ST) { st = 0; pp ^= 1; }
        }
    }
#pragma unroll 1
    for (int i = 0; i < ST; i++) mbar_wait_w(empty + 8 * i, pp ^ (i < st));
}
__device__ __forceinline__ void post_acts(uint32_t sb, const PostMaps& mp, int mb, int nb, int rank) {
    const int rh = 2 * mb + rank, lane = threadIdx.x & 31;
    const uint32_t full = sb + P_BAR + 8 * PB_F, empty = sb + P_BAR + 8 * PB_E;
    int st = 0, pp = 1;
#pragma unroll 1
    for (int ph = 0; ph < 7; ph++) {
        const int NK = ph == 0 ? 64 : ph == 6 ? 56 : 16, km = NK == 16 ? 15 : 63;
        const CUtensorMap* ta = &mp.o + 2 * (ph < 3 ? ph : ph < 6 ? 3 : 4);
        const int amul = ph == 0 ? 256 : 64, arow = ph == 0 ? rh * 8 : rh * 64;
        const int rot = NK == 16 ? 2 * (nb & 6) : 0, own = ph == 1 || ph == 3 ? 4 : 0;
        const uint32_t shifts = ph == 2 ? 0x04000301u : 0x02020202u;
        const uint32_t* fl = &g_pflag[(ph == 6 ? C_U : min(ph - 1, 2)) * 256 + (ph == 2 ? min(max(rh + min(lane >> 3, 2) - 1, 0), 31) : rh) * 8 + (lane & 7)];
        uint32_t have = ph == 0 || ph == 5;
        if (own) { if (st) { st--; pp ^= 1; } else st = 4; }
#pragma unroll 1
        for (int i = own; i < NK; i++) {
            const int kb = (i + rot) & km;
            const uint32_t need = ph == 6 ? 255u : (ph == 2 ? 0x10101u : 1u) << ((kb >> 1) & 7), lvl = ph == 6 ? i >> 3 : 0;
            PH_(ph == PPH && i == own, 0, 27) PH_(ph == PPH && i == own, 1, 27)
            if ((__ballot_sync(~0u, have > lvl) & need) != need) {
                int it = 0;
#pragma unroll 1
                do asm volatile(FLAG_LD " %0, [%1];" : "=r"(have) : "l"(fl) : "memory");
                while (((__ballot_sync(~0u, have > lvl) & need) != need) & (++it < SPIN_LIMIT));
                PH_(ph == PPH && i == own, 0, 23) PH_(ph == PPH, 0, 24) PH_(ph == PPH && i == own, 1, 23) PH_(ph == PPH, 1, 24)
                asm volatile("fence.proxy.async.global;" ::: "memory");
            }
            const int d = own && (i == 5 || i == 6) ? 2 : 0, s2 = st + d < ST ? st + d : st + d - ST;
            mbar_wait_w(empty + 8 * s2, pp ^ (s2 < st));
            e_tma2d_mc(sb + st * 16384 + rank * 8192, ta, kb * amul, arow + (int)((shifts >> ((kb & 12) * 2)) & 7) - 2, full + 8 * st);
            if (++st == ST) { st = 0; pp ^= 1; }
        }
    }
}

template <int PH, class F>
__device__ __forceinline__ void post_kb(uint32_t sb, float* acc, Pipe& p, int wg, bool lead, bool first, F mid) {
    constexpr uint64_t DA = PH == 0 ? mkdesc(SB0, 128, 1024, 0) : mkdesc(SB0, 16, 1024, 1);
    constexpr uint64_t DB = mkdesc(SB0 + P_B, P_PL, 1024, 1);
    mbar_wait_w(sb + P_BAR + 8 * PB_F + 8 * p.st, p.ph);
    const uint32_t a = (uint32_t)DA + p.st * 1024 + wg * 512, b = (uint32_t)DB + p.st * 512;
    wg_fence();
#pragma unroll
    for (int k = 0; k < 4; k++) {
        const uint64_t da = (DA & 0xffffffff00000000ull) | (a + k * (PH == 0 ? 16 : 2)), db = (DB & 0xffffffff00000000ull) | (b + k * 128);
        if (PH == 3) wgmma_ss192(acc, da, db, k || !first);
        else wgmma_ss128<PH == 0>(acc, da, db, k || !first);
    }
    wg_commit();
    wg_wait<1>();
    release(p.rel, p.st, !first);
    mid();
    adv(p);
}
__device__ __forceinline__ void post_end(uint32_t sb, Pipe& p, bool lead) {
    wg_wait<0>();
    release(p.rel, p.st, true);
}
template <int PH>
__device__ __forceinline__ void post_mma(uint32_t sb, float* acc, Pipe& p, int wg, bool lead, int nout, int pi, int mb, int nb) {
#pragma unroll 1
    for (int kb = 0; kb < 16; kb++)
        post_kb<PH>(sb, acc, p, wg, lead, kb == 0, [&]() {
            if (kb == 0) { PP(pi) }
            if (nout && kb == 0) wait_smem(sb + P_BAR + 8 * (PB_OUT + wg), nout);
        });
    post_end(sb, p, lead);
    PP(pi + 1)
}

__global__ void __cluster_dims__(2, 1, 1) __launch_bounds__(384, 1)
k_post(const __grid_constant__ PostMaps mp, const __grid_constant__ PostPtrs pp) {
    extern __shared__ uint8_t smraw[];
    const uint32_t sb = smem_u32(smraw);
    if ((sb & 0x3FFFF) != SB0) __trap();
    const int tid = threadIdx.x, lane = tid & 31;
    const int rank = blockIdx.x & 1;
    const uint32_t bars = sb + P_BAR;
    int c = 0;
    unsigned long long v = 0;
    const int wid = __reduce_max_sync(~0u, tid >> 5);
    const bool draw = tid == 352 && rank == 0;
    if (draw) {
        c = min(ldg_rlx1(&g_cls[smid() & 255]), 8u);
        asm volatile("{.reg .b64 a; cvt.u64.u32 a, %%laneid; add.u64 a, a, %1; atom.relaxed.gpu.global.add.u64 %0, [a], %2;}" : "=l"(v) : "l"(&g_pt), "l"(1ull << (7 * c)) : "memory");
    }
    if (wid < 11) {
        asm volatile("{.reg .pred p; elect.sync _|p, 0xffffffff; @p mbarrier.init.shared.b64 [%0], %1; @p prefetch.tensormap [%2]; fence.mbarrier_init.release.cluster;}"
                     ::"r"(bars + 8 * wid), "r"(wid >= PB_E && wid < PB_R ? 4 : 1), "l"(&mp.o + wid) : "memory");
        if (wid == PB_R) { sts4(bars + 8 * PB_OUT, 0, 0, 0, 0); e_expect(bars + 8 * PB_R, 4); }
    }
    __syncwarp();
    asm volatile("barrier.cluster.arrive.relaxed.aligned; barrier.cluster.wait.aligned;" ::: "memory");
    if (draw) {
        int r = (v >> (7 * c)) & 127, role = c * 8 + r;
        if (c == 8 || r >= 8) {
            int n, x, it = 0;
#pragma unroll 1
            do {
                __nanosleep(200);
                v = ldg_u64(&g_pt); n = 0; x = c < 8 ? r - 8 : r;
#pragma unroll 1
                for (int i = 0; i < 63; i += 7) { const int m = v >> i & 127; n += m; if (i < 7 * c) x += max(m - 8, 0); }
            } while (n < gridDim.x / 2 && ++it < SPIN_LIMIT);
            role = -1;
#pragma unroll 1
            for (int i = 0; i < 64; i += 8, v >>= 7) {
                n = v & 127;
                if (x >= 0 && n + x < 8) role = i + n + x;
                x -= max(8 - n, 0);
            }
        }
#pragma unroll
        for (int i = 0; i < 2; i++)
            asm volatile("{.reg .b32 d; mapa.shared::cluster.u32 d, %0, %2; st.async.shared::cluster.mbarrier::complete_tx::bytes.u32 [d+8], %1, [d];}"
                         ::"r"(bars + 8 * PB_R), "r"(role), "r"(i) : "memory");
    }
    __syncwarp();
    mbar_wait_w(bars + 8 * PB_R, 0);
    const int pr = __reduce_max_sync(~0u, (int)lds1(bars + 8 * PB_R + 8));
    if (pr < 0) return;
    const int mb = (pr >> 5) * 8 + (pr & 7), nb = (pr >> 2 & 6) + rank, cta = pr * 2 + rank;
    if (wid >= 8) {
        asm volatile("setmaxnreg.dec.sync.aligned.u32 40;");
        const int w = wid - 8;
        if (w == 0) {
            post_weights(sb, mp, nb, rank);
        } else if (w == 3) {
            asm volatile("griddepcontrol.wait;" ::: "memory");
            TLP(15)
            post_acts(sb, mp, mb, nb, rank);
        } else {
            const int wg = w - 1, rh = 2 * mb + wg;
            float* rowc = (float*)(smraw + P_ROW) + (wg * 64 + lane * 2) * 8;
            int nout = 0, sig = 0;
#pragma unroll 1
            for (int i = 0; i < 13; i++) {
                const int cnt = (0x4333333392180ull >> (4 * i)) & 15;
                if (cnt < C_S1) {
                    const int ng = cnt == C_U ? 1 : 2, c0 = cnt == C_U ? (i - 5) * 512 + nb * 64 : nb * 128;
                    const bool fast = (cnt == C_Y || cnt == C_X1);
#pragma unroll 1
                    for (int j = 0; j < ng; j++) {
                        const uint32_t st = j ? cnt : cnt ? 1 : 4;
                        const uint32_t src = sb + (fast ? st * 16384 + wg * 8192 : P_OUT + wg * 16384 + ((nout + j) & 1) * 8192);
                        bar_sync(4 + 4 * wg + (sig++ & 3), 160);
                        if (lane == 0) {
                            PH_(cnt == PPH - 1, wg, 20)
                            if (fast) asm volatile("mbarrier.complete_tx.relaxed.cta.shared::cta.b64 [%0], 8192;" ::"r"(bars + 8 * (PB_F + st)) : "memory");
                            asm volatile("cp.async.bulk.tensor.2d.global.shared::cta.bulk_group [%0, {%2, %3}], [%1]; cp.async.bulk.commit_group;"
                                         ::"l"(&mp.y + 2 * cnt), "r"(src), "r"(c0 + j * 64), "r"(rh * 64) : "memory");
                        }
                        __syncwarp();
                    }
                    if (lane == 0) {
                        auto to_peer = [&]() {
                            const uint32_t n = cnt ? 1 : 4;
                            mbar_wait(bars + 8 * (PB_E + (cnt ? 4 : 2)), 0);
#pragma unroll
                            for (int i = 0; i < 2; i++)
                                asm volatile("{.reg .b32 d, m; mapa.shared::cluster.u32 d, %0, %3; mapa.shared::cluster.u32 m, %2, %3;\n"
                                             " cp.async.bulk.shared::cluster.shared::cta.mbarrier::complete_tx::bytes [d], [%1], 8192, [m];}"
                                             ::"r"(sb + (cnt + 1 + i) * 16384 + wg * 8192), "r"(sb + (i ? cnt : n) * 16384 + wg * 8192), "r"(bars + 8 * (PB_F + cnt + 1 + i)), "r"(rank ^ 1) : "memory");
                        };
                        asm volatile("cp.async.bulk.wait_group 0; fence.proxy.async.global;" ::: "memory");
                        asm volatile("st.release.cta.shared.u32 [%0], %1;" ::"r"(bars + 8 * (PB_OUT + wg)), "r"(nout + ng) : "memory");
                        PH_(cnt == PPH - 1, wg, 21)
                        if (i < 12) asm volatile(FLAG_ST " [%0], %1;" ::"l"(&g_pflag[cnt * 256 + rh * 8 + nb]), "r"(max(i - 4, 1)) : "memory");
                        PH_(cnt == PPH - 1, wg, 22)
                        if (fast) to_peer();
                    }
                    nout += ng;
                    __syncwarp();
                    continue;
                }
                bar_sync(4 + 4 * wg + (sig++ & 3), 160);
                uint32_t* c = &g_pcnt[(cnt - C_S1) * 256 + rh * 8];
                if (lane == 0) signal_count(c);
                __syncwarp();
                wait_count_w(c, 8);
                const float4* sp = (const float4*)g_st + rh * 32 + lane;
                float4 u[3] = {__ldcg(sp + (cnt == C_S1 ? 0 : 3) * (S_ / 2)), __ldcg(sp + S_ / 2), __ldcg(sp + S_)};
#pragma unroll 1
                for (int h = 0; h < 2; h++) {
                    const float id = 1.0f / DM;
                    const float m = u[0].x * id, var = fmaxf(u[0].y * id - m * m, 0.f) + 1e-5f, r = rsqrtf(var);
                    float sc = r, m2 = 0.f;
                    if (cnt == C_S1) {
                        m2 = r * (u[1].x * id - m * g_cst[0]) + g_cst[3];
                        const float e2 = r * r * (u[2].x * id - 2.0f * m * u[1].y * id + m * m * g_cst[1]) + 2.0f * r * (u[2].y * id - m * g_cst[2]) + g_cst[4];
                        sc = r * rsqrtf(fmaxf(e2 - m2 * m2, 0.f) + 1e-5f);
                    }
                    const GeluK k = gelu_k(sc);
                    *(float4*)(rowc + h * 8) = make_float4(k.k0, k.k1, k.kh, -m);
                    *(float4*)(rowc + h * 8 + 4) = make_float4(var * r, -m2 * var * r, r, -m * r);
#pragma unroll
                    for (int q = 0; q < 3; q++) { u[q].x = u[q].z; u[q].y = u[q].w; }
                }
                bar_arrive(1 + wg, 160);
            }
        }
    } else {
        asm volatile("setmaxnreg.inc.sync.aligned.u32 232;");
        const bf16* xin = pp.x;
        const int wg = wid >> 2, wi = (tid >> 5) & 3, g = lane >> 2, tq = lane & 3;
        const int rh = 2 * mb + wg, row = rh * 64 + wi * 16 + g;
        const bool lead = (tid & 127) == 0;
        PP(0)
        if (tid == 0) TLP(10)
        uint32_t keep[32];
#pragma unroll
        for (int i = 0; i < 8; i++)
            *(uint4*)(keep + 4 * i) = __ldg((const uint4*)(xin + (size_t)(rh * 64 + wi * 16 + (i & 3) * 4 + (lane >> 3)) * DM + nb * 128 + (i >> 2) * 64 + (lane & 7) * 8));
        asm volatile("griddepcontrol.wait;" ::: "memory");
        if (cta < 64) g_modp[cta * 256 + tid] = 0;
        if (cta == 64 && tid < 196) g_tick[tid] = 0;
        const float* src = wg ? g_vec + nb * 128 + tid - 128 : g_mod + 2 * DM + nb * 128 + tid;
        const float* c3 = &g_vec[3 * DM + (tid >> 6) * 512 + nb * 64 + (tid & 63)];
        const float cv[6] = {__ldcg(src), __ldcg(src + (wg ? 1 : 2) * DM), __ldcg(src + (wg ? 2 : 1) * DM), __ldcg(src + 3 * DM), __ldcg(c3), __ldcg(c3 + (tid < 192 ? 2048 : 0))};
        uint32_t vec = sb + P_VEC + tq * 8;
        const uint32_t stw = sb + (wi * 16 + ((lane >> 3) & 1) * 8 + (lane & 7)) * 128 + (((lane >> 4) ^ (lane & 7)) << 4);
        int sig = 0;
        auto signal = [&]() { bar_arrive(4 + 4 * wg + (sig++ & 3), 160); };
        auto put64 = [&](uint32_t o, const float* v) {
#pragma unroll
            for (int jj = 0; jj < 4; jj++, v += 8) stsm4((stw + o) ^ (jj << 5), pack2(v[0], v[1]), pack2(v[2], v[3]), pack2(v[4], v[5]), pack2(v[6], v[7]));
            fence_async_smem();
            signal();
        };
        auto slot = [&](int n) {
            mbar_wait_w(bars + 8 * (PB_E + n % 5), ((n / 5) & 1) ^ 1);
            return (n % 5) * 16384 + wg * 8192;
        };
        const uint32_t rowc = sb + P_ROW + (wg * 64 + wi * 16 + g) * 32, o128 = P_OUT + wg * 16384;
        Pipe pa = {0, 0, 0};
        asm("mapa.shared::cluster.u32 %0, %1, %2;" : "=r"(pa.rel) : "r"(bars + 8 * PB_E), "r"(tid & 1));
        if (tid & 126) pa.rel = 0;
#define KEEP(jn, e) (((e) & 1) ? bfhi(keep[2 * (jn) + ((e) >> 1)]) : bflo(keep[2 * (jn) + ((e) >> 1)]))
        float mu1[2], r1[2];
        {
            float acc[64];
#pragma unroll 1
            for (int kb = 0; kb < 64; kb++) {
                post_kb<0>(sb, acc, pa, wg, lead, kb == 0, []() {});
                if (kb == 0) { PP(1) if (wg == 0) TLP(11) }
                if (kb == 24) bar_sync(3, 256);
                if (kb != 8 + 8 * wg) continue;
                float* sv = (float*)(smraw + P_VEC) + tid;
                const uint32_t xo = sb + o128 + wi * 2048 + (lane >> 3) * 128;
#pragma unroll
                for (int i = 0; i < 8; i++) sts4(xo + (i >> 2) * 8192 + (i & 3) * 512 + (((lane & 7) ^ ((i & 1) * 4 + (lane >> 3))) << 4), keep[4 * i], keep[4 * i + 1], keep[4 * i + 2], keep[4 * i + 3]);
                __syncwarp();
#pragma unroll
                for (int jj = 0; jj < 8; jj++) ldsm4(keep + jj * 4, (stw + o128 + (jj >> 2) * 8192) ^ ((jj & 3) << 5));
                sv[wg * 384] = cv[0]; sv[wg * 384 + 128] = cv[1] + (wg ? 0.0f : 1.0f); sv[wg * 384 + 256] = cv[2];
                if (!wg) sv[384] = cv[3];
                sv[V_C3 * 128] = cv[4]; sv[V_C3 * 128 + 256] = cv[5];
            }
            post_end(sb, pa, lead);
            PP(2)
            asm volatile("" : "+r"(vec) :: "memory");
            float st[2][6];
#pragma unroll
            for (int q = 0; q < 6; q++) st[0][q] = st[1][q] = 0.f;
#pragma unroll
            for (int jn = 0; jn < 16; jn++) {
                const float2 ga = ldsv(vec + V_GA * 512 + jn * 32), a = ldsv(vec + V_A * 512 + jn * 32);
                float xa[4];
#pragma unroll
                for (int e = 0; e < 4; e++) {
                    xa[e] = fmaf((e & 1) ? ga.y : ga.x, acc[4 * jn + e], KEEP(jn, e));
                    st[e >> 1][0] += xa[e]; st[e >> 1][1] = fmaf(xa[e], xa[e], st[e >> 1][1]);
                    acc[4 * jn + e] = ((e & 1) ? a.y : a.x) * xa[e];
                }
                keep[2 * jn] = pack2(xa[0], xa[1]); keep[2 * jn + 1] = pack2(xa[2], xa[3]);
                if ((jn & 7) == 7) put64(slot(64 + (jn >> 3)), acc + 4 * jn - 28);
            }
            PP(3)
#pragma unroll
            for (int jn = 0; jn < 16; jn++) {
                const float2 a = ldsv(vec + V_A * 512 + jn * 32), b = ldsv(vec + V_B * 512 + jn * 32);
#pragma unroll
                for (int e = 0; e < 4; e++) {
                    const float y = acc[4 * jn + e], aa = (e & 1) ? a.y : a.x, bb = (e & 1) ? b.y : b.x;
                    float* s = st[e >> 1];
                    s[2] += y; s[3] = fmaf(aa, y, s[3]); s[4] = fmaf(y, y, s[4]); s[5] = fmaf(bb, y, s[5]);
                }
            }
#pragma unroll
            for (int h = 0; h < 2; h++)
#pragma unroll
                for (int q = 0; q < 6; q++) { st[h][q] += __shfl_xor_sync(~0u, st[h][q], 1); st[h][q] += __shfl_xor_sync(~0u, st[h][q], 2); }
            if (tq < 3) {
#pragma unroll
                for (int h = 0; h < 2; h++)
                    red2(g_st + (tq * S_ + row + h * 8) * 2, tq == 0 ? st[h][0] : tq == 1 ? st[h][2] : st[h][4], tq == 0 ? st[h][1] : tq == 1 ? st[h][3] : st[h][5]);
            }
            signal();
            PP(29)
        }
        {
            float acc[64];
            post_mma<1>(sb, acc, pa, wg, lead, 2, 4, mb, nb);
            float c1[2], c2[2], c3[2];
            GeluK gk[2];
            bar_sync(1 + wg, 160);
#pragma unroll
            for (int h = 0; h < 2; h++) {
                const float4 a = lds4f(rowc + h * 256), b = lds4f(rowc + h * 256 + 16);
                gk[h] = {a.x, a.y, a.z}; c1[h] = a.w; c2[h] = b.x; c3[h] = b.y; mu1[h] = b.w; r1[h] = b.z;
            }
#pragma unroll
            for (int jn = 0; jn < 16; jn++) {
                const float2 va = ldsv(vec + V_VA * 512 + jn * 32), vb = ldsv(vec + V_VB * 512 + jn * 32), vc = ldsv(vec + V_VC * 512 + jn * 32);
#pragma unroll
                for (int e = 0; e < 4; e++) {
                    const int h = e >> 1;
                    const float t = fmaf(c1[h], (e & 1) ? va.y : va.x, fmaf(c2[h], (e & 1) ? vb.y : vb.x, fmaf(c3[h], (e & 1) ? vc.y : vc.x, acc[4 * jn + e])));
                    acc[4 * jn + e] = gelu_s(t, gk[h]);
                }
                if ((jn & 7) == 7) put64(o128 + (jn >> 3) * 8192, acc + 4 * jn - 28);
            }
            PP(6)
        }
        {
            float acc[64];
            post_mma<2>(sb, acc, pa, wg, lead, 0, 7, mb, nb);
#pragma unroll
            for (int jn = 0; jn < 16; jn++) {
                const float2 a = ldsv(vec + V_A * 512 + jn * 32), b = ldsv(vec + V_B * 512 + jn * 32);
#pragma unroll
                for (int e = 0; e < 4; e++) {
                    const int h = e >> 1;
                    acc[4 * jn + e] += fmaf(fmaf(KEEP(jn, e), r1[h], mu1[h]), (e & 1) ? a.y : a.x, (e & 1) ? b.y : b.x);
                }
                if ((jn & 7) == 7) put64(slot(96 + (jn >> 3)), acc + 4 * jn - 28);
            }
            BLOCK_FENCE
#pragma unroll
            for (int i = 0; i < 64; i += 16) asm volatile("" : F16(acc, i));
            PP(9)
            float st[2][2] = {{0.f, 0.f}, {0.f, 0.f}};
#pragma unroll
            for (int jn = 0; jn < 16; jn++) {
                const float2 gb = ldsv(vec + V_GB * 512 + jn * 32);
                float z[4];
#pragma unroll
                for (int e = 0; e < 4; e++) {
                    const float x1 = acc[4 * jn + e];
                    st[e >> 1][0] += x1; st[e >> 1][1] = fmaf(x1, x1, st[e >> 1][1]);
                    z[e] = fmaf((e & 1) ? gb.y : gb.x, x1, KEEP(jn, e));
                }
                keep[2 * jn] = pack2(z[0], z[1]); keep[2 * jn + 1] = pack2(z[2], z[3]);
            }
#pragma unroll
            for (int h = 0; h < 2; h++)
#pragma unroll
                for (int q = 0; q < 2; q++) { st[h][q] += __shfl_xor_sync(~0u, st[h][q], 1); st[h][q] += __shfl_xor_sync(~0u, st[h][q], 2); }
            if (tq < 2) red2(g_st + (3 * S_ + row + tq * 8) * 2, tq ? st[1][0] : st[0][0], tq ? st[1][1] : st[0][1]);
            signal();
            PP(30)
        }
        {
            float old[96], acc[64];
            post_mma<3>(sb, old, pa, wg, lead, 6, 10, mb, nb);
#pragma unroll
            for (int i = 0; i < 96; i += 16) asm volatile("" : F16(old, i));
            uint32_t v3 = vec + V_C3 * 512;
            bar_sync(1 + wg, 160);
            const float4 rc[2] = {lds4f(rowc), lds4f(rowc + 256)};
            float2 vc[2] = {lds2f(v3), lds2f(v3 + 32)};
            v3 += wg ? 0 : 64;
            bar_sync(3, 256);
#pragma unroll 1
            for (int blk = 0; blk < 11; blk++) {
                const uint32_t o = stw + o128 + (blk & 1) * 8192;
#pragma unroll
                for (int q = 0; q < 4; q++) {
#pragma unroll 1
                    for (int rep = 0; rep < 2; rep++) {
                        post_kb<1>(sb, acc, pa, wg, lead, q == 0 && rep == 0 && blk < 6 && !(blk & 1), []() {});
                        if (rep != wg) {
                            vc[0] = lds2f(v3 + q * 64); vc[1] = lds2f(v3 + q * 64 + 32);
                            if (q == 2) wait_smem(bars + 8 * (PB_OUT + wg), 6 + min(blk, 7));
                            if ((q == 0 && wg && (uint32_t)(blk - 1) < 7) || (q == 3 && !wg && blk < 7)) { fence_async_smem(); signal(); }
                        } else if (blk < 7) {
                            asm volatile("" : F4(old, 8 * q), F4(old, 8 * q + 4));
                            float t[8];
#pragma unroll
                            for (int i = 0; i < 8; i++) {
                                const float4& c = rc[(i >> 1) & 1];
                                t[i] = gelu_s(fmaf(c.w, (i & 1) ? vc[i >> 2].y : vc[i >> 2].x, old[8 * q + i]), GeluK{c.x, c.y, c.z});
                                old[8 * q + i] = old[32 + 8 * q + i];
                                old[32 + 8 * q + i] = old[64 + 8 * q + i];
                            }
                            uint32_t r[4] = {pack2(t[0], t[1]), pack2(t[2], t[3]), pack2(t[4], t[5]), pack2(t[6], t[7])};
                            asm volatile("pmevent 0;" : F4(old, 8 * q), F4(old, 8 * q + 4), F4(old, 8 * q + 32), F4(old, 8 * q + 36), "+r"(r[0]), "+r"(r[1]), "+r"(r[2]), "+r"(r[3]));
                            stsm4(o ^ (q << 5), r[0], r[1], r[2], r[3]);
                        }
                    }
                }
                v3 += 256;
                if (blk != 1 && blk != 3) continue;
                post_end(sb, pa, lead);
                PP(12 + blk)
                asm volatile("" : F16(acc, 0), F4(acc, 16), F4(acc, 20), F4(acc, 24));
                asm volatile("" : F16(acc, 28), F4(acc, 44), F4(acc, 48), F4(acc, 52));
                asm volatile("" : F4(acc, 56), F4(acc, 60));
#pragma unroll
                for (int i = 0; i < 64; i++) old[32 + i] = acc[i];
            }
            post_end(sb, pa, lead);
            PP(17)
#pragma unroll
            for (int jn = 0; jn < 16; jn++) {
                const float2 gb = ldsv(vec + V_GB * 512 + jn * 32);
#pragma unroll
                for (int e = 0; e < 4; e++) acc[4 * jn + e] = fmaf((e & 1) ? gb.y : gb.x, acc[4 * jn + e], KEEP(jn, e));
                if ((jn & 7) == 7) put64(o128 + ((jn >> 3) ^ 1) * 8192, acc + 4 * jn - 28);
            }
            PP(18)
            if (tid == 0) TLP(12)
        }
    }
}

typedef CUresult (*EncFn)(CUtensorMap*, CUtensorMapDataType, cuuint32_t, void*, const cuuint64_t*, const cuuint64_t*, const cuuint32_t*,
                          const cuuint32_t*, CUtensorMapInterleave, CUtensorMapSwizzle, CUtensorMapL2promotion, CUtensorMapFloatOOBfill);

static CUtensorMap make_map(EncFn enc, const void* p, uint64_t inner, uint64_t outer, uint32_t bi = 64) {
    CUtensorMap m;
    cuuint64_t dims[2] = {inner, outer};
    cuuint64_t str[1] = {inner * 2};
    cuuint32_t box[2] = {bi, bi == 64 ? 64u : 16u};
    cuuint32_t es[2] = {1, 1};
    enc(&m, CU_TENSOR_MAP_DATA_TYPE_BFLOAT16, 2, (void*)p, dims, str, box, es, CU_TENSOR_MAP_INTERLEAVE_NONE,
        bi == 64 ? CU_TENSOR_MAP_SWIZZLE_128B : CU_TENSOR_MAP_SWIZZLE_NONE, CU_TENSOR_MAP_L2_PROMOTION_L2_256B, CU_TENSOR_MAP_FLOAT_OOB_FILL_NONE);
    return m;
}
static CUtensorMap make_map_o(EncFn enc, const void* p) {
    CUtensorMap m;
    cuuint64_t dims[2] = {16384, 256};
    cuuint64_t str[1] = {65536};
    cuuint32_t box[2] = {256, 8};
    cuuint32_t es[2] = {1, 1};
    enc(&m, CU_TENSOR_MAP_DATA_TYPE_UINT32, 2, (void*)p, dims, str, box, es, CU_TENSOR_MAP_INTERLEAVE_NONE, CU_TENSOR_MAP_SWIZZLE_NONE,
        CU_TENSOR_MAP_L2_PROMOTION_L2_256B, CU_TENSOR_MAP_FLOAT_OOB_FILL_NONE);
    return m;
}
template <class T> static T* sym(T& s) { void* p = nullptr; cudaGetSymbolAddress(&p, s); return (T*)p; }

static const Delays h_dly = {D_NEAR, D_FAR, D_X2, D_V, D_W2, D_PA, 0, D_MORE};
extern "C" void kernel_launch(void* const* d_in, const int* in_sizes, int n_in, void* d_out, int out_size) {
    const bf16* x = (const bf16*)d_in[0];
    const bf16* mem0 = (const bf16*)d_in[1];
    const bf16 *Wq = (const bf16*)d_in[2], *Wk = (const bf16*)d_in[3], *Wv = (const bf16*)d_in[4], *Wo = (const bf16*)d_in[5];
    const bf16 *w1 = (const bf16*)d_in[8], *w2 = (const bf16*)d_in[9], *w3 = (const bf16*)d_in[10], *w4 = (const bf16*)d_in[11];
    const bf16 *c = (const bf16*)d_in[12], *wmod = (const bf16*)d_in[13];
    bf16* out = (bf16*)d_out;

    EncFn enc = nullptr;
    cudaDriverEntryPointQueryResult qr;
    cudaGetDriverEntryPoint("cuTensorMapEncodeTiled", (void**)&enc, cudaEnableDefault, &qr);
    CUtensorMap tWq = make_map(enc, Wq, NH * DH, DM), tWk = make_map(enc, Wk, NH * DH, DM), tWv = make_map(enc, Wv, NH * DH, DM);
    PostMaps mp;
    mp.o = make_map_o(enc, sym(g_O)); mp.wo = make_map(enc, Wo, DM, NH * DH);
    mp.y = make_map(enc, sym(g_y), DM, S_); mp.w1 = make_map(enc, w1, DM, DM);
    mp.g = make_map(enc, sym(g_g), DM, S_); mp.w2 = make_map(enc, w2, DM, DM);
    mp.x1 = make_map(enc, sym(g_x1), DM, S_); mp.w3 = make_map(enc, w3, FF, DM);
    mp.u = make_map(enc, sym(g_u), FF, S_); mp.w4 = make_map(enc, w4, DM, FF);
    mp.out = make_map(enc, out, DM, S_);
    cudaFuncSetAttribute(k_rec, cudaFuncAttributeMaxDynamicSharedMemorySize, SM_REC_TOTAL + 2048);
    cudaFuncSetAttribute(k_post, cudaFuncAttributeMaxDynamicSharedMemorySize, P_SMEM);

    uint8_t* arena = (uint8_t*)(((uintptr_t)sym(g_arena) + (2u << 20) - 1) & ~(uintptr_t)((2u << 20) - 1));
    const PostPtrs pp = {x};
    const RecPtrs rp = {x, mem0, c, wmod, w1, w3, arena, 0u, w2, w4, Wo, h_dly};
    const RecMaps rm = {tWq, tWk, tWv, mp.wo, make_map(enc, wmod, 6 * DM, DM, 256), make_map(enc, w3, FF, DM, 256), make_map(enc, w1, DM, DM, 256)};
    k_rec<<<132, 384, SM_REC_TOTAL + 2048>>>(rm, rp);
    cudaLaunchConfig_t cfg = {};
    cfg.gridDim = dim3(132); cfg.blockDim = dim3(384); cfg.dynamicSmemBytes = P_SMEM; cfg.stream = cudaStreamPerThread;
    cudaLaunchAttribute at[1];
    at[0].id = cudaLaunchAttributeProgrammaticStreamSerialization; at[0].val.programmaticStreamSerializationAllowed = PDL;
    cfg.attrs = at; cfg.numAttrs = 1;
    cudaLaunchKernelEx(&cfg, k_post, mp, pp);
}
```

```cpp
#include <cuda_runtime.h>
#include <cuda.h>
#include <cuda_bf16.h>
#include <stdint.h>
#include <limits.h>

typedef __nv_bfloat16 bf16;

constexpr int S_ = 2048, DM = 1024, NH = 32, DH = 128, NSEG = 64, FF = 3584;
constexpr int SPIN_LIMIT = 1 << 22;
#define W_INFL 2
#define H_PIECES 4
#define PDL 1
#define NPROBE 3

__device__ uint8_t g_arena[10 << 20];
__device__ __align__(128) uint32_t g_tick[64 + 132];
#define g_clk ((uint2*)(g_tick + 64))
__device__ uint32_t g_cls[256];
__device__ unsigned long long g_pt;
__device__ __align__(16) uint32_t g_modp[8 * 2 * DM];
__host__ __device__ constexpr uint32_t blk(uint32_t lb, uint32_t par) {
    return (lb << 13) | ((((lb) ^ (lb >> 3) ^ (lb >> 4) ^ (lb >> 6) ^ par) & 1) << 12);
}
__host__ __device__ constexpr uint32_t lb_x2(uint32_t h) { return (h & 1) | ((h >> 1) << 3); }
__host__ __device__ constexpr uint32_t mem_row(uint32_t kh, uint32_t b, uint32_t r) { return blk(128 | b, kh) + r * 1024; }
__device__ __forceinline__ uint32_t mem_slot(uint32_t s) { return ((s & 1) << 15) | ((s & 2) << 17); }
constexpr uint32_t CNT1 = 0x3d80, CNT_ALL = 0x4000;
constexpr uint32_t LB_PROBE = 6 | 64, LB_TIME = 6;
__host__ __device__ constexpr uint32_t lb_tok(uint32_t h) { return (h & 1) | ((h >> 1) << 3); }
__device__ float g_mod[6 * DM];
__device__ __align__(1024) bf16 g_himg[(S_ + 32) * DM];
__device__ __align__(1024) bf16 g_O[S_ * NH * DH];
__device__ __align__(1024) bf16 g_y[S_ * DM];
__device__ __align__(1024) bf16 g_g[S_ * DM];
__device__ __align__(1024) bf16 g_x1[S_ * DM];
__device__ __align__(16) float g_st[4 * S_ * 2];
__device__ float g_vec[3 * DM + FF];
__device__ float g_cst[8];
__device__ uint32_t g_pcnt[2 * 32 * 8], g_pflag[7 * 32 * 8];
__device__ __align__(1024) bf16 g_u[S_ * FF];

#define TL(i) {}
#define TLX(i) {}
#define TLP(i) TL(i)
#define TLC(i) {}
__device__ __forceinline__ uint32_t smem_u32(const void* p) { return (uint32_t)__cvta_generic_to_shared(p); }
__device__ __forceinline__ void spin_guard(int it) {
    asm volatile("{.reg .pred p; setp.gt.s32 p, %0, %1; @p st.global.u32 [%2], %0;}" ::"r"(it), "n"(SPIN_LIMIT), "l"(1ull));
}
__device__ __forceinline__ void wg_fence() { asm volatile("wgmma.fence.sync.aligned;" ::: "memory"); }
__device__ __forceinline__ void wg_commit() { asm volatile("wgmma.commit_group.sync.aligned;" ::: "memory"); }
template <int N> __device__ __forceinline__ void wg_wait() { asm volatile("wgmma.wait_group.sync.aligned %0;" ::"n"(N) : "memory"); }
__host__ __device__ constexpr uint64_t mkdesc(uint32_t addr, uint32_t lbo, uint32_t sbo, uint32_t swz) {
    return (uint64_t)((addr & 0x3FFFF) >> 4) | ((uint64_t)(lbo >> 4) << 16) | ((uint64_t)(sbo >> 4) << 32) | ((uint64_t)swz << 62);
}
__device__ __forceinline__ uint64_t dadd(uint64_t d, uint32_t o) { return (d & 0xffffffff00000000ull) | (uint32_t)((uint32_t)d + o); }
__device__ __forceinline__ void mbar_init(uint32_t b, uint32_t c) { asm volatile("mbarrier.init.shared.b64 [%0], %1;" ::"r"(b), "r"(c) : "memory"); }
__device__ __forceinline__ void mbar_arrive_cluster(uint32_t b, uint32_t cta) {
    asm volatile("{.reg .b32 r; mapa.shared::cluster.u32 r, %0, %1; mbarrier.arrive.shared::cluster.b64 _, [r];}" ::"r"(b), "r"(cta) : "memory");
}
__device__ __forceinline__ bool mbar_try(uint32_t b, uint32_t par) {
    uint32_t ok;
    asm volatile("{.reg .pred p; mbarrier.try_wait.parity.shared.b64 p, [%1], %2; selp.u32 %0, 1, 0, p;}" : "=r"(ok) : "r"(b), "r"(par) : "memory");
    return ok;
}
__device__ __forceinline__ void mbar_wait(uint32_t b, uint32_t par) {
    int it = 0;
#pragma unroll 1
    while (!mbar_try(b, par) & (++it < SPIN_LIMIT)) {}
}
__device__ __forceinline__ void mbar_wait_w(uint32_t b, uint32_t par) {
    int it = 0;
#pragma unroll 1
    while (!__all_sync(~0u, mbar_try(b, par)) & (++it < SPIN_LIMIT)) {}
}
constexpr uint64_t EVICT_FIRST = 0x12F0000000000000ull, EVICT_NORMAL = 0x1000000000000000ull;   __device__ __forceinline__ void bar_sync(int id, int n) { asm volatile("bar.sync %0, %1;" ::"r"(id), "r"(n) : "memory"); }
__device__ __forceinline__ void bar_arrive(int id, int n) { asm volatile("bar.arrive %0, %1;" ::"r"(id), "r"(n) : "memory"); }
__device__ __forceinline__ void fence_async_smem() { asm volatile("fence.proxy.async.shared::cta;" ::: "memory"); }
__device__ __forceinline__ void ldsm4t(uint32_t* r, uint32_t a) {
    asm volatile("ldmatrix.sync.aligned.m8n8.x4.trans.shared.b16 {%0,%1,%2,%3}, [%4];" : "=r"(r[0]), "=r"(r[1]), "=r"(r[2]), "=r"(r[3]) : "r"(a) : "memory");
}
__device__ __forceinline__ void ldsm4(uint32_t* r, uint32_t a) {
    asm volatile("ldmatrix.sync.aligned.m8n8.x4.shared.b16 {%0,%1,%2,%3}, [%4];" : "=r"(r[0]), "=r"(r[1]), "=r"(r[2]), "=r"(r[3]) : "r"(a) : "memory");
}
__device__ __forceinline__ uint32_t movm(uint32_t a) {
    uint32_t d; asm volatile("movmatrix.sync.aligned.m8n8.trans.b16 %0, %1;" : "=r"(d) : "r"(a)); return d;
}
__device__ __forceinline__ void mma16816(float* d, uint32_t a0, uint32_t a1, uint32_t a2, uint32_t a3, uint32_t b0, uint32_t b1) {
    asm volatile("mma.sync.aligned.m16n8k16.row.col.f32.bf16.bf16.f32 {%0,%1,%2,%3},{%4,%5,%6,%7},{%8,%9},{%0,%1,%2,%3};"
                 : "+f"(d[0]), "+f"(d[1]), "+f"(d[2]), "+f"(d[3]) : "r"(a0), "r"(a1), "r"(a2), "r"(a3), "r"(b0), "r"(b1));
}
__device__ __forceinline__ void mma16816z(float* d, const uint32_t* a, uint32_t b0, uint32_t b1) {
    asm volatile("mma.sync.aligned.m16n8k16.row.col.f32.bf16.bf16.f32 {%0,%1,%2,%3},{%4,%5,%6,%7},{%8,%9},{%10,%10,%10,%10};"
                 : "=f"(d[0]), "=f"(d[1]), "=f"(d[2]), "=f"(d[3]) : "r"(a[0]), "r"(a[1]), "r"(a[2]), "r"(a[3]), "r"(b0), "r"(b1), "f"(0.f));
}
__device__ __forceinline__ void mma1688(float* d, uint32_t a0, uint32_t a1, uint32_t b0) {
    asm volatile("mma.sync.aligned.m16n8k8.row.col.f32.bf16.bf16.f32 {%0,%1,%2,%3},{%4,%5},{%6},{%0,%1,%2,%3};"
                 : "+f"(d[0]), "+f"(d[1]), "+f"(d[2]), "+f"(d[3]) : "r"(a0), "r"(a1), "r"(b0));
}
__device__ __forceinline__ uint32_t pack2(float lo, float hi) {
    uint32_t r; asm("cvt.rn.bf16x2.f32 %0, %1, %2;" : "=r"(r) : "f"(hi), "f"(lo)); return r;
}
__device__ __forceinline__ uint32_t hadd2(uint32_t a, uint32_t b) {
    uint32_t r; asm("add.rn.bf16x2 %0, %1, %2;" : "=r"(r) : "r"(a), "r"(b)); return r;
}
__device__ __forceinline__ float bflo(uint32_t u) { return __uint_as_float(u << 16); }
__device__ __forceinline__ float bfhi(uint32_t u) { return __uint_as_float(u & 0xffff0000u); }
__device__ __forceinline__ float ex2(float x) { float r; asm("ex2.approx.ftz.f32 %0, %1;" : "=f"(r) : "f"(x)); return r; }
__device__ __forceinline__ uint4 ldg_rlx4(const void* p) {
    uint4 v; asm volatile("ld.relaxed.gpu.global.v4.u32 {%0,%1,%2,%3}, [%4];" : "=r"(v.x), "=r"(v.y), "=r"(v.z), "=r"(v.w) : "l"(p) : "memory"); return v;
}
__device__ __forceinline__ uint32_t ldg_rlx1(const void* p) {
    uint32_t v; asm volatile("ld.relaxed.gpu.global.u32 %0, [%1];" : "=r"(v) : "l"(p) : "memory"); return v;
}
__device__ __forceinline__ void stg_rlx1(void* p, uint32_t v) { asm volatile("st.relaxed.gpu.global.u32 [%0], %1;" ::"l"(p), "r"(v) : "memory"); }
__device__ __forceinline__ void stg_rlx2(void* p, uint32_t x, uint32_t y) {
    unsigned long long v = (unsigned long long)x | ((unsigned long long)y << 32);
    asm volatile("st.relaxed.gpu.global.b64 [%0], %1;" ::"l"(p), "l"(v) : "memory");
}
__device__ __forceinline__ void stg_rlx4(void* p, uint32_t x, uint32_t y, uint32_t z, uint32_t w) {
    asm volatile("st.relaxed.gpu.global.v4.u32 [%0], {%1,%2,%3,%4};" ::"l"(p), "r"(x), "r"(y), "r"(z), "r"(w) : "memory");
}
__device__ __forceinline__ void sts4(uint32_t a, uint32_t x, uint32_t y, uint32_t z, uint32_t w) {
    asm volatile("st.shared.v4.u32 [%0], {%1,%2,%3,%4};" ::"r"(a), "r"(x), "r"(y), "r"(z), "r"(w) : "memory");
}
__device__ __forceinline__ uint4 lds4(uint32_t a) {
    uint4 v; asm volatile("ld.shared.v4.u32 {%0,%1,%2,%3}, [%4];" : "=r"(v.x), "=r"(v.y), "=r"(v.z), "=r"(v.w) : "r"(a) : "memory"); return v;
}
#define F4(d, i) "+f"(d[i]), "+f"(d[i + 1]), "+f"(d[i + 2]), "+f"(d[i + 3])
__device__ __forceinline__ void wgmma_rs32(float* d, const uint32_t* a, uint64_t b, int sc) {
    asm volatile("{.reg .pred p; setp.ne.b32 p, %21, 0;\n wgmma.mma_async.sync.aligned.m64n32k16.f32.bf16.bf16 {%0,%1,%2,%3,%4,%5,%6,%7,%8,%9,%10,%11,%12,%13,%14,%15}, {%16,%17,%18,%19}, %20, p, 1, 1, 0;}"
                 : F4(d, 0), F4(d, 4), F4(d, 8), F4(d, 12) : "r"(a[0]), "r"(a[1]), "r"(a[2]), "r"(a[3]), "l"(b), "r"(sc));
}
__device__ __forceinline__ void wgmma_ss32(float* d, uint64_t a, uint64_t b, int sc) {
    asm volatile("{.reg .pred p; setp.ne.b32 p, %18, 0;\n wgmma.mma_async.sync.aligned.m64n32k16.f32.bf16.bf16 {%0,%1,%2,%3,%4,%5,%6,%7,%8,%9,%10,%11,%12,%13,%14,%15}, %16, %17, p, 1, 1, 1, 0;}"
                 : F4(d, 0), F4(d, 4), F4(d, 8), F4(d, 12) : "l"(a), "l"(b), "r"(sc));
}
__device__ __forceinline__ void wgmma_rs40(float* d, const uint32_t* a, uint64_t b, int sc) {
    asm volatile("{.reg .pred p; setp.ne.b32 p, %25, 0;\n wgmma.mma_async.sync.aligned.m64n40k16.f32.bf16.bf16 {%0,%1,%2,%3,%4,%5,%6,%7,%8,%9,%10,%11,%12,%13,%14,%15,%16,%17,%18,%19}, {%20,%21,%22,%23}, %24, p, 1, 1, 0;}"
                 : F4(d, 0), F4(d, 4), F4(d, 8), F4(d, 12), F4(d, 16) : "r"(a[0]), "r"(a[1]), "r"(a[2]), "r"(a[3]), "l"(b), "r"(sc));
}
__device__ __forceinline__ void wgmma_ss40(float* d, uint64_t a, uint64_t b, int sc) {
    asm volatile("{.reg .pred p; setp.ne.b32 p, %22, 0;\n wgmma.mma_async.sync.aligned.m64n40k16.f32.bf16.bf16 {%0,%1,%2,%3,%4,%5,%6,%7,%8,%9,%10,%11,%12,%13,%14,%15,%16,%17,%18,%19}, %20, %21, p, 1, 1, 1, 0;}"
                 : F4(d, 0), F4(d, 4), F4(d, 8), F4(d, 12), F4(d, 16) : "l"(a), "l"(b), "r"(sc));
}
#define F16(d, i) F4(d, i), F4(d, i + 4), F4(d, i + 8), F4(d, i + 12)
template <int TA>
__device__ __forceinline__ void wgmma_ss128(float* d, uint64_t a, uint64_t b, int sc) {
    asm volatile("{.reg .pred p; setp.ne.b32 p, %66, 0;\n wgmma.mma_async.sync.aligned.m64n128k16.f32.bf16.bf16 "
                 "{%0,%1,%2,%3,%4,%5,%6,%7,%8,%9,%10,%11,%12,%13,%14,%15,%16,%17,%18,%19,%20,%21,%22,%23,%24,%25,%26,%27,%28,%29,%30,%31,"
                 "%32,%33,%34,%35,%36,%37,%38,%39,%40,%41,%42,%43,%44,%45,%46,%47,%48,%49,%50,%51,%52,%53,%54,%55,%56,%57,%58,%59,%60,%61,%62,%63}, %64, %65, p, 1, 1, %67, 1;}"
                 : F16(d, 0), F16(d, 16), F16(d, 32), F16(d, 48) : "l"(a), "l"(b), "r"(sc), "n"(TA));
}

__device__ __forceinline__ float warp_sum(float v) {
#pragma unroll
    for (int o = 16; o; o >>= 1) v += __shfl_xor_sync(~0u, v, o);
    return v;
}
__device__ __forceinline__ float bfround(float x) { return __bfloat162float(__float2bfloat16(x)); }

__device__ __forceinline__ void wait_count1(const uint32_t* p, uint32_t target) {
    int it = 0;
#pragma unroll 1
    while (true) {
        uint32_t v;
        asm volatile("ld.acquire.gpu.global.u32 %0, [%1];" : "=r"(v) : "l"(p) : "memory");
        if (v >= target) break;
        spin_guard(++it);
    }
}
__device__ __forceinline__ void red2(float* p, float a, float b) {
    asm volatile("red.relaxed.gpu.global.add.v2.f32 [%0], {%1, %2};" ::"l"(p), "f"(a), "f"(b) : "memory");
}
__device__ __forceinline__ void signal_count(uint32_t* p) { asm volatile("red.release.gpu.global.add.u32 [%0], 1;" ::"l"(p) : "memory"); }
__device__ __forceinline__ void e_expect(uint32_t b, uint32_t tx) {
    asm volatile("{.reg .pred p; elect.sync _|p, 0xffffffff; @p mbarrier.arrive.expect_tx.shared.b64 _, [%0], %1;}" ::"r"(b), "r"(tx) : "memory");
}
__device__ __forceinline__ void e_tma2d(uint32_t dst, const CUtensorMap* m, int c0, int c1, uint32_t bar) {
    asm volatile("{.reg .pred p; elect.sync _|p, 0xffffffff;\n @p cp.async.bulk.tensor.2d.shared::cluster.global.mbarrier::complete_tx::bytes [%0], [%1, {%3, %4}], [%2];}"
                 ::"r"(dst), "l"(m), "r"(bar), "r"(c0), "r"(c1) : "memory");
}
__device__ __forceinline__ void e_tma2d_hint(uint32_t dst, const CUtensorMap* m, int c0, int c1, uint32_t bar, uint64_t pol) {
    asm volatile("{.reg .pred p; elect.sync _|p, 0xffffffff;\n @p cp.async.bulk.tensor.2d.shared::cluster.global.mbarrier::complete_tx::bytes.L2::cache_hint [%0], [%1, {%3, %4}], [%2], %5;}"
                 ::"r"(dst), "l"(m), "r"(bar), "r"(c0), "r"(c1), "l"(pol) : "memory");
}
__device__ __forceinline__ void e_tma2d_mc(uint32_t dst, const CUtensorMap* m, int c0, int c1, uint32_t bar) {
    asm volatile("{.reg .pred p; elect.sync _|p, 0xffffffff;\n @p cp.async.bulk.tensor.2d.shared::cluster.global.mbarrier::complete_tx::bytes.multicast::cluster [%0], [%1, {%3, %4}], [%2], %5;}"
                 ::"r"(dst), "l"(m), "r"(bar), "r"(c0), "r"(c1), "h"((uint16_t)3) : "memory");
}
__device__ __forceinline__ void wait_count_w(const uint32_t* p, uint32_t target) {
    int it = 0;
#pragma unroll 1
    while (true) {
        uint32_t v;
        asm volatile("ld.acquire.gpu.global.u32 %0, [%1];" : "=r"(v) : "l"(p) : "memory");
        if (__all_sync(~0u, v >= target) | (++it > SPIN_LIMIT)) break;
        __nanosleep(100);
    }
}

#define NL 6
constexpr uint32_t SM_HB = 16384, HBK = 5120, SM_SX = 57344, SM_OX = 122880, SM_PX = 124928, SM_PA = 126976, SM_WO = 147456,
                   SM_TAB = 212992, SM_PRE = SM_TAB + 5120, SM_BAR = 227328, SM_REC_TOTAL = 227328 + 256;
constexpr uint32_t SB0 = 1024;
constexpr int B_WO = 0, B_HE = 1, B_HB = 3, B_W = 5;
constexpr int NB_MEM = 1, NB_QK = 2, NB_X1 = 3, NB_X2 = 4, NB_WIN = 5, NB_WG = 6, NB_KDONE = 7, NB_FIN0 = 8, NB_P = 9, NB_PX = 10, NB_G = 11, NB_A = 12, NB_B = 13, NB_C = 14, NB_S = 15;
#define D_NEAR 1620
#define D_FAR (D_NEAR - 90)
#define D_X2 400
#define D_V 280
#define D_W2 40
#define D_PA 40
#define D_MORE 40
constexpr int E_MUL = 28;
constexpr int NPF = NL + 6, NE1 = 10;
constexpr int W0_E = 3, W0_RS = NL - 1, G_AT = 18;
struct Delays { uint32_t near, far, x2, v, w2, pa, spare, more; };
#define MISS(i, v)
#define MISS_INIT
#define MISS_OUT
#define HT(i)

__device__ __forceinline__ uint32_t clk32() { uint32_t t; asm volatile("mov.u32 %0, %%clock;" : "=r"(t) :: "memory"); return t; }
__device__ __forceinline__ uint32_t smid() { uint32_t t; asm volatile("mov.u32 %0, %%smid;" : "=r"(t)); return t; }
__device__ __forceinline__ uint32_t gtime() { uint32_t t; asm volatile("mov.u32 %0, %%globaltimer_lo;" : "=r"(t) :: "memory"); return t; }
__device__ __forceinline__ void spin_until(uint32_t t0, uint32_t d) { while (clk32() - t0 < d) {} }
template <int N> __device__ __forceinline__ uint32_t delay(uint32_t zero) {
    float x = __uint_as_float(clk32());
#pragma unroll
    for (int i = 0; i < N; i++) asm volatile("ex2.approx.ftz.f32 %0, %0;" : "+f"(x));
    return __float_as_uint(x) & zero;
}
__device__ __forceinline__ uint32_t opaque(uint32_t v) { return __shfl_sync(~0u, v, threadIdx.x & 31); }
__device__ __forceinline__ uint32_t xor_or(uint32_t a, uint32_t b, uint32_t t) {
    uint32_t r; asm volatile("lop3.b32 %0, %1, %2, %3, 0x7E;" : "=r"(r) : "r"(a), "r"(b), "r"(t)); return r;
}
__device__ __forceinline__ uint32_t settag(uint32_t v, uint32_t tag) {
    uint32_t r; asm("lop3.b32 %0, %1, 1, %2, 0xB8;" : "=r"(r) : "r"(v), "r"(tag)); return r;
}
__device__ __forceinline__ void sts2(uint32_t a, float x, float y) { asm volatile("st.shared.v2.f32 [%0], {%1,%2};" ::"r"(a), "f"(x), "f"(y) : "memory"); }
__device__ __forceinline__ void sts4f(uint32_t a, float x, float y, float z, float w) {
    asm volatile("st.shared.v4.f32 [%0], {%1,%2,%3,%4};" ::"r"(a), "f"(x), "f"(y), "f"(z), "f"(w) : "memory");
}
__device__ __forceinline__ void sts1(uint32_t a, uint32_t x) { asm volatile("st.shared.u32 [%0], %1;" ::"r"(a), "r"(x) : "memory"); }
__device__ __forceinline__ uint32_t lds1(uint32_t a) { uint32_t v; asm volatile("ld.shared.u32 %0, [%1];" : "=r"(v) : "r"(a) : "memory"); return v; }
__device__ __forceinline__ float4 lds4f(uint32_t a) {
    float4 v; asm volatile("ld.shared.v4.f32 {%0,%1,%2,%3}, [%4];" : "=f"(v.x), "=f"(v.y), "=f"(v.z), "=f"(v.w) : "r"(a) : "memory"); return v;
}
__device__ __forceinline__ float2 lds2f(uint32_t a) {
    float2 v; asm volatile("ld.shared.v2.f32 {%0,%1}, [%2];" : "=f"(v.x), "=f"(v.y) : "r"(a) : "memory"); return v;
}
__device__ __forceinline__ bool any_bit0(uint32_t x) {
    uint32_t r;
    asm volatile("{.reg .pred p, q; .reg .b32 t; and.b32 t, %1, 1; setp.ne.u32 p, t, 0; vote.sync.any.pred q, p, 0xffffffff; selp.u32 %0, 1, 0, q;}" : "=r"(r) : "r"(x));
    return r;
}
__device__ __forceinline__ float rcp_fast(float x) { float r; asm("rcp.approx.ftz.f32 %0, %1;" : "=f"(r) : "f"(x)); return r; }
__device__ __forceinline__ void stsm4(uint32_t a, uint32_t r0, uint32_t r1, uint32_t r2, uint32_t r3) {
    asm volatile("stmatrix.sync.aligned.m8n8.x4.shared.b16 [%0], {%1,%2,%3,%4};" ::"r"(a), "r"(r0), "r"(r1), "r"(r2), "r"(r3) : "memory");
}
__device__ __forceinline__ void stsm4t(uint32_t a, uint32_t r0, uint32_t r1, uint32_t r2, uint32_t r3) {
    asm volatile("stmatrix.sync.aligned.m8n8.x4.trans.shared.b16 [%0], {%1,%2,%3,%4};" ::"r"(a), "r"(r0), "r"(r1), "r"(r2), "r"(r3) : "memory");
}
__device__ __forceinline__ uint32_t and3(uint32_t a, uint32_t b, uint32_t c) {
    uint32_t r; asm("lop3.b32 %0, %1, %2, %3, 0x80;" : "=r"(r) : "r"(a), "r"(b), "r"(c)); return r;
}
__device__ __forceinline__ void red_mem(void* p, uint32_t x, uint32_t y, uint32_t z, uint32_t w, void* q, uint32_t e, bool c) {
    asm volatile("{.reg .pred p; setp.ne.u32 p, %7, 0; red.relaxed.gpu.global.add.noftz.v4.bf16x2 [%0], {%1,%2,%3,%4}; @p red.relaxed.gpu.global.add.noftz.bf16x2 [%5], %6;}"
                 ::"l"(p), "r"(x), "r"(y), "r"(z), "r"(w), "l"(q), "r"(e), "r"((uint32_t)c) : "memory");
}
__device__ __forceinline__ void stg4_if(bool c, void* p, uint32_t x) {
    asm volatile("{.reg .pred p; setp.ne.u32 p, %2, 0; @p st.relaxed.gpu.global.v4.u32 [%0], {%1,%1,%1,%1};}" ::"l"(p), "r"(x), "r"((uint32_t)c) : "memory");
}

__device__ __forceinline__ void h_load(uint32_t sb, const uint8_t* hsrc, int pass, uint32_t rank, uint32_t rot) {
    const uint8_t* src = hsrc + (size_t)pass * 65536;
    const uint32_t bar = sb + SM_BAR + 8 * (B_HB + (pass & 1)), dst = sb + SM_HB + (pass & 1) * 65536 + rank * 4 * HBK;
    e_expect(bar, 32768);
#pragma unroll 1
    for (int i = 0; i < H_PIECES; i++) {
        const uint32_t o = ((i + rot) & (H_PIECES - 1)) * (16384 / H_PIECES);
        asm volatile("{.reg .pred p; elect.sync _|p, 0xffffffff;\n"
                     " @p cp.async.bulk.shared::cluster.global.mbarrier::complete_tx::bytes.multicast::cluster [%0], [%1], %4, [%2], %3;}"
                     ::"r"(dst + o + (o >> 12) * 1024), "l"(src + o), "r"(bar), "h"((uint16_t)3), "n"(16384 / H_PIECES) : "memory");
    }
}
__device__ __forceinline__ uint4 ldg_b128(const void* p) {
    uint4 v;
    asm volatile("{.reg .b128 t; .reg .b64 a, b; ld.relaxed.gpu.global.b128 t, [%4]; mov.b128 {a, b}, t; mov.b64 {%0,%1}, a; mov.b64 {%2,%3}, b;}"
                 : "=r"(v.x), "=r"(v.y), "=r"(v.z), "=r"(v.w) : "l"(p) : "memory");
    return v;
}
__device__ __forceinline__ void stg_b128_if(bool c, void* p, uint32_t x, uint32_t y, uint32_t z, uint32_t w) {
    asm volatile("{.reg .pred p; setp.ne.u32 p, %5, 0; @p st.relaxed.gpu.global.v4.u32 [%0], {%1,%2,%3,%4};}"
                 ::"l"(p), "r"(x), "r"(y), "r"(z), "r"(w), "r"((uint32_t)c) : "memory");
}
__device__ __forceinline__ float pretag(float x, uint32_t add, uint32_t keep) { return __uint_as_float((__float_as_uint(x) + add) & keep); }

template <class F, class G>
__device__ __forceinline__ void softmax_rows(uint32_t src, uint32_t dst, uint32_t g16, int row0, F ready, G mid) {
    const uint32_t u = (g16 >> 7) & 3, e = ((g16 >> 9) << 3) | ((g16 >> 4) & 7);
    uint32_t se = src + e * 8, su = se + u * 1088, d0 = dst + e * 16 + u * 4, d1 = dst + 512 + e * 4;
    int vis = row0 + (e >> 2) - 2 * (e & 3) - 8 * u;
    asm volatile("" : "+r"(se), "+r"(su), "+r"(d0), "+r"(d1), "+r"(vis));
    ready();
    const float2 p0 = lds2f(su), p1 = lds2f(su + 256), p2 = lds2f(su + 512), p3 = lds2f(su + 768);
    const float2 m0 = lds2f(se + 4352), m1 = lds2f(se + 4352 + 256), m2 = lds2f(se + 4352 + 512), m3 = lds2f(se + 4352 + 768);
    float a0 = (p0.x + p1.x) + (p2.x + p3.x), a1 = (p0.y + p1.y) + (p2.y + p3.y);
    const float a2 = (m0.x + m1.x) + (m2.x + m3.x), a3 = (m0.y + m1.y) + (m2.y + m3.y);
    if (vis < 0) a0 = -1e9f / 0.08838834764831845f;
    if (vis < 1) a1 = -1e9f / 0.08838834764831845f;
    int k = __float_as_int(fmaxf(fmaxf(a0, a1), fmaxf(a2, a3)));
    k ^= (k >> 31) & 0x7fffffff;
    const bool hi = g16 & 64;
    const int k0 = __reduce_max_sync(~0u, hi ? INT_MIN : k), k1 = __reduce_max_sync(~0u, hi ? k : INT_MIN);
    mid();
    k = hi ? k1 : k0;
    const float m = __int_as_float(k ^ ((k >> 31) & 0x7fffffff));
    const float sl2 = 0.08838834764831845f * 1.4426950408889634f, mb = -m * sl2;
    sts1(d0, pack2(ex2(fmaf(a0, sl2, mb)), ex2(fmaf(a1, sl2, mb))));
    sts1(d1, pack2(ex2(fmaf(a2, sl2, mb)), ex2(fmaf(a3, sl2, mb))));
}

__device__ __forceinline__ uint32_t pack_h2(float lo, float hi) {
    uint32_t r; asm("cvt.rn.satfinite.f16x2.f32 %0, %1, %2;" : "=r"(r) : "f"(hi), "f"(lo)); return r;
}
__device__ __forceinline__ float2 unpack_h2(uint32_t u) {
    float2 r; asm("{.reg .b16 l, h; mov.b32 {l, h}, %2; cvt.f32.f16 %0, l; cvt.f32.f16 %1, h;}" : "=f"(r.x), "=f"(r.y) : "r"(u)); return r;
}
__device__ __forceinline__ uint32_t add_h2(uint32_t a, uint32_t b) { uint32_t r; asm("add.rn.f16x2 %0, %1, %2;" : "=r"(r) : "r"(a), "r"(b)); return r; }
__device__ __forceinline__ uint32_t max_h2(uint32_t a, uint32_t b) { uint32_t r; asm("max.f16x2 %0, %1, %2;" : "=r"(r) : "r"(a), "r"(b)); return r; }
struct U2 { uint32_t x, y; };
__device__ __forceinline__ U2 ldg_u2(const void* p) {
    U2 v; asm volatile("{.reg .b64 t; ld.relaxed.gpu.global.b64 t, [%2]; mov.b64 {%0, %1}, t;}" : "=r"(v.x), "=r"(v.y) : "l"(p) : "memory"); return v;
}
constexpr int POLL_LIMIT = 1 << 16;
constexpr float SM_L2E = 0.08838834764831845f * 1.4426950408889634f;
template <int V> struct IC { static constexpr int value = V; };
typedef unsigned long long u64;
__device__ __forceinline__ u64 ldg_u64(const void* p) { u64 v; asm volatile("ld.relaxed.gpu.global.b64 %0, [%1];" : "=l"(v) : "l"(p) : "memory"); return v; }
__device__ __forceinline__ void rec_main(uint32_t sb, const CUtensorMap* tWo, uint8_t* arena, int role, int hinfo, int wg, uint32_t zero, const Delays& dly) {
    const int hA = hinfo & 255;
    const int tid = threadIdx.x, t = tid & 127, lane = tid & 31, wi = t >> 5;
    const uint32_t bars = sb + SM_BAR;
    const int head = role >> 2, qd = role & 3, j = blockIdx.x & 1, kh = role & 1;
    const uint32_t mypar = head >= hA;
    const uint32_t wu = __reduce_max_sync(~0u, wi);
    const bool warp0 = wu == 0, warp1 = wu == 1;
    const uint8_t* hsrc = (const uint8_t*)g_himg + kh * 32768 + j * 16384;
    auto tokbase = [&](int ty) { return ((ty + 1) << 21) + blk(lb_tok(head), mypar ^ ((hinfo >> (8 + ty)) & 1)); };
    const uint32_t tbw = tokbase(wg), tbq = tokbase(0) + (qd >> 1) * 2048 + (qd & 1) * 8;
    uint32_t w[32 - NL][4];
    const uint32_t frow = ((lane >> 4) * 8 + (lane & 7)) * 128, fx = ((lane >> 3) & 1) ^ (lane & 7);
    const uint32_t wl0 = sb + wg * 65536 + frow + ((fx ^ (2 * wi)) << 4);
    uint32_t g16 = opaque(t * 16);
    auto G16 = [&]() { asm volatile("" : "+r"(g16)); return g16; };
    const uint32_t sbl = sb - wu * 512;
    const uint32_t xso = blk(lb_x2(head), mypar), cu = kh * 2048 + (2 * j + (wu >> 1)) * 512;
    const uint32_t u_xo = xso + wg * 16384 + (wu & 1) * 2048 + (cu >> 1) - wu * 256, u_to = tbw + (wu & 1) * 16384 + cu - wu * 512;
    {
        uint8_t* pp = arena + (tbw + (1 << 20) + j * 16384 + (kh ^ 1) * 2048 + g16);
        stg_rlx4(pp, 0, 0, 0, 0);
        stg_rlx4(pp + 32768, 0, 0, 0, 0);
        stg_rlx4(arena + (u_to + g16), 0, 0, 0, 0);
        stg_rlx2(arena + (u_xo + (g16 >> 1)), 0, 0);
    }
    {
        if (wg > 0) wait_count_w(&g_tick[32 + (lane & 3) * 8], 1);
        if (wg == 1) asm volatile("fence.proxy.async.global;" ::: "memory");
#pragma unroll 1
        for (int i = 0; i < 4; i++) mbar_wait_w(bars + 8 * (B_W + (wg == 2 ? 8 + i : 2 * i + wg)), 0);
#pragma unroll
        for (int p = NL; p < 32; p++) ldsm4t(w[p - NL], wl0 + p * 2048);
        fence_async_smem();
        bar_sync(wg < 2 ? NB_WG : NB_X2, wg < 2 ? 256 : 128);
        if (wg == 2 && wu < 3) {
            e_expect(bars + 8 * B_WO, 16384);
            e_tma2d(sb + SM_WO + wu * 16384, tWo, (wu >> 1) * 512 + qd * 128 + (wu & 1) * 64, head * DH, bars + 8 * B_WO);
            e_tma2d(sb + SM_WO + wu * 16384 + 8192, tWo, (wu >> 1) * 512 + qd * 128 + (wu & 1) * 64, head * DH + 64, bars + 8 * B_WO);
        }
        if (wg == 1 && warp0) {
            if (lane == 0) mbar_arrive_cluster(bars + 8 * B_HE, j ^ 1);
            mbar_wait_w(bars + 8 * B_HE, 0);
#pragma unroll 1
            for (int i = 0; i < 2; i++) h_load(sb, hsrc, i, j, head);
        }
        TL(3 + wg)
    }
    const uint32_t mrow = wg < 2 ? mem_row(wu >> 1, wg * 2 + (wu & 1), qd) : mem_row(kh, wu, 0);
    const uint32_t u_m = mrow - wu * 512, u_e = mrow + 512 - wu * 64;
#define TAB(i) lds1(sb + SM_TAB + (i) * 512 + (G16() >> 2))
    {
        const uint32_t r8 = lane & 7;
        const uint32_t tb = sb + SM_TAB + wg * 1536 + t * 4, ma = sb + SM_HB + 4096 + r8 * 128;
        if (wg < 2) {
            sts1(tb, sb + SM_WO + wi * 16384 + frow + ((fx ^ (2 * wg)) << 4));
            sts1(tb + 512, wl0);
            sts1(tb + 1024, ma + (((lane >> 3) ^ r8) << 4));
        } else {
            sts1(tb, ma + (wi & 1) * HBK + ((((wi & 2) + (lane >> 4) * 4 + ((lane >> 3) & 1)) ^ r8) << 4));
            sts1(tb + 512, ((((wi & 2) + 4) ^ r8) << 4) + ((lane & 3) == 2 ? ma + 128 + ((wi & 1) + (lane >> 3) * 2) * HBK : sb + SM_HB - 128));
            sts1(tb + 1024, mem_row(role >> 6, (role >> 4) & 3, (role >> 2) & 3) + (lane < 8 ? qd * 128 + lane * 16 : 512 + qd * 32 + (lane & 1) * 16));
        }
    }
    MISS_INIT
#define HB(ks) dadd(mkdesc(SB0 + SM_HB + ((ks) >> 2) * HBK + ((ks) & 3) * 32, 16, 1024, 1), hbo)
#define STEP_CONSTS                                                                                  \
    const uint32_t tag = (s & 1) ^ 1, ttag = ((s >> 1) & 1) ^ 1, tso = (s & 1) * 32768;              \
    G16();                            \
    const int p = s + 2, b = p & 1;                                                                  \
    uint32_t hbo = b * 4096, fz[5] = {0, 0, 0, 0, 0};                                                   \
    const uint32_t ftag = (((p - 1) >> 1) & 1) ^ 1, ptag = ((p >> 1) & 1) ^ 1;                       \
    const uint32_t pso = tbw + (1 << 20) + (b ^ 1) * 32768 + j * 16384 + kh * 2048;
#define SCHED_FENCE(i) fz[i] = clk32();
#define FZ ((fz[0] | fz[1] | fz[2] | fz[3] | fz[4]) & zero)
#define BLOCK_FENCE asm volatile("pmevent 0;" ::: "memory");
    constexpr int GAP = 32 / NL;
#define l16 (sbl + g16)
#define g8 (g16 >> 1)
    uint4 u, v;
    uint8_t *pdst, *fdst;
    auto tok_pack = [&](int ty, const float* acc, uint32_t ftag, uint32_t ptag, bool later = false) {
        const bool tg = ty == 2 || !(g16 & 64);
        const uint32_t add = tg ? (ftag ^ 1) << 16 : 0u, keep = tg ? 0xfffe0000u : ~0u;
        const uint32_t add1 = ty == 2 ? 0u : add, keep1 = ty == 2 ? ~0u : keep;
        const uint32_t add2 = ty == 0 ? add : 0u, keep2 = ty == 0 ? keep : ~0u;
        v = {pack2(pretag(acc[0], add, keep), pretag(acc[1], add1, keep1)), pack2(acc[2], acc[3]),
             pack2(pretag(acc[4], add2, keep2), pretag(acc[5], add2, keep2)), pack2(acc[6], acc[7])};
        if (ty < 2) { v.x = movm(v.x); v.z = movm(v.z); v.y = movm(v.y); v.w = movm(v.w); }
        u = {pack2(pretag(acc[8], (ptag ^ 1) << 16, 0xfffe0000u), acc[9]) | ptag, pack2(acc[10], acc[11]), pack2(acc[12], acc[13]), pack2(acc[14], acc[15])};
        if (later) return;
        v.x = settag(v.x, ftag);
        if (ty == 0) v.z = settag(v.z, ftag);
    };

#pragma unroll 1
    for (int s = -2; s < 0; s++) {
        STEP_CONSTS
        (void)tag; (void)ttag; (void)tso; (void)fz;
        float acc[16];
        mbar_wait_w(bars + 8 * (B_HB + b), 0);
        wg_fence();
#pragma unroll
        for (int i = 0; i < 32; i++) {
            if (i < NL) wgmma_ss32(acc, dadd(mkdesc(SB0 + i * 2048, 8192, 1024, 1), wg * 4096), HB(i), i != 0);
            else wgmma_rs32(acc, w[i < NL ? 0 : i - NL], HB(i), 1);
        }
        wg_commit();
        uint4 pa = {0, 0, 0, 0};
        int it = 0;
#pragma unroll 1
        while ((p > 0) & any_bit0(pa.x ^ ftag) & (++it < POLL_LIMIT)) pa = ldg_b128(arena + (pso + g16));
        pdst = arena + ((pso ^ (32768 + 2048)) + G16());
        fdst = arena + ((b ^ 1) * 32768 + u_to + g16);
        wg_wait<0>();
#pragma unroll
        for (int k = 0; k < 4; k++) { acc[2 * k] += bflo((&pa.x)[k]); acc[2 * k + 1] += bfhi((&pa.x)[k]); }
        tok_pack(wg, acc, ftag, ptag);
        stg_b128_if(true, pdst, u.x, u.y, u.z, u.w);
        stg_b128_if(p > 0, fdst, v.x, v.y, v.z, v.w);
        if (p == 0) {
            TL(2)
            if (wg != 1) bar_arrive(NB_C, 288);
        }
    }
    if (wg == 1 && warp0) {
        wait_count_w(&g_tick[32 + (lane & 3) * 8], 2);
        asm volatile("fence.proxy.async.global;" ::: "memory");
        bar_sync(NB_C, 288);
        if (g16 == 0) mbar_arrive_cluster(bars + 8 * B_HE, j ^ 1);
        mbar_wait_w(bars + 8 * B_HE, 1);
        h_load(sb, hsrc, 2, j, head);
    }

    auto qk_loop = [&](auto wgc) {
        constexpr int WG = decltype(wgc)::value;
        uint32_t w0[NL][4], lm0;
        auto w0_load = [&]() {
            const uint32_t wl = TAB(WG * 3 + 1);
            lm0 = TAB(WG * 3 + 2);
#pragma unroll
            for (int k = 0; k < NL; k++) ldsm4t(w0[k], wl + k * 2048);
        };
        const uint32_t wlo = WG * 65536 - SM_WO - wu * 16384, wlx = __reduce_max_sync(~0u, (wi ^ WG) << 5);
        uint32_t tq0, lm, lm1;
        auto proj_pre = [&](int s) {
            uint32_t wz0 = zero;
#pragma unroll
            for (int k = 0; k < NL; k += 2) wz0 = and3(wz0, w0[k][0], w0[k + 1 < NL ? k + 1 : k][0]);
            lm = lm0 + (s & 1) * 65536 + wz0; lm1 = lm ^ 64;
            asm volatile("" : "+r"(lm), "+r"(lm1));
        };
        auto proj = [&](int s, auto mid) {
            bar_sync(NB_MEM, 384);
            float c[4][4];
            uint32_t bf[16][4], tq1;
#pragma unroll
            for (int it = 0; it < 3; it++) ldsm4(bf[it], (it & 1 ? lm1 : lm) + (it >> 1) * HBK);
            mid(-1);
#pragma unroll
            for (int it = 0; it < 16; it++) {
                const uint32_t* bfr = bf[it];
                if (it + 3 < 16) ldsm4(bf[it + 3 < 16 ? it + 3 : 0], (it & 1 ? lm : lm1) + ((it + 3) >> 1) * HBK);
                const uint32_t* wa = 2 * it < NL ? w0[2 * it < NL ? 2 * it : 0] : w[2 * it < NL ? 0 : 2 * it - NL];
                const uint32_t* wb = 2 * it + 1 < NL ? w0[2 * it + 1 < NL ? 2 * it + 1 : 0] : w[2 * it + 1 < NL ? 0 : 2 * it + 1 - NL];
                float *ca = c[(2 * it) & 3], *cb = c[(2 * it + 1) & 3];
                if (it < 2) { mma16816z(ca, wa, bfr[0], bfr[1]); mma16816z(cb, wb, bfr[2], bfr[3]); }
                else { mma16816(ca, wa[0], wa[1], wa[2], wa[3], bfr[0], bfr[1]); mma16816(cb, wb[0], wb[1], wb[2], wb[3], bfr[2], bfr[3]); }
                mid(it);
                if (it == 15) { tq1 = clk32(); bar_arrive(NB_QK, 384); }
            }
            const uint32_t xo = u_xo + (G16() >> 1);
            float r[4];
#pragma unroll
            for (int e = 0; e < 4; e++) {
                constexpr float SH = SM_L2E / 64;
                r[e] = WG ? (c[0][e] + c[1][e]) + (c[2][e] + c[3][e]) : fmaf(c[2][e] + c[3][e], SH, (c[0][e] + c[1][e]) * SH);
            }
            const uint32_t r0 = pack2(r[0], r[1]), r1 = pack2(r[2], r[3]);
            const uint32_t m0 = movm(r0), m1 = movm(r1);
            tq0 = clk32();
            stg_rlx2(arena + xo, settag(m0, (s & 1) ^ 1), m1);
            tq0 += tq1 & zero;
        };
        w0_load();
        proj_pre(0);
        if (WG == 1) bar_sync(NB_P, 256);
        proj(0, [](int) {});
        if (WG == 0) mbar_wait_w(bars + 8 * B_WO, 0);
#pragma unroll 1
        for (int s = 0;; s++) {
            STEP_CONSTS
            uint4 pa;
            float acc[16];
            auto acc_init = [&]() {
#pragma unroll
                for (int k = 0; k < 4; k++) { acc[2 * k] = bflo((&pa.x)[k]); acc[2 * k + 1] = bfhi((&pa.x)[k]); acc[8 + 2 * k] = __uint_as_float((&pa.x)[k] & zero); acc[9 + 2 * k] = __uint_as_float(~(&pa.x)[k] & zero); }
            };
            uint32_t wf[NPF][4], a3;
#define WF(f) ((a3 ^ (((f) & 1) * 64)) + ((f) >> 1) * 2048)
            if (WG == 1) {
                float sc[5][4];
                uint32_t sx0 = sb + SM_SX - wu * (2560 - 16) + G16() * 5;
                asm volatile("" : "+r"(sx0));
                int it = 0;
                bool bad;
#pragma unroll 1
                do {
                    uint4 kf[2][2];
                    U2 qf[2], x[8];
                    const uint32_t gz = g16 | (it & zero);
                    const uint8_t *ts = arena + (tso + tbw + gz), *tq = arena + (tso + tbq + gz), *xp = arena + (xso + (gz >> 1));
#pragma unroll
                    for (int a = 0; a < 4; a++) kf[a >> 1][a & 1] = ldg_b128(ts + (a >> 1) * 16384 + (a & 1) * 2048);
                    spin_until(tq0, dly.x2 - 100);
#pragma unroll
                    for (int a = 0; a < 2; a++) qf[a] = ldg_u2(tq + a * 16384);
                    spin_until(tq0, dly.x2);
#pragma unroll
                    for (int i = 0; i < 8; i++) x[i] = ldg_u2(xp + (i >> 2) * 16384 + (i & 3) * 1024);
                    const uint32_t q0[4] = {hadd2(x[0].x, x[1].x), qf[0].x, hadd2(x[0].y, x[1].y), qf[0].y};
                    const uint32_t q1[4] = {hadd2(x[2].x, x[3].x), qf[1].x, hadd2(x[2].y, x[3].y), qf[1].y};
                    const uint32_t bt = ((qf[0].x ^ ttag) | (qf[1].x ^ ttag)) | ((kf[0][0].x ^ ttag) | (kf[0][1].x ^ ttag)) | ((kf[1][0].x ^ ttag) | (kf[1][1].x ^ ttag));
                    uint32_t bx = 0;
#pragma unroll
                    for (int i = 0; i < 8; i += 2) bx |= (x[i].x ^ tag) | (x[i + 1].x ^ tag);
                    mma16816z(sc[0], q0, kf[0][0].x, kf[0][0].y);
                    mma16816z(sc[1], q0, kf[0][0].z, kf[0][0].w);
                    mma16816z(sc[2], q0, kf[0][1].x, kf[0][1].y);
                    mma16816z(sc[3], q0, kf[0][1].z, kf[0][1].w);
                    mma16816z(sc[4], q0, hadd2(x[4].x, x[5].x), hadd2(x[4].y, x[5].y));
                    bad = any_bit0(bt | bx) & (++it < POLL_LIMIT);
                    mma16816(sc[0], q1[0], q1[1], q1[2], q1[3], kf[1][0].x, kf[1][0].y);
                    mma16816(sc[1], q1[0], q1[1], q1[2], q1[3], kf[1][0].z, kf[1][0].w);
                    mma16816(sc[2], q1[0], q1[1], q1[2], q1[3], kf[1][1].x, kf[1][1].y);
                    mma16816(sc[3], q1[0], q1[1], q1[2], q1[3], kf[1][1].z, kf[1][1].w);
                    mma16816(sc[4], q1[0], q1[1], q1[2], q1[3], hadd2(x[6].x, x[7].x), hadd2(x[6].y, x[7].y));
                } while (bad);
                MISS(1, it - 1)
                sts4(sx0, pack_h2(sc[0][0], sc[0][1]), pack_h2(sc[1][0], sc[1][1]), pack_h2(sc[2][0], sc[2][1]), pack_h2(sc[3][0], sc[3][1]));
                sts1(sx0 + 64 - wu * 12, pack_h2(sc[4][0], sc[4][1]));
                bar_arrive(NB_X1, 384);
                auto tok_sts = [&]() {
#pragma unroll
                    for (int n = 0; n < 5; n++) sts2(sb + SM_SX + 2560 + g8 + n * 1088, sc[n][2], sc[n][3]);
                };
                a3 = TAB(WG * 3);
                if (s == 0) mbar_wait_w(bars + 8 * B_WO, 0);
                softmax_rows(sb + SM_SX + 2560, sb + SM_PX + 1024, g16 | (clk32() & zero), qd * 8, [&]() { BLOCK_FENCE tok_sts(); bar_sync(NB_PX, 128); }, [&]() {
                    BLOCK_FENCE
#pragma unroll
                    for (int f = 0; f < NE1; f++) ldsm4t(wf[f], WF(f));
                    BLOCK_FENCE
                });
            } else {
                a3 = TAB(WG * 3);
                if (warp1 && (s & 3) == 1) asm volatile("fence.proxy.async.global;" ::: "memory");
                spin_until(tq0, dly.pa);
                uint4 x, y;
                int it = 0;
#pragma unroll 1
                do { x = ldg_b128(arena + (pso + g16)); y = ldg_b128(arena + (pso + tokbase(1) - tokbase(0) + g16)); }
                while ((p <= NSEG) & any_bit0(xor_or(x.x, y.x, ftag)) & (++it < POLL_LIMIT));
                sts4(sb + SM_PA + g16, x.x, x.y, x.z, x.w);
                sts4(sb + SM_PA + 2048 + g16, y.x, y.y, y.z, y.w);
                bar_sync(NB_X1, 384);
                if (g16 < 32) asm volatile("red.relaxed.gpu.global.max.u32 [%0], %1; red.relaxed.gpu.global.add.u32 [%0+4], 1;"
                                                    ::"l"(arena + ((blk(LB_TIME, 0) ^ (g16 << 8)) + qd * 1024 + (tq0 & zero))), "r"(gtime()) : "memory");
                __syncwarp();
                const uint32_t tx = clk32();
                spin_until(tx, dly.w2);
            }
#pragma unroll
            for (int f = WG ? NE1 : 0; f < NPF; f++) ldsm4t(wf[f], WF(f));
            if (s + 1 == NSEG) { bar_arrive(NB_X2, 384); break; }
            const uint32_t oa = l16 + SM_OX, slot = mem_slot(s + 1);
            float c[4][4];
            uint32_t ob[4][4];
            BLOCK_FENCE
            bar_sync(NB_X2, 384);
            ldsm4t(ob[0], oa);
            ldsm4t(ob[1], oa + 512);
            SCHED_FENCE(0)
#pragma unroll
            for (int f = 0; f < 16; f++) {
                const uint32_t *a = wf[f % NPF], *o = ob[f >> 2] + (f & 2);
                if (f < 4) mma16816z(c[f], a, o[0], o[1]);
                else mma16816(c[f & 3], a[0], a[1], a[2], a[3], o[0], o[1]);
                if (f == 3) ldsm4t(ob[2], oa + 1024);
                if (f == 5) { ldsm4t(ob[3], oa + 1536); if (NPF < 16) ldsm4t(wf[0], WF(NPF)); }
                if (f == 7) {
#pragma unroll
                    for (int k = NPF + 1; k < 16; k++) ldsm4t(wf[k - NPF], WF(k));
                }
                if (f == 3 || f == 5 || f == 7) SCHED_FENCE(f / 2)
                if (f == 11) {
#pragma unroll
                    for (int k = NL - W0_E; k < NL; k++) ldsm4t(w0[k], (a3 ^ wlx) + wlo + k * 2048);
                    SCHED_FENCE(4)
                }
            }
            const float last = c[1][3] + c[3][3], one = __uint_as_float(CNT1 << 16);
            red_mem(arena + (u_m + slot + G16()), pack2(c[0][0] + c[2][0], c[0][1] + c[2][1]), pack2(c[0][2] + c[2][2], c[0][3] + c[2][3]),
                    pack2(c[1][0] + c[3][0], c[1][1] + c[3][1]), pack2(c[1][2] + c[3][2], g16 & 16 ? one : last),
                    arena + (u_e + slot + ((g16 >> 3) & ~3u)), pack2(last, one), g16 & 16);
            hbo += FZ;
            constexpr int NS = NL - W0_RS, GS = (32 - NL + NS) / NS;
            BLOCK_FENCE
#pragma unroll
            for (int k = NL - W0_E - 1; k >= 0; k--) ldsm4t(w0[k], (a3 ^ wlx) + wlo + k * 2048);
            lm0 = TAB(WG * 3 + 2);
            if (WG == 1) pa = lds4(sb + SM_PA + 2048 + g16);
            if (WG == 0) {
                bar_arrive(NB_WIN, 384);
                pa = lds4(sb + SM_PA + g16);
                acc_init();
                asm volatile("" : F16(acc, 0));
                BLOCK_FENCE
            }
            wg_fence();
            bar_sync(WG ? NB_WIN : NB_B, WG ? 384 : 256);
#pragma unroll
            for (int i = 0; i < 32; i++) {
                const int k = i / GS;
                if (i >= 32 - NL + NS) wgmma_rs32(acc, w0[i < 32 - NL + NS ? 0 : i - 32 + NL], HB(i - 32 + NL), 1);
                else if (i % GS == GS - 1 && k < NS) wgmma_ss32(acc, mkdesc(SB0 + WG * 65536 + k * 2048, 8192, 1024, 1), HB(k), 1);
                else wgmma_rs32(acc, w[i - (k < NS ? k : NS)], HB(NL + i - (k < NS ? k : NS)), WG == 0 || i);
                if (WG == 1 && i == G_AT) bar_arrive(NB_B, 256);
                if (WG == 1 && i == 31 - NL + NS) wg_fence();
            }
            wg_commit();
            BLOCK_FENCE
            if (WG == 1 && warp0 && !(s & 3)) wait_count_w(&g_tick[32 + ((G16() >> 4) & 3) * 8], min((s + 1) / 4 + 3, 17));
            auto tok_store = [&](int m) {
                if (m & 1) stg_b128_if(true, arena + ((b ^ 1) * 32768 + u_to + G16()), v.x, v.y, v.z, v.w);
                if (m & 2) stg_b128_if(p < NSEG, arena + ((pso ^ (32768 + 2048)) + G16()), u.x, u.y, u.z, u.w);
            };
            if (WG == 0) proj_pre(s + 1);
            BLOCK_FENCE
            wg_wait<0>();
            if (WG == 0) {
                asm volatile("" : F16(acc, 0));
                proj(s + 1, [&](int it) {
                    if (it < 0) {
                        SCHED_FENCE(0)
                        asm volatile("" : F16(acc, 0));
                        tok_pack(WG, acc, ftag, ptag, true);
                        tok_store(2);
                        SCHED_FENCE(1)
                    }
                    if (it == 2) { SCHED_FENCE(2) v.x = settag(v.x, ftag); v.z = settag(v.z, ftag); tok_store(1); SCHED_FENCE(3) }
                });
                tq0 += (fz[0] | fz[1] | fz[2] | fz[3]) & zero;
            } else {
#pragma unroll
                for (int k = 0; k < 4; k++) { acc[2 * k] += bflo((&pa.x)[k]); acc[2 * k + 1] += bfhi((&pa.x)[k]); }
                tok_pack(WG, acc, ftag, ptag);
                proj_pre(s + 1);
                asm volatile("" : "+r"(u.x), "+r"(u.y), "+r"(u.z), "+r"(u.w), "+r"(v.x), "+r"(v.y), "+r"(v.z), "+r"(v.w));
                BLOCK_FENCE
                bar_sync(NB_P, 256);
                tok_store(3);
                proj(s + 1, [](int) {});
            }
        }
    };
    if (wg == 0) {
        qk_loop(IC<0>());
    } else if (wg == 1) {
        qk_loop(IC<1>());
    } else {
        const uint32_t ONES = 0x3f803f80u, u_o = qd * 65536 + head * 2048 + wu * 384;
        uint32_t tw = 0, dl = 0, dbase = kh == mypar ? dly.near : dly.far, dst0, dx0;
        dst0 = TAB(6); dx0 = TAB(7);
        uint32_t ov[4] = {0, 0, 0, 0};
        auto o_store = [&](int s) {
            uint8_t* od = (uint8_t*)g_O + (uint32_t)(s * (32 * NH * DH * 2) + u_o + (G16() >> 2));
#pragma unroll
            for (int a = 0; a < 4; a++) stg_rlx1(od + a * 128, ov[a]);
        };
        uint4 vf[2][2], pa;
        auto tok_fetch = [&](int s) {
            const uint8_t* ts = arena + ((s & 1) * 32768 + tbw + g16);
#pragma unroll
            for (int a = 0; a < 4; a++) vf[a >> 1][a & 1] = ldg_b128(ts + (a >> 1) * 16384 + (a & 1) * 2048);
            pa = ldg_b128(arena + (tbw + (1 << 20) + (~s & 1) * 32768 + j * 16384 + kh * 2048 + g16));
        };
        tok_fetch(0);
        TL(9)
        TL(6)
#pragma unroll 1
        for (int s = 0; s < NSEG; s++) {
            STEP_CONSTS
#define VFBAD ((vf[0][0].x ^ ttag) | (vf[0][1].x ^ ttag) | (vf[1][0].x ^ ttag) | (vf[1][1].x ^ ttag))
#define TOKBAD (VFBAD | (p <= NSEG ? pa.x ^ ftag : 0))
            {
                const uint32_t dst = dst0 + b * 65536, dx = dx0 + b * 65536;
                const uint8_t *ms = arena + (u_m + mem_slot(s) + g16), *me = arena + (u_e + mem_slot(s) + ((g16 >> 3) & ~3u));
                uint32_t em = g16 & 16 ? 0u : ~0u;
                asm volatile("" : "+l"(ms), "+l"(me), "+r"(em));
                spin_until(tw, dl);
                int it = 0;
                bool bad;
#pragma unroll 1
                do {
                    uint4 m[4];
                    uint32_t x[4];
#pragma unroll
                    for (int i = 0; i < 4; i++) m[i] = ldg_rlx4(ms + i * 1024);
#pragma unroll
                    for (int i = 0; i < 4; i++) x[i] = ldg_rlx1(me + i * 1024);
#pragma unroll
                    for (int i = 0; i < 3; i++) {
                        stsm4t(dst + i * 2 * HBK, m[i].x, m[i].y, m[i].z, m[i].w);
                        if (i == 1) asm volatile("{.reg .pred p; setp.eq.s32 p, %0, 0; @p bar.arrive %1, 256;}" ::"r"(it), "n"(NB_P) : "memory");
                    }
                    uint32_t c = m[0].w & m[1].w, r, msk = ~(it << 16) & CNT_ALL << 16;
                    asm volatile("" : "+r"(c), "+r"(msk));
                    SCHED_FENCE(1)
                    stsm4t(dst + 6 * HBK, m[3].x, m[3].y, m[3].z, m[3].w);
                    stsm4t(dx, x[0], x[1], x[2], x[3]);
                    asm volatile("{.reg .pred p, q; .reg .b32 t, u; lop3.b32 t, %1, %2, %3, 0x80; lop3.b32 u, %4, %5, %6, 0x80; lop3.b32 t, t, %8, %7, 0xa8;\n"
                                 " lop3.b32 t, t, u, %9, 0x2a; setp.ne.u32 p, t, 0; vote.sync.any.pred q, p, 0xffffffff; @!q bar.arrive %10, 384; selp.u32 %0, 1, 0, q;}"
                                 : "=r"(r) : "r"(c), "r"(m[2].w), "r"(m[3].w), "r"(x[0]), "r"(x[1]), "r"(x[2]), "r"(x[3]), "r"(em), "r"(msk), "n"(NB_MEM) : "memory");
                    bad = r; it++;
                } while (bad);
                if (it > 1 && s > 1) dbase += dly.more;
                MISS(0, it - 1) HT(5)
            }
            if (s == 1) { TL(7) TLC(0) }
            if (s == 63) TLC(1)
            if (s == 0) TL(13)
            o_store(max(s - 1, 0));
            fence_async_smem();
            hbo += fz[1] & zero;
            int it = 0;
#pragma unroll 1
            while (any_bit0(TOKBAD) & (++it < POLL_LIMIT)) tok_fetch(s + (it & zero));
            float acc[20];
#pragma unroll
            for (int k = 0; k < 4; k++) { acc[2 * k] = bflo((&pa.x)[k]); acc[2 * k + 1] = bfhi((&pa.x)[k]); acc[8 + 2 * k] = acc[9 + 2 * k] = acc[16 + k] = __uint_as_float(pa.x & zero); }
            if (p <= NSEG) mbar_wait_w(bars + 8 * (B_HB + b), (p >> 1) & 1);
            asm volatile("" : F16(acc, 0), F4(acc, 16));
            BLOCK_FENCE
            wg_fence();
            bar_sync(NB_QK, 384);
#pragma unroll
            for (int i = 0; i < 32; i++) {
                const int k = i / GAP;
                if (i % GAP == GAP - 1 && k < NL) wgmma_ss40(acc, mkdesc(SB0 + 131072 + k * 2048, 8192, 1024, 1), HB(k), 1);
                else wgmma_rs40(acc, w[i - (k < NL ? k : NL)], HB(NL + i - (k < NL ? k : NL)), 1);
            }
            wg_commit();
            uint8_t* vo = arena + (u_xo + (G16() >> 1));
            pdst = arena + ((pso ^ (32768 + 2048)) + G16());
            fdst = arena + ((b ^ 1) * 32768 + u_to + g16);
            BLOCK_FENCE
            wg_wait<0>();
            stg_rlx2(vo, settag(pack2(acc[16], acc[17]), tag), pack2(acc[18], acc[19]));
            const uint32_t tv = clk32();
            tok_pack(2, acc, ftag, ptag);
            stg_b128_if(p <= NSEG, fdst, v.x, v.y, v.z, v.w);
            stg_b128_if(p < NSEG, pdst, u.x, u.y, u.z, u.w);
            const uint8_t* xp = arena + (xso + 32768 + (G16() >> 1));
            const uint32_t sxa = sb + SM_SX - wu * 2560 + G16() * 5;
            uint32_t sel[2];
            {
                const uint32_t q = (G16() >> 4 ^ g16 >> 6 & 1) & 3;
                sel[0] = q == 0 ? 0x3c00 : 0; sel[1] = q == 2 ? 0x3c00 : 0;
                asm volatile("" : "+r"(sel[0]), "+r"(sel[1]));
            }
            uint32_t xv[4], gt = 0;
            auto pv = [&](uint32_t p0, uint32_t p1, uint32_t p2, uint32_t p3, uint32_t p4, auto getv, auto done) {
                float oc[2][4], lc[4] = {0.f, 0.f, 0.f, 0.f};
                mma16816(lc, ONES, ONES, ONES, ONES, p0, p1);
                mma16816z(oc[0], &vf[0][0].x, p0, p1);
                mma16816z(oc[1], &vf[1][0].x, p0, p1);
                mma16816(lc, ONES, ONES, ONES, ONES, p2, p3);
                mma16816(oc[0], vf[0][1].x, vf[0][1].y, vf[0][1].z, vf[0][1].w, p2, p3);
                mma16816(oc[1], vf[1][1].x, vf[1][1].y, vf[1][1].z, vf[1][1].w, p2, p3);
                mma1688(lc, ONES, ONES, p4);
                getv();
                mma1688(oc[0], xv[0], xv[1], p4);
                mma1688(oc[1], xv[2], xv[3], p4);
                done(__float_as_uint(oc[0][0]) | __float_as_uint(oc[1][0]) | __float_as_uint(lc[0]));
                const float r0 = rcp_fast(lc[0]), r1 = rcp_fast(lc[1]);
                ov[0] = pack2(oc[0][0] * r0, oc[0][1] * r1); ov[1] = pack2(oc[0][2] * r0, oc[0][3] * r1);
                ov[2] = pack2(oc[1][0] * r0, oc[1][1] * r1); ov[3] = pack2(oc[1][2] * r0, oc[1][3] * r1);
            };
            bool bad;
            it = 0;
#pragma unroll 1
            do {
                U2 xr[4];
                asm volatile("{.reg .pred p; setp.eq.s32 p, %0, 0; @p bar.sync %1, 384;}" ::"r"(it), "n"(NB_X1) : "memory");
                uint4 sx[5];
#pragma unroll
                for (int i = 0; i < 5; i++) sx[i] = lds4(sxa + i * 16);
                if (it == 0) { gt = gtime(); tw = clk32(); }
                spin_until(tv, dly.v);
#pragma unroll
                for (int i = 0; i < 4; i++) xr[i] = ldg_u2(xp + i * 1024);
                uint32_t h[5], h0[4];
#pragma unroll
                for (int n = 0; n < 4; n++) h0[n] = add_h2((&sx[0].x)[n], (&sx[1].x)[n]);
#pragma unroll
                for (int n = 0; n < 4; n++) h[n] = add_h2(h0[n], add_h2((&sx[2].x)[n], (&sx[3].x)[n]));
                h[4] = add_h2(add_h2(sx[4].x, sx[4].y), add_h2(sx[4].z, sx[4].w));
                uint32_t hm = max_h2(max_h2(max_h2(h[0], h[1]), h[2]), max_h2(h[3], h[4]));
                float2 a[5];
                float mb;
                {
                    float d[2][4];
                    const uint32_t hs = __byte_perm(hm, hm, 0x1032);
#pragma unroll
                    for (int k = 0; k < 2; k++)
                        asm volatile("mma.sync.aligned.m16n8k8.row.col.f32.f16.f16.f32 {%0,%1,%2,%3},{%4,%5},{%6},{%7,%7,%7,%7};"
                                     : "=f"(d[k][0]), "=f"(d[k][1]), "=f"(d[k][2]), "=f"(d[k][3]) : "r"(hm), "r"(hs), "r"(sel[k]), "f"(0.f));
#pragma unroll
                    for (int n = 0; n < 5; n++) a[n] = unpack_h2(h[n]);
                    mb = -64.0f * fmaxf(fmaxf(fmaxf(d[0][0], d[0][1]), fmaxf(d[0][2], d[0][3])), fmaxf(fmaxf(d[1][0], d[1][1]), fmaxf(d[1][2], d[1][3])));
                }
                uint32_t pm[5];
#pragma unroll
                for (int n = 0; n < 5; n++) pm[n] = pack2(ex2(fmaf(a[n].x, 64.0f, mb)), ex2(fmaf(a[n].y, 64.0f, mb)));
                pv(pm[0], pm[1], pm[2], pm[3], pm[4], [&]() {
                    xv[0] = hadd2(xr[0].x, xr[1].x); xv[1] = hadd2(xr[0].y, xr[1].y);
                    xv[2] = hadd2(xr[2].x, xr[3].x); xv[3] = hadd2(xr[2].y, xr[3].y);
                }, [](uint32_t) {});
                bad = any_bit0((xr[0].x ^ tag) | (xr[1].x ^ tag) | (xr[2].x ^ tag) | (xr[3].x ^ tag)) & (++it < POLL_LIMIT);
                stsm4(sb + SM_OX + g16, ov[0], ov[1], ov[2], ov[3]);
            } while (bad);
                MISS(2, it - 1)
            bar_sync(NB_X2, 384);
            BLOCK_FENCE
            U2 tv2 = {0, 0};
            const uint8_t* tp = arena + (blk(LB_TIME, mypar) + ((G16() << 6) & 0xc00));
            {
                const uint4 pp = lds4(l16 + SM_PX + 1024);
                const uint32_t p4 = lds1(sb + SM_PX + 512 + 1024 - wu * 128 + (G16() >> 2));
                tv2 = ldg_u2(tp);
                if (warp0 && s + 3 <= NSEG) h_load(sb, hsrc, s + 3, j, head);
                pv(pp.x, pp.y, pp.z, pp.w, p4, []() {}, [&](uint32_t r) { bar_arrive(NB_WIN + (r & zero), 384); });
            }
            dst0 = TAB(6); dx0 = TAB(7);
            const uint32_t zo = TAB(8);
                HT(7)
            BLOCK_FENCE
            asm volatile("" : "+r"(tv2.y));
            it = 0;
            uint32_t tm = __reduce_max_sync(~0u, tv2.y < 32 * (s + 1) ? ~0u : tv2.x);
#pragma unroll 1
            while ((tm == ~0u) & (++it < 16)) { tv2 = ldg_u2(tp); tm = __reduce_max_sync(~0u, tv2.y < 32 * (s + 1) ? ~0u : tv2.x); }
            const uint32_t e = tm - gt;
            MISS(3, it - 1) MISS(4, gt)
            tok_fetch(s + 1);
            stg4_if(g16 < 160, arena + (zo + mem_slot(s + 3)), 0);
            dl = dbase + (e > 4096 ? 0 : e * E_MUL >> 4);
        }
        o_store(NSEG - 1);
        TL(8)
    }
    MISS_OUT
}

struct RecMaps { CUtensorMap wq, wk, wv, wo, wmod, w3, w1; };
struct RecPtrs { const bf16 *x, *mem0, *c, *wmod, *w1, *w3; uint8_t* arena; uint32_t zero; const bf16 *w2, *w4, *wo; Delays dly; };

__device__ __forceinline__ float silu_bf(const bf16* c, int i) {
    const float v = __bfloat162float(c[i]);
    return bfround(__fdividef(v, 1.0f + __expf(-v)));
}
#define LN_FREE 6
#define LN_SEQ 0xcba6420987531ull
#define W_LATE 1000
#define W_OPEN 1400
__device__ __noinline__ uint32_t side_window_(const uint8_t* arena, uint32_t n);
#define side_window(arena, n) n = side_window_(arena, n)
__device__ __noinline__ void rec_ln(uint32_t sb, const bf16* x, const uint8_t* arena, int id, int r0) {
    int r1 = 32;
    uint32_t n = 0;
    const int tid = threadIdx.x, lane = tid & 31, wid = __reduce_max_sync(~0u, tid >> 5);
    const uint32_t ring = sb + wid * 8192 + lane * 16, coef = sb + SM_PRE;
    x += (id * 8 + wid) * 2 * DM + lane * 8;
#pragma unroll 1
    for (int r = r0 - 1; r < r1; r++) {
        if (r > 3) side_window(arena, n);
        if (r + 1 < r1) {
#pragma unroll
            for (int i = 0; i < 8; i++)
                asm volatile("cp.async.cg.shared.global [%0], [%1], 16;" ::"r"(ring + (~r & 1) * 4096 + i * 512), "l"(x + (r + 1) * 64 * DM + i * 256) : "memory");
        }
        asm volatile("cp.async.commit_group; cp.async.wait_group 1;" ::: "memory");
        if (r < r0) continue;
        const uint32_t src = ring + (r & 1) * 4096;
        float m[2] = {0.f, 0.f}, rs[2];
#pragma unroll 1
        for (int ps = 0; ps < 2; ps++) {
            float t[2][2] = {{0.f, 0.f}, {0.f, 0.f}};
#pragma unroll 1
            for (int i = 0; i < 2048; i += 512) {
#pragma unroll
                for (int h = 0; h < 2; h++) {
                    const uint4 u = lds4(src + h * 2048 + i);
#pragma unroll
                    for (int e = 0; e < 4; e++) {
                        const float a = bflo((&u.x)[e]) - m[h], c = bfhi((&u.x)[e]) - m[h];
                        t[h][0] = fmaf(a, ps ? a : 1.0f, t[h][0]); t[h][1] = fmaf(c, ps ? c : 1.0f, t[h][1]);
                    }
                }
            }
            rs[0] = t[0][0] + t[0][1]; rs[1] = t[1][0] + t[1][1];
#pragma unroll 1
            for (int o = 16; o; o >>= 1) { rs[0] += __shfl_xor_sync(~0u, rs[0], o); rs[1] += __shfl_xor_sync(~0u, rs[1], o); }
            if (!ps) { m[0] = rs[0] * (1.0f / DM); m[1] = rs[1] * (1.0f / DM); }
        }
        rs[0] = rsqrtf(rs[0] * (1.0f / DM) + 1e-5f); rs[1] = rsqrtf(rs[1] * (1.0f / DM) + 1e-5f);
        if (r == r0) {
#pragma unroll 1
            for (int i = tid; i < 2 * DM / 4; i += 256) {
                float t[4];
                int it = 0;
                uint32_t ok;
#pragma unroll 1
                do {
                    uint4 u[8];
#pragma unroll
                    for (int k = 0; k < 8; k++) u[k] = ldg_rlx4(g_modp + k * 2 * DM + i * 4);
                    ok = 1;
#pragma unroll
                    for (int k = 0; k < 32; k++) { const uint32_t w = (&u[k >> 2].x)[k & 3]; ok &= w; t[k & 3] = k < 4 ? __uint_as_float(w) : t[k & 3] + __uint_as_float(w); }
                } while (!__all_sync(~0u, ok) & (++it < SPIN_LIMIT));
                const float o = i >> 8;
                const uint32_t lo = pack2(t[0], t[1]), hi = pack2(t[2], t[3]);
                sts4f(coef + (i >> 8) * 4096 + (i & 1) * 2048 + ((i & 255) >> 1) * 16, bflo(lo) + o, bfhi(lo) + o, bflo(hi) + o, bfhi(hi) + o);
            }
            bar_sync(NB_FIN0, 256);
            if (tid == 0 && r0 == 0) TL(2)
        }
        uint8_t* dst = (uint8_t*)g_himg + (r * 2 + (id >> 1)) * 65536 + (lane >> 3) * 4096 + wid * 256;
#pragma unroll 1
        for (int i = 0; i < 4; i++) {
            const uint32_t ca = coef + i * 512 + lane * 16;
            const float4 s0 = lds4f(ca), s1 = lds4f(ca + 2048), c0 = lds4f(ca + 4096), c1 = lds4f(ca + 6144);
            const float sh[8] = {s0.x, s0.y, s0.z, s0.w, s1.x, s1.y, s1.z, s1.w}, sc[8] = {c0.x, c0.y, c0.z, c0.w, c1.x, c1.y, c1.z, c1.w};
#pragma unroll
            for (int h = 0; h < 2; h++) {
                uint4 u = lds4(src + h * 2048 + i * 512);
#pragma unroll
                for (int e = 0; e < 4; e++) {
                    uint32_t& w = (&u.x)[e];
                    w = pack2(fmaf((bflo(w) - m[h]) * rs[h], sc[2 * e], sh[2 * e]), fmaf((bfhi(w) - m[h]) * rs[h], sc[2 * e + 1], sh[2 * e + 1]));
                }
                *(uint4*)(dst + i * 16384 + ((id & 1) == (i >> 1) ? 65536 : 2048) + h * 128 + (((lane ^ (2 * wid + h)) & 7) << 4)) = u;
            }
        }
        if (r == 0) {
            if (tid == 0) TLX(10)
            int ro, it = 0;
#pragma unroll 1
            do asm volatile("ld.volatile.shared.u32 %0, [%1];" : "=r"(ro) : "r"(sb + SM_BAR + 192) : "memory"); while ((ro == INT_MIN) & (++it < SPIN_LIMIT));
            if (ro >= 0) r1 = 2;
        }
        if (r && !(r & 1)) continue;
        bar_sync(r ? NB_FIN0 : NB_C, r ? 256 : 320);
        if (tid == 0 && r == 0) TLX(11)
        if (wid == (r >> 1 & 7)) {
            if (r == 1) bar_arrive(NB_B, 64);
            if (r == 3) wait_count_w(&g_tick[32 + id * 8], 2);
            if (lane == 0) { signal_count(&g_tick[32 + id * 8]); if (r == 0) TLX(12) }
            __syncwarp();
        }
    }
}
__device__ __noinline__ uint32_t side_window_(const uint8_t* arena, uint32_t n) {
    U2 v;
    int it = 0;
#pragma unroll 1
    while (v = ldg_u2(arena + (LB_TIME << 13)), ((v.y >> 5) == n || gtime() - v.x > W_OPEN + W_LATE) && v.y < 32 * NSEG && ++it < 64) __nanosleep(100);
    it = 0;
#pragma unroll 1
    while ((int)(gtime() - v.x - W_OPEN) < 0 && ++it < 256) {}
    return v.y >> 5;
}
#define SIDE_T 300
template <int NQ, int NB>
__device__ __forceinline__ void side_gemv(const CUtensorMap* tm, int c0, int k0, int k1, uint32_t cs, uint32_t sb, const uint8_t* arena, uint32_t& n, uint32_t& ph, float (*acc)[8], bool once = false) {
    const uint32_t w = __reduce_max_sync(~0u, threadIdx.x >> 5 & 3), ring = sb + (NB == 3 ? 65536 : 0) + w * NB * 8192;
    const uint32_t bars = sb + SM_BAR + (NB == 3 ? 8 * B_W + w * 24 : 8 + w * 8), bs = NB == 3 ? 8 : 0;
#pragma unroll
    for (int q = 0; q < NQ; q++)
#pragma unroll
        for (int j = 0; j < 8; j++) acc[q][j] = 0.f;
#pragma unroll 1
    for (; k0 < k1; k0 += NB * 16, ph ^= 1) {
        const int nr = min(NB * 16, k1 - k0);
        side_window(arena, n);
        const uint32_t t0 = clk32();
#pragma unroll 1
        for (int g = 0; g < NB; g++) {
            spin_until(t0, (g * 4 + w) * (SIDE_T / 4));
            if (bs || !g) e_expect(bars + bs * g, !bs ? NB * 8192 : g * 16 < nr ? 8192 : 0);
            if (g * 16 < nr) e_tma2d_hint(ring + g * 8192, tm, c0, k0 + g * 16, bars + bs * g, once ? EVICT_FIRST : EVICT_NORMAL);
        }
#pragma unroll 1
        for (int r = 0; r < nr; r += 16) {
            mbar_wait_w(bars + bs * (r >> 4), ph);
            uint4 v[16];
#pragma unroll
            for (int h = 0; h < 16; h++) v[h] = lds4(ring + (r + h) * 512 + (threadIdx.x & 31) * 16);
            float4 cf[NQ][4];
#pragma unroll
            for (int q = 0; q < NQ * 4; q++) cf[q >> 2][q & 3] = lds4f(cs + ((q >> 2) * DM + k0 + r + (q & 3) * 4) * 4);
#pragma unroll
            for (int h = 0; h < 16; h++) {
                const float f[8] = {bflo(v[h].x), bfhi(v[h].x), bflo(v[h].y), bfhi(v[h].y), bflo(v[h].z), bfhi(v[h].z), bflo(v[h].w), bfhi(v[h].w)};
#pragma unroll
                for (int q = 0; q < NQ; q++)
#pragma unroll
                    for (int j = 0; j < 8; j++) acc[q][j] = fmaf((&cf[q][h >> 2].x)[h & 3], f[j], acc[q][j]);
            }
        }
        fence_async_smem();
        __syncwarp();
    }
}
__device__ __noinline__ void rec_side(float* sm, const RecMaps& mp, const RecPtrs& p, int id) {
    const int tid = threadIdx.x, t = tid & 127, w = __reduce_max_sync(~0u, t >> 5);
    float* coef = sm + (tid < 256 ? 44032 : 40960);
    const uint32_t sb = smem_u32(sm), cs = smem_u32(coef);
    uint32_t n = 0, ph = 0;
    float acc[3][8];
    if (tid < 256) {
        if (blockIdx.x < 128) rec_ln(smem_u32(sm), p.x, p.arena, id, 2);
        if (tid == 0) TL(14)
        for (int i = tid; i < 2 * S_; i += 256) g_st[id * 2 * S_ + i] = 0.f;
        if (id == 0 && tid < 64) g_pcnt[tid * 8] = 0;
        if (id == 1) for (int i = tid; i < 6 * 256; i += 256) g_pflag[i] = 0;
        if (id == 2 && tid == 0) g_pt = 0;
        fence_async_smem();
        bar_sync(NB_FIN0, 256);
        if (PDL && tid == 0) asm volatile("fence.acq_rel.gpu; griddepcontrol.launch_dependents;" ::: "memory");
        if (tid >= 128) return;
        float* red = coef + 3 * DM;
        if (t == 0) wait_count1(&g_tick[8], 4);
        bar_sync(NB_S, 128);
        for (int i = t; i < DM; i += 128) { coef[i] = 1.0f + __ldcg(g_mod + 4 * DM + i); coef[DM + i] = __ldcg(g_mod + 3 * DM + i); coef[2 * DM + i] = 1.0f; }
        bar_sync(NB_S, 128);
        if (id == 1 && t < 32) {
            float u[5] = {0, 0, 0, 0, 0};
            for (int i = t; i < DM; i += 32) {
                const float a = coef[i], b = coef[DM + i];
                u[0] += a; u[1] += a * a; u[2] += a * b; u[3] += b; u[4] += b * b;
            }
#pragma unroll
            for (int q = 0; q < 5; q++) { const float r = warp_sum(u[q]); if (t == 0) g_cst[q] = r * (1.0f / DM); }
        }
        side_gemv<3, 2>(&mp.w1, id * 256, w * 256, w * 256 + 256, cs, sb, p.arena, n, ph, acc);
#pragma unroll
        for (int q = 0; q < 3; q++)
#pragma unroll
            for (int j = 0; j < 8; j++) red[((t >> 5) * 3 + q) * 256 + (t & 31) * 8 + j] = acc[q][j];
        bar_sync(NB_S, 128);
        for (int i = t; i < 768; i += 128) g_vec[(i >> 8) * DM + id * 256 + (i & 255)] = (red[i] + red[768 + i]) + (red[1536 + i] + red[2304 + i]);
        if (tid == 0) TL(6)
        return;
    }
    for (int i = t; i < DM; i += 128) { coef[i] = silu_bf(p.c, i); coef[2 * DM + i] = 1.0f; }
    if (t == 0) wait_count1(&g_tick[32], 1);
    bar_sync(NB_G, 128);
    side_gemv<1, 3>(&mp.wmod, (2 + id) * DM + w * 256, 0, DM, cs, sb, p.arena, n, ph, acc, true);
#pragma unroll
    for (int j = 0; j < 8; j++) g_mod[(2 + id) * DM + t * 8 + j] = bfround(acc[0][j]);
    bar_sync(NB_G, 128);
    if (t == 0) signal_count(&g_tick[8]);
    side_gemv<1, 3>(&mp.w3, id * (FF / 4) + w * 256, 0, DM, cs + 8 * DM, sb, p.arena, n, ph, acc);
    if (t < FF / 32) {
#pragma unroll
        for (int j = 0; j < 8; j++) g_vec[3 * DM + id * (FF / 4) + t * 8 + j] = acc[0][j];
    }
    if (t == 0) TL(9)
}

__global__ void __cluster_dims__(2, 1, 1) __launch_bounds__(384, 1)
k_rec(const __grid_constant__ RecMaps mp, const __grid_constant__ RecPtrs p) {
    extern __shared__ uint8_t smraw[];
    const uint32_t sb = smem_u32(smraw);
    if ((sb & 0x3FFFF) != SB0) __trap();
    const uint32_t bars = sb + SM_BAR;
    const int tid = threadIdx.x, lane = tid & 31, b = blockIdx.x;
    const int wid = __reduce_max_sync(~0u, tid >> 5);
    const uint32_t rank = b & 1;
    uint8_t* arena = p.arena;
    volatile int* sinfo = (volatile int*)(smraw + SM_BAR + 192);
    if (tid == 0) TL(0)
    if (tid == 0) sinfo[0] = INT_MIN;
    if (tid == 352) {
        for (int i = 0; i < 17; i++) mbar_init(bars + 8 * i, i == B_WO ? 4 : 1);
        asm volatile("fence.mbarrier_init.release.cluster;" ::: "memory");
    }
    __syncwarp();
    asm volatile("barrier.cluster.arrive.relaxed.aligned;" ::: "memory");
    int pr = 0, hA = 0;
    if (wid < 8) {
        if (b < 128) {
            const int cb = (b & 15) * 128, k0 = (b >> 4) * 128 + (tid >> 4);
            uint4 v[8];
#pragma unroll
            for (int i = 0; i < 8; i++) v[i] = __ldg((const uint4*)(p.wmod + (size_t)(k0 + 16 * i) * (6 * DM) + cb + (tid & 15) * 8));
            float acc[8] = {0, 0, 0, 0, 0, 0, 0, 0};
            const float s8 = silu_bf(p.c, k0 + 16 * (lane & 7));
#pragma unroll
            for (int i = 0; i < 8; i++) {
                const float sv = __shfl_sync(~0u, s8, i, 16);
                acc[0] += sv * bflo(v[i].x); acc[1] += sv * bfhi(v[i].x); acc[2] += sv * bflo(v[i].y); acc[3] += sv * bfhi(v[i].y);
                acc[4] += sv * bflo(v[i].z); acc[5] += sv * bfhi(v[i].z); acc[6] += sv * bflo(v[i].w); acc[7] += sv * bfhi(v[i].w);
            }
            float* red = (float*)(smraw + SM_PRE);
            *(float4*)(red + (tid >> 4) * 128 + (tid & 15) * 8) = make_float4(acc[0], acc[1], acc[2], acc[3]);
            *(float4*)(red + (tid >> 4) * 128 + (tid & 15) * 8 + 4) = make_float4(acc[4], acc[5], acc[6], acc[7]);
            bar_sync(NB_FIN0, 256);
            if (wid < 4) {
                float t = 0;
#pragma unroll
                for (int i = 0; i < 16; i++) t += red[i * 128 + tid];
                stg_rlx1(&g_modp[(b >> 4) * 2 * DM + cb + tid], __float_as_uint(t) | 1u);
                TLX(14)
            }
        } else {
            rec_ln(sb, p.x, p.arena, b - 128, 0);
        }
    } else if (wid >= 10 && b >= 128) {
        {
            const int w = (b - 128) * 2 + wid - 10;
            const uint16_t* src = (const uint16_t*)p.mem0 + (lane & 3) * 2 * DM + (w >> 2) * 512 + (w & 1) * 64 + (w & 2) * 8 + (lane >> 2);
            uint32_t v[4][4];
#pragma unroll
            for (int i = 0; i < 16; i++) v[i >> 2][i & 3] = src[(i >> 2) * 128 + (i & 2) * 16 + (i & 1) * 8] | ((uint32_t)src[DM + (i >> 2) * 128 + (i & 2) * 16 + (i & 1) * 8] << 16);
            uint8_t* d = arena + mem_row(w >> 2, w & 3, 0);
            uint8_t* e = d + 512 + (lane >> 1) * 4;
            d += lane * 16;
#pragma unroll
            for (int i = 0; i < 4; i++, d += 1024, e += 1024) {
                stg_rlx4(d, v[i][0], v[i][1], v[i][2], lane & 1 ? (v[i][3] & 0xffff) | CNT_ALL << 16 : v[i][3]);
                stg_rlx4(d + mem_slot(1), 0, 0, 0, 0);
                stg_rlx4(d + mem_slot(2), 0, 0, 0, 0);
                if (lane & 1) { stg_rlx1(e, v[i][3] >> 16 | CNT_ALL << 16); stg_rlx1(e + mem_slot(1), 0); stg_rlx1(e + mem_slot(2), 0); }
            }
            if (w == 0 && lane < 8) stg_rlx2(arena + (LB_TIME << 13) + lane * 1024, 0, 0);
            bar_arrive(NB_C, 320);
        }
    } else if (rank == 0) {
        uint32_t best = ~0u;
        const int pg = wid < 10 ? 0 : 1 + (b >> 1) / 22;
        uint32_t* q = (uint32_t*)(arena + (pg << 21) + (pg ? blk(b >> 1, wid & 1) : blk(LB_PROBE, wid & 1) + b * 16));
        if (lane < 8) stg_rlx1(q + lane, 0);
        __syncwarp();
        if (lane == 0) {
            q += 3;
            uint32_t v = p.zero;
#pragma unroll 1
            for (int r = v; r <= NPROBE; r++) {
                const uint32_t t0 = clk32() + (v >> 8);
                v = atomicAdd(q + (v >> 8), 1u);
                uint32_t t1;
                asm volatile("{.reg .pred p; setp.eq.u32 p, %1, 0xffffffff; @p exit; mov.u32 %0, %%clock;}" : "=r"(t1) : "r"(v) : "memory");
                best = min(best, t1 - t0);
            }
            sinfo[wid - 6] = best;
        }
        bar_sync(NB_KDONE, b < 128 ? 128 : 64);
        if (tid == 256) {
            const uint32_t par = sinfo[2] > sinfo[3], vote = b < 128 && (sinfo[4] > sinfo[5]) != par;
            stg_rlx2(&g_clk[b >> 1], ((clk32() - 2 * gtime()) & ~127u) | b >> 1, 1 + 2 * par + 4 * vote);
        }
    }
    if (wid == 8) {
        U2 v[3], my;
        uint32_t c0;
        const int me = b >> 1;
        int it = 0;
        __syncwarp();
#pragma unroll 1
        do {
            my = ldg_u2(&g_clk[me]);
#pragma unroll
            for (int k = 0; k < 3; k++) v[k] = ldg_u2(&g_clk[k * 22 + min(lane, 21)]);
        } while (!__all_sync(~0u, my.y & v[0].y & v[1].y & v[2].y & 1) & (++it < SPIN_LIMIT));
        TLX(15)
        c0 = __reduce_min_sync(~0u, lane ? ~0u : v[0].x) - 4096;
        const uint32_t mc = me >= 64 ? ~0u : my.x - c0;
        const int par = my.y >> 1 & 1;
        uint32_t cnt = 0, flip = 0;
#pragma unroll
        for (int k = 0; k < 3; k++) {
            const uint32_t c = v[k].x - c0, o = v[k].y >> 1 & 1;
            const bool ln = k == 2 && lane >= 20;
            cnt += o + (o == par ? (ln ? 44 + lane < me : c < mc) * 256 + (c < my.x - c0) * 65536 : 0);
            flip |= __popc(__ballot_sync(~0u, v[k].y & 4) & 0x3fffff) > 10 ? 256 << k : 0;
        }
        cnt = __reduce_add_sync(~0u, lane < 22 ? cnt : 0);
        const int n1 = cnt & 255, n0 = 66 - n1, tk = cnt >> 8 & 255;
        if (lane == 0) g_cls[smid() & 255] = cnt < 32 << 16 ? par * 4 + (cnt >> 19) : 8;
        hA = min(n0 >> 1, NH);
        const int q0 = 2 * hA, q1 = 2 * NH - q0;
        const int over = tk - (par ? q1 : q0), lack = max(par ? q0 - n0 : q1 - n1, 0);
        if (over < 0) pr = par ? q0 + tk : tk;
        else if (over < lack) pr = (par ? n0 : q0 + n1) + over;
        else pr = -1 - (over - lack + (par ? max(n0 - q0, 0) : 0));
        hA |= flip;
        if (lane == 0) {
            sinfo[1] = hA; sinfo[0] = pr;
            if (b >= 128 && rank == 0) atomicOr(&g_tick[6], (pr < 0 ? 4u : 1u) << ((b - 128) >> 1));
        }
    }
    asm volatile("barrier.cluster.wait.aligned;" ::: "memory");
    if (wid == 8) {
        TL(1)
        __syncwarp();
        bar_arrive(NB_A, 288);
        bar_arrive(NB_S, 128);
        if (b >= 128 && pr < 0) bar_sync(NB_B, 64);
        if (pr >= 0) {
            const int pu = __reduce_max_sync(~0u, pr), c0 = (pu >> 1) * 128 + rank * 64, r0 = (pu & 1) * 512;
#pragma unroll 1
            for (int n = 0; n < 13; n++) {
                const u64 seq = b >= 128 ? LN_SEQ : 0xcba9876543210ull;
                const int i = seq >> (4 * n) & 15;
                if (b >= 128 && i == 0) bar_sync(NB_B, 64);
                if (n >= W_INFL && (b < 128 || n < LN_FREE)) mbar_wait_w(bars + 8 * (B_W + (seq >> (4 * (n - W_INFL)) & 15)), 0);
                const int m = i < 8 ? i & 1 : i >> 2, k = i < 8 ? i >> 1 : i & 3;
                const uint32_t dst = sb + m * 65536 + k * 16384, br = bars + 8 * (m < 3 ? B_W + i : B_WO);
                const int c = m < 3 ? c0 : 576 + rank * 256 + (pu & 1) * 128, r = m < 3 ? r0 + k * 128 : (pu >> 1) * DH;
                const uint64_t pol = m < 3 ? EVICT_FIRST : EVICT_NORMAL;
                e_expect(br, 16384);
                e_tma2d_hint(dst, &mp.wq + m, c, r, br, pol);
                e_tma2d_hint(dst + 8192, &mp.wq + m, c, r + 64, br, pol);
            }
        }
    } else {
        bar_sync(wid < 8 ? NB_A : NB_S, wid < 8 ? 288 : 128);
    }
    const int prr = __reduce_max_sync(~0u, sinfo[0]);
    hA = __reduce_max_sync(~0u, sinfo[1]);
    if (prr < 0) {
        int j = (b - 128) >> 1;
        if (b < 128) {
            uint32_t v;
            int it = 0;
#pragma unroll 1
            do { v = __reduce_max_sync(~0u, ldg_rlx1(&g_tick[6])); spin_guard(++it); } while (__popc(v) < 2);
            j = v == 3 ? -1 - prr : (v & 1) ^ 1;
        }
        rec_side((float*)smraw, mp, p, j * 2 + rank);
        return;
    }
    if (PDL) asm volatile("griddepcontrol.launch_dependents;" ::: "memory");
    const int role = (prr >> 1) * 4 + rank * 2 + (prr & 1);
    rec_main(sb, &mp.wo, arena, role, hA, wid >> 2, p.zero, p.dly);
}

__device__ __forceinline__ void wgmma_ss192(float* d, uint64_t a, uint64_t b, int sc) {
    asm volatile("{.reg .pred p; setp.ne.b32 p, %98, 0;\n wgmma.mma_async.sync.aligned.m64n192k16.f32.bf16.bf16 "
                 "{%0,%1,%2,%3,%4,%5,%6,%7,%8,%9,%10,%11,%12,%13,%14,%15,%16,%17,%18,%19,%20,%21,%22,%23,%24,%25,%26,%27,%28,%29,%30,%31,%32,%33,%34,%35,%36,%37,%38,%39,%40,%41,%42,%43,%44,%45,%46,%47,%48,%49,%50,%51,%52,%53,%54,%55,%56,%57,%58,%59,%60,%61,%62,%63,%64,%65,%66,%67,%68,%69,%70,%71,%72,%73,%74,%75,%76,%77,%78,%79,%80,%81,%82,%83,%84,%85,%86,%87,%88,%89,%90,%91,%92,%93,%94,%95}, %96, %97, p, 1, 1, 0, 1;}"
                 : F16(d, 0), F16(d, 16), F16(d, 32), F16(d, 48), F16(d, 64), F16(d, 80) : "l"(a), "l"(b), "r"(sc));
}

constexpr uint32_t P_B = 81920, P_PL = 40960, P_OUT = 180224, P_VEC = 212992, P_ROW = P_VEC + 6144, P_BAR = P_ROW + 4096, P_SMEM = P_BAR + 256;
#define PPH 1
#define FLAG_ST "st.release.gpu.global.u32"
#define FLAG_LD "ld.acquire.gpu.global.u32"
constexpr int ST = 5;
constexpr int PB_F = 0, PB_E = 5, PB_R = 10, PB_OUT = 16;
enum { C_Y = 0, C_G = 1, C_X1 = 2, C_U = 3, C_S1 = 8, C_S3 = 9 };
enum { V_GA = 0, V_A = 1, V_B = 2, V_GB = 3, V_VA = 4, V_VB = 5, V_VC = 6, V_C3 = 7 };
struct PostMaps { CUtensorMap o, wo, y, w1, g, w2, x1, w3, u, w4, out; };
struct PostPtrs { const bf16* x; };

struct GeluK { float k0, k1, kh; };
__device__ __forceinline__ GeluK gelu_k(float c) { return {0.7978845608028654f * c, 0.7978845608028654f * 0.044715f * c * c * c, 0.5f * c}; }
__device__ __forceinline__ float gelu_s(float t, const GeluK& k) {
    const float u = t * fmaf(t * t, k.k1, k.k0);
    float th; asm("tanh.approx.f32 %0, %1;" : "=f"(th) : "f"(u));
    const float hx = k.kh * t;
    return fmaf(hx, th, hx);
}
__device__ __forceinline__ float2 ldsv(uint32_t a) {
    float2 v; asm("ld.shared.v2.f32 {%0,%1}, [%2];" : "=f"(v.x), "=f"(v.y) : "r"(a)); return v;
}
__device__ __forceinline__ void wait_smem(uint32_t a, int target) {
    int it = 0;
#pragma unroll 1
    while (true) {
        int v;
        asm volatile("ld.acquire.cta.shared.u32 %0, [%1];" : "=r"(v) : "r"(a) : "memory");
        if (__all_sync(~0u, v >= target) | (++it > SPIN_LIMIT)) break;
    }
}

#define PP(i)
#define PH_(c, w, i)
__device__ __forceinline__ void release(uint32_t rel, int st, bool c) {
    asm volatile("{.reg .pred p; setp.ne.u32 p, %1, 0; setp.ne.and.u32 p, %2, 0, p; @p mbarrier.arrive.shared::cluster.b64 _, [%0];}"
                 ::"r"(rel + 8 * (st ? st - 1 : ST - 1)), "r"(rel), "r"((uint32_t)c) : "memory");
}
struct Pipe { int st, ph; uint32_t rel; };
__device__ __forceinline__ void adv(Pipe& p) { if (++p.st == ST) { p.st = 0; p.ph ^= 1; } }

__device__ __forceinline__ void post_weights(uint32_t sb, const PostMaps& mp, int nb, int rank) {
    const uint32_t full = sb + P_BAR + 8 * PB_F, empty = sb + P_BAR + 8 * PB_E;
    int st = 0, pp = 1;
#pragma unroll 1
    for (int ph = 0; ph < 7; ph++) {
        const int NK = ph == 0 ? 64 : ph == 6 ? 56 : 16, km = NK == 16 ? 15 : 63;
        const CUtensorMap* tb = &mp.wo + 2 * (ph < 3 ? ph : ph < 6 ? 3 : 4);
        const bool w3 = ph >= 3 && ph < 6;
        const int n0 = w3 ? nb * 64 + (ph == 4 ? 1536 : ph == 5 ? 2560 : 0) : nb * 128, dn = w3 ? 512 : 64;
        const int rot = NK == 16 ? 2 * (nb & 6) : 0, sw = ph == 1 || ph == 3 ? 2 * rank : 0;
#pragma unroll 1
        for (int i = 0; i < NK; i++) {
            const int k0 = (((i < 4 ? i ^ sw : i) + rot) & km) * 64;
            const uint32_t a = sb + P_B + st * 8192, f = full + 8 * st;
            mbar_wait_w(empty + 8 * st, pp);
            e_expect(f, ph == 3 ? 40960 : 32768);
            e_tma2d(a, tb, n0, k0, f);
            e_tma2d(a + P_PL, tb, n0 + dn, k0, f);
            if (ph == 3) e_tma2d(a + 2 * P_PL, tb, n0 + 1024, k0, f);
            if (++st == ST) { st = 0; pp ^= 1; }
        }
    }
#pragma unroll 1
    for (int i = 0; i < ST; i++) mbar_wait_w(empty + 8 * i, pp ^ (i < st));
}
__device__ __forceinline__ void post_acts(uint32_t sb, const PostMaps& mp, int mb, int nb, int rank) {
    const int rh = 2 * mb + rank, lane = threadIdx.x & 31;
    const uint32_t full = sb + P_BAR + 8 * PB_F, empty = sb + P_BAR + 8 * PB_E;
    int st = 0, pp = 1;
#pragma unroll 1
    for (int ph = 0; ph < 7; ph++) {
        const int NK = ph == 0 ? 64 : ph == 6 ? 56 : 16, km = NK == 16 ? 15 : 63;
        const CUtensorMap* ta = &mp.o + 2 * (ph < 3 ? ph : ph < 6 ? 3 : 4);
        const int amul = ph == 0 ? 256 : 64, arow = ph == 0 ? rh * 8 : rh * 64;
        const int rot = NK == 16 ? 2 * (nb & 6) : 0, own = ph == 1 || ph == 3 ? 4 : 0;
        const uint32_t shifts = ph == 2 ? 0x04000301u : 0x02020202u;
        const uint32_t* fl = &g_pflag[(ph == 6 ? C_U : min(ph - 1, 2)) * 256 + (ph == 2 ? min(max(rh + min(lane >> 3, 2) - 1, 0), 31) : rh) * 8 + (lane & 7)];
        uint32_t have = ph == 0 || ph == 5;
        if (own) { if (st) { st--; pp ^= 1; } else st = 4; }
#pragma unroll 1
        for (int i = own; i < NK; i++) {
            const int kb = (i + rot) & km;
            const uint32_t need = ph == 6 ? 255u : (ph == 2 ? 0x10101u : 1u) << ((kb >> 1) & 7), lvl = ph == 6 ? i >> 3 : 0;
            PH_(ph == PPH && i == own, 0, 27) PH_(ph == PPH && i == own, 1, 27)
            if ((__ballot_sync(~0u, have > lvl) & need) != need) {
                int it = 0;
#pragma unroll 1
                do asm volatile(FLAG_LD " %0, [%1];" : "=r"(have) : "l"(fl) : "memory");
                while (((__ballot_sync(~0u, have > lvl) & need) != need) & (++it < SPIN_LIMIT));
                PH_(ph == PPH && i == own, 0, 23) PH_(ph == PPH, 0, 24) PH_(ph == PPH && i == own, 1, 23) PH_(ph == PPH, 1, 24)
                asm volatile("fence.proxy.async.global;" ::: "memory");
            }
            const int d = own && (i == 5 || i == 6) ? 2 : 0, s2 = st + d < ST ? st + d : st + d - ST;
            mbar_wait_w(empty + 8 * s2, pp ^ (s2 < st));
            e_tma2d_mc(sb + st * 16384 + rank * 8192, ta, kb * amul, arow + (int)((shifts >> ((kb & 12) * 2)) & 7) - 2, full + 8 * st);
            if (++st == ST) { st = 0; pp ^= 1; }
        }
    }
}

template <int PH, class F>
__device__ __forceinline__ void post_kb(uint32_t sb, float* acc, Pipe& p, int wg, bool lead, bool first, F mid) {
    constexpr uint64_t DA = PH == 0 ? mkdesc(SB0, 128, 1024, 0) : mkdesc(SB0, 16, 1024, 1);
    constexpr uint64_t DB = mkdesc(SB0 + P_B, P_PL, 1024, 1);
    mbar_wait_w(sb + P_BAR + 8 * PB_F + 8 * p.st, p.ph);
    const uint32_t a = (uint32_t)DA + p.st * 1024 + wg * 512, b = (uint32_t)DB + p.st * 512;
    wg_fence();
#pragma unroll
    for (int k = 0; k < 4; k++) {
        const uint64_t da = (DA & 0xffffffff00000000ull) | (a + k * (PH == 0 ? 16 : 2)), db = (DB & 0xffffffff00000000ull) | (b + k * 128);
        if (PH == 3) wgmma_ss192(acc, da, db, k || !first);
        else wgmma_ss128<PH == 0>(acc, da, db, k || !first);
    }
    wg_commit();
    wg_wait<1>();
    release(p.rel, p.st, !first);
    mid();
    adv(p);
}
__device__ __forceinline__ void post_end(uint32_t sb, Pipe& p, bool lead) {
    wg_wait<0>();
    release(p.rel, p.st, true);
}
template <int PH>
__device__ __forceinline__ void post_mma(uint32_t sb, float* acc, Pipe& p, int wg, bool lead, int nout, int pi, int mb, int nb) {
#pragma unroll 1
    for (int kb = 0; kb < 16; kb++)
        post_kb<PH>(sb, acc, p, wg, lead, kb == 0, [&]() {
            if (kb == 0) { PP(pi) }
            if (nout && kb == 0) wait_smem(sb + P_BAR + 8 * (PB_OUT + wg), nout);
        });
    post_end(sb, p, lead);
    PP(pi + 1)
}

__global__ void __cluster_dims__(2, 1, 1) __launch_bounds__(384, 1)
k_post(const __grid_constant__ PostMaps mp, const __grid_constant__ PostPtrs pp) {
    extern __shared__ uint8_t smraw[];
    const uint32_t sb = smem_u32(smraw);
    if ((sb & 0x3FFFF) != SB0) __trap();
    const int tid = threadIdx.x, lane = tid & 31;
    const int rank = blockIdx.x & 1;
    const uint32_t bars = sb + P_BAR;
    int c = 0;
    unsigned long long v = 0;
    const int wid = __reduce_max_sync(~0u, tid >> 5);
    const bool draw = tid == 352 && rank == 0;
    if (draw) {
        c = min(ldg_rlx1(&g_cls[smid() & 255]), 8u);
        asm volatile("{.reg .b64 a; cvt.u64.u32 a, %%laneid; add.u64 a, a, %1; atom.relaxed.gpu.global.add.u64 %0, [a], %2;}" : "=l"(v) : "l"(&g_pt), "l"(1ull << (7 * c)) : "memory");
    }
    if (wid < 11) {
        asm volatile("{.reg .pred p; elect.sync _|p, 0xffffffff; @p mbarrier.init.shared.b64 [%0], %1; @p prefetch.tensormap [%2]; fence.mbarrier_init.release.cluster;}"
                     ::"r"(bars + 8 * wid), "r"(wid >= PB_E && wid < PB_R ? 4 : 1), "l"(&mp.o + wid) : "memory");
        if (wid == PB_R) { sts4(bars + 8 * PB_OUT, 0, 0, 0, 0); e_expect(bars + 8 * PB_R, 4); }
    }
    __syncwarp();
    asm volatile("barrier.cluster.arrive.relaxed.aligned; barrier.cluster.wait.aligned;" ::: "memory");
    if (draw) {
        int r = (v >> (7 * c)) & 127, role = c * 8 + r;
        if (c == 8 || r >= 8) {
            int n, x, it = 0;
#pragma unroll 1
            do {
                __nanosleep(200);
                v = ldg_u64(&g_pt); n = 0; x = c < 8 ? r - 8 : r;
#pragma unroll 1
                for (int i = 0; i < 63; i += 7) { const int m = v >> i & 127; n += m; if (i < 7 * c) x += max(m - 8, 0); }
            } while (n < gridDim.x / 2 && ++it < SPIN_LIMIT);
            role = -1;
#pragma unroll 1
            for (int i = 0; i < 64; i += 8, v >>= 7) {
                n = v & 127;
                if (x >= 0 && n + x < 8) role = i + n + x;
                x -= max(8 - n, 0);
            }
        }
#pragma unroll
        for (int i = 0; i < 2; i++)
            asm volatile("{.reg .b32 d; mapa.shared::cluster.u32 d, %0, %2; st.async.shared::cluster.mbarrier::complete_tx::bytes.u32 [d+8], %1, [d];}"
                         ::"r"(bars + 8 * PB_R), "r"(role), "r"(i) : "memory");
    }
    __syncwarp();
    mbar_wait_w(bars + 8 * PB_R, 0);
    const int pr = __reduce_max_sync(~0u, (int)lds1(bars + 8 * PB_R + 8));
    if (pr < 0) return;
    const int mb = (pr >> 5) * 8 + (pr & 7), nb = (pr >> 2 & 6) + rank, cta = pr * 2 + rank;
    if (wid >= 8) {
        asm volatile("setmaxnreg.dec.sync.aligned.u32 40;");
        const int w = wid - 8;
        if (w == 0) {
            post_weights(sb, mp, nb, rank);
        } else if (w == 3) {
            asm volatile("griddepcontrol.wait;" ::: "memory");
            TLP(15)
            post_acts(sb, mp, mb, nb, rank);
        } else {
            const int wg = w - 1, rh = 2 * mb + wg;
            float* rowc = (float*)(smraw + P_ROW) + (wg * 64 + lane * 2) * 8;
            int nout = 0, sig = 0;
#pragma unroll 1
            for (int i = 0; i < 13; i++) {
                const int cnt = (0x4333333392180ull >> (4 * i)) & 15;
                if (cnt < C_S1) {
                    const int ng = cnt == C_U ? 1 : 2, c0 = cnt == C_U ? (i - 5) * 512 + nb * 64 : nb * 128;
                    const bool fast = (cnt == C_Y || cnt == C_X1);
#pragma unroll 1
                    for (int j = 0; j < ng; j++) {
                        const uint32_t st = j ? cnt : cnt ? 1 : 4;
                        const uint32_t src = sb + (fast ? st * 16384 + wg * 8192 : P_OUT + wg * 16384 + ((nout + j) & 1) * 8192);
                        bar_sync(4 + 4 * wg + (sig++ & 3), 160);
                        if (lane == 0) {
                            PH_(cnt == PPH - 1, wg, 20)
                            if (fast) asm volatile("mbarrier.complete_tx.relaxed.cta.shared::cta.b64 [%0], 8192;" ::"r"(bars + 8 * (PB_F + st)) : "memory");
                            asm volatile("cp.async.bulk.tensor.2d.global.shared::cta.bulk_group [%0, {%2, %3}], [%1]; cp.async.bulk.commit_group;"
                                         ::"l"(&mp.y + 2 * cnt), "r"(src), "r"(c0 + j * 64), "r"(rh * 64) : "memory");
                        }
                        __syncwarp();
                    }
                    if (lane == 0) {
                        auto to_peer = [&]() {
                            const uint32_t n = cnt ? 1 : 4;
                            mbar_wait(bars + 8 * (PB_E + (cnt ? 4 : 2)), 0);
#pragma unroll
                            for (int i = 0; i < 2; i++)
                                asm volatile("{.reg .b32 d, m; mapa.shared::cluster.u32 d, %0, %3; mapa.shared::cluster.u32 m, %2, %3;\n"
                                             " cp.async.bulk.shared::cluster.shared::cta.mbarrier::complete_tx::bytes [d], [%1], 8192, [m];}"
                                             ::"r"(sb + (cnt + 1 + i) * 16384 + wg * 8192), "r"(sb + (i ? cnt : n) * 16384 + wg * 8192), "r"(bars + 8 * (PB_F + cnt + 1 + i)), "r"(rank ^ 1) : "memory");
                        };
                        asm volatile("cp.async.bulk.wait_group 0; fence.proxy.async.global;" ::: "memory");
                        asm volatile("st.release.cta.shared.u32 [%0], %1;" ::"r"(bars + 8 * (PB_OUT + wg)), "r"(nout + ng) : "memory");
                        PH_(cnt == PPH - 1, wg, 21)
                        if (i < 12) asm volatile(FLAG_ST " [%0], %1;" ::"l"(&g_pflag[cnt * 256 + rh * 8 + nb]), "r"(max(i - 4, 1)) : "memory");
                        PH_(cnt == PPH - 1, wg, 22)
                        if (fast) to_peer();
                    }
                    nout += ng;
                    __syncwarp();
                    continue;
                }
                bar_sync(4 + 4 * wg + (sig++ & 3), 160);
                uint32_t* c = &g_pcnt[(cnt - C_S1) * 256 + rh * 8];
                if (lane == 0) signal_count(c);
                __syncwarp();
                wait_count_w(c, 8);
                const float4* sp = (const float4*)g_st + rh * 32 + lane;
                float4 u[3] = {__ldcg(sp + (cnt == C_S1 ? 0 : 3) * (S_ / 2)), __ldcg(sp + S_ / 2), __ldcg(sp + S_)};
#pragma unroll 1
                for (int h = 0; h < 2; h++) {
                    const float id = 1.0f / DM;
                    const float m = u[0].x * id, var = fmaxf(u[0].y * id - m * m, 0.f) + 1e-5f, r = rsqrtf(var);
                    float sc = r, m2 = 0.f;
                    if (cnt == C_S1) {
                        m2 = r * (u[1].x * id - m * g_cst[0]) + g_cst[3];
                        const float e2 = r * r * (u[2].x * id - 2.0f * m * u[1].y * id + m * m * g_cst[1]) + 2.0f * r * (u[2].y * id - m * g_cst[2]) + g_cst[4];
                        sc = r * rsqrtf(fmaxf(e2 - m2 * m2, 0.f) + 1e-5f);
                    }
                    const GeluK k = gelu_k(sc);
                    *(float4*)(rowc + h * 8) = make_float4(k.k0, k.k1, k.kh, -m);
                    *(float4*)(rowc + h * 8 + 4) = make_float4(var * r, -m2 * var * r, r, -m * r);
#pragma unroll
                    for (int q = 0; q < 3; q++) { u[q].x = u[q].z; u[q].y = u[q].w; }
                }
                bar_arrive(1 + wg, 160);
            }
        }
    } else {
        asm volatile("setmaxnreg.inc.sync.aligned.u32 232;");
        const bf16* xin = pp.x;
        const int wg = wid >> 2, wi = (tid >> 5) & 3, g = lane >> 2, tq = lane & 3;
        const int rh = 2 * mb + wg, row = rh * 64 + wi * 16 + g;
        const bool lead = (tid & 127) == 0;
        PP(0)
        if (tid == 0) TLP(10)
        uint32_t keep[32];
#pragma unroll
        for (int i = 0; i < 8; i++)
            *(uint4*)(keep + 4 * i) = __ldg((const uint4*)(xin + (size_t)(rh * 64 + wi * 16 + (i & 3) * 4 + (lane >> 3)) * DM + nb * 128 + (i >> 2) * 64 + (lane & 7) * 8));
        asm volatile("griddepcontrol.wait;" ::: "memory");
        if (cta < 64) g_modp[cta * 256 + tid] = 0;
        if (cta == 64 && tid < 196) g_tick[tid] = 0;
        const float* src = wg ? g_vec + nb * 128 + tid - 128 : g_mod + 2 * DM + nb * 128 + tid;
        const float* c3 = &g_vec[3 * DM + (tid >> 6) * 512 + nb * 64 + (tid & 63)];
        const float cv[6] = {__ldcg(src), __ldcg(src + (wg ? 1 : 2) * DM), __ldcg(src + (wg ? 2 : 1) * DM), __ldcg(src + 3 * DM), __ldcg(c3), __ldcg(c3 + (tid < 192 ? 2048 : 0))};
        uint32_t vec = sb + P_VEC + tq * 8;
        const uint32_t stw = sb + (wi * 16 + ((lane >> 3) & 1) * 8 + (lane & 7)) * 128 + (((lane >> 4) ^ (lane & 7)) << 4);
        int sig = 0;
        auto signal = [&]() { bar_arrive(4 + 4 * wg + (sig++ & 3), 160); };
        auto put64 = [&](uint32_t o, const float* v) {
#pragma unroll
            for (int jj = 0; jj < 4; jj++, v += 8) stsm4((stw + o) ^ (jj << 5), pack2(v[0], v[1]), pack2(v[2], v[3]), pack2(v[4], v[5]), pack2(v[6], v[7]));
            fence_async_smem();
            signal();
        };
        auto slot = [&](int n) {
            mbar_wait_w(bars + 8 * (PB_E + n % 5), ((n / 5) & 1) ^ 1);
            return (n % 5) * 16384 + wg * 8192;
        };
        const uint32_t rowc = sb + P_ROW + (wg * 64 + wi * 16 + g) * 32, o128 = P_OUT + wg * 16384;
        Pipe pa = {0, 0, 0};
        asm("mapa.shared::cluster.u32 %0, %1, %2;" : "=r"(pa.rel) : "r"(bars + 8 * PB_E), "r"(tid & 1));
        if (tid & 126) pa.rel = 0;
#define KEEP(jn, e) (((e) & 1) ? bfhi(keep[2 * (jn) + ((e) >> 1)]) : bflo(keep[2 * (jn) + ((e) >> 1)]))
        float mu1[2], r1[2];
        {
            float acc[64];
#pragma unroll 1
            for (int kb = 0; kb < 64; kb++) {
                post_kb<0>(sb, acc, pa, wg, lead, kb == 0, []() {});
                if (kb == 0) { PP(1) if (wg == 0) TLP(11) }
                if (kb == 24) bar_sync(3, 256);
                if (kb != 8 + 8 * wg) continue;
                float* sv = (float*)(smraw + P_VEC) + tid;
                const uint32_t xo = sb + o128 + wi * 2048 + (lane >> 3) * 128;
#pragma unroll
                for (int i = 0; i < 8; i++) sts4(xo + (i >> 2) * 8192 + (i & 3) * 512 + (((lane & 7) ^ ((i & 1) * 4 + (lane >> 3))) << 4), keep[4 * i], keep[4 * i + 1], keep[4 * i + 2], keep[4 * i + 3]);
                __syncwarp();
#pragma unroll
                for (int jj = 0; jj < 8; jj++) ldsm4(keep + jj * 4, (stw + o128 + (jj >> 2) * 8192) ^ ((jj & 3) << 5));
                sv[wg * 384] = cv[0]; sv[wg * 384 + 128] = cv[1] + (wg ? 0.0f : 1.0f); sv[wg * 384 + 256] = cv[2];
                if (!wg) sv[384] = cv[3];
                sv[V_C3 * 128] = cv[4]; sv[V_C3 * 128 + 256] = cv[5];
            }
            post_end(sb, pa, lead);
            PP(2)
            asm volatile("" : "+r"(vec) :: "memory");
            float st[2][6];
#pragma unroll
            for (int q = 0; q < 6; q++) st[0][q] = st[1][q] = 0.f;
#pragma unroll
            for (int jn = 0; jn < 16; jn++) {
                const float2 ga = ldsv(vec + V_GA * 512 + jn * 32), a = ldsv(vec + V_A * 512 + jn * 32);
                float xa[4];
#pragma unroll
                for (int e = 0; e < 4; e++) {
                    xa[e] = fmaf((e & 1) ? ga.y : ga.x, acc[4 * jn + e], KEEP(jn, e));
                    st[e >> 1][0] += xa[e]; st[e >> 1][1] = fmaf(xa[e], xa[e], st[e >> 1][1]);
                    acc[4 * jn + e] = ((e & 1) ? a.y : a.x) * xa[e];
                }
                keep[2 * jn] = pack2(xa[0], xa[1]); keep[2 * jn + 1] = pack2(xa[2], xa[3]);
                if ((jn & 7) == 7) put64(slot(64 + (jn >> 3)), acc + 4 * jn - 28);
            }
            PP(3)
#pragma unroll
            for (int jn = 0; jn < 16; jn++) {
                const float2 a = ldsv(vec + V_A * 512 + jn * 32), b = ldsv(vec + V_B * 512 + jn * 32);
#pragma unroll
                for (int e = 0; e < 4; e++) {
                    const float y = acc[4 * jn + e], aa = (e & 1) ? a.y : a.x, bb = (e & 1) ? b.y : b.x;
                    float* s = st[e >> 1];
                    s[2] += y; s[3] = fmaf(aa, y, s[3]); s[4] = fmaf(y, y, s[4]); s[5] = fmaf(bb, y, s[5]);
                }
            }
#pragma unroll
            for (int h = 0; h < 2; h++)
#pragma unroll
                for (int q = 0; q < 6; q++) { st[h][q] += __shfl_xor_sync(~0u, st[h][q], 1); st[h][q] += __shfl_xor_sync(~0u, st[h][q], 2); }
            if (tq < 3) {
#pragma unroll
                for (int h = 0; h < 2; h++)
                    red2(g_st + (tq * S_ + row + h * 8) * 2, tq == 0 ? st[h][0] : tq == 1 ? st[h][2] : st[h][4], tq == 0 ? st[h][1] : tq == 1 ? st[h][3] : st[h][5]);
            }
            signal();
            PP(29)
        }
        {
            float acc[64];
            post_mma<1>(sb, acc, pa, wg, lead, 2, 4, mb, nb);
            float c1[2], c2[2], c3[2];
            GeluK gk[2];
            bar_sync(1 + wg, 160);
#pragma unroll
            for (int h = 0; h < 2; h++) {
                const float4 a = lds4f(rowc + h * 256), b = lds4f(rowc + h * 256 + 16);
                gk[h] = {a.x, a.y, a.z}; c1[h] = a.w; c2[h] = b.x; c3[h] = b.y; mu1[h] = b.w; r1[h] = b.z;
            }
#pragma unroll
            for (int jn = 0; jn < 16; jn++) {
                const float2 va = ldsv(vec + V_VA * 512 + jn * 32), vb = ldsv(vec + V_VB * 512 + jn * 32), vc = ldsv(vec + V_VC * 512 + jn * 32);
#pragma unroll
                for (int e = 0; e < 4; e++) {
                    const int h = e >> 1;
                    const float t = fmaf(c1[h], (e & 1) ? va.y : va.x, fmaf(c2[h], (e & 1) ? vb.y : vb.x, fmaf(c3[h], (e & 1) ? vc.y : vc.x, acc[4 * jn + e])));
                    acc[4 * jn + e] = gelu_s(t, gk[h]);
                }
                if ((jn & 7) == 7) put64(o128 + (jn >> 3) * 8192, acc + 4 * jn - 28);
            }
            PP(6)
        }
        {
            float acc[64];
            post_mma<2>(sb, acc, pa, wg, lead, 0, 7, mb, nb);
#pragma unroll
            for (int jn = 0; jn < 16; jn++) {
                const float2 a = ldsv(vec + V_A * 512 + jn * 32), b = ldsv(vec + V_B * 512 + jn * 32);
#pragma unroll
                for (int e = 0; e < 4; e++) {
                    const int h = e >> 1;
                    acc[4 * jn + e] += fmaf(fmaf(KEEP(jn, e), r1[h], mu1[h]), (e & 1) ? a.y : a.x, (e & 1) ? b.y : b.x);
                }
                if ((jn & 7) == 7) put64(slot(96 + (jn >> 3)), acc + 4 * jn - 28);
            }
            BLOCK_FENCE
#pragma unroll
            for (int i = 0; i < 64; i += 16) asm volatile("" : F16(acc, i));
            PP(9)
            float st[2][2] = {{0.f, 0.f}, {0.f, 0.f}};
#pragma unroll
            for (int jn = 0; jn < 16; jn++) {
                const float2 gb = ldsv(vec + V_GB * 512 + jn * 32);
                float z[4];
#pragma unroll
                for (int e = 0; e < 4; e++) {
                    const float x1 = acc[4 * jn + e];
                    st[e >> 1][0] += x1; st[e >> 1][1] = fmaf(x1, x1, st[e >> 1][1]);
                    z[e] = fmaf((e & 1) ? gb.y : gb.x, x1, KEEP(jn, e));
                }
                keep[2 * jn] = pack2(z[0], z[1]); keep[2 * jn + 1] = pack2(z[2], z[3]);
            }
#pragma unroll
            for (int h = 0; h < 2; h++)
#pragma unroll
                for (int q = 0; q < 2; q++) { st[h][q] += __shfl_xor_sync(~0u, st[h][q], 1); st[h][q] += __shfl_xor_sync(~0u, st[h][q], 2); }
            if (tq < 2) red2(g_st + (3 * S_ + row + tq * 8) * 2, tq ? st[1][0] : st[0][0], tq ? st[1][1] : st[0][1]);
            signal();
            PP(30)
        }
        {
            float old[96], acc[64];
            post_mma<3>(sb, old, pa, wg, lead, 6, 10, mb, nb);
#pragma unroll
            for (int i = 0; i < 96; i += 16) asm volatile("" : F16(old, i));
            uint32_t v3 = vec + V_C3 * 512;
            bar_sync(1 + wg, 160);
            const float4 rc[2] = {lds4f(rowc), lds4f(rowc + 256)};
            float2 vc[2] = {lds2f(v3), lds2f(v3 + 32)};
            v3 += wg ? 0 : 64;
            bar_sync(3, 256);
#pragma unroll 1
            for (int blk = 0; blk < 11; blk++) {
                const uint32_t o = stw + o128 + (blk & 1) * 8192;
#pragma unroll
                for (int q = 0; q < 4; q++) {
#pragma unroll 1
                    for (int rep = 0; rep < 2; rep++) {
                        post_kb<1>(sb, acc, pa, wg, lead, q == 0 && rep == 0 && blk < 6 && !(blk & 1), []() {});
                        if (rep != wg) {
                            vc[0] = lds2f(v3 + q * 64); vc[1] = lds2f(v3 + q * 64 + 32);
                            if (q == 2) wait_smem(bars + 8 * (PB_OUT + wg), 6 + min(blk, 7));
                            if ((q == 0 && wg && (uint32_t)(blk - 1) < 7) || (q == 3 && !wg && blk < 7)) { fence_async_smem(); signal(); }
                        } else if (blk < 7) {
                            asm volatile("" : F4(old, 8 * q), F4(old, 8 * q + 4));
                            float t[8];
#pragma unroll
                            for (int i = 0; i < 8; i++) {
                                const float4& c = rc[(i >> 1) & 1];
                                t[i] = gelu_s(fmaf(c.w, (i & 1) ? vc[i >> 2].y : vc[i >> 2].x, old[8 * q + i]), GeluK{c.x, c.y, c.z});
                                old[8 * q + i] = old[32 + 8 * q + i];
                                old[32 + 8 * q + i] = old[64 + 8 * q + i];
                            }
                            uint32_t r[4] = {pack2(t[0], t[1]), pack2(t[2], t[3]), pack2(t[4], t[5]), pack2(t[6], t[7])};
                            asm volatile("pmevent 0;" : F4(old, 8 * q), F4(old, 8 * q + 4), F4(old, 8 * q + 32), F4(old, 8 * q + 36), "+r"(r[0]), "+r"(r[1]), "+r"(r[2]), "+r"(r[3]));
                            stsm4(o ^ (q << 5), r[0], r[1], r[2], r[3]);
                        }
                    }
                }
                v3 += 256;
                if (blk != 1 && blk != 3) continue;
                post_end(sb, pa, lead);
                PP(12 + blk)
                asm volatile("" : F16(acc, 0), F4(acc, 16), F4(acc, 20), F4(acc, 24));
                asm volatile("" : F16(acc, 28), F4(acc, 44), F4(acc, 48), F4(acc, 52));
                asm volatile("" : F4(acc, 56), F4(acc, 60));
#pragma unroll
                for (int i = 0; i < 64; i++) old[32 + i] = acc[i];
            }
            post_end(sb, pa, lead);
            PP(17)
#pragma unroll
            for (int jn = 0; jn < 16; jn++) {
                const float2 gb = ldsv(vec + V_GB * 512 + jn * 32);
#pragma unroll
                for (int e = 0; e < 4; e++) acc[4 * jn + e] = fmaf((e & 1) ? gb.y : gb.x, acc[4 * jn + e], KEEP(jn, e));
                if ((jn & 7) == 7) put64(o128 + ((jn >> 3) ^ 1) * 8192, acc + 4 * jn - 28);
            }
            PP(18)
            if (tid == 0) TLP(12)
        }
    }
}

typedef CUresult (*EncFn)(CUtensorMap*, CUtensorMapDataType, cuuint32_t, void*, const cuuint64_t*, const cuuint64_t*, const cuuint32_t*,
                          const cuuint32_t*, CUtensorMapInterleave, CUtensorMapSwizzle, CUtensorMapL2promotion, CUtensorMapFloatOOBfill);

static CUtensorMap make_map(EncFn enc, const void* p, uint64_t inner, uint64_t outer, uint32_t bi = 64) {
    CUtensorMap m;
    cuuint64_t dims[2] = {inner, outer};
    cuuint64_t str[1] = {inner * 2};
    cuuint32_t box[2] = {bi, bi == 64 ? 64u : 16u};
    cuuint32_t es[2] = {1, 1};
    enc(&m, CU_TENSOR_MAP_DATA_TYPE_BFLOAT16, 2, (void*)p, dims, str, box, es, CU_TENSOR_MAP_INTERLEAVE_NONE,
        bi == 64 ? CU_TENSOR_MAP_SWIZZLE_128B : CU_TENSOR_MAP_SWIZZLE_NONE, CU_TENSOR_MAP_L2_PROMOTION_L2_256B, CU_TENSOR_MAP_FLOAT_OOB_FILL_NONE);
    return m;
}
static CUtensorMap make_map_o(EncFn enc, const void* p) {
    CUtensorMap m;
    cuuint64_t dims[2] = {16384, 256};
    cuuint64_t str[1] = {65536};
    cuuint32_t box[2] = {256, 8};
    cuuint32_t es[2] = {1, 1};
    enc(&m, CU_TENSOR_MAP_DATA_TYPE_UINT32, 2, (void*)p, dims, str, box, es, CU_TENSOR_MAP_INTERLEAVE_NONE, CU_TENSOR_MAP_SWIZZLE_NONE,
        CU_TENSOR_MAP_L2_PROMOTION_L2_256B, CU_TENSOR_MAP_FLOAT_OOB_FILL_NONE);
    return m;
}
template <class T> static T* sym(T& s) { void* p = nullptr; cudaGetSymbolAddress(&p, s); return (T*)p; }

static const Delays h_dly = {D_NEAR, D_FAR, D_X2, D_V, D_W2, D_PA, 0, D_MORE};
extern "C" void kernel_launch(void* const* d_in, const int* in_sizes, int n_in, void* d_out, int out_size) {
    const bf16* x = (const bf16*)d_in[0];
    const bf16* mem0 = (const bf16*)d_in[1];
    const bf16 *Wq = (const bf16*)d_in[2], *Wk = (const bf16*)d_in[3], *Wv = (const bf16*)d_in[4], *Wo = (const bf16*)d_in[5];
    const bf16 *w1 = (const bf16*)d_in[8], *w2 = (const bf16*)d_in[9], *w3 = (const bf16*)d_in[10], *w4 = (const bf16*)d_in[11];
    const bf16 *c = (const bf16*)d_in[12], *wmod = (const bf16*)d_in[13];
    bf16* out = (bf16*)d_out;

    EncFn enc = nullptr;
    cudaDriverEntryPointQueryResult qr;
    cudaGetDriverEntryPoint("cuTensorMapEncodeTiled", (void**)&enc, cudaEnableDefault, &qr);
    CUtensorMap tWq = make_map(enc, Wq, NH * DH, DM), tWk = make_map(enc, Wk, NH * DH, DM), tWv = make_map(enc, Wv, NH * DH, DM);
    PostMaps mp;
    mp.o = make_map_o(enc, sym(g_O)); mp.wo = make_map(enc, Wo, DM, NH * DH);
    mp.y = make_map(enc, sym(g_y), DM, S_); mp.w1 = make_map(enc, w1, DM, DM);
    mp.g = make_map(enc, sym(g_g), DM, S_); mp.w2 = make_map(enc, w2, DM, DM);
    mp.x1 = make_map(enc, sym(g_x1), DM, S_); mp.w3 = make_map(enc, w3, FF, DM);
    mp.u = make_map(enc, sym(g_u), FF, S_); mp.w4 = make_map(enc, w4, DM, FF);
    mp.out = make_map(enc, out, DM, S_);
    cudaFuncSetAttribute(k_rec, cudaFuncAttributeMaxDynamicSharedMemorySize, SM_REC_TOTAL + 2048);
    cudaFuncSetAttribute(k_post, cudaFuncAttributeMaxDynamicSharedMemorySize, P_SMEM);

    uint8_t* arena = (uint8_t*)(((uintptr_t)sym(g_arena) + (2u << 20) - 1) & ~(uintptr_t)((2u << 20) - 1));
    const PostPtrs pp = {x};
    const RecPtrs rp = {x, mem0, c, wmod, w1, w3, arena, 0u, w2, w4, Wo, h_dly};
    const RecMaps rm = {tWq, tWk, tWv, mp.wo, make_map(enc, wmod, 6 * DM, DM, 256), make_map(enc, w3, FF, DM, 256), make_map(enc, w1, DM, DM, 256)};
    k_rec<<<132, 384, SM_REC_TOTAL + 2048>>>(rm, rp);
    cudaLaunchConfig_t cfg = {};
    cfg.gridDim = dim3(132); cfg.blockDim = dim3(384); cfg.dynamicSmemBytes = P_SMEM; cfg.stream = cudaStreamPerThread;
    cudaLaunchAttribute at[1];
    at[0].id = cudaLaunchAttributeProgrammaticStreamSerialization; at[0].val.programmaticStreamSerializationAllowed = PDL;
    cfg.attrs = at; cfg.numAttrs = 1;
    cudaLaunchKernelEx(&cfg, k_post, mp, pp);
}
```

```cpp
#include <cuda_runtime.h>
#include <cuda.h>
#include <cuda_bf16.h>
#include <stdint.h>
#include <limits.h>

typedef __nv_bfloat16 bf16;

constexpr int S_ = 2048, DM = 1024, NH = 32, DH = 128, NSEG = 64, FF = 3584;
constexpr int SPIN_LIMIT = 1 << 22;
#define W_INFL 2
#define H_PIECES 4
#define PDL 1
#define NPROBE 3

__device__ uint8_t g_arena[10 << 20];
__device__ __align__(128) uint32_t g_tick[64 + 132];
#define g_clk ((uint2*)(g_tick + 64))
__device__ uint32_t g_cls[256];
__device__ unsigned long long g_pt;
__device__ __align__(16) uint32_t g_modp[8 * 2 * DM];
__host__ __device__ constexpr uint32_t blk(uint32_t lb, uint32_t par) {
    return (lb << 13) | ((((lb) ^ (lb >> 3) ^ (lb >> 4) ^ (lb >> 6) ^ par) & 1) << 12);
}
__host__ __device__ constexpr uint32_t lb_x2(uint32_t h) { return (h & 1) | ((h >> 1) << 3); }
__host__ __device__ constexpr uint32_t mem_row(uint32_t kh, uint32_t b, uint32_t r) { return blk(128 | b, kh) + r * 1024; }
__device__ __forceinline__ uint32_t mem_slot(uint32_t s) { return ((s & 1) << 15) | ((s & 2) << 17); }
constexpr uint32_t CNT1 = 0x3d80, CNT_ALL = 0x4000;
constexpr uint32_t LB_PROBE = 6 | 64, LB_TIME = 6;
__host__ __device__ constexpr uint32_t lb_tok(uint32_t h) { return (h & 1) | ((h >> 1) << 3); }
__device__ float g_mod[6 * DM];
__device__ __align__(1024) bf16 g_himg[(S_ + 32) * DM];
__device__ __align__(1024) bf16 g_O[S_ * NH * DH];
__device__ __align__(1024) bf16 g_y[S_ * DM];
__device__ __align__(1024) bf16 g_g[S_ * DM];
__device__ __align__(1024) bf16 g_x1[S_ * DM];
__device__ __align__(16) float g_st[4 * S_ * 2];
__device__ float g_vec[3 * DM + FF];
__device__ float g_cst[8];
__device__ uint32_t g_pcnt[2 * 32 * 8], g_pflag[7 * 32 * 8];
__device__ __align__(1024) bf16 g_u[S_ * FF];

#define TL(i) {}
#define TLX(i) {}
#define TLP(i) TL(i)
#define TLC(i) {}
__device__ __forceinline__ uint32_t smem_u32(const void* p) { return (uint32_t)__cvta_generic_to_shared(p); }
__device__ __forceinline__ void spin_guard(int it) {
    asm volatile("{.reg .pred p; setp.gt.s32 p, %0, %1; @p st.global.u32 [%2], %0;}" ::"r"(it), "n"(SPIN_LIMIT), "l"(1ull));
}
__device__ __forceinline__ void wg_fence() { asm volatile("wgmma.fence.sync.aligned;" ::: "memory"); }
__device__ __forceinline__ void wg_commit() { asm volatile("wgmma.commit_group.sync.aligned;" ::: "memory"); }
template <int N> __device__ __forceinline__ void wg_wait() { asm volatile("wgmma.wait_group.sync.aligned %0;" ::"n"(N) : "memory"); }
__host__ __device__ constexpr uint64_t mkdesc(uint32_t addr, uint32_t lbo, uint32_t sbo, uint32_t swz) {
    return (uint64_t)((addr & 0x3FFFF) >> 4) | ((uint64_t)(lbo >> 4) << 16) | ((uint64_t)(sbo >> 4) << 32) | ((uint64_t)swz << 62);
}
__device__ __forceinline__ uint64_t dadd(uint64_t d, uint32_t o) { return (d & 0xffffffff00000000ull) | (uint32_t)((uint32_t)d + o); }
__device__ __forceinline__ void mbar_init(uint32_t b, uint32_t c) { asm volatile("mbarrier.init.shared.b64 [%0], %1;" ::"r"(b), "r"(c) : "memory"); }
__device__ __forceinline__ void mbar_arrive_cluster(uint32_t b, uint32_t cta) {
    asm volatile("{.reg .b32 r; mapa.shared::cluster.u32 r, %0, %1; mbarrier.arrive.shared::cluster.b64 _, [r];}" ::"r"(b), "r"(cta) : "memory");
}
__device__ __forceinline__ bool mbar_try(uint32_t b, uint32_t par) {
    uint32_t ok;
    asm volatile("{.reg .pred p; mbarrier.try_wait.parity.shared.b64 p, [%1], %2; selp.u32 %0, 1, 0, p;}" : "=r"(ok) : "r"(b), "r"(par) : "memory");
    return ok;
}
__device__ __forceinline__ void mbar_wait(uint32_t b, uint32_t par) {
    int it = 0;
#pragma unroll 1
    while (!mbar_try(b, par) & (++it < SPIN_LIMIT)) {}
}
__device__ __forceinline__ void mbar_wait_w(uint32_t b, uint32_t par) {
    int it = 0;
#pragma unroll 1
    while (!__all_sync(~0u, mbar_try(b, par)) & (++it < SPIN_LIMIT)) {}
}
constexpr uint64_t EVICT_FIRST = 0x12F0000000000000ull, EVICT_NORMAL = 0x1000000000000000ull;   __device__ __forceinline__ void bar_sync(int id, int n) { asm volatile("bar.sync %0, %1;" ::"r"(id), "r"(n) : "memory"); }
__device__ __forceinline__ void bar_arrive(int id, int n) { asm volatile("bar.arrive %0, %1;" ::"r"(id), "r"(n) : "memory"); }
__device__ __forceinline__ void fence_async_smem() { asm volatile("fence.proxy.async.shared::cta;" ::: "memory"); }
__device__ __forceinline__ void ldsm4t(uint32_t* r, uint32_t a) {
    asm volatile("ldmatrix.sync.aligned.m8n8.x4.trans.shared.b16 {%0,%1,%2,%3}, [%4];" : "=r"(r[0]), "=r"(r[1]), "=r"(r[2]), "=r"(r[3]) : "r"(a) : "memory");
}
__device__ __forceinline__ void ldsm4(uint32_t* r, uint32_t a) {
    asm volatile("ldmatrix.sync.aligned.m8n8.x4.shared.b16 {%0,%1,%2,%3}, [%4];" : "=r"(r[0]), "=r"(r[1]), "=r"(r[2]), "=r"(r[3]) : "r"(a) : "memory");
}
__device__ __forceinline__ uint32_t movm(uint32_t a) {
    uint32_t d; asm volatile("movmatrix.sync.aligned.m8n8.trans.b16 %0, %1;" : "=r"(d) : "r"(a)); return d;
}
__device__ __forceinline__ void mma16816(float* d, uint32_t a0, uint32_t a1, uint32_t a2, uint32_t a3, uint32_t b0, uint32_t b1) {
    asm volatile("mma.sync.aligned.m16n8k16.row.col.f32.bf16.bf16.f32 {%0,%1,%2,%3},{%4,%5,%6,%7},{%8,%9},{%0,%1,%2,%3};"
                 : "+f"(d[0]), "+f"(d[1]), "+f"(d[2]), "+f"(d[3]) : "r"(a0), "r"(a1), "r"(a2), "r"(a3), "r"(b0), "r"(b1));
}
__device__ __forceinline__ void mma16816z(float* d, const uint32_t* a, uint32_t b0, uint32_t b1) {
    asm volatile("mma.sync.aligned.m16n8k16.row.col.f32.bf16.bf16.f32 {%0,%1,%2,%3},{%4,%5,%6,%7},{%8,%9},{%10,%10,%10,%10};"
                 : "=f"(d[0]), "=f"(d[1]), "=f"(d[2]), "=f"(d[3]) : "r"(a[0]), "r"(a[1]), "r"(a[2]), "r"(a[3]), "r"(b0), "r"(b1), "f"(0.f));
}
__device__ __forceinline__ void mma1688(float* d, uint32_t a0, uint32_t a1, uint32_t b0) {
    asm volatile("mma.sync.aligned.m16n8k8.row.col.f32.bf16.bf16.f32 {%0,%1,%2,%3},{%4,%5},{%6},{%0,%1,%2,%3};"
                 : "+f"(d[0]), "+f"(d[1]), "+f"(d[2]), "+f"(d[3]) : "r"(a0), "r"(a1), "r"(b0));
}
__device__ __forceinline__ uint32_t pack2(float lo, float hi) {
    uint32_t r; asm("cvt.rn.bf16x2.f32 %0, %1, %2;" : "=r"(r) : "f"(hi), "f"(lo)); return r;
}
__device__ __forceinline__ uint32_t hadd2(uint32_t a, uint32_t b) {
    uint32_t r; asm("add.rn.bf16x2 %0, %1, %2;" : "=r"(r) : "r"(a), "r"(b)); return r;
}
__device__ __forceinline__ float bflo(uint32_t u) { return __uint_as_float(u << 16); }
__device__ __forceinline__ float bfhi(uint32_t u) { return __uint_as_float(u & 0xffff0000u); }
__device__ __forceinline__ float ex2(float x) { float r; asm("ex2.approx.ftz.f32 %0, %1;" : "=f"(r) : "f"(x)); return r; }
__device__ __forceinline__ uint4 ldg_rlx4(const void* p) {
    uint4 v; asm volatile("ld.relaxed.gpu.global.v4.u32 {%0,%1,%2,%3}, [%4];" : "=r"(v.x), "=r"(v.y), "=r"(v.z), "=r"(v.w) : "l"(p) : "memory"); return v;
}
__device__ __forceinline__ uint32_t ldg_rlx1(const void* p) {
    uint32_t v; asm volatile("ld.relaxed.gpu.global.u32 %0, [%1];" : "=r"(v) : "l"(p) : "memory"); return v;
}
__device__ __forceinline__ void stg_rlx1(void* p, uint32_t v) { asm volatile("st.relaxed.gpu.global.u32 [%0], %1;" ::"l"(p), "r"(v) : "memory"); }
__device__ __forceinline__ void stg_rlx2(void* p, uint32_t x, uint32_t y) {
    unsigned long long v = (unsigned long long)x | ((unsigned long long)y << 32);
    asm volatile("st.relaxed.gpu.global.b64 [%0], %1;" ::"l"(p), "l"(v) : "memory");
}
__device__ __forceinline__ void stg_rlx4(void* p, uint32_t x, uint32_t y, uint32_t z, uint32_t w) {
    asm volatile("st.relaxed.gpu.global.v4.u32 [%0], {%1,%2,%3,%4};" ::"l"(p), "r"(x), "r"(y), "r"(z), "r"(w) : "memory");
}
__device__ __forceinline__ void sts4(uint32_t a, uint32_t x, uint32_t y, uint32_t z, uint32_t w) {
    asm volatile("st.shared.v4.u32 [%0], {%1,%2,%3,%4};" ::"r"(a), "r"(x), "r"(y), "r"(z), "r"(w) : "memory");
}
__device__ __forceinline__ uint4 lds4(uint32_t a) {
    uint4 v; asm volatile("ld.shared.v4.u32 {%0,%1,%2,%3}, [%4];" : "=r"(v.x), "=r"(v.y), "=r"(v.z), "=r"(v.w) : "r"(a) : "memory"); return v;
}
#define F4(d, i) "+f"(d[i]), "+f"(d[i + 1]), "+f"(d[i + 2]), "+f"(d[i + 3])
__device__ __forceinline__ void wgmma_rs32(float* d, const uint32_t* a, uint64_t b, int sc) {
    asm volatile("{.reg .pred p; setp.ne.b32 p, %21, 0;\n wgmma.mma_async.sync.aligned.m64n32k16.f32.bf16.bf16 {%0,%1,%2,%3,%4,%5,%6,%7,%8,%9,%10,%11,%12,%13,%14,%15}, {%16,%17,%18,%19}, %20, p, 1, 1, 0;}"
                 : F4(d, 0), F4(d, 4), F4(d, 8), F4(d, 12) : "r"(a[0]), "r"(a[1]), "r"(a[2]), "r"(a[3]), "l"(b), "r"(sc));
}
__device__ __forceinline__ void wgmma_ss32(float* d, uint64_t a, uint64_t b, int sc) {
    asm volatile("{.reg .pred p; setp.ne.b32 p, %18, 0;\n wgmma.mma_async.sync.aligned.m64n32k16.f32.bf16.bf16 {%0,%1,%2,%3,%4,%5,%6,%7,%8,%9,%10,%11,%12,%13,%14,%15}, %16, %17, p, 1, 1, 1, 0;}"
                 : F4(d, 0), F4(d, 4), F4(d, 8), F4(d, 12) : "l"(a), "l"(b), "r"(sc));
}
__device__ __forceinline__ void wgmma_rs40(float* d, const uint32_t* a, uint64_t b, int sc) {
    asm volatile("{.reg .pred p; setp.ne.b32 p, %25, 0;\n wgmma.mma_async.sync.aligned.m64n40k16.f32.bf16.bf16 {%0,%1,%2,%3,%4,%5,%6,%7,%8,%9,%10,%11,%12,%13,%14,%15,%16,%17,%18,%19}, {%20,%21,%22,%23}, %24, p, 1, 1, 0;}"
                 : F4(d, 0), F4(d, 4), F4(d, 8), F4(d, 12), F4(d, 16) : "r"(a[0]), "r"(a[1]), "r"(a[2]), "r"(a[3]), "l"(b), "r"(sc));
}
__device__ __forceinline__ void wgmma_ss40(float* d, uint64_t a, uint64_t b, int sc) {
    asm volatile("{.reg .pred p; setp.ne.b32 p, %22, 0;\n wgmma.mma_async.sync.aligned.m64n40k16.f32.bf16.bf16 {%0,%1,%2,%3,%4,%5,%6,%7,%8,%9,%10,%11,%12,%13,%14,%15,%16,%17,%18,%19}, %20, %21, p, 1, 1, 1, 0;}"
                 : F4(d, 0), F4(d, 4), F4(d, 8), F4(d, 12), F4(d, 16) : "l"(a), "l"(b), "r"(sc));
}
#define F16(d, i) F4(d, i), F4(d, i + 4), F4(d, i + 8), F4(d, i + 12)
template <int TA>
__device__ __forceinline__ void wgmma_ss128(float* d, uint64_t a, uint64_t b, int sc) {
    asm volatile("{.reg .pred p; setp.ne.b32 p, %66, 0;\n wgmma.mma_async.sync.aligned.m64n128k16.f32.bf16.bf16 "
                 "{%0,%1,%2,%3,%4,%5,%6,%7,%8,%9,%10,%11,%12,%13,%14,%15,%16,%17,%18,%19,%20,%21,%22,%23,%24,%25,%26,%27,%28,%29,%30,%31,"
                 "%32,%33,%34,%35,%36,%37,%38,%39,%40,%41,%42,%43,%44,%45,%46,%47,%48,%49,%50,%51,%52,%53,%54,%55,%56,%57,%58,%59,%60,%61,%62,%63}, %64, %65, p, 1, 1, %67, 1;}"
                 : F16(d, 0), F16(d, 16), F16(d, 32), F16(d, 48) : "l"(a), "l"(b), "r"(sc), "n"(TA));
}

__device__ __forceinline__ float warp_sum(float v) {
#pragma unroll
    for (int o = 16; o; o >>= 1) v += __shfl_xor_sync(~0u, v, o);
    return v;
}
__device__ __forceinline__ float bfround(float x) { return __bfloat162float(__float2bfloat16(x)); }

__device__ __forceinline__ void wait_count1(const uint32_t* p, uint32_t target) {
    int it = 0;
#pragma unroll 1
    while (true) {
        uint32_t v;
        asm volatile("ld.acquire.gpu.global.u32 %0, [%1];" : "=r"(v) : "l"(p) : "memory");
        if (v >= target) break;
        spin_guard(++it);
    }
}
__device__ __forceinline__ void red2(float* p, float a, float b) {
    asm volatile("red.relaxed.gpu.global.add.v2.f32 [%0], {%1, %2};" ::"l"(p), "f"(a), "f"(b) : "memory");
}
__device__ __forceinline__ void signal_count(uint32_t* p) { asm volatile("red.release.gpu.global.add.u32 [%0], 1;" ::"l"(p) : "memory"); }
__device__ __forceinline__ void e_expect(uint32_t b, uint32_t tx) {
    asm volatile("{.reg .pred p; elect.sync _|p, 0xffffffff; @p mbarrier.arrive.expect_tx.shared.b64 _, [%0], %1;}" ::"r"(b), "r"(tx) : "memory");
}
__device__ __forceinline__ void e_tma2d(uint32_t dst, const CUtensorMap* m, int c0, int c1, uint32_t bar) {
    asm volatile("{.reg .pred p; elect.sync _|p, 0xffffffff;\n @p cp.async.bulk.tensor.2d.shared::cluster.global.mbarrier::complete_tx::bytes [%0], [%1, {%3, %4}], [%2];}"
                 ::"r"(dst), "l"(m), "r"(bar), "r"(c0), "r"(c1) : "memory");
}
__device__ __forceinline__ void e_tma2d_hint(uint32_t dst, const CUtensorMap* m, int c0, int c1, uint32_t bar, uint64_t pol) {
    asm volatile("{.reg .pred p; elect.sync _|p, 0xffffffff;\n @p cp.async.bulk.tensor.2d.shared::cluster.global.mbarrier::complete_tx::bytes.L2::cache_hint [%0], [%1, {%3, %4}], [%2], %5;}"
                 ::"r"(dst), "l"(m), "r"(bar), "r"(c0), "r"(c1), "l"(pol) : "memory");
}
__device__ __forceinline__ void e_tma2d_mc(uint32_t dst, const CUtensorMap* m, int c0, int c1, uint32_t bar) {
    asm volatile("{.reg .pred p; elect.sync _|p, 0xffffffff;\n @p cp.async.bulk.tensor.2d.shared::cluster.global.mbarrier::complete_tx::bytes.multicast::cluster [%0], [%1, {%3, %4}], [%2], %5;}"
                 ::"r"(dst), "l"(m), "r"(bar), "r"(c0), "r"(c1), "h"((uint16_t)3) : "memory");
}
__device__ __forceinline__ void wait_count_w(const uint32_t* p, uint32_t target) {
    int it = 0;
#pragma unroll 1
    while (true) {
        uint32_t v;
        asm volatile("ld.acquire.gpu.global.u32 %0, [%1];" : "=r"(v) : "l"(p) : "memory");
        if (__all_sync(~0u, v >= target) | (++it > SPIN_LIMIT)) break;
        __nanosleep(100);
    }
}

#define NL 6
constexpr uint32_t SM_HB = 16384, HBK = 5120, SM_SX = 57344, SM_OX = 122880, SM_PX = 124928, SM_PA = 126976, SM_WO = 147456,
                   SM_TAB = 212992, SM_PRE = SM_TAB + 5120, SM_BAR = 227328, SM_REC_TOTAL = 227328 + 256;
constexpr uint32_t SB0 = 1024;
constexpr int B_WO = 0, B_HE = 1, B_HB = 3, B_W = 5;
constexpr int NB_MEM = 1, NB_QK = 2, NB_X1 = 3, NB_X2 = 4, NB_WIN = 5, NB_WG = 6, NB_KDONE = 7, NB_FIN0 = 8, NB_P = 9, NB_PX = 10, NB_G = 11, NB_A = 12, NB_B = 13, NB_C = 14, NB_S = 15;
#define D_NEAR 1620
#define D_FAR (D_NEAR - 90)
#define D_X2 400
#define D_V 280
#define D_W2 40
#define D_PA 40
#define D_MORE 40
constexpr int E_MUL = 28;
constexpr int NPF = NL + 6, NE1 = 10;
constexpr int W0_E = 3, W0_RS = NL - 1, G_AT = 18;
struct Delays { uint32_t near, far, x2, v, w2, pa, spare, more; };
#define MISS(i, v)
#define MISS_INIT
#define MISS_OUT
#define HT(i)

__device__ __forceinline__ uint32_t clk32() { uint32_t t; asm volatile("mov.u32 %0, %%clock;" : "=r"(t) :: "memory"); return t; }
__device__ __forceinline__ uint32_t smid() { uint32_t t; asm volatile("mov.u32 %0, %%smid;" : "=r"(t)); return t; }
__device__ __forceinline__ uint32_t gtime() { uint32_t t; asm volatile("mov.u32 %0, %%globaltimer_lo;" : "=r"(t) :: "memory"); return t; }
__device__ __forceinline__ void spin_until(uint32_t t0, uint32_t d) { while (clk32() - t0 < d) {} }
template <int N> __device__ __forceinline__ uint32_t delay(uint32_t zero) {
    float x = __uint_as_float(clk32());
#pragma unroll
    for (int i = 0; i < N; i++) asm volatile("ex2.approx.ftz.f32 %0, %0;" : "+f"(x));
    return __float_as_uint(x) & zero;
}
__device__ __forceinline__ uint32_t opaque(uint32_t v) { return __shfl_sync(~0u, v, threadIdx.x & 31); }
__device__ __forceinline__ uint32_t xor_or(uint32_t a, uint32_t b, uint32_t t) {
    uint32_t r; asm volatile("lop3.b32 %0, %1, %2, %3, 0x7E;" : "=r"(r) : "r"(a), "r"(b), "r"(t)); return r;
}
__device__ __forceinline__ uint32_t settag(uint32_t v, uint32_t tag) {
    uint32_t r; asm("lop3.b32 %0, %1, 1, %2, 0xB8;" : "=r"(r) : "r"(v), "r"(tag)); return r;
}
__device__ __forceinline__ void sts2(uint32_t a, float x, float y) { asm volatile("st.shared.v2.f32 [%0], {%1,%2};" ::"r"(a), "f"(x), "f"(y) : "memory"); }
__device__ __forceinline__ void sts4f(uint32_t a, float x, float y, float z, float w) {
    asm volatile("st.shared.v4.f32 [%0], {%1,%2,%3,%4};" ::"r"(a), "f"(x), "f"(y), "f"(z), "f"(w) : "memory");
}
__device__ __forceinline__ void sts1(uint32_t a, uint32_t x) { asm volatile("st.shared.u32 [%0], %1;" ::"r"(a), "r"(x) : "memory"); }
__device__ __forceinline__ uint32_t lds1(uint32_t a) { uint32_t v; asm volatile("ld.shared.u32 %0, [%1];" : "=r"(v) : "r"(a) : "memory"); return v; }
__device__ __forceinline__ float4 lds4f(uint32_t a) {
    float4 v; asm volatile("ld.shared.v4.f32 {%0,%1,%2,%3}, [%4];" : "=f"(v.x), "=f"(v.y), "=f"(v.z), "=f"(v.w) : "r"(a) : "memory"); return v;
}
__device__ __forceinline__ float2 lds2f(uint32_t a) {
    float2 v; asm volatile("ld.shared.v2.f32 {%0,%1}, [%2];" : "=f"(v.x), "=f"(v.y) : "r"(a) : "memory"); return v;
}
__device__ __forceinline__ bool any_bit0(uint32_t x) {
    uint32_t r;
    asm volatile("{.reg .pred p, q; .reg .b32 t; and.b32 t, %1, 1; setp.ne.u32 p, t, 0; vote.sync.any.pred q, p, 0xffffffff; selp.u32 %0, 1, 0, q;}" : "=r"(r) : "r"(x));
    return r;
}
__device__ __forceinline__ float rcp_fast(float x) { float r; asm("rcp.approx.ftz.f32 %0, %1;" : "=f"(r) : "f"(x)); return r; }
__device__ __forceinline__ void stsm4(uint32_t a, uint32_t r0, uint32_t r1, uint32_t r2, uint32_t r3) {
    asm volatile("stmatrix.sync.aligned.m8n8.x4.shared.b16 [%0], {%1,%2,%3,%4};" ::"r"(a), "r"(r0), "r"(r1), "r"(r2), "r"(r3) : "memory");
}
__device__ __forceinline__ void stsm4t(uint32_t a, uint32_t r0, uint32_t r1, uint32_t r2, uint32_t r3) {
    asm volatile("stmatrix.sync.aligned.m8n8.x4.trans.shared.b16 [%0], {%1,%2,%3,%4};" ::"r"(a), "r"(r0), "r"(r1), "r"(r2), "r"(r3) : "memory");
}
__device__ __forceinline__ uint32_t and3(uint32_t a, uint32_t b, uint32_t c) {
    uint32_t r; asm("lop3.b32 %0, %1, %2, %3, 0x80;" : "=r"(r) : "r"(a), "r"(b), "r"(c)); return r;
}
__device__ __forceinline__ void red_mem(void* p, uint32_t x, uint32_t y, uint32_t z, uint32_t w, void* q, uint32_t e, bool c) {
    asm volatile("{.reg .pred p; setp.ne.u32 p, %7, 0; red.relaxed.gpu.global.add.noftz.v4.bf16x2 [%0], {%1,%2,%3,%4}; @p red.relaxed.gpu.global.add.noftz.bf16x2 [%5], %6;}"
                 ::"l"(p), "r"(x), "r"(y), "r"(z), "r"(w), "l"(q), "r"(e), "r"((uint32_t)c) : "memory");
}
__device__ __forceinline__ void stg4_if(bool c, void* p, uint32_t x) {
    asm volatile("{.reg .pred p; setp.ne.u32 p, %2, 0; @p st.relaxed.gpu.global.v4.u32 [%0], {%1,%1,%1,%1};}" ::"l"(p), "r"(x), "r"((uint32_t)c) : "memory");
}

__device__ __forceinline__ void h_load(uint32_t sb, const uint8_t* hsrc, int pass, uint32_t rank, uint32_t rot) {
    const uint8_t* src = hsrc + (size_t)pass * 65536;
    const uint32_t bar = sb + SM_BAR + 8 * (B_HB + (pass & 1)), dst = sb + SM_HB + (pass & 1) * 65536 + rank * 4 * HBK;
    e_expect(bar, 32768);
#pragma unroll 1
    for (int i = 0; i < H_PIECES; i++) {
        const uint32_t o = ((i + rot) & (H_PIECES - 1)) * (16384 / H_PIECES);
        asm volatile("{.reg .pred p; elect.sync _|p, 0xffffffff;\n"
                     " @p cp.async.bulk.shared::cluster.global.mbarrier::complete_tx::bytes.multicast::cluster [%0], [%1], %4, [%2], %3;}"
                     ::"r"(dst + o + (o >> 12) * 1024), "l"(src + o), "r"(bar), "h"((uint16_t)3), "n"(16384 / H_PIECES) : "memory");
    }
}
__device__ __forceinline__ uint4 ldg_b128(const void* p) {
    uint4 v;
    asm volatile("{.reg .b128 t; .reg .b64 a, b; ld.relaxed.gpu.global.b128 t, [%4]; mov.b128 {a, b}, t; mov.b64 {%0,%1}, a; mov.b64 {%2,%3}, b;}"
                 : "=r"(v.x), "=r"(v.y), "=r"(v.z), "=r"(v.w) : "l"(p) : "memory");
    return v;
}
__device__ __forceinline__ void stg_b128_if(bool c, void* p, uint32_t x, uint32_t y, uint32_t z, uint32_t w) {
    asm volatile("{.reg .pred p; setp.ne.u32 p, %5, 0; @p st.relaxed.gpu.global.v4.u32 [%0], {%1,%2,%3,%4};}"
                 ::"l"(p), "r"(x), "r"(y), "r"(z), "r"(w), "r"((uint32_t)c) : "memory");
}
__device__ __forceinline__ float pretag(float x, uint32_t add, uint32_t keep) { return __uint_as_float((__float_as_uint(x) + add) & keep); }

template <class F, class G>
__device__ __forceinline__ void softmax_rows(uint32_t src, uint32_t dst, uint32_t g16, int row0, F ready, G mid) {
    const uint32_t u = (g16 >> 7) & 3, e = ((g16 >> 9) << 3) | ((g16 >> 4) & 7);
    uint32_t se = src + e * 8, su = se + u * 1088, d0 = dst + e * 16 + u * 4, d1 = dst + 512 + e * 4;
    int vis = row0 + (e >> 2) - 2 * (e & 3) - 8 * u;
    asm volatile("" : "+r"(se), "+r"(su), "+r"(d0), "+r"(d1), "+r"(vis));
    ready();
    const float2 p0 = lds2f(su), p1 = lds2f(su + 256), p2 = lds2f(su + 512), p3 = lds2f(su + 768);
    const float2 m0 = lds2f(se + 4352), m1 = lds2f(se + 4352 + 256), m2 = lds2f(se + 4352 + 512), m3 = lds2f(se + 4352 + 768);
    float a0 = (p0.x + p1.x) + (p2.x + p3.x), a1 = (p0.y + p1.y) + (p2.y + p3.y);
    const float a2 = (m0.x + m1.x) + (m2.x + m3.x), a3 = (m0.y + m1.y) + (m2.y + m3.y);
    if (vis < 0) a0 = -1e9f / 0.08838834764831845f;
    if (vis < 1) a1 = -1e9f / 0.08838834764831845f;
    int k = __float_as_int(fmaxf(fmaxf(a0, a1), fmaxf(a2, a3)));
    k ^= (k >> 31) & 0x7fffffff;
    const bool hi = g16 & 64;
    const int k0 = __reduce_max_sync(~0u, hi ? INT_MIN : k), k1 = __reduce_max_sync(~0u, hi ? k : INT_MIN);
    mid();
    k = hi ? k1 : k0;
    const float m = __int_as_float(k ^ ((k >> 31) & 0x7fffffff));
    const float sl2 = 0.08838834764831845f * 1.4426950408889634f, mb = -m * sl2;
    sts1(d0, pack2(ex2(fmaf(a0, sl2, mb)), ex2(fmaf(a1, sl2, mb))));
    sts1(d1, pack2(ex2(fmaf(a2, sl2, mb)), ex2(fmaf(a3, sl2, mb))));
}

__device__ __forceinline__ uint32_t pack_h2(float lo, float hi) {
    uint32_t r; asm("cvt.rn.satfinite.f16x2.f32 %0, %1, %2;" : "=r"(r) : "f"(hi), "f"(lo)); return r;
}
__device__ __forceinline__ float2 unpack_h2(uint32_t u) {
    float2 r; asm("{.reg .b16 l, h; mov.b32 {l, h}, %2; cvt.f32.f16 %0, l; cvt.f32.f16 %1, h;}" : "=f"(r.x), "=f"(r.y) : "r"(u)); return r;
}
__device__ __forceinline__ uint32_t add_h2(uint32_t a, uint32_t b) { uint32_t r; asm("add.rn.f16x2 %0, %1, %2;" : "=r"(r) : "r"(a), "r"(b)); return r; }
__device__ __forceinline__ uint32_t max_h2(uint32_t a, uint32_t b) { uint32_t r; asm("max.f16x2 %0, %1, %2;" : "=r"(r) : "r"(a), "r"(b)); return r; }
struct U2 { uint32_t x, y; };
__device__ __forceinline__ U2 ldg_u2(const void* p) {
    U2 v; asm volatile("{.reg .b64 t; ld.relaxed.gpu.global.b64 t, [%2]; mov.b64 {%0, %1}, t;}" : "=r"(v.x), "=r"(v.y) : "l"(p) : "memory"); return v;
}
constexpr int POLL_LIMIT = 1 << 16;
constexpr float SM_L2E = 0.08838834764831845f * 1.4426950408889634f;
template <int V> struct IC { static constexpr int value = V; };
typedef unsigned long long u64;
__device__ __forceinline__ u64 ldg_u64(const void* p) { u64 v; asm volatile("ld.relaxed.gpu.global.b64 %0, [%1];" : "=l"(v) : "l"(p) : "memory"); return v; }
__device__ __forceinline__ void rec_main(uint32_t sb, const CUtensorMap* tWo, uint8_t* arena, int role, int hinfo, int wg, uint32_t zero, const Delays& dly) {
    const int hA = hinfo & 255;
    const int tid = threadIdx.x, t = tid & 127, lane = tid & 31, wi = t >> 5;
    const uint32_t bars = sb + SM_BAR;
    const int head = role >> 2, qd = role & 3, j = blockIdx.x & 1, kh = role & 1;
    const uint32_t mypar = head >= hA;
    const uint32_t wu = __reduce_max_sync(~0u, wi);
    const bool warp0 = wu == 0, warp1 = wu == 1;
    const uint8_t* hsrc = (const uint8_t*)g_himg + kh * 32768 + j * 16384;
    auto tokbase = [&](int ty) { return ((ty + 1) << 21) + blk(lb_tok(head), mypar ^ ((hinfo >> (8 + ty)) & 1)); };
    const uint32_t tbw = tokbase(wg), tbq = tokbase(0) + (qd >> 1) * 2048 + (qd & 1) * 8;
    uint32_t w[32 - NL][4];
    const uint32_t frow = ((lane >> 4) * 8 + (lane & 7)) * 128, fx = ((lane >> 3) & 1) ^ (lane & 7);
    const uint32_t wl0 = sb + wg * 65536 + frow + ((fx ^ (2 * wi)) << 4);
    uint32_t g16 = opaque(t * 16);
    auto G16 = [&]() { asm volatile("" : "+r"(g16)); return g16; };
    const uint32_t sbl = sb - wu * 512;
    const uint32_t xso = blk(lb_x2(head), mypar), cu = kh * 2048 + (2 * j + (wu >> 1)) * 512;
    const uint32_t u_xo = xso + wg * 16384 + (wu & 1) * 2048 + (cu >> 1) - wu * 256, u_to = tbw + (wu & 1) * 16384 + cu - wu * 512;
    {
        uint8_t* pp = arena + (tbw + (1 << 20) + j * 16384 + (kh ^ 1) * 2048 + g16);
        stg_rlx4(pp, 0, 0, 0, 0);
        stg_rlx4(pp + 32768, 0, 0, 0, 0);
        stg_rlx4(arena + (u_to + g16), 0, 0, 0, 0);
        stg_rlx2(arena + (u_xo + (g16 >> 1)), 0, 0);
    }
    {
        if (wg > 0) wait_count_w(&g_tick[32 + (lane & 3) * 8], 1);
        if (wg == 1) asm volatile("fence.proxy.async.global;" ::: "memory");
#pragma unroll 1
        for (int i = 0; i < 4; i++) mbar_wait_w(bars + 8 * (B_W + (wg == 2 ? 8 + i : 2 * i + wg)), 0);
#pragma unroll
        for (int p = NL; p < 32; p++) ldsm4t(w[p - NL], wl0 + p * 2048);
        fence_async_smem();
        bar_sync(wg < 2 ? NB_WG : NB_X2, wg < 2 ? 256 : 128);
        if (wg == 2 && wu < 3) {
            e_expect(bars + 8 * B_WO, 16384);
            e_tma2d(sb + SM_WO + wu * 16384, tWo, (wu >> 1) * 512 + qd * 128 + (wu & 1) * 64, head * DH, bars + 8 * B_WO);
            e_tma2d(sb + SM_WO + wu * 16384 + 8192, tWo, (wu >> 1) * 512 + qd * 128 + (wu & 1) * 64, head * DH + 64, bars + 8 * B_WO);
        }
        if (wg == 1 && warp0) {
            if (lane == 0) mbar_arrive_cluster(bars + 8 * B_HE, j ^ 1);
            mbar_wait_w(bars + 8 * B_HE, 0);
#pragma unroll 1
            for (int i = 0; i < 2; i++) h_load(sb, hsrc, i, j, head);
        }
        TL(3 + wg)
    }
    const uint32_t mrow = wg < 2 ? mem_row(wu >> 1, wg * 2 + (wu & 1), qd) : mem_row(kh, wu, 0);
    const uint32_t u_m = mrow - wu * 512, u_e = mrow + 512 - wu * 64;
#define TAB(i) lds1(sb + SM_TAB + (i) * 512 + (G16() >> 2))
    {
        const uint32_t r8 = lane & 7;
        const uint32_t tb = sb + SM_TAB + wg * 1536 + t * 4, ma = sb + SM_HB + 4096 + r8 * 128;
        if (wg < 2) {
            sts1(tb, sb + SM_WO + wi * 16384 + frow + ((fx ^ (2 * wg)) << 4));
            sts1(tb + 512, wl0);
            sts1(tb + 1024, ma + (((lane >> 3) ^ r8) << 4));
        } else {
            sts1(tb, ma + (wi & 1) * HBK + ((((wi & 2) + (lane >> 4) * 4 + ((lane >> 3) & 1)) ^ r8) << 4));
            sts1(tb + 512, ((((wi & 2) + 4) ^ r8) << 4) + ((lane & 3) == 2 ? ma + 128 + ((wi & 1) + (lane >> 3) * 2) * HBK : sb + SM_HB - 128));
            sts1(tb + 1024, mem_row(role >> 6, (role >> 4) & 3, (role >> 2) & 3) + (lane < 8 ? qd * 128 + lane * 16 : 512 + qd * 32 + (lane & 1) * 16));
        }
    }
    MISS_INIT
#define HB(ks) dadd(mkdesc(SB0 + SM_HB + ((ks) >> 2) * HBK + ((ks) & 3) * 32, 16, 1024, 1), hbo)
#define STEP_CONSTS                                                                                  \
    const uint32_t tag = (s & 1) ^ 1, ttag = ((s >> 1) & 1) ^ 1, tso = (s & 1) * 32768;              \
    G16();                            \
    const int p = s + 2, b = p & 1;                                                                  \
    uint32_t hbo = b * 4096, fz[5] = {0, 0, 0, 0, 0};                                                   \
    const uint32_t ftag = (((p - 1) >> 1) & 1) ^ 1, ptag = ((p >> 1) & 1) ^ 1;                       \
    const uint32_t pso = tbw + (1 << 20) + (b ^ 1) * 32768 + j * 16384 + kh * 2048;
#define SCHED_FENCE(i) fz[i] = clk32();
#define FZ ((fz[0] | fz[1] | fz[2] | fz[3] | fz[4]) & zero)
#define BLOCK_FENCE asm volatile("pmevent 0;" ::: "memory");
    constexpr int GAP = 32 / NL;
#define l16 (sbl + g16)
#define g8 (g16 >> 1)
    uint4 u, v;
    uint8_t *pdst, *fdst;
    auto tok_pack = [&](int ty, const float* acc, uint32_t ftag, uint32_t ptag, bool later = false) {
        const bool tg = ty == 2 || !(g16 & 64);
        const uint32_t add = tg ? (ftag ^ 1) << 16 : 0u, keep = tg ? 0xfffe0000u : ~0u;
        const uint32_t add1 = ty == 2 ? 0u : add, keep1 = ty == 2 ? ~0u : keep;
        const uint32_t add2 = ty == 0 ? add : 0u, keep2 = ty == 0 ? keep : ~0u;
        v = {pack2(pretag(acc[0], add, keep), pretag(acc[1], add1, keep1)), pack2(acc[2], acc[3]),
             pack2(pretag(acc[4], add2, keep2), pretag(acc[5], add2, keep2)), pack2(acc[6], acc[7])};
        if (ty < 2) { v.x = movm(v.x); v.z = movm(v.z); v.y = movm(v.y); v.w = movm(v.w); }
        u = {pack2(pretag(acc[8], (ptag ^ 1) << 16, 0xfffe0000u), acc[9]) | ptag, pack2(acc[10], acc[11]), pack2(acc[12], acc[13]), pack2(acc[14], acc[15])};
        if (later) return;
        v.x = settag(v.x, ftag);
        if (ty == 0) v.z = settag(v.z, ftag);
    };

#pragma unroll 1
    for (int s = -2; s < 0; s++) {
        STEP_CONSTS
        (void)tag; (void)ttag; (void)tso; (void)fz;
        float acc[16];
        mbar_wait_w(bars + 8 * (B_HB + b), 0);
        wg_fence();
#pragma unroll
        for (int i = 0; i < 32; i++) {
            if (i < NL) wgmma_ss32(acc, dadd(mkdesc(SB0 + i * 2048, 8192, 1024, 1), wg * 4096), HB(i), i != 0);
            else wgmma_rs32(acc, w[i < NL ? 0 : i - NL], HB(i), 1);
        }
        wg_commit();
        uint4 pa = {0, 0, 0, 0};
        int it = 0;
#pragma unroll 1
        while ((p > 0) & any_bit0(pa.x ^ ftag) & (++it < POLL_LIMIT)) pa = ldg_b128(arena + (pso + g16));
        pdst = arena + ((pso ^ (32768 + 2048)) + G16());
        fdst = arena + ((b ^ 1) * 32768 + u_to + g16);
        wg_wait<0>();
#pragma unroll
        for (int k = 0; k < 4; k++) { acc[2 * k] += bflo((&pa.x)[k]); acc[2 * k + 1] += bfhi((&pa.x)[k]); }
        tok_pack(wg, acc, ftag, ptag);
        stg_b128_if(true, pdst, u.x, u.y, u.z, u.w);
        stg_b128_if(p > 0, fdst, v.x, v.y, v.z, v.w);
        if (p == 0) {
            TL(2)
            if (wg != 1) bar_arrive(NB_C, 288);
        }
    }
    if (wg == 1 && warp0) {
        wait_count_w(&g_tick[32 + (lane & 3) * 8], 2);
        asm volatile("fence.proxy.async.global;" ::: "memory");
        bar_sync(NB_C, 288);
        if (g16 == 0) mbar_arrive_cluster(bars + 8 * B_HE, j ^ 1);
        mbar_wait_w(bars + 8 * B_HE, 1);
        h_load(sb, hsrc, 2, j, head);
    }

    auto qk_loop = [&](auto wgc) {
        constexpr int WG = decltype(wgc)::value;
        uint32_t w0[NL][4], lm0;
        auto w0_load = [&]() {
            const uint32_t wl = TAB(WG * 3 + 1);
            lm0 = TAB(WG * 3 + 2);
#pragma unroll
            for (int k = 0; k < NL; k++) ldsm4t(w0[k], wl + k * 2048);
        };
        const uint32_t wlo = WG * 65536 - SM_WO - wu * 16384, wlx = __reduce_max_sync(~0u, (wi ^ WG) << 5);
        uint32_t tq0, lm, lm1;
        auto proj_pre = [&](int s) {
            uint32_t wz0 = zero;
#pragma unroll
            for (int k = 0; k < NL; k += 2) wz0 = and3(wz0, w0[k][0], w0[k + 1 < NL ? k + 1 : k][0]);
            lm = lm0 + (s & 1) * 65536 + wz0; lm1 = lm ^ 64;
            asm volatile("" : "+r"(lm), "+r"(lm1));
        };
        auto proj = [&](int s, auto mid) {
            bar_sync(NB_MEM, 384);
            float c[4][4];
            uint32_t bf[16][4], tq1;
#pragma unroll
            for (int it = 0; it < 3; it++) ldsm4(bf[it], (it & 1 ? lm1 : lm) + (it >> 1) * HBK);
            mid(-1);
#pragma unroll
            for (int it = 0; it < 16; it++) {
                const uint32_t* bfr = bf[it];
                if (it + 3 < 16) ldsm4(bf[it + 3 < 16 ? it + 3 : 0], (it & 1 ? lm : lm1) + ((it + 3) >> 1) * HBK);
                const uint32_t* wa = 2 * it < NL ? w0[2 * it < NL ? 2 * it : 0] : w[2 * it < NL ? 0 : 2 * it - NL];
                const uint32_t* wb = 2 * it + 1 < NL ? w0[2 * it + 1 < NL ? 2 * it + 1 : 0] : w[2 * it + 1 < NL ? 0 : 2 * it + 1 - NL];
                float *ca = c[(2 * it) & 3], *cb = c[(2 * it + 1) & 3];
                if (it < 2) { mma16816z(ca, wa, bfr[0], bfr[1]); mma16816z(cb, wb, bfr[2], bfr[3]); }
                else { mma16816(ca, wa[0], wa[1], wa[2], wa[3], bfr[0], bfr[1]); mma16816(cb, wb[0], wb[1], wb[2], wb[3], bfr[2], bfr[3]); }
                mid(it);
                if (it == 15) { tq1 = clk32(); bar_arrive(NB_QK, 384); }
            }
            const uint32_t xo = u_xo + (G16() >> 1);
            float r[4];
#pragma unroll
            for (int e = 0; e < 4; e++) {
                constexpr float SH = SM_L2E / 64;
                r[e] = WG ? (c[0][e] + c[1][e]) + (c[2][e] + c[3][e]) : fmaf(c[2][e] + c[3][e], SH, (c[0][e] + c[1][e]) * SH);
            }
            const uint32_t r0 = pack2(r[0], r[1]), r1 = pack2(r[2], r[3]);
            const uint32_t m0 = movm(r0), m1 = movm(r1);
            tq0 = clk32();
            stg_rlx2(arena + xo, settag(m0, (s & 1) ^ 1), m1);
            tq0 += tq1 & zero;
        };
        w0_load();
        proj_pre(0);
        if (WG == 1) bar_sync(NB_P, 256);
        proj(0, [](int) {});
        if (WG == 0) mbar_wait_w(bars + 8 * B_WO, 0);
#pragma unroll 1
        for (int s = 0;; s++) {
            STEP_CONSTS
            uint4 pa;
            float acc[16];
            auto acc_init = [&]() {
#pragma unroll
                for (int k = 0; k < 4; k++) { acc[2 * k] = bflo((&pa.x)[k]); acc[2 * k + 1] = bfhi((&pa.x)[k]); acc[8 + 2 * k] = __uint_as_float((&pa.x)[k] & zero); acc[9 + 2 * k] = __uint_as_float(~(&pa.x)[k] & zero); }
            };
            uint32_t wf[NPF][4], a3;
#define WF(f) ((a3 ^ (((f) & 1) * 64)) + ((f) >> 1) * 2048)
            if (WG == 1) {
                float sc[5][4];
                uint32_t sx0 = sb + SM_SX - wu * (2560 - 16) + G16() * 5;
                asm volatile("" : "+r"(sx0));
                int it = 0;
                bool bad;
#pragma unroll 1
                do {
                    uint4 kf[2][2];
                    U2 qf[2], x[8];
                    const uint32_t gz = g16 | (it & zero);
                    const uint8_t *ts = arena + (tso + tbw + gz), *tq = arena + (tso + tbq + gz), *xp = arena + (xso + (gz >> 1));
#pragma unroll
                    for (int a = 0; a < 4; a++) kf[a >> 1][a & 1] = ldg_b128(ts + (a >> 1) * 16384 + (a & 1) * 2048);
                    spin_until(tq0, dly.x2 - 100);
#pragma unroll
                    for (int a = 0; a < 2; a++) qf[a] = ldg_u2(tq + a * 16384);
                    spin_until(tq0, dly.x2);
#pragma unroll
                    for (int i = 0; i < 8; i++) x[i] = ldg_u2(xp + (i >> 2) * 16384 + (i & 3) * 1024);
                    const uint32_t q0[4] = {hadd2(x[0].x, x[1].x), qf[0].x, hadd2(x[0].y, x[1].y), qf[0].y};
                    const uint32_t q1[4] = {hadd2(x[2].x, x[3].x), qf[1].x, hadd2(x[2].y, x[3].y), qf[1].y};
                    const uint32_t bt = ((qf[0].x ^ ttag) | (qf[1].x ^ ttag)) | ((kf[0][0].x ^ ttag) | (kf[0][1].x ^ ttag)) | ((kf[1][0].x ^ ttag) | (kf[1][1].x ^ ttag));
                    uint32_t bx = 0;
#pragma unroll
                    for (int i = 0; i < 8; i += 2) bx |= (x[i].x ^ tag) | (x[i + 1].x ^ tag);
                    mma16816z(sc[0], q0, kf[0][0].x, kf[0][0].y);
                    mma16816z(sc[1], q0, kf[0][0].z, kf[0][0].w);
                    mma16816z(sc[2], q0, kf[0][1].x, kf[0][1].y);
                    mma16816z(sc[3], q0, kf[0][1].z, kf[0][1].w);
                    mma16816z(sc[4], q0, hadd2(x[4].x, x[5].x), hadd2(x[4].y, x[5].y));
                    bad = any_bit0(bt | bx) & (++it < POLL_LIMIT);
                    mma16816(sc[0], q1[0], q1[1], q1[2], q1[3], kf[1][0].x, kf[1][0].y);
                    mma16816(sc[1], q1[0], q1[1], q1[2], q1[3], kf[1][0].z, kf[1][0].w);
                    mma16816(sc[2], q1[0], q1[1], q1[2], q1[3], kf[1][1].x, kf[1][1].y);
                    mma16816(sc[3], q1[0], q1[1], q1[2], q1[3], kf[1][1].z, kf[1][1].w);
                    mma16816(sc[4], q1[0], q1[1], q1[2], q1[3], hadd2(x[6].x, x[7].x), hadd2(x[6].y, x[7].y));
                } while (bad);
                MISS(1, it - 1)
                sts4(sx0, pack_h2(sc[0][0], sc[0][1]), pack_h2(sc[1][0], sc[1][1]), pack_h2(sc[2][0], sc[2][1]), pack_h2(sc[3][0], sc[3][1]));
                sts1(sx0 + 64 - wu * 12, pack_h2(sc[4][0], sc[4][1]));
                bar_arrive(NB_X1, 384);
                auto tok_sts = [&]() {
#pragma unroll
                    for (int n = 0; n < 5; n++) sts2(sb + SM_SX + 2560 + g8 + n * 1088, sc[n][2], sc[n][3]);
                };
                a3 = TAB(WG * 3);
                if (s == 0) mbar_wait_w(bars + 8 * B_WO, 0);
                softmax_rows(sb + SM_SX + 2560, sb + SM_PX + 1024, g16 | (clk32() & zero), qd * 8, [&]() { BLOCK_FENCE tok_sts(); bar_sync(NB_PX, 128); }, [&]() {
                    BLOCK_FENCE
#pragma unroll
                    for (int f = 0; f < NE1; f++) ldsm4t(wf[f], WF(f));
                    BLOCK_FENCE
                });
            } else {
                a3 = TAB(WG * 3);
                if (warp1 && (s & 3) == 1) asm volatile("fence.proxy.async.global;" ::: "memory");
                spin_until(tq0, dly.pa);
                uint4 x, y;
                int it = 0;
#pragma unroll 1
                do { x = ldg_b128(arena + (pso + g16)); y = ldg_b128(arena + (pso + tokbase(1) - tokbase(0) + g16)); }
                while ((p <= NSEG) & any_bit0(xor_or(x.x, y.x, ftag)) & (++it < POLL_LIMIT));
                sts4(sb + SM_PA + g16, x.x, x.y, x.z, x.w);
                sts4(sb + SM_PA + 2048 + g16, y.x, y.y, y.z, y.w);
                bar_sync(NB_X1, 384);
                if (g16 < 32) asm volatile("red.relaxed.gpu.global.max.u32 [%0], %1; red.relaxed.gpu.global.add.u32 [%0+4], 1;"
                                                    ::"l"(arena + ((blk(LB_TIME, 0) ^ (g16 << 8)) + qd * 1024 + (tq0 & zero))), "r"(gtime()) : "memory");
                __syncwarp();
                const uint32_t tx = clk32();
                spin_until(tx, dly.w2);
            }
#pragma unroll
            for (int f = WG ? NE1 : 0; f < NPF; f++) ldsm4t(wf[f], WF(f));
            if (s + 1 == NSEG) { bar_arrive(NB_X2, 384); break; }
            const uint32_t oa = l16 + SM_OX, slot = mem_slot(s + 1);
            float c[4][4];
            uint32_t ob[4][4];
            BLOCK_FENCE
            bar_sync(NB_X2, 384);
            ldsm4t(ob[0], oa);
            ldsm4t(ob[1], oa + 512);
            SCHED_FENCE(0)
#pragma unroll
            for (int f = 0; f < 16; f++) {
                const uint32_t *a = wf[f % NPF], *o = ob[f >> 2] + (f & 2);
                if (f < 4) mma16816z(c[f], a, o[0], o[1]);
                else mma16816(c[f & 3], a[0], a[1], a[2], a[3], o[0], o[1]);
                if (f == 3) ldsm4t(ob[2], oa + 1024);
                if (f == 5) { ldsm4t(ob[3], oa + 1536); if (NPF < 16) ldsm4t(wf[0], WF(NPF)); }
                if (f == 7) {
#pragma unroll
                    for (int k = NPF + 1; k < 16; k++) ldsm4t(wf[k - NPF], WF(k));
                }
                if (f == 3 || f == 5 || f == 7) SCHED_FENCE(f / 2)
                if (f == 11) {
#pragma unroll
                    for (int k = NL - W0_E; k < NL; k++) ldsm4t(w0[k], (a3 ^ wlx) + wlo + k * 2048);
                    SCHED_FENCE(4)
                }
            }
            const float last = c[1][3] + c[3][3], one = __uint_as_float(CNT1 << 16);
            red_mem(arena + (u_m + slot + G16()), pack2(c[0][0] + c[2][0], c[0][1] + c[2][1]), pack2(c[0][2] + c[2][2], c[0][3] + c[2][3]),
                    pack2(c[1][0] + c[3][0], c[1][1] + c[3][1]), pack2(c[1][2] + c[3][2], g16 & 16 ? one : last),
                    arena + (u_e + slot + ((g16 >> 3) & ~3u)), pack2(last, one), g16 & 16);
            hbo += FZ;
            constexpr int NS = NL - W0_RS, GS = (32 - NL + NS) / NS;
            BLOCK_FENCE
#pragma unroll
            for (int k = NL - W0_E - 1; k >= 0; k--) ldsm4t(w0[k], (a3 ^ wlx) + wlo + k * 2048);
            lm0 = TAB(WG * 3 + 2);
            if (WG == 1) pa = lds4(sb + SM_PA + 2048 + g16);
            if (WG == 0) {
                bar_arrive(NB_WIN, 384);
                pa = lds4(sb + SM_PA + g16);
                acc_init();
                asm volatile("" : F16(acc, 0));
                BLOCK_FENCE
            }
            wg_fence();
            bar_sync(WG ? NB_WIN : NB_B, WG ? 384 : 256);
#pragma unroll
            for (int i = 0; i < 32; i++) {
                const int k = i / GS;
                if (i >= 32 - NL + NS) wgmma_rs32(acc, w0[i < 32 - NL + NS ? 0 : i - 32 + NL], HB(i - 32 + NL), 1);
                else if (i % GS == GS - 1 && k < NS) wgmma_ss32(acc, mkdesc(SB0 + WG * 65536 + k * 2048, 8192, 1024, 1), HB(k), 1);
                else wgmma_rs32(acc, w[i - (k < NS ? k : NS)], HB(NL + i - (k < NS ? k : NS)), WG == 0 || i);
                if (WG == 1 && i == G_AT) bar_arrive(NB_B, 256);
                if (WG == 1 && i == 31 - NL + NS) wg_fence();
            }
            wg_commit();
            BLOCK_FENCE
            if (WG == 1 && warp0 && !(s & 3)) wait_count_w(&g_tick[32 + ((G16() >> 4) & 3) * 8], min((s + 1) / 4 + 3, 17));
            auto tok_store = [&](int m) {
                if (m & 1) stg_b128_if(true, arena + ((b ^ 1) * 32768 + u_to + G16()), v.x, v.y, v.z, v.w);
                if (m & 2) stg_b128_if(p < NSEG, arena + ((pso ^ (32768 + 2048)) + G16()), u.x, u.y, u.z, u.w);
            };
            if (WG == 0) proj_pre(s + 1);
            BLOCK_FENCE
            wg_wait<0>();
            if (WG == 0) {
                asm volatile("" : F16(acc, 0));
                proj(s + 1, [&](int it) {
                    if (it < 0) {
                        SCHED_FENCE(0)
                        asm volatile("" : F16(acc, 0));
                        tok_pack(WG, acc, ftag, ptag, true);
                        tok_store(2);
                        SCHED_FENCE(1)
                    }
                    if (it == 2) { SCHED_FENCE(2) v.x = settag(v.x, ftag); v.z = settag(v.z, ftag); tok_store(1); SCHED_FENCE(3) }
                });
                tq0 += (fz[0] | fz[1] | fz[2] | fz[3]) & zero;
            } else {
#pragma unroll
                for (int k = 0; k < 4; k++) { acc[2 * k] += bflo((&pa.x)[k]); acc[2 * k + 1] += bfhi((&pa.x)[k]); }
                tok_pack(WG, acc, ftag, ptag);
                proj_pre(s + 1);
                asm volatile("" : "+r"(u.x), "+r"(u.y), "+r"(u.z), "+r"(u.w), "+r"(v.x), "+r"(v.y), "+r"(v.z), "+r"(v.w));
                BLOCK_FENCE
                bar_sync(NB_P, 256);
                tok_store(3);
                proj(s + 1, [](int) {});
            }
        }
    };
    if (wg == 0) {
        qk_loop(IC<0>());
    } else if (wg == 1) {
        qk_loop(IC<1>());
    } else {
        const uint32_t ONES = 0x3f803f80u, u_o = qd * 65536 + head * 2048 + wu * 384;
        uint32_t tw = 0, dl = 0, dbase = kh == mypar ? dly.near : dly.far, dst0, dx0;
        dst0 = TAB(6); dx0 = TAB(7);
        uint32_t ov[4] = {0, 0, 0, 0};
        auto o_store = [&](int s) {
            uint8_t* od = (uint8_t*)g_O + (uint32_t)(s * (32 * NH * DH * 2) + u_o + (G16() >> 2));
#pragma unroll
            for (int a = 0; a < 4; a++) stg_rlx1(od + a * 128, ov[a]);
        };
        uint4 vf[2][2], pa;
        auto tok_fetch = [&](int s) {
            const uint8_t* ts = arena + ((s & 1) * 32768 + tbw + g16);
#pragma unroll
            for (int a = 0; a < 4; a++) vf[a >> 1][a & 1] = ldg_b128(ts + (a >> 1) * 16384 + (a & 1) * 2048);
            pa = ldg_b128(arena + (tbw + (1 << 20) + (~s & 1) * 32768 + j * 16384 + kh * 2048 + g16));
        };
        tok_fetch(0);
        TL(9)
        TL(6)
#pragma unroll 1
        for (int s = 0;; s++) {
            STEP_CONSTS
#define VFBAD ((vf[0][0].x ^ ttag) | (vf[0][1].x ^ ttag) | (vf[1][0].x ^ ttag) | (vf[1][1].x ^ ttag))
#define TOKBAD (VFBAD | (p <= NSEG ? pa.x ^ ftag : 0))
            {
                const uint32_t dst = dst0 + b * 65536, dx = dx0 + b * 65536;
                const uint8_t *ms = arena + (u_m + mem_slot(s) + g16), *me = arena + (u_e + mem_slot(s) + ((g16 >> 3) & ~3u));
                uint32_t em = g16 & 16 ? 0u : ~0u;
                asm volatile("" : "+l"(ms), "+l"(me), "+r"(em));
                spin_until(tw, dl);
                int it = 0;
                bool bad;
#pragma unroll 1
                do {
                    uint4 m[4];
                    uint32_t x[4];
#pragma unroll
                    for (int i = 0; i < 4; i++) m[i] = ldg_rlx4(ms + i * 1024);
#pragma unroll
                    for (int i = 0; i < 4; i++) x[i] = ldg_rlx1(me + i * 1024);
#pragma unroll
                    for (int i = 0; i < 3; i++) {
                        stsm4t(dst + i * 2 * HBK, m[i].x, m[i].y, m[i].z, m[i].w);
                        if (i == 1) asm volatile("{.reg .pred p; setp.eq.s32 p, %0, 0; @p bar.arrive %1, 256;}" ::"r"(it), "n"(NB_P) : "memory");
                    }
                    uint32_t c = m[0].w & m[1].w, r, msk = ~(it << 16) & CNT_ALL << 16;
                    asm volatile("" : "+r"(c), "+r"(msk));
                    SCHED_FENCE(1)
                    stsm4t(dst + 6 * HBK, m[3].x, m[3].y, m[3].z, m[3].w);
                    stsm4t(dx, x[0], x[1], x[2], x[3]);
                    asm volatile("{.reg .pred p, q; .reg .b32 t, u; lop3.b32 t, %1, %2, %3, 0x80; lop3.b32 u, %4, %5, %6, 0x80; lop3.b32 t, t, %8, %7, 0xa8;\n"
                                 " lop3.b32 t, t, u, %9, 0x2a; setp.ne.u32 p, t, 0; vote.sync.any.pred q, p, 0xffffffff; @!q bar.arrive %10, 384; selp.u32 %0, 1, 0, q;}"
                                 : "=r"(r) : "r"(c), "r"(m[2].w), "r"(m[3].w), "r"(x[0]), "r"(x[1]), "r"(x[2]), "r"(x[3]), "r"(em), "r"(msk), "n"(NB_MEM) : "memory");
                    bad = r; it++;
                } while (bad);
                if (it > 1 && s > 1) dbase += dly.more;
                MISS(0, it - 1) HT(5)
            }
            if (s == 1) { TL(7) TLC(0) }
            if (s == 63) TLC(1)
            if (s == 0) TL(13)
            o_store(max(s - 1, 0));
            fence_async_smem();
            hbo += fz[1] & zero;
            int it = 0;
#pragma unroll 1
            while (any_bit0(TOKBAD) & (++it < POLL_LIMIT)) tok_fetch(s + (it & zero));
            float acc[20];
#pragma unroll
            for (int k = 0; k < 4; k++) { acc[2 * k] = bflo((&pa.x)[k]); acc[2 * k + 1] = bfhi((&pa.x)[k]); acc[8 + 2 * k] = acc[9 + 2 * k] = acc[16 + k] = __uint_as_float(pa.x & zero); }
            if (p <= NSEG) mbar_wait_w(bars + 8 * (B_HB + b), (p >> 1) & 1);
            asm volatile("" : F16(acc, 0), F4(acc, 16));
            BLOCK_FENCE
            wg_fence();
            bar_sync(NB_QK, 384);
#pragma unroll
            for (int i = 0; i < 32; i++) {
                const int k = i / GAP;
                if (i % GAP == GAP - 1 && k < NL) wgmma_ss40(acc, mkdesc(SB0 + 131072 + k * 2048, 8192, 1024, 1), HB(k), 1);
                else wgmma_rs40(acc, w[i - (k < NL ? k : NL)], HB(NL + i - (k < NL ? k : NL)), 1);
            }
            wg_commit();
            uint8_t* vo = arena + (u_xo + (G16() >> 1));
            pdst = arena + ((pso ^ (32768 + 2048)) + G16());
            fdst = arena + ((b ^ 1) * 32768 + u_to + g16);
            BLOCK_FENCE
            wg_wait<0>();
            stg_rlx2(vo, settag(pack2(acc[16], acc[17]), tag), pack2(acc[18], acc[19]));
            const uint32_t tv = clk32();
            tok_pack(2, acc, ftag, ptag);
            stg_b128_if(p <= NSEG, fdst, v.x, v.y, v.z, v.w);
            stg_b128_if(p < NSEG, pdst, u.x, u.y, u.z, u.w);
            const uint8_t* xp = arena + (xso + 32768 + (G16() >> 1));
            const uint32_t sxa = sb + SM_SX - wu * 2560 + G16() * 5;
            uint32_t sel[2];
            {
                const uint32_t q = (G16() >> 4 ^ g16 >> 6 & 1) & 3;
                sel[0] = q == 0 ? 0x3c00 : 0; sel[1] = q == 2 ? 0x3c00 : 0;
                asm volatile("" : "+r"(sel[0]), "+r"(sel[1]));
            }
            uint32_t xv[4], gt = 0;
            auto pv = [&](uint32_t p0, uint32_t p1, uint32_t p2, uint32_t p3, uint32_t p4, auto getv, auto done) {
                float oc[2][4], lc[4] = {0.f, 0.f, 0.f, 0.f};
                mma16816(lc, ONES, ONES, ONES, ONES, p0, p1);
                mma16816z(oc[0], &vf[0][0].x, p0, p1);
                mma16816z(oc[1], &vf[1][0].x, p0, p1);
                mma16816(lc, ONES, ONES, ONES, ONES, p2, p3);
                mma16816(oc[0], vf[0][1].x, vf[0][1].y, vf[0][1].z, vf[0][1].w, p2, p3);
                mma16816(oc[1], vf[1][1].x, vf[1][1].y, vf[1][1].z, vf[1][1].w, p2, p3);
                mma1688(lc, ONES, ONES, p4);
                getv();
                mma1688(oc[0], xv[0], xv[1], p4);
                mma1688(oc[1], xv[2], xv[3], p4);
                done(__float_as_uint(oc[0][0]) | __float_as_uint(oc[1][0]) | __float_as_uint(lc[0]));
                const float r0 = rcp_fast(lc[0]), r1 = rcp_fast(lc[1]);
                ov[0] = pack2(oc[0][0] * r0, oc[0][1] * r1); ov[1] = pack2(oc[0][2] * r0, oc[0][3] * r1);
                ov[2] = pack2(oc[1][0] * r0, oc[1][1] * r1); ov[3] = pack2(oc[1][2] * r0, oc[1][3] * r1);
            };
            bool bad;
            it = 0;
#pragma unroll 1
            do {
                U2 xr[4];
                asm volatile("{.reg .pred p; setp.eq.s32 p, %0, 0; @p bar.sync %1, 384;}" ::"r"(it), "n"(NB_X1) : "memory");
                uint4 sx[5];
#pragma unroll
                for (int i = 0; i < 5; i++) sx[i] = lds4(sxa + i * 16);
                if (it == 0) { gt = gtime(); tw = clk32(); }
                spin_until(tv, dly.v);
#pragma unroll
                for (int i = 0; i < 4; i++) xr[i] = ldg_u2(xp + i * 1024);
                uint32_t h[5], h0[4];
#pragma unroll
                for (int n = 0; n < 4; n++) h0[n] = add_h2((&sx[0].x)[n], (&sx[1].x)[n]);
#pragma unroll
                for (int n = 0; n < 4; n++) h[n] = add_h2(h0[n], add_h2((&sx[2].x)[n], (&sx[3].x)[n]));
                h[4] = add_h2(add_h2(sx[4].x, sx[4].y), add_h2(sx[4].z, sx[4].w));
                uint32_t hm = max_h2(max_h2(max_h2(h[0], h[1]), h[2]), max_h2(h[3], h[4]));
                float2 a[5];
                float mb;
                {
                    float d[2][4];
                    const uint32_t hs = __byte_perm(hm, hm, 0x1032);
#pragma unroll
                    for (int k = 0; k < 2; k++)
                        asm volatile("mma.sync.aligned.m16n8k8.row.col.f32.f16.f16.f32 {%0,%1,%2,%3},{%4,%5},{%6},{%7,%7,%7,%7};"
                                     : "=f"(d[k][0]), "=f"(d[k][1]), "=f"(d[k][2]), "=f"(d[k][3]) : "r"(hm), "r"(hs), "r"(sel[k]), "f"(0.f));
#pragma unroll
                    for (int n = 0; n < 5; n++) a[n] = unpack_h2(h[n]);
                    mb = -64.0f * fmaxf(fmaxf(fmaxf(d[0][0], d[0][1]), fmaxf(d[0][2], d[0][3])), fmaxf(fmaxf(d[1][0], d[1][1]), fmaxf(d[1][2], d[1][3])));
                }
                uint32_t pm[5];
#pragma unroll
                for (int n = 0; n < 5; n++) pm[n] = pack2(ex2(fmaf(a[n].x, 64.0f, mb)), ex2(fmaf(a[n].y, 64.0f, mb)));
                pv(pm[0], pm[1], pm[2], pm[3], pm[4], [&]() {
                    xv[0] = hadd2(xr[0].x, xr[1].x); xv[1] = hadd2(xr[0].y, xr[1].y);
                    xv[2] = hadd2(xr[2].x, xr[3].x); xv[3] = hadd2(xr[2].y, xr[3].y);
                }, [](uint32_t) {});
                bad = any_bit0((xr[0].x ^ tag) | (xr[1].x ^ tag) | (xr[2].x ^ tag) | (xr[3].x ^ tag)) & (++it < POLL_LIMIT);
                stsm4(sb + SM_OX + g16, ov[0], ov[1], ov[2], ov[3]);
            } while (bad);
                MISS(2, it - 1)
            bar_sync(NB_X2, 384);
            BLOCK_FENCE
            U2 tv2 = {0, 0};
            const uint8_t* tp = arena + (blk(LB_TIME, mypar) + ((G16() << 6) & 0xc00));
            {
                const uint4 pp = lds4(l16 + SM_PX + 1024);
                const uint32_t p4 = lds1(sb + SM_PX + 512 + 1024 - wu * 128 + (G16() >> 2));
                tv2 = ldg_u2(tp);
                if (warp0 && s + 3 <= NSEG) h_load(sb, hsrc, s + 3, j, head);
                pv(pp.x, pp.y, pp.z, pp.w, p4, []() {}, [&](uint32_t r) { bar_arrive(NB_WIN + (r & zero), 384); });
            }
            dst0 = TAB(6); dx0 = TAB(7);
            const uint32_t zo = TAB(8);
                HT(7)
            BLOCK_FENCE
            if (s + 1 == NSEG) break;
            asm volatile("" : "+r"(tv2.y));
            it = 0;
            uint32_t tm = __reduce_max_sync(~0u, tv2.y < 32 * (s + 1) ? ~0u : tv2.x);
#pragma unroll 1
            while ((tm == ~0u) & (++it < 16)) { tv2 = ldg_u2(tp); tm = __reduce_max_sync(~0u, tv2.y < 32 * (s + 1) ? ~0u : tv2.x); }
            const uint32_t e = tm - gt;
            MISS(3, it - 1) MISS(4, gt)
            tok_fetch(s + 1);
            stg4_if(g16 < 160, arena + (zo + mem_slot(s + 3)), 0);
            dl = dbase + (e > 4096 ? 0 : e * E_MUL >> 4);
        }
        o_store(NSEG - 1);
        TL(8)
    }
    MISS_OUT
}

struct RecMaps { CUtensorMap wq, wk, wv, wo, wmod, w3, w1; };
struct RecPtrs { const bf16 *x, *mem0, *c, *wmod, *w1, *w3; uint8_t* arena; uint32_t zero; const bf16 *w2, *w4, *wo; Delays dly; };

__device__ __forceinline__ float silu_bf(const bf16* c, int i) {
    const float v = __bfloat162float(c[i]);
    return bfround(__fdividef(v, 1.0f + __expf(-v)));
}
#define LN_FREE 6
#define LN_SEQ 0xcba6420987531ull
#define W_LATE 1000
#define W_OPEN 1400
__device__ __noinline__ uint32_t side_window_(const uint8_t* arena, uint32_t n);
#define side_window(arena, n) n = side_window_(arena, n)
__device__ __noinline__ void rec_ln(uint32_t sb, const bf16* x, const uint8_t* arena, int id, int r0) {
    int r1 = 32;
    uint32_t n = 0;
    const int tid = threadIdx.x, lane = tid & 31, wid = __reduce_max_sync(~0u, tid >> 5);
    const uint32_t ring = sb + wid * 8192 + lane * 16, coef = sb + SM_PRE;
    x += (id * 8 + wid) * 2 * DM + lane * 8;
#pragma unroll 1
    for (int r = r0 - 1; r < r1; r++) {
        if (r > 3) side_window(arena, n);
        if (r + 1 < r1) {
#pragma unroll
            for (int i = 0; i < 8; i++)
                asm volatile("cp.async.cg.shared.global [%0], [%1], 16;" ::"r"(ring + (~r & 1) * 4096 + i * 512), "l"(x + (r + 1) * 64 * DM + i * 256) : "memory");
        }
        asm volatile("cp.async.commit_group; cp.async.wait_group 1;" ::: "memory");
        if (r < r0) continue;
        const uint32_t src = ring + (r & 1) * 4096;
        float m[2] = {0.f, 0.f}, rs[2];
#pragma unroll 1
        for (int ps = 0; ps < 2; ps++) {
            float t[2][2] = {{0.f, 0.f}, {0.f, 0.f}};
#pragma unroll 1
            for (int i = 0; i < 2048; i += 512) {
#pragma unroll
                for (int h = 0; h < 2; h++) {
                    const uint4 u = lds4(src + h * 2048 + i);
#pragma unroll
                    for (int e = 0; e < 4; e++) {
                        const float a = bflo((&u.x)[e]) - m[h], c = bfhi((&u.x)[e]) - m[h];
                        t[h][0] = fmaf(a, ps ? a : 1.0f, t[h][0]); t[h][1] = fmaf(c, ps ? c : 1.0f, t[h][1]);
                    }
                }
            }
            rs[0] = t[0][0] + t[0][1]; rs[1] = t[1][0] + t[1][1];
#pragma unroll 1
            for (int o = 16; o; o >>= 1) { rs[0] += __shfl_xor_sync(~0u, rs[0], o); rs[1] += __shfl_xor_sync(~0u, rs[1], o); }
            if (!ps) { m[0] = rs[0] * (1.0f / DM); m[1] = rs[1] * (1.0f / DM); }
        }
        rs[0] = rsqrtf(rs[0] * (1.0f / DM) + 1e-5f); rs[1] = rsqrtf(rs[1] * (1.0f / DM) + 1e-5f);
        if (r == r0) {
#pragma unroll 1
            for (int i = tid; i < 2 * DM / 4; i += 256) {
                float t[4];
                int it = 0;
                uint32_t ok;
#pragma unroll 1
                do {
                    uint4 u[8];
#pragma unroll
                    for (int k = 0; k < 8; k++) u[k] = ldg_rlx4(g_modp + k * 2 * DM + i * 4);
                    ok = 1;
#pragma unroll
                    for (int k = 0; k < 32; k++) { const uint32_t w = (&u[k >> 2].x)[k & 3]; ok &= w; t[k & 3] = k < 4 ? __uint_as_float(w) : t[k & 3] + __uint_as_float(w); }
                } while (!__all_sync(~0u, ok) & (++it < SPIN_LIMIT));
                const float o = i >> 8;
                const uint32_t lo = pack2(t[0], t[1]), hi = pack2(t[2], t[3]);
                sts4f(coef + (i >> 8) * 4096 + (i & 1) * 2048 + ((i & 255) >> 1) * 16, bflo(lo) + o, bfhi(lo) + o, bflo(hi) + o, bfhi(hi) + o);
            }
            bar_sync(NB_FIN0, 256);
            if (tid == 0 && r0 == 0) TL(2)
        }
        uint8_t* dst = (uint8_t*)g_himg + (r * 2 + (id >> 1)) * 65536 + (lane >> 3) * 4096 + wid * 256;
#pragma unroll 1
        for (int i = 0; i < 4; i++) {
            const uint32_t ca = coef + i * 512 + lane * 16;
            const float4 s0 = lds4f(ca), s1 = lds4f(ca + 2048), c0 = lds4f(ca + 4096), c1 = lds4f(ca + 6144);
            const float sh[8] = {s0.x, s0.y, s0.z, s0.w, s1.x, s1.y, s1.z, s1.w}, sc[8] = {c0.x, c0.y, c0.z, c0.w, c1.x, c1.y, c1.z, c1.w};
#pragma unroll
            for (int h = 0; h < 2; h++) {
                uint4 u = lds4(src + h * 2048 + i * 512);
#pragma unroll
                for (int e = 0; e < 4; e++) {
                    uint32_t& w = (&u.x)[e];
                    w = pack2(fmaf((bflo(w) - m[h]) * rs[h], sc[2 * e], sh[2 * e]), fmaf((bfhi(w) - m[h]) * rs[h], sc[2 * e + 1], sh[2 * e + 1]));
                }
                *(uint4*)(dst + i * 16384 + ((id & 1) == (i >> 1) ? 65536 : 2048) + h * 128 + (((lane ^ (2 * wid + h)) & 7) << 4)) = u;
            }
        }
        if (r == 0) {
            if (tid == 0) TLX(10)
            int ro, it = 0;
#pragma unroll 1
            do asm volatile("ld.volatile.shared.u32 %0, [%1];" : "=r"(ro) : "r"(sb + SM_BAR + 192) : "memory"); while ((ro == INT_MIN) & (++it < SPIN_LIMIT));
            if (ro >= 0) r1 = 2;
        }
        if (r && !(r & 1)) continue;
        bar_sync(r ? NB_FIN0 : NB_C, r ? 256 : 320);
        if (tid == 0 && r == 0) TLX(11)
        if (wid == (r >> 1 & 7)) {
            if (r == 1) bar_arrive(NB_B, 64);
            if (r == 3) wait_count_w(&g_tick[32 + id * 8], 2);
            if (lane == 0) { signal_count(&g_tick[32 + id * 8]); if (r == 0) TLX(12) }
            __syncwarp();
        }
    }
}
__device__ __noinline__ uint32_t side_window_(const uint8_t* arena, uint32_t n) {
    U2 v;
    int it = 0;
#pragma unroll 1
    while (v = ldg_u2(arena + (LB_TIME << 13)), ((v.y >> 5) == n || gtime() - v.x > W_OPEN + W_LATE) && v.y < 32 * NSEG && ++it < 64) __nanosleep(100);
    it = 0;
#pragma unroll 1
    while ((int)(gtime() - v.x - W_OPEN) < 0 && ++it < 256) {}
    return v.y >> 5;
}
#define SIDE_T 300
template <int NQ, int NB>
__device__ __forceinline__ void side_gemv(const CUtensorMap* tm, int c0, int k0, int k1, uint32_t cs, uint32_t sb, const uint8_t* arena, uint32_t& n, uint32_t& ph, float (*acc)[8], bool once = false) {
    const uint32_t w = __reduce_max_sync(~0u, threadIdx.x >> 5 & 3), ring = sb + (NB == 3 ? 65536 : 0) + w * NB * 8192;
    const uint32_t bars = sb + SM_BAR + (NB == 3 ? 8 * B_W + w * 24 : 8 + w * 8), bs = NB == 3 ? 8 : 0;
#pragma unroll
    for (int q = 0; q < NQ; q++)
#pragma unroll
        for (int j = 0; j < 8; j++) acc[q][j] = 0.f;
#pragma unroll 1
    for (; k0 < k1; k0 += NB * 16, ph ^= 1) {
        const int nr = min(NB * 16, k1 - k0);
        side_window(arena, n);
        const uint32_t t0 = clk32();
#pragma unroll 1
        for (int g = 0; g < NB; g++) {
            spin_until(t0, (g * 4 + w) * (SIDE_T / 4));
            if (bs || !g) e_expect(bars + bs * g, !bs ? NB * 8192 : g * 16 < nr ? 8192 : 0);
            if (g * 16 < nr) e_tma2d_hint(ring + g * 8192, tm, c0, k0 + g * 16, bars + bs * g, once ? EVICT_FIRST : EVICT_NORMAL);
        }
#pragma unroll 1
        for (int r = 0; r < nr; r += 16) {
            mbar_wait_w(bars + bs * (r >> 4), ph);
            uint4 v[16];
#pragma unroll
            for (int h = 0; h < 16; h++) v[h] = lds4(ring + (r + h) * 512 + (threadIdx.x & 31) * 16);
            float4 cf[NQ][4];
#pragma unroll
            for (int q = 0; q < NQ * 4; q++) cf[q >> 2][q & 3] = lds4f(cs + ((q >> 2) * DM + k0 + r + (q & 3) * 4) * 4);
#pragma unroll
            for (int h = 0; h < 16; h++) {
                const float f[8] = {bflo(v[h].x), bfhi(v[h].x), bflo(v[h].y), bfhi(v[h].y), bflo(v[h].z), bfhi(v[h].z), bflo(v[h].w), bfhi(v[h].w)};
#pragma unroll
                for (int q = 0; q < NQ; q++)
#pragma unroll
                    for (int j = 0; j < 8; j++) acc[q][j] = fmaf((&cf[q][h >> 2].x)[h & 3], f[j], acc[q][j]);
            }
        }
        fence_async_smem();
        __syncwarp();
    }
}
__device__ __noinline__ void rec_side(float* sm, const RecMaps& mp, const RecPtrs& p, int id) {
    const int tid = threadIdx.x, t = tid & 127, w = __reduce_max_sync(~0u, t >> 5);
    float* coef = sm + (tid < 256 ? 44032 : 40960);
    const uint32_t sb = smem_u32(sm), cs = smem_u32(coef);
    uint32_t n = 0, ph = 0;
    float acc[3][8];
    if (tid < 256) {
        if (blockIdx.x < 128) rec_ln(smem_u32(sm), p.x, p.arena, id, 2);
        if (tid == 0) TL(14)
        for (int i = tid; i < 2 * S_; i += 256) g_st[id * 2 * S_ + i] = 0.f;
        if (id == 0 && tid < 64) g_pcnt[tid * 8] = 0;
        if (id == 1) for (int i = tid; i < 6 * 256; i += 256) g_pflag[i] = 0;
        if (id == 2 && tid == 0) g_pt = 0;
        fence_async_smem();
        bar_sync(NB_FIN0, 256);
        if (PDL && tid == 0) asm volatile("fence.acq_rel.gpu; griddepcontrol.launch_dependents;" ::: "memory");
        if (tid >= 128) return;
        float* red = coef + 3 * DM;
        if (t == 0) wait_count1(&g_tick[8], 4);
        bar_sync(NB_S, 128);
        for (int i = t; i < DM; i += 128) { coef[i] = 1.0f + __ldcg(g_mod + 4 * DM + i); coef[DM + i] = __ldcg(g_mod + 3 * DM + i); coef[2 * DM + i] = 1.0f; }
        bar_sync(NB_S, 128);
        if (id == 1 && t < 32) {
            float u[5] = {0, 0, 0, 0, 0};
            for (int i = t; i < DM; i += 32) {
                const float a = coef[i], b = coef[DM + i];
                u[0] += a; u[1] += a * a; u[2] += a * b; u[3] += b; u[4] += b * b;
            }
#pragma unroll
            for (int q = 0; q < 5; q++) { const float r = warp_sum(u[q]); if (t == 0) g_cst[q] = r * (1.0f / DM); }
        }
        side_gemv<3, 2>(&mp.w1, id * 256, w * 256, w * 256 + 256, cs, sb, p.arena, n, ph, acc);
#pragma unroll
        for (int q = 0; q < 3; q++)
#pragma unroll
            for (int j = 0; j < 8; j++) red[((t >> 5) * 3 + q) * 256 + (t & 31) * 8 + j] = acc[q][j];
        bar_sync(NB_S, 128);
        for (int i = t; i < 768; i += 128) g_vec[(i >> 8) * DM + id * 256 + (i & 255)] = (red[i] + red[768 + i]) + (red[1536 + i] + red[2304 + i]);
        if (tid == 0) TL(6)
        return;
    }
    for (int i = t; i < DM; i += 128) { coef[i] = silu_bf(p.c, i); coef[2 * DM + i] = 1.0f; }
    if (t == 0) wait_count1(&g_tick[32], 1);
    bar_sync(NB_G, 128);
    side_gemv<1, 3>(&mp.wmod, (2 + id) * DM + w * 256, 0, DM, cs, sb, p.arena, n, ph, acc, true);
#pragma unroll
    for (int j = 0; j < 8; j++) g_mod[(2 + id) * DM + t * 8 + j] = bfround(acc[0][j]);
    bar_sync(NB_G, 128);
    if (t == 0) signal_count(&g_tick[8]);
    side_gemv<1, 3>(&mp.w3, id * (FF / 4) + w * 256, 0, DM, cs + 8 * DM, sb, p.arena, n, ph, acc);
    if (t < FF / 32) {
#pragma unroll
        for (int j = 0; j < 8; j++) g_vec[3 * DM + id * (FF / 4) + t * 8 + j] = acc[0][j];
    }
    if (t == 0) TL(9)
}

__global__ void __cluster_dims__(2, 1, 1) __launch_bounds__(384, 1)
k_rec(const __grid_constant__ RecMaps mp, const __grid_constant__ RecPtrs p) {
    extern __shared__ uint8_t smraw[];
    const uint32_t sb = smem_u32(smraw);
    if ((sb & 0x3FFFF) != SB0) __trap();
    const uint32_t bars = sb + SM_BAR;
    const int tid = threadIdx.x, lane = tid & 31, b = blockIdx.x;
    const int wid = __reduce_max_sync(~0u, tid >> 5);
    const uint32_t rank = b & 1;
    uint8_t* arena = p.arena;
    volatile int* sinfo = (volatile int*)(smraw + SM_BAR + 192);
    if (tid == 0) TL(0)
    if (tid == 0) sinfo[0] = INT_MIN;
    if (tid == 352) {
        for (int i = 0; i < 17; i++) mbar_init(bars + 8 * i, i == B_WO ? 4 : 1);
        asm volatile("fence.mbarrier_init.release.cluster;" ::: "memory");
    }
    __syncwarp();
    asm volatile("barrier.cluster.arrive.relaxed.aligned;" ::: "memory");
    int pr = 0, hA = 0;
    if (wid < 8) {
        if (b < 128) {
            const int cb = (b & 15) * 128, k0 = (b >> 4) * 128 + (tid >> 4);
            uint4 v[8];
#pragma unroll
            for (int i = 0; i < 8; i++) v[i] = __ldg((const uint4*)(p.wmod + (size_t)(k0 + 16 * i) * (6 * DM) + cb + (tid & 15) * 8));
            float acc[8] = {0, 0, 0, 0, 0, 0, 0, 0};
            const float s8 = silu_bf(p.c, k0 + 16 * (lane & 7));
#pragma unroll
            for (int i = 0; i < 8; i++) {
                const float sv = __shfl_sync(~0u, s8, i, 16);
                acc[0] += sv * bflo(v[i].x); acc[1] += sv * bfhi(v[i].x); acc[2] += sv * bflo(v[i].y); acc[3] += sv * bfhi(v[i].y);
                acc[4] += sv * bflo(v[i].z); acc[5] += sv * bfhi(v[i].z); acc[6] += sv * bflo(v[i].w); acc[7] += sv * bfhi(v[i].w);
            }
            float* red = (float*)(smraw + SM_PRE);
            *(float4*)(red + (tid >> 4) * 128 + (tid & 15) * 8) = make_float4(acc[0], acc[1], acc[2], acc[3]);
            *(float4*)(red + (tid >> 4) * 128 + (tid & 15) * 8 + 4) = make_float4(acc[4], acc[5], acc[6], acc[7]);
            bar_sync(NB_FIN0, 256);
            if (wid < 4) {
                float t = 0;
#pragma unroll
                for (int i = 0; i < 16; i++) t += red[i * 128 + tid];
                stg_rlx1(&g_modp[(b >> 4) * 2 * DM + cb + tid], __float_as_uint(t) | 1u);
                TLX(14)
            }
        } else {
            rec_ln(sb, p.x, p.arena, b - 128, 0);
        }
    } else if (wid >= 10 && b >= 128) {
        {
            const int w = (b - 128) * 2 + wid - 10;
            const uint16_t* src = (const uint16_t*)p.mem0 + (lane & 3) * 2 * DM + (w >> 2) * 512 + (w & 1) * 64 + (w & 2) * 8 + (lane >> 2);
            uint32_t v[4][4];
#pragma unroll
            for (int i = 0; i < 16; i++) v[i >> 2][i & 3] = src[(i >> 2) * 128 + (i & 2) * 16 + (i & 1) * 8] | ((uint32_t)src[DM + (i >> 2) * 128 + (i & 2) * 16 + (i & 1) * 8] << 16);
            uint8_t* d = arena + mem_row(w >> 2, w & 3, 0);
            uint8_t* e = d + 512 + (lane >> 1) * 4;
            d += lane * 16;
#pragma unroll
            for (int i = 0; i < 4; i++, d += 1024, e += 1024) {
                stg_rlx4(d, v[i][0], v[i][1], v[i][2], lane & 1 ? (v[i][3] & 0xffff) | CNT_ALL << 16 : v[i][3]);
                stg_rlx4(d + mem_slot(1), 0, 0, 0, 0);
                stg_rlx4(d + mem_slot(2), 0, 0, 0, 0);
                if (lane & 1) { stg_rlx1(e, v[i][3] >> 16 | CNT_ALL << 16); stg_rlx1(e + mem_slot(1), 0); stg_rlx1(e + mem_slot(2), 0); }
            }
            if (w == 0 && lane < 8) stg_rlx2(arena + (LB_TIME << 13) + lane * 1024, 0, 0);
            bar_arrive(NB_C, 320);
        }
    } else if (rank == 0) {
        uint32_t best = ~0u;
        const int pg = wid < 10 ? 0 : 1 + (b >> 1) / 22;
        uint32_t* q = (uint32_t*)(arena + (pg << 21) + (pg ? blk(b >> 1, wid & 1) : blk(LB_PROBE, wid & 1) + b * 16));
        if (lane < 8) stg_rlx1(q + lane, 0);
        __syncwarp();
        if (lane == 0) {
            q += 3;
            uint32_t v = p.zero;
#pragma unroll 1
            for (int r = v; r <= NPROBE; r++) {
                const uint32_t t0 = clk32() + (v >> 8);
                v = atomicAdd(q + (v >> 8), 1u);
                uint32_t t1;
                asm volatile("{.reg .pred p; setp.eq.u32 p, %1, 0xffffffff; @p exit; mov.u32 %0, %%clock;}" : "=r"(t1) : "r"(v) : "memory");
                best = min(best, t1 - t0);
            }
            sinfo[wid - 6] = best;
        }
        bar_sync(NB_KDONE, b < 128 ? 128 : 64);
        if (tid == 256) {
            const uint32_t par = sinfo[2] > sinfo[3], vote = b < 128 && (sinfo[4] > sinfo[5]) != par;
            stg_rlx2(&g_clk[b >> 1], ((clk32() - 2 * gtime()) & ~127u) | b >> 1, 1 + 2 * par + 4 * vote);
        }
    }
    if (wid == 8) {
        U2 v[3], my;
        uint32_t c0;
        const int me = b >> 1;
        int it = 0;
        __syncwarp();
#pragma unroll 1
        do {
            my = ldg_u2(&g_clk[me]);
#pragma unroll
            for (int k = 0; k < 3; k++) v[k] = ldg_u2(&g_clk[k * 22 + min(lane, 21)]);
        } while (!__all_sync(~0u, my.y & v[0].y & v[1].y & v[2].y & 1) & (++it < SPIN_LIMIT));
        TLX(15)
        c0 = __reduce_min_sync(~0u, lane ? ~0u : v[0].x) - 4096;
        const uint32_t mc = me >= 64 ? ~0u : my.x - c0;
        const int par = my.y >> 1 & 1;
        uint32_t cnt = 0, flip = 0;
#pragma unroll
        for (int k = 0; k < 3; k++) {
            const uint32_t c = v[k].x - c0, o = v[k].y >> 1 & 1;
            const bool ln = k == 2 && lane >= 20;
            cnt += o + (o == par ? (ln ? 44 + lane < me : c < mc) * 256 + (c < my.x - c0) * 65536 : 0);
            flip |= __popc(__ballot_sync(~0u, v[k].y & 4) & 0x3fffff) > 10 ? 256 << k : 0;
        }
        cnt = __reduce_add_sync(~0u, lane < 22 ? cnt : 0);
        const int n1 = cnt & 255, n0 = 66 - n1, tk = cnt >> 8 & 255;
        if (lane == 0) g_cls[smid() & 255] = cnt < 32 << 16 ? par * 4 + (cnt >> 19) : 8;
        hA = min(n0 >> 1, NH);
        const int q0 = 2 * hA, q1 = 2 * NH - q0;
        const int over = tk - (par ? q1 : q0), lack = max(par ? q0 - n0 : q1 - n1, 0);
        if (over < 0) pr = par ? q0 + tk : tk;
        else if (over < lack) pr = (par ? n0 : q0 + n1) + over;
        else pr = -1 - (over - lack + (par ? max(n0 - q0, 0) : 0));
        hA |= flip;
        if (lane == 0) {
            sinfo[1] = hA; sinfo[0] = pr;
            if (b >= 128 && rank == 0) atomicOr(&g_tick[6], (pr < 0 ? 4u : 1u) << ((b - 128) >> 1));
        }
    }
    asm volatile("barrier.cluster.wait.aligned;" ::: "memory");
    if (wid == 8) {
        TL(1)
        __syncwarp();
        bar_arrive(NB_A, 288);
        bar_arrive(NB_S, 128);
        if (b >= 128 && pr < 0) bar_sync(NB_B, 64);
        if (pr >= 0) {
            const int pu = __reduce_max_sync(~0u, pr), c0 = (pu >> 1) * 128 + rank * 64, r0 = (pu & 1) * 512;
#pragma unroll 1
            for (int n = 0; n < 13; n++) {
                const u64 seq = b >= 128 ? LN_SEQ : 0xcba9876543210ull;
                const int i = seq >> (4 * n) & 15;
                if (b >= 128 && i == 0) bar_sync(NB_B, 64);
                if (n >= W_INFL && (b < 128 || n < LN_FREE)) mbar_wait_w(bars + 8 * (B_W + (seq >> (4 * (n - W_INFL)) & 15)), 0);
                const int m = i < 8 ? i & 1 : i >> 2, k = i < 8 ? i >> 1 : i & 3;
                const uint32_t dst = sb + m * 65536 + k * 16384, br = bars + 8 * (m < 3 ? B_W + i : B_WO);
                const int c = m < 3 ? c0 : 576 + rank * 256 + (pu & 1) * 128, r = m < 3 ? r0 + k * 128 : (pu >> 1) * DH;
                const uint64_t pol = m < 3 ? EVICT_FIRST : EVICT_NORMAL;
                e_expect(br, 16384);
                e_tma2d_hint(dst, &mp.wq + m, c, r, br, pol);
                e_tma2d_hint(dst + 8192, &mp.wq + m, c, r + 64, br, pol);
            }
        }
    } else {
        bar_sync(wid < 8 ? NB_A : NB_S, wid < 8 ? 288 : 128);
    }
    const int prr = __reduce_max_sync(~0u, sinfo[0]);
    hA = __reduce_max_sync(~0u, sinfo[1]);
    if (prr < 0) {
        int j = (b - 128) >> 1;
        if (b < 128) {
            uint32_t v;
            int it = 0;
#pragma unroll 1
            do { v = __reduce_max_sync(~0u, ldg_rlx1(&g_tick[6])); spin_guard(++it); } while (__popc(v) < 2);
            j = v == 3 ? -1 - prr : (v & 1) ^ 1;
        }
        rec_side((float*)smraw, mp, p, j * 2 + rank);
        return;
    }
    if (PDL) asm volatile("griddepcontrol.launch_dependents;" ::: "memory");
    const int role = (prr >> 1) * 4 + rank * 2 + (prr & 1);
    rec_main(sb, &mp.wo, arena, role, hA, wid >> 2, p.zero, p.dly);
}

__device__ __forceinline__ void wgmma_ss192(float* d, uint64_t a, uint64_t b, int sc) {
    asm volatile("{.reg .pred p; setp.ne.b32 p, %98, 0;\n wgmma.mma_async.sync.aligned.m64n192k16.f32.bf16.bf16 "
                 "{%0,%1,%2,%3,%4,%5,%6,%7,%8,%9,%10,%11,%12,%13,%14,%15,%16,%17,%18,%19,%20,%21,%22,%23,%24,%25,%26,%27,%28,%29,%30,%31,%32,%33,%34,%35,%36,%37,%38,%39,%40,%41,%42,%43,%44,%45,%46,%47,%48,%49,%50,%51,%52,%53,%54,%55,%56,%57,%58,%59,%60,%61,%62,%63,%64,%65,%66,%67,%68,%69,%70,%71,%72,%73,%74,%75,%76,%77,%78,%79,%80,%81,%82,%83,%84,%85,%86,%87,%88,%89,%90,%91,%92,%93,%94,%95}, %96, %97, p, 1, 1, 0, 1;}"
                 : F16(d, 0), F16(d, 16), F16(d, 32), F16(d, 48), F16(d, 64), F16(d, 80) : "l"(a), "l"(b), "r"(sc));
}

constexpr uint32_t P_B = 81920, P_PL = 40960, P_OUT = 180224, P_VEC = 212992, P_ROW = P_VEC + 6144, P_BAR = P_ROW + 4096, P_SMEM = P_BAR + 256;
#define PPH 1
#define FLAG_ST "st.release.gpu.global.u32"
#define FLAG_LD "ld.acquire.gpu.global.u32"
constexpr int ST = 5;
constexpr int PB_F = 0, PB_E = 5, PB_R = 10, PB_OUT = 16;
enum { C_Y = 0, C_G = 1, C_X1 = 2, C_U = 3, C_S1 = 8, C_S3 = 9 };
enum { V_GA = 0, V_A = 1, V_B = 2, V_GB = 3, V_VA = 4, V_VB = 5, V_VC = 6, V_C3 = 7 };
struct PostMaps { CUtensorMap o, wo, y, w1, g, w2, x1, w3, u, w4, out; };
struct PostPtrs { const bf16* x; };

struct GeluK { float k0, k1, kh; };
__device__ __forceinline__ GeluK gelu_k(float c) { return {0.7978845608028654f * c, 0.7978845608028654f * 0.044715f * c * c * c, 0.5f * c}; }
__device__ __forceinline__ float gelu_s(float t, const GeluK& k) {
    const float u = t * fmaf(t * t, k.k1, k.k0);
    float th; asm("tanh.approx.f32 %0, %1;" : "=f"(th) : "f"(u));
    const float hx = k.kh * t;
    return fmaf(hx, th, hx);
}
__device__ __forceinline__ float2 ldsv(uint32_t a) {
    float2 v; asm("ld.shared.v2.f32 {%0,%1}, [%2];" : "=f"(v.x), "=f"(v.y) : "r"(a)); return v;
}
__device__ __forceinline__ void wait_smem(uint32_t a, int target) {
    int it = 0;
#pragma unroll 1
    while (true) {
        int v;
        asm volatile("ld.acquire.cta.shared.u32 %0, [%1];" : "=r"(v) : "r"(a) : "memory");
        if (__all_sync(~0u, v >= target) | (++it > SPIN_LIMIT)) break;
    }
}

#define PP(i)
#define PH_(c, w, i)
__device__ __forceinline__ void release(uint32_t rel, int st, bool c) {
    asm volatile("{.reg .pred p; setp.ne.u32 p, %1, 0; setp.ne.and.u32 p, %2, 0, p; @p mbarrier.arrive.shared::cluster.b64 _, [%0];}"
                 ::"r"(rel + 8 * (st ? st - 1 : ST - 1)), "r"(rel), "r"((uint32_t)c) : "memory");
}
struct Pipe { int st, ph; uint32_t rel; };
__device__ __forceinline__ void adv(Pipe& p) { if (++p.st == ST) { p.st = 0; p.ph ^= 1; } }

__device__ __forceinline__ void post_weights(uint32_t sb, const PostMaps& mp, int nb, int rank) {
    const uint32_t full = sb + P_BAR + 8 * PB_F, empty = sb + P_BAR + 8 * PB_E;
    int st = 0, pp = 1;
#pragma unroll 1
    for (int ph = 0; ph < 7; ph++) {
        const int NK = ph == 0 ? 64 : ph == 6 ? 56 : 16, km = NK == 16 ? 15 : 63;
        const CUtensorMap* tb = &mp.wo + 2 * (ph < 3 ? ph : ph < 6 ? 3 : 4);
        const bool w3 = ph >= 3 && ph < 6;
        const int n0 = w3 ? nb * 64 + (ph == 4 ? 1536 : ph == 5 ? 2560 : 0) : nb * 128, dn = w3 ? 512 : 64;
        const int rot = NK == 16 ? 2 * (nb & 6) : 0, sw = ph == 1 || ph == 3 ? 2 * rank : 0;
#pragma unroll 1
        for (int i = 0; i < NK; i++) {
            const int k0 = (((i < 4 ? i ^ sw : i) + rot) & km) * 64;
            const uint32_t a = sb + P_B + st * 8192, f = full + 8 * st;
            mbar_wait_w(empty + 8 * st, pp);
            e_expect(f, ph == 3 ? 40960 : 32768);
            e_tma2d(a, tb, n0, k0, f);
            e_tma2d(a + P_PL, tb, n0 + dn, k0, f);
            if (ph == 3) e_tma2d(a + 2 * P_PL, tb, n0 + 1024, k0, f);
            if (++st == ST) { st = 0; pp ^= 1; }
        }
    }
#pragma unroll 1
    for (int i = 0; i < ST; i++) mbar_wait_w(empty + 8 * i, pp ^ (i < st));
}
__device__ __forceinline__ void post_acts(uint32_t sb, const PostMaps& mp, int mb, int nb, int rank) {
    const int rh = 2 * mb + rank, lane = threadIdx.x & 31;
    const uint32_t bars = sb + P_BAR;
    int st = 0, pp = 1;
#pragma unroll 1
    for (int ph = 0; ph < 7; ph++) {
        const int NK = ph == 0 ? 64 : ph == 6 ? 56 : 16, km = NK == 16 ? 15 : 63;
        const CUtensorMap* ta = &mp.o + 2 * (ph < 3 ? ph : ph < 6 ? 3 : 4);
        const int amul = ph == 0 ? 256 : 64, arow = (ph == 0 ? rh * 8 : rh * 64) - 2, rot = NK == 16 ? 2 * (nb & 6) : 0;
        const bool own = ph == 1 || ph == 3;
        const uint32_t shifts = ph == 2 ? 0x04000301u : 0x02020202u;
        const uint32_t* fl = &g_pflag[(ph == 6 ? C_U : min(ph - 1, 2)) * 256 + (ph == 2 ? min(max(rh + min(lane >> 3, 2) - 1, 0), 31) : rh) * 8 + ((lane + nb - rank) & 7)];
        int i = 0, n = ph == 0 || ph == 5 ? NK : 0;
        if (own) { i = 4; if (st) { st--; pp ^= 1; } else st = 4; }
#pragma unroll 1
        while (i < NK) {
            if (n <= i) {
                int it = 0;
                PH_(ph == PPH && n == 0, 0, 27) PH_(ph == PPH && n == 0, 1, 27)
#pragma unroll 1
                do {
                    uint32_t v;
                    asm volatile(FLAG_LD " %0, [%1];" : "=r"(v) : "l"(fl) : "memory");
                    n = __reduce_min_sync(~0u, ph == 6 ? 8 * v : v || (own && !(lane & 6)) ? 16 : 2 * (lane & 7));
                    if (++it > SPIN_LIMIT) n = NK;
                } while (n <= i);
                PH_(ph == PPH && i <= 4, 0, 23) PH_(ph == PPH, 0, 24) PH_(ph == PPH && i <= 4, 1, 23) PH_(ph == PPH, 1, 24)
                asm volatile("fence.proxy.async.global;" ::: "memory");
            }
            if (own && (i == 5 || i == 6)) mbar_wait_w(bars + 8 * (PB_E + ph + i - 5), 1);
#pragma unroll 1
            for (const int e = own && i < 6 ? i + 1 : n; i < e; i++) {
                const int kb = (i + rot) & km;
                const uint32_t f = bars + 8 * (PB_F + st);
                mbar_wait_w(f + 8 * PB_E, pp);
                e_tma2d_mc(sb + st * 16384 + rank * 8192, ta, kb * amul, arow + (int)((shifts >> ((kb & 12) * 2)) & 7), f);
                if (++st == ST) { st = 0; pp ^= 1; }
            }
        }
    }
}

template <int PH, class F>
__device__ __forceinline__ void post_kb(uint32_t sb, float* acc, Pipe& p, int wg, bool lead, bool first, F mid) {
    constexpr uint64_t DA = PH == 0 ? mkdesc(SB0, 128, 1024, 0) : mkdesc(SB0, 16, 1024, 1);
    constexpr uint64_t DB = mkdesc(SB0 + P_B, P_PL, 1024, 1);
    mbar_wait_w(sb + P_BAR + 8 * PB_F + 8 * p.st, p.ph);
    const uint32_t a = (uint32_t)DA + p.st * 1024 + wg * 512, b = (uint32_t)DB + p.st * 512;
    wg_fence();
#pragma unroll
    for (int k = 0; k < 4; k++) {
        const uint64_t da = (DA & 0xffffffff00000000ull) | (a + k * (PH == 0 ? 16 : 2)), db = (DB & 0xffffffff00000000ull) | (b + k * 128);
        if (PH == 3) wgmma_ss192(acc, da, db, k || !first);
        else wgmma_ss128<PH == 0>(acc, da, db, k || !first);
    }
    wg_commit();
    wg_wait<1>();
    release(p.rel, p.st, !first);
    mid();
    adv(p);
}
__device__ __forceinline__ void post_end(uint32_t sb, Pipe& p, bool lead) {
    wg_wait<0>();
    release(p.rel, p.st, true);
}
template <int PH>
__device__ __forceinline__ void post_mma(uint32_t sb, float* acc, Pipe& p, int wg, bool lead, int nout, int pi, int mb, int nb) {
#pragma unroll 1
    for (int kb = 0; kb < 16; kb++)
        post_kb<PH>(sb, acc, p, wg, lead, kb == 0, [&]() {
            if (kb == 0) { PP(pi) }
            if (nout && kb == 0) wait_smem(sb + P_BAR + 8 * (PB_OUT + wg), nout);
        });
    post_end(sb, p, lead);
    PP(pi + 1)
}

__global__ void __cluster_dims__(2, 1, 1) __launch_bounds__(384, 1)
k_post(const __grid_constant__ PostMaps mp, const __grid_constant__ PostPtrs pp) {
    extern __shared__ uint8_t smraw[];
    const uint32_t sb = smem_u32(smraw);
    if ((sb & 0x3FFFF) != SB0) __trap();
    const int tid = threadIdx.x, lane = tid & 31;
    const int rank = blockIdx.x & 1;
    const uint32_t bars = sb + P_BAR;
    int c = 0;
    unsigned long long v = 0;
    const int wid = __reduce_max_sync(~0u, tid >> 5);
    const bool draw = tid == 352 && rank == 0;
    if (draw) {
        c = min(ldg_rlx1(&g_cls[smid() & 255]), 8u);
        asm volatile("{.reg .b64 a; cvt.u64.u32 a, %%laneid; add.u64 a, a, %1; atom.relaxed.gpu.global.add.u64 %0, [a], %2;}" : "=l"(v) : "l"(&g_pt), "l"(1ull << (7 * c)) : "memory");
    }
    if (wid < 11) {
        asm volatile("{.reg .pred p; elect.sync _|p, 0xffffffff; @p mbarrier.init.shared.b64 [%0], %1; @p prefetch.tensormap [%2]; fence.mbarrier_init.release.cluster;}"
                     ::"r"(bars + 8 * wid), "r"(wid >= PB_E && wid < PB_R ? 4 : 1), "l"(&mp.o + wid) : "memory");
        if (wid == PB_R) { sts4(bars + 8 * PB_OUT, 0, 0, 0, 0); e_expect(bars + 8 * PB_R, 4); }
    }
    __syncwarp();
    asm volatile("barrier.cluster.arrive.relaxed.aligned; barrier.cluster.wait.aligned;" ::: "memory");
    if (draw) {
        int r = (v >> (7 * c)) & 127, role = c * 8 + r;
        if (c == 8 || r >= 8) {
            int n, x, it = 0;
#pragma unroll 1
            do {
                __nanosleep(200);
                v = ldg_u64(&g_pt); n = 0; x = c < 8 ? r - 8 : r;
#pragma unroll 1
                for (int i = 0; i < 63; i += 7) { const int m = v >> i & 127; n += m; if (i < 7 * c) x += max(m - 8, 0); }
            } while (n < gridDim.x / 2 && ++it < SPIN_LIMIT);
            role = -1;
#pragma unroll 1
            for (int i = 0; i < 64; i += 8, v >>= 7) {
                n = v & 127;
                if (x >= 0 && n + x < 8) role = i + n + x;
                x -= max(8 - n, 0);
            }
        }
#pragma unroll
        for (int i = 0; i < 2; i++)
            asm volatile("{.reg .b32 d; mapa.shared::cluster.u32 d, %0, %2; st.async.shared::cluster.mbarrier::complete_tx::bytes.u32 [d+8], %1, [d];}"
                         ::"r"(bars + 8 * PB_R), "r"(role), "r"(i) : "memory");
    }
    __syncwarp();
    mbar_wait_w(bars + 8 * PB_R, 0);
    const int pr = __reduce_max_sync(~0u, (int)lds1(bars + 8 * PB_R + 8));
    if (pr < 0) return;
    const int mb = (pr >> 5) * 8 + (pr & 7), nb = (pr >> 2 & 6) + rank, cta = pr * 2 + rank;
    if (wid >= 8) {
        asm volatile("setmaxnreg.dec.sync.aligned.u32 40;");
        const int w = wid - 8;
        if (w == 0) {
            post_weights(sb, mp, nb, rank);
        } else if (w == 3) {
            asm volatile("griddepcontrol.wait;" ::: "memory");
            TLP(15)
            post_acts(sb, mp, mb, nb, rank);
        } else {
            const int wg = w - 1, rh = 2 * mb + wg;
            float* rowc = (float*)(smraw + P_ROW) + (wg * 64 + lane * 2) * 8;
            int nout = 0, sig = 0;
#pragma unroll 1
            for (int i = 0; i < 13; i++) {
                const int cnt = (0x4333333392180ull >> (4 * i)) & 15;
                if (cnt < C_S1) {
                    const int ng = cnt == C_U ? 1 : 2, c0 = cnt == C_U ? (i - 5) * 512 + nb * 64 : nb * 128;
                    const bool fast = (cnt == C_Y || cnt == C_X1);
#pragma unroll 1
                    for (int j = 0; j < ng; j++) {
                        const uint32_t st = j ? cnt : cnt ? 1 : 4;
                        const uint32_t src = sb + (fast ? st * 16384 + wg * 8192 : P_OUT + wg * 16384 + ((nout + j) & 1) * 8192);
                        bar_sync(4 + 4 * wg + (sig++ & 3), 160);
                        if (lane == 0) {
                            PH_(cnt == PPH - 1, wg, 20)
                            if (fast) asm volatile("mbarrier.complete_tx.relaxed.cta.shared::cta.b64 [%0], 8192;" ::"r"(bars + 8 * (PB_F + st)) : "memory");
                            asm volatile("cp.async.bulk.tensor.2d.global.shared::cta.bulk_group [%0, {%2, %3}], [%1]; cp.async.bulk.commit_group;"
                                         ::"l"(&mp.y + 2 * cnt), "r"(src), "r"(c0 + j * 64), "r"(rh * 64) : "memory");
                        }
                        __syncwarp();
                    }
                    if (lane == 0) {
                        auto to_peer = [&]() {
                            const uint32_t n = cnt ? 1 : 4;
                            mbar_wait(bars + 8 * (PB_E + (cnt ? 4 : 2)), 0);
#pragma unroll
                            for (int i = 0; i < 2; i++)
                                asm volatile("{.reg .b32 d, m; mapa.shared::cluster.u32 d, %0, %3; mapa.shared::cluster.u32 m, %2, %3;\n"
                                             " cp.async.bulk.shared::cluster.shared::cta.mbarrier::complete_tx::bytes [d], [%1], 8192, [m];}"
                                             ::"r"(sb + (cnt + 1 + i) * 16384 + wg * 8192), "r"(sb + (i ? cnt : n) * 16384 + wg * 8192), "r"(bars + 8 * (PB_F + cnt + 1 + i)), "r"(rank ^ 1) : "memory");
                        };
                        asm volatile("cp.async.bulk.wait_group 0; fence.proxy.async.global;" ::: "memory");
                        asm volatile("st.release.cta.shared.u32 [%0], %1;" ::"r"(bars + 8 * (PB_OUT + wg)), "r"(nout + ng) : "memory");
                        PH_(cnt == PPH - 1, wg, 21)
                        if (i < 12) asm volatile(FLAG_ST " [%0], %1;" ::"l"(&g_pflag[cnt * 256 + rh * 8 + nb]), "r"(max(i - 4, 1)) : "memory");
                        PH_(cnt == PPH - 1, wg, 22)
                        if (fast) to_peer();
                    }
                    nout += ng;
                    __syncwarp();
                    continue;
                }
                bar_sync(4 + 4 * wg + (sig++ & 3), 160);
                uint32_t* c = &g_pcnt[(cnt - C_S1) * 256 + rh * 8];
                if (lane == 0) signal_count(c);
                __syncwarp();
                wait_count_w(c, 8);
                const float4* sp = (const float4*)g_st + rh * 32 + lane;
                float4 u[3] = {__ldcg(sp + (cnt == C_S1 ? 0 : 3) * (S_ / 2)), __ldcg(sp + S_ / 2), __ldcg(sp + S_)};
#pragma unroll 1
                for (int h = 0; h < 2; h++) {
                    const float id = 1.0f / DM;
                    const float m = u[0].x * id, var = fmaxf(u[0].y * id - m * m, 0.f) + 1e-5f, r = rsqrtf(var);
                    float sc = r, m2 = 0.f;
                    if (cnt == C_S1) {
                        m2 = r * (u[1].x * id - m * g_cst[0]) + g_cst[3];
                        const float e2 = r * r * (u[2].x * id - 2.0f * m * u[1].y * id + m * m * g_cst[1]) + 2.0f * r * (u[2].y * id - m * g_cst[2]) + g_cst[4];
                        sc = r * rsqrtf(fmaxf(e2 - m2 * m2, 0.f) + 1e-5f);
                    }
                    const GeluK k = gelu_k(sc);
                    *(float4*)(rowc + h * 8) = make_float4(k.k0, k.k1, k.kh, -m);
                    *(float4*)(rowc + h * 8 + 4) = make_float4(var * r, -m2 * var * r, r, -m * r);
#pragma unroll
                    for (int q = 0; q < 3; q++) { u[q].x = u[q].z; u[q].y = u[q].w; }
                }
                bar_arrive(1 + wg, 160);
            }
        }
    } else {
        asm volatile("setmaxnreg.inc.sync.aligned.u32 232;");
        const bf16* xin = pp.x;
        const int wg = wid >> 2, wi = (tid >> 5) & 3, g = lane >> 2, tq = lane & 3;
        const int rh = 2 * mb + wg, row = rh * 64 + wi * 16 + g;
        const bool lead = (tid & 127) == 0;
        PP(0)
        if (tid == 0) TLP(10)
        uint32_t keep[32];
#pragma unroll
        for (int i = 0; i < 8; i++)
            *(uint4*)(keep + 4 * i) = __ldg((const uint4*)(xin + (size_t)(rh * 64 + wi * 16 + (i & 3) * 4 + (lane >> 3)) * DM + nb * 128 + (i >> 2) * 64 + (lane & 7) * 8));
        asm volatile("griddepcontrol.wait;" ::: "memory");
        if (cta < 64) g_modp[cta * 256 + tid] = 0;
        if (cta == 64 && tid < 196) g_tick[tid] = 0;
        const float* src = wg ? g_vec + nb * 128 + tid - 128 : g_mod + 2 * DM + nb * 128 + tid;
        const float* c3 = &g_vec[3 * DM + (tid >> 6) * 512 + nb * 64 + (tid & 63)];
        const float cv[6] = {__ldcg(src), __ldcg(src + (wg ? 1 : 2) * DM), __ldcg(src + (wg ? 2 : 1) * DM), __ldcg(src + 3 * DM), __ldcg(c3), __ldcg(c3 + (tid < 192 ? 2048 : 0))};
        uint32_t vec = sb + P_VEC + tq * 8;
        const uint32_t stw = sb + (wi * 16 + ((lane >> 3) & 1) * 8 + (lane & 7)) * 128 + (((lane >> 4) ^ (lane & 7)) << 4);
        int sig = 0;
        auto signal = [&]() { bar_arrive(4 + 4 * wg + (sig++ & 3), 160); };
        auto put64 = [&](uint32_t o, const float* v) {
#pragma unroll
            for (int jj = 0; jj < 4; jj++, v += 8) stsm4((stw + o) ^ (jj << 5), pack2(v[0], v[1]), pack2(v[2], v[3]), pack2(v[4], v[5]), pack2(v[6], v[7]));
            fence_async_smem();
            signal();
        };
        auto slot = [&](int n) {
            mbar_wait_w(bars + 8 * (PB_E + n % 5), ((n / 5) & 1) ^ 1);
            return (n % 5) * 16384 + wg * 8192;
        };
        const uint32_t rowc = sb + P_ROW + (wg * 64 + wi * 16 + g) * 32, o128 = P_OUT + wg * 16384;
        Pipe pa = {0, 0, 0};
        asm("mapa.shared::cluster.u32 %0, %1, %2;" : "=r"(pa.rel) : "r"(bars + 8 * PB_E), "r"(tid & 1));
        if (tid & 126) pa.rel = 0;
#define KEEP(jn, e) (((e) & 1) ? bfhi(keep[2 * (jn) + ((e) >> 1)]) : bflo(keep[2 * (jn) + ((e) >> 1)]))
        float mu1[2], r1[2];
        {
            float acc[64];
#pragma unroll 1
            for (int kb = 0; kb < 64; kb++) {
                post_kb<0>(sb, acc, pa, wg, lead, kb == 0, []() {});
                if (kb == 0) { PP(1) if (wg == 0) TLP(11) }
                if (kb == 24) bar_sync(3, 256);
                if (kb != 8 + 8 * wg) continue;
                float* sv = (float*)(smraw + P_VEC) + tid;
                const uint32_t xo = sb + o128 + wi * 2048 + (lane >> 3) * 128;
#pragma unroll
                for (int i = 0; i < 8; i++) sts4(xo + (i >> 2) * 8192 + (i & 3) * 512 + (((lane & 7) ^ ((i & 1) * 4 + (lane >> 3))) << 4), keep[4 * i], keep[4 * i + 1], keep[4 * i + 2], keep[4 * i + 3]);
                __syncwarp();
#pragma unroll
                for (int jj = 0; jj < 8; jj++) ldsm4(keep + jj * 4, (stw + o128 + (jj >> 2) * 8192) ^ ((jj & 3) << 5));
                sv[wg * 384] = cv[0]; sv[wg * 384 + 128] = cv[1] + (wg ? 0.0f : 1.0f); sv[wg * 384 + 256] = cv[2];
                if (!wg) sv[384] = cv[3];
                sv[V_C3 * 128] = cv[4]; sv[V_C3 * 128 + 256] = cv[5];
            }
            post_end(sb, pa, lead);
            PP(2)
            asm volatile("" : "+r"(vec) :: "memory");
            float st[2][6];
#pragma unroll
            for (int q = 0; q < 6; q++) st[0][q] = st[1][q] = 0.f;
#pragma unroll
            for (int jn = 0; jn < 16; jn++) {
                const float2 ga = ldsv(vec + V_GA * 512 + jn * 32), a = ldsv(vec + V_A * 512 + jn * 32);
                float xa[4];
#pragma unroll
                for (int e = 0; e < 4; e++) {
                    xa[e] = fmaf((e & 1) ? ga.y : ga.x, acc[4 * jn + e], KEEP(jn, e));
                    st[e >> 1][0] += xa[e]; st[e >> 1][1] = fmaf(xa[e], xa[e], st[e >> 1][1]);
                    acc[4 * jn + e] = ((e & 1) ? a.y : a.x) * xa[e];
                }
                keep[2 * jn] = pack2(xa[0], xa[1]); keep[2 * jn + 1] = pack2(xa[2], xa[3]);
                if ((jn & 7) == 7) put64(slot(64 + (jn >> 3)), acc + 4 * jn - 28);
            }
            PP(3)
#pragma unroll
            for (int jn = 0; jn < 16; jn++) {
                const float2 a = ldsv(vec + V_A * 512 + jn * 32), b = ldsv(vec + V_B * 512 + jn * 32);
#pragma unroll
                for (int e = 0; e < 4; e++) {
                    const float y = acc[4 * jn + e], aa = (e & 1) ? a.y : a.x, bb = (e & 1) ? b.y : b.x;
                    float* s = st[e >> 1];
                    s[2] += y; s[3] = fmaf(aa, y, s[3]); s[4] = fmaf(y, y, s[4]); s[5] = fmaf(bb, y, s[5]);
                }
            }
#pragma unroll
            for (int h = 0; h < 2; h++)
#pragma unroll
                for (int q = 0; q < 6; q++) { st[h][q] += __shfl_xor_sync(~0u, st[h][q], 1); st[h][q] += __shfl_xor_sync(~0u, st[h][q], 2); }
            if (tq < 3) {
#pragma unroll
                for (int h = 0; h < 2; h++)
                    red2(g_st + (tq * S_ + row + h * 8) * 2, tq == 0 ? st[h][0] : tq == 1 ? st[h][2] : st[h][4], tq == 0 ? st[h][1] : tq == 1 ? st[h][3] : st[h][5]);
            }
            signal();
            PP(29)
        }
        {
            float acc[64];
            post_mma<1>(sb, acc, pa, wg, lead, 2, 4, mb, nb);
            float c1[2], c2[2], c3[2];
            GeluK gk[2];
            bar_sync(1 + wg, 160);
#pragma unroll
            for (int h = 0; h < 2; h++) {
                const float4 a = lds4f(rowc + h * 256), b = lds4f(rowc + h * 256 + 16);
                gk[h] = {a.x, a.y, a.z}; c1[h] = a.w; c2[h] = b.x; c3[h] = b.y; mu1[h] = b.w; r1[h] = b.z;
            }
#pragma unroll
            for (int jn = 0; jn < 16; jn++) {
                const float2 va = ldsv(vec + V_VA * 512 + jn * 32), vb = ldsv(vec + V_VB * 512 + jn * 32), vc = ldsv(vec + V_VC * 512 + jn * 32);
#pragma unroll
                for (int e = 0; e < 4; e++) {
                    const int h = e >> 1;
                    const float t = fmaf(c1[h], (e & 1) ? va.y : va.x, fmaf(c2[h], (e & 1) ? vb.y : vb.x, fmaf(c3[h], (e & 1) ? vc.y : vc.x, acc[4 * jn + e])));
                    acc[4 * jn + e] = gelu_s(t, gk[h]);
                }
                if ((jn & 7) == 7) put64(o128 + (jn >> 3) * 8192, acc + 4 * jn - 28);
            }
            PP(6)
        }
        {
            float acc[64];
            post_mma<2>(sb, acc, pa, wg, lead, 0, 7, mb, nb);
#pragma unroll
            for (int jn = 0; jn < 16; jn++) {
                const float2 a = ldsv(vec + V_A * 512 + jn * 32), b = ldsv(vec + V_B * 512 + jn * 32);
#pragma unroll
                for (int e = 0; e < 4; e++) {
                    const int h = e >> 1;
                    acc[4 * jn + e] += fmaf(fmaf(KEEP(jn, e), r1[h], mu1[h]), (e & 1) ? a.y : a.x, (e & 1) ? b.y : b.x);
                }
                if ((jn & 7) == 7) put64(slot(96 + (jn >> 3)), acc + 4 * jn - 28);
            }
            BLOCK_FENCE
#pragma unroll
            for (int i = 0; i < 64; i += 16) asm volatile("" : F16(acc, i));
            PP(9)
            float st[2][2] = {{0.f, 0.f}, {0.f, 0.f}};
#pragma unroll
            for (int jn = 0; jn < 16; jn++) {
                const float2 gb = ldsv(vec + V_GB * 512 + jn * 32);
                float z[4];
#pragma unroll
                for (int e = 0; e < 4; e++) {
                    const float x1 = acc[4 * jn + e];
                    st[e >> 1][0] += x1; st[e >> 1][1] = fmaf(x1, x1, st[e >> 1][1]);
                    z[e] = fmaf((e & 1) ? gb.y : gb.x, x1, KEEP(jn, e));
                }
                keep[2 * jn] = pack2(z[0], z[1]); keep[2 * jn + 1] = pack2(z[2], z[3]);
            }
#pragma unroll
            for (int h = 0; h < 2; h++)
#pragma unroll
                for (int q = 0; q < 2; q++) { st[h][q] += __shfl_xor_sync(~0u, st[h][q], 1); st[h][q] += __shfl_xor_sync(~0u, st[h][q], 2); }
            if (tq < 2) red2(g_st + (3 * S_ + row + tq * 8) * 2, tq ? st[1][0] : st[0][0], tq ? st[1][1] : st[0][1]);
            signal();
            PP(30)
        }
        {
            float old[96], acc[64];
            post_mma<3>(sb, old, pa, wg, lead, 6, 10, mb, nb);
#pragma unroll
            for (int i = 0; i < 96; i += 16) asm volatile("" : F16(old, i));
            uint32_t v3 = vec + V_C3 * 512;
            bar_sync(1 + wg, 160);
            const float4 rc[2] = {lds4f(rowc), lds4f(rowc + 256)};
            float2 vc[2] = {lds2f(v3), lds2f(v3 + 32)};
            v3 += wg ? 0 : 64;
            bar_sync(3, 256);
#pragma unroll 1
            for (int blk = 0; blk < 11; blk++) {
                const uint32_t o = stw + o128 + (blk & 1) * 8192;
#pragma unroll
                for (int q = 0; q < 4; q++) {
#pragma unroll 1
                    for (int rep = 0; rep < 2; rep++) {
                        post_kb<1>(sb, acc, pa, wg, lead, q == 0 && rep == 0 && blk < 6 && !(blk & 1), []() {});
                        if (rep != wg) {
                            vc[0] = lds2f(v3 + q * 64); vc[1] = lds2f(v3 + q * 64 + 32);
                            if (q == 2) wait_smem(bars + 8 * (PB_OUT + wg), 6 + min(blk, 7));
                            if ((q == 0 && wg && (uint32_t)(blk - 1) < 7) || (q == 3 && !wg && blk < 7)) { fence_async_smem(); signal(); }
                        } else if (blk < 7) {
                            asm volatile("" : F4(old, 8 * q), F4(old, 8 * q + 4));
                            float t[8];
#pragma unroll
                            for (int i = 0; i < 8; i++) {
                                const float4& c = rc[(i >> 1) & 1];
                                t[i] = gelu_s(fmaf(c.w, (i & 1) ? vc[i >> 2].y : vc[i >> 2].x, old[8 * q + i]), GeluK{c.x, c.y, c.z});
                                old[8 * q + i] = old[32 + 8 * q + i];
                                old[32 + 8 * q + i] = old[64 + 8 * q + i];
                            }
                            uint32_t r[4] = {pack2(t[0], t[1]), pack2(t[2], t[3]), pack2(t[4], t[5]), pack2(t[6], t[7])};
                            asm volatile("pmevent 0;" : F4(old, 8 * q), F4(old, 8 * q + 4), F4(old, 8 * q + 32), F4(old, 8 * q + 36), "+r"(r[0]), "+r"(r[1]), "+r"(r[2]), "+r"(r[3]));
                            stsm4(o ^ (q << 5), r[0], r[1], r[2], r[3]);
                        }
                    }
                }
                v3 += 256;
                if (blk != 1 && blk != 3) continue;
                post_end(sb, pa, lead);
                PP(12 + blk)
                asm volatile("" : F16(acc, 0), F4(acc, 16), F4(acc, 20), F4(acc, 24));
                asm volatile("" : F16(acc, 28), F4(acc, 44), F4(acc, 48), F4(acc, 52));
                asm volatile("" : F4(acc, 56), F4(acc, 60));
#pragma unroll
                for (int i = 0; i < 64; i++) old[32 + i] = acc[i];
            }
            post_end(sb, pa, lead);
            PP(17)
#pragma unroll
            for (int jn = 0; jn < 16; jn++) {
                const float2 gb = ldsv(vec + V_GB * 512 + jn * 32);
#pragma unroll
                for (int e = 0; e < 4; e++) acc[4 * jn + e] = fmaf((e & 1) ? gb.y : gb.x, acc[4 * jn + e], KEEP(jn, e));
                if ((jn & 7) == 7) put64(o128 + ((jn >> 3) ^ 1) * 8192, acc + 4 * jn - 28);
            }
            PP(18)
            if (tid == 0) TLP(12)
        }
    }
}

typedef CUresult (*EncFn)(CUtensorMap*, CUtensorMapDataType, cuuint32_t, void*, const cuuint64_t*, const cuuint64_t*, const cuuint32_t*,
                          const cuuint32_t*, CUtensorMapInterleave, CUtensorMapSwizzle, CUtensorMapL2promotion, CUtensorMapFloatOOBfill);

static CUtensorMap make_map(EncFn enc, const void* p, uint64_t inner, uint64_t outer, uint32_t bi = 64) {
    CUtensorMap m;
    cuuint64_t dims[2] = {inner, outer};
    cuuint64_t str[1] = {inner * 2};
    cuuint32_t box[2] = {bi, bi == 64 ? 64u : 16u};
    cuuint32_t es[2] = {1, 1};
    enc(&m, CU_TENSOR_MAP_DATA_TYPE_BFLOAT16, 2, (void*)p, dims, str, box, es, CU_TENSOR_MAP_INTERLEAVE_NONE,
        bi == 64 ? CU_TENSOR_MAP_SWIZZLE_128B : CU_TENSOR_MAP_SWIZZLE_NONE, CU_TENSOR_MAP_L2_PROMOTION_L2_256B, CU_TENSOR_MAP_FLOAT_OOB_FILL_NONE);
    return m;
}
static CUtensorMap make_map_o(EncFn enc, const void* p) {
    CUtensorMap m;
    cuuint64_t dims[2] = {16384, 256};
    cuuint64_t str[1] = {65536};
    cuuint32_t box[2] = {256, 8};
    cuuint32_t es[2] = {1, 1};
    enc(&m, CU_TENSOR_MAP_DATA_TYPE_UINT32, 2, (void*)p, dims, str, box, es, CU_TENSOR_MAP_INTERLEAVE_NONE, CU_TENSOR_MAP_SWIZZLE_NONE,
        CU_TENSOR_MAP_L2_PROMOTION_L2_256B, CU_TENSOR_MAP_FLOAT_OOB_FILL_NONE);
    return m;
}
template <class T> static T* sym(T& s) { void* p = nullptr; cudaGetSymbolAddress(&p, s); return (T*)p; }

static const Delays h_dly = {D_NEAR, D_FAR, D_X2, D_V, D_W2, D_PA, 0, D_MORE};
extern "C" void kernel_launch(void* const* d_in, const int* in_sizes, int n_in, void* d_out, int out_size) {
    const bf16* x = (const bf16*)d_in[0];
    const bf16* mem0 = (const bf16*)d_in[1];
    const bf16 *Wq = (const bf16*)d_in[2], *Wk = (const bf16*)d_in[3], *Wv = (const bf16*)d_in[4], *Wo = (const bf16*)d_in[5];
    const bf16 *w1 = (const bf16*)d_in[8], *w2 = (const bf16*)d_in[9], *w3 = (const bf16*)d_in[10], *w4 = (const bf16*)d_in[11];
    const bf16 *c = (const bf16*)d_in[12], *wmod = (const bf16*)d_in[13];
    bf16* out = (bf16*)d_out;

    EncFn enc = nullptr;
    cudaDriverEntryPointQueryResult qr;
    cudaGetDriverEntryPoint("cuTensorMapEncodeTiled", (void**)&enc, cudaEnableDefault, &qr);
    CUtensorMap tWq = make_map(enc, Wq, NH * DH, DM), tWk = make_map(enc, Wk, NH * DH, DM), tWv = make_map(enc, Wv, NH * DH, DM);
    PostMaps mp;
    mp.o = make_map_o(enc, sym(g_O)); mp.wo = make_map(enc, Wo, DM, NH * DH);
    mp.y = make_map(enc, sym(g_y), DM, S_); mp.w1 = make_map(enc, w1, DM, DM);
    mp.g = make_map(enc, sym(g_g), DM, S_); mp.w2 = make_map(enc, w2, DM, DM);
    mp.x1 = make_map(enc, sym(g_x1), DM, S_); mp.w3 = make_map(enc, w3, FF, DM);
    mp.u = make_map(enc, sym(g_u), FF, S_); mp.w4 = make_map(enc, w4, DM, FF);
    mp.out = make_map(enc, out, DM, S_);
    cudaFuncSetAttribute(k_rec, cudaFuncAttributeMaxDynamicSharedMemorySize, SM_REC_TOTAL + 2048);
    cudaFuncSetAttribute(k_post, cudaFuncAttributeMaxDynamicSharedMemorySize, P_SMEM);

    uint8_t* arena = (uint8_t*)(((uintptr_t)sym(g_arena) + (2u << 20) - 1) & ~(uintptr_t)((2u << 20) - 1));
    const PostPtrs pp = {x};
    const RecPtrs rp = {x, mem0, c, wmod, w1, w3, arena, 0u, w2, w4, Wo, h_dly};
    const RecMaps rm = {tWq, tWk, tWv, mp.wo, make_map(enc, wmod, 6 * DM, DM, 256), make_map(enc, w3, FF, DM, 256), make_map(enc, w1, DM, DM, 256)};
    k_rec<<<132, 384, SM_REC_TOTAL + 2048>>>(rm, rp);
    cudaLaunchConfig_t cfg = {};
    cfg.gridDim = dim3(132); cfg.blockDim = dim3(384); cfg.dynamicSmemBytes = P_SMEM; cfg.stream = cudaStreamPerThread;
    cudaLaunchAttribute at[1];
    at[0].id = cudaLaunchAttributeProgrammaticStreamSerialization; at[0].val.programmaticStreamSerializationAllowed = PDL;
    cfg.attrs = at; cfg.numAttrs = 1;
    cudaLaunchKernelEx(&cfg, k_post, mp, pp);
}
```

```cpp
#include <cuda_runtime.h>
#include <cuda.h>
#include <cuda_bf16.h>
#include <stdint.h>
#include <limits.h>

typedef __nv_bfloat16 bf16;

constexpr int S_ = 2048, DM = 1024, NH = 32, DH = 128, NSEG = 64, FF = 3584;
constexpr int SPIN_LIMIT = 1 << 22;
#define W_INFL 2
#define H_PIECES 4
#define PDL 1
#define NPROBE 3

__device__ uint8_t g_arena[10 << 20];
__device__ __align__(128) uint32_t g_tick[64 + 132];
#define g_clk ((uint2*)(g_tick + 64))
__device__ uint32_t g_cls[256];
__device__ unsigned long long g_pt;
__device__ __align__(16) uint32_t g_modp[8 * 2 * DM];
__host__ __device__ constexpr uint32_t blk(uint32_t lb, uint32_t par) {
    return (lb << 13) | ((((lb) ^ (lb >> 3) ^ (lb >> 4) ^ (lb >> 6) ^ par) & 1) << 12);
}
__host__ __device__ constexpr uint32_t lb_x2(uint32_t h) { return (h & 1) | ((h >> 1) << 3); }
__host__ __device__ constexpr uint32_t mem_row(uint32_t kh, uint32_t b, uint32_t r) { return blk(128 | b, kh) + r * 1024; }
__device__ __forceinline__ uint32_t mem_slot(uint32_t s) { return ((s & 1) << 15) | ((s & 2) << 17); }
constexpr uint32_t CNT1 = 0x3d80, CNT_ALL = 0x4000;
constexpr uint32_t LB_PROBE = 6 | 64, LB_TIME = 6;
__host__ __device__ constexpr uint32_t lb_tok(uint32_t h) { return (h & 1) | ((h >> 1) << 3); }
__device__ float g_mod[6 * DM];
__device__ __align__(1024) bf16 g_himg[(S_ + 32) * DM];
__device__ __align__(1024) bf16 g_O[S_ * NH * DH];
__device__ __align__(1024) bf16 g_y[S_ * DM];
__device__ __align__(1024) bf16 g_g[S_ * DM];
__device__ __align__(1024) bf16 g_x1[S_ * DM];
__device__ __align__(16) float g_st[4 * S_ * 2];
__device__ float g_vec[3 * DM + FF];
__device__ float g_cst[8];
__device__ uint32_t g_pcnt[2 * 32 * 8], g_pflag[7 * 32 * 8];
__device__ __align__(1024) bf16 g_u[S_ * FF];

#define TL(i) {}
#define TLX(i) {}
#define TLP(i) TL(i)
#define TLC(i) {}
__device__ __forceinline__ uint32_t smem_u32(const void* p) { return (uint32_t)__cvta_generic_to_shared(p); }
__device__ __forceinline__ void spin_guard(int it) {
    asm volatile("{.reg .pred p; setp.gt.s32 p, %0, %1; @p st.global.u32 [%2], %0;}" ::"r"(it), "n"(SPIN_LIMIT), "l"(1ull));
}
__device__ __forceinline__ void wg_fence() { asm volatile("wgmma.fence.sync.aligned;" ::: "memory"); }
__device__ __forceinline__ void wg_commit() { asm volatile("wgmma.commit_group.sync.aligned;" ::: "memory"); }
template <int N> __device__ __forceinline__ void wg_wait() { asm volatile("wgmma.wait_group.sync.aligned %0;" ::"n"(N) : "memory"); }
__host__ __device__ constexpr uint64_t mkdesc(uint32_t addr, uint32_t lbo, uint32_t sbo, uint32_t swz) {
    return (uint64_t)((addr & 0x3FFFF) >> 4) | ((uint64_t)(lbo >> 4) << 16) | ((uint64_t)(sbo >> 4) << 32) | ((uint64_t)swz << 62);
}
__device__ __forceinline__ uint64_t dadd(uint64_t d, uint32_t o) { return (d & 0xffffffff00000000ull) | (uint32_t)((uint32_t)d + o); }
__device__ __forceinline__ void mbar_init(uint32_t b, uint32_t c) { asm volatile("mbarrier.init.shared.b64 [%0], %1;" ::"r"(b), "r"(c) : "memory"); }
__device__ __forceinline__ void mbar_arrive_cluster(uint32_t b, uint32_t cta) {
    asm volatile("{.reg .b32 r; mapa.shared::cluster.u32 r, %0, %1; mbarrier.arrive.shared::cluster.b64 _, [r];}" ::"r"(b), "r"(cta) : "memory");
}
__device__ __forceinline__ bool mbar_try(uint32_t b, uint32_t par) {
    uint32_t ok;
    asm volatile("{.reg .pred p; mbarrier.try_wait.parity.shared.b64 p, [%1], %2; selp.u32 %0, 1, 0, p;}" : "=r"(ok) : "r"(b), "r"(par) : "memory");
    return ok;
}
__device__ __forceinline__ void mbar_wait(uint32_t b, uint32_t par) {
    int it = 0;
#pragma unroll 1
    while (!mbar_try(b, par) & (++it < SPIN_LIMIT)) {}
}
__device__ __forceinline__ void mbar_wait_w(uint32_t b, uint32_t par) {
    int it = 0;
#pragma unroll 1
    while (!__all_sync(~0u, mbar_try(b, par)) & (++it < SPIN_LIMIT)) {}
}
constexpr uint64_t EVICT_FIRST = 0x12F0000000000000ull, EVICT_NORMAL = 0x1000000000000000ull;   __device__ __forceinline__ void bar_sync(int id, int n) { asm volatile("bar.sync %0, %1;" ::"r"(id), "r"(n) : "memory"); }
__device__ __forceinline__ void bar_arrive(int id, int n) { asm volatile("bar.arrive %0, %1;" ::"r"(id), "r"(n) : "memory"); }
__device__ __forceinline__ void fence_async_smem() { asm volatile("fence.proxy.async.shared::cta;" ::: "memory"); }
__device__ __forceinline__ void ldsm4t(uint32_t* r, uint32_t a) {
    asm volatile("ldmatrix.sync.aligned.m8n8.x4.trans.shared.b16 {%0,%1,%2,%3}, [%4];" : "=r"(r[0]), "=r"(r[1]), "=r"(r[2]), "=r"(r[3]) : "r"(a) : "memory");
}
__device__ __forceinline__ void ldsm4(uint32_t* r, uint32_t a) {
    asm volatile("ldmatrix.sync.aligned.m8n8.x4.shared.b16 {%0,%1,%2,%3}, [%4];" : "=r"(r[0]), "=r"(r[1]), "=r"(r[2]), "=r"(r[3]) : "r"(a) : "memory");
}
__device__ __forceinline__ uint32_t movm(uint32_t a) {
    uint32_t d; asm volatile("movmatrix.sync.aligned.m8n8.trans.b16 %0, %1;" : "=r"(d) : "r"(a)); return d;
}
__device__ __forceinline__ void mma16816(float* d, uint32_t a0, uint32_t a1, uint32_t a2, uint32_t a3, uint32_t b0, uint32_t b1) {
    asm volatile("mma.sync.aligned.m16n8k16.row.col.f32.bf16.bf16.f32 {%0,%1,%2,%3},{%4,%5,%6,%7},{%8,%9},{%0,%1,%2,%3};"
                 : "+f"(d[0]), "+f"(d[1]), "+f"(d[2]), "+f"(d[3]) : "r"(a0), "r"(a1), "r"(a2), "r"(a3), "r"(b0), "r"(b1));
}
__device__ __forceinline__ void mma16816z(float* d, const uint32_t* a, uint32_t b0, uint32_t b1) {
    asm volatile("mma.sync.aligned.m16n8k16.row.col.f32.bf16.bf16.f32 {%0,%1,%2,%3},{%4,%5,%6,%7},{%8,%9},{%10,%10,%10,%10};"
                 : "=f"(d[0]), "=f"(d[1]), "=f"(d[2]), "=f"(d[3]) : "r"(a[0]), "r"(a[1]), "r"(a[2]), "r"(a[3]), "r"(b0), "r"(b1), "f"(0.f));
}
__device__ __forceinline__ void mma1688(float* d, uint32_t a0, uint32_t a1, uint32_t b0) {
    asm volatile("mma.sync.aligned.m16n8k8.row.col.f32.bf16.bf16.f32 {%0,%1,%2,%3},{%4,%5},{%6},{%0,%1,%2,%3};"
                 : "+f"(d[0]), "+f"(d[1]), "+f"(d[2]), "+f"(d[3]) : "r"(a0), "r"(a1), "r"(b0));
}
__device__ __forceinline__ uint32_t pack2(float lo, float hi) {
    uint32_t r; asm("cvt.rn.bf16x2.f32 %0, %1, %2;" : "=r"(r) : "f"(hi), "f"(lo)); return r;
}
__device__ __forceinline__ uint32_t hadd2(uint32_t a, uint32_t b) {
    uint32_t r; asm("add.rn.bf16x2 %0, %1, %2;" : "=r"(r) : "r"(a), "r"(b)); return r;
}
__device__ __forceinline__ float bflo(uint32_t u) { return __uint_as_float(u << 16); }
__device__ __forceinline__ float bfhi(uint32_t u) { return __uint_as_float(u & 0xffff0000u); }
__device__ __forceinline__ float ex2(float x) { float r; asm("ex2.approx.ftz.f32 %0, %1;" : "=f"(r) : "f"(x)); return r; }
__device__ __forceinline__ uint4 ldg_rlx4(const void* p) {
    uint4 v; asm volatile("ld.relaxed.gpu.global.v4.u32 {%0,%1,%2,%3}, [%4];" : "=r"(v.x), "=r"(v.y), "=r"(v.z), "=r"(v.w) : "l"(p) : "memory"); return v;
}
__device__ __forceinline__ uint32_t ldg_rlx1(const void* p) {
    uint32_t v; asm volatile("ld.relaxed.gpu.global.u32 %0, [%1];" : "=r"(v) : "l"(p) : "memory"); return v;
}
__device__ __forceinline__ void stg_rlx1(void* p, uint32_t v) { asm volatile("st.relaxed.gpu.global.u32 [%0], %1;" ::"l"(p), "r"(v) : "memory"); }
__device__ __forceinline__ void stg_rlx2(void* p, uint32_t x, uint32_t y) {
    unsigned long long v = (unsigned long long)x | ((unsigned long long)y << 32);
    asm volatile("st.relaxed.gpu.global.b64 [%0], %1;" ::"l"(p), "l"(v) : "memory");
}
__device__ __forceinline__ void stg_rlx4(void* p, uint32_t x, uint32_t y, uint32_t z, uint32_t w) {
    asm volatile("st.relaxed.gpu.global.v4.u32 [%0], {%1,%2,%3,%4};" ::"l"(p), "r"(x), "r"(y), "r"(z), "r"(w) : "memory");
}
__device__ __forceinline__ void sts4(uint32_t a, uint32_t x, uint32_t y, uint32_t z, uint32_t w) {
    asm volatile("st.shared.v4.u32 [%0], {%1,%2,%3,%4};" ::"r"(a), "r"(x), "r"(y), "r"(z), "r"(w) : "memory");
}
__device__ __forceinline__ uint4 lds4(uint32_t a) {
    uint4 v; asm volatile("ld.shared.v4.u32 {%0,%1,%2,%3}, [%4];" : "=r"(v.x), "=r"(v.y), "=r"(v.z), "=r"(v.w) : "r"(a) : "memory"); return v;
}
#define F4(d, i) "+f"(d[i]), "+f"(d[i + 1]), "+f"(d[i + 2]), "+f"(d[i + 3])
__device__ __forceinline__ void wgmma_rs32(float* d, const uint32_t* a, uint64_t b, int sc) {
    asm volatile("{.reg .pred p; setp.ne.b32 p, %21, 0;\n wgmma.mma_async.sync.aligned.m64n32k16.f32.bf16.bf16 {%0,%1,%2,%3,%4,%5,%6,%7,%8,%9,%10,%11,%12,%13,%14,%15}, {%16,%17,%18,%19}, %20, p, 1, 1, 0;}"
                 : F4(d, 0), F4(d, 4), F4(d, 8), F4(d, 12) : "r"(a[0]), "r"(a[1]), "r"(a[2]), "r"(a[3]), "l"(b), "r"(sc));
}
__device__ __forceinline__ void wgmma_ss32(float* d, uint64_t a, uint64_t b, int sc) {
    asm volatile("{.reg .pred p; setp.ne.b32 p, %18, 0;\n wgmma.mma_async.sync.aligned.m64n32k16.f32.bf16.bf16 {%0,%1,%2,%3,%4,%5,%6,%7,%8,%9,%10,%11,%12,%13,%14,%15}, %16, %17, p, 1, 1, 1, 0;}"
                 : F4(d, 0), F4(d, 4), F4(d, 8), F4(d, 12) : "l"(a), "l"(b), "r"(sc));
}
__device__ __forceinline__ void wgmma_rs40(float* d, const uint32_t* a, uint64_t b, int sc) {
    asm volatile("{.reg .pred p; setp.ne.b32 p, %25, 0;\n wgmma.mma_async.sync.aligned.m64n40k16.f32.bf16.bf16 {%0,%1,%2,%3,%4,%5,%6,%7,%8,%9,%10,%11,%12,%13,%14,%15,%16,%17,%18,%19}, {%20,%21,%22,%23}, %24, p, 1, 1, 0;}"
                 : F4(d, 0), F4(d, 4), F4(d, 8), F4(d, 12), F4(d, 16) : "r"(a[0]), "r"(a[1]), "r"(a[2]), "r"(a[3]), "l"(b), "r"(sc));
}
__device__ __forceinline__ void wgmma_ss40(float* d, uint64_t a, uint64_t b, int sc) {
    asm volatile("{.reg .pred p; setp.ne.b32 p, %22, 0;\n wgmma.mma_async.sync.aligned.m64n40k16.f32.bf16.bf16 {%0,%1,%2,%3,%4,%5,%6,%7,%8,%9,%10,%11,%12,%13,%14,%15,%16,%17,%18,%19}, %20, %21, p, 1, 1, 1, 0;}"
                 : F4(d, 0), F4(d, 4), F4(d, 8), F4(d, 12), F4(d, 16) : "l"(a), "l"(b), "r"(sc));
}
#define F16(d, i) F4(d, i), F4(d, i + 4), F4(d, i + 8), F4(d, i + 12)
template <int TA>
__device__ __forceinline__ void wgmma_ss128(float* d, uint64_t a, uint64_t b, int sc) {
    asm volatile("{.reg .pred p; setp.ne.b32 p, %66, 0;\n wgmma.mma_async.sync.aligned.m64n128k16.f32.bf16.bf16 "
                 "{%0,%1,%2,%3,%4,%5,%6,%7,%8,%9,%10,%11,%12,%13,%14,%15,%16,%17,%18,%19,%20,%21,%22,%23,%24,%25,%26,%27,%28,%29,%30,%31,"
                 "%32,%33,%34,%35,%36,%37,%38,%39,%40,%41,%42,%43,%44,%45,%46,%47,%48,%49,%50,%51,%52,%53,%54,%55,%56,%57,%58,%59,%60,%61,%62,%63}, %64, %65, p, 1, 1, %67, 1;}"
                 : F16(d, 0), F16(d, 16), F16(d, 32), F16(d, 48) : "l"(a), "l"(b), "r"(sc), "n"(TA));
}

__device__ __forceinline__ float warp_sum(float v) {
#pragma unroll
    for (int o = 16; o; o >>= 1) v += __shfl_xor_sync(~0u, v, o);
    return v;
}
__device__ __forceinline__ float bfround(float x) { return __bfloat162float(__float2bfloat16(x)); }

__device__ __forceinline__ void wait_count1(const uint32_t* p, uint32_t target) {
    int it = 0;
#pragma unroll 1
    while (true) {
        uint32_t v;
        asm volatile("ld.acquire.gpu.global.u32 %0, [%1];" : "=r"(v) : "l"(p) : "memory");
        if (v >= target) break;
        spin_guard(++it);
    }
}
__device__ __forceinline__ void red2(float* p, float a, float b) {
    asm volatile("red.relaxed.gpu.global.add.v2.f32 [%0], {%1, %2};" ::"l"(p), "f"(a), "f"(b) : "memory");
}
__device__ __forceinline__ void signal_count(uint32_t* p) { asm volatile("red.release.gpu.global.add.u32 [%0], 1;" ::"l"(p) : "memory"); }
__device__ __forceinline__ void e_expect(uint32_t b, uint32_t tx) {
    asm volatile("{.reg .pred p; elect.sync _|p, 0xffffffff; @p mbarrier.arrive.expect_tx.shared.b64 _, [%0], %1;}" ::"r"(b), "r"(tx) : "memory");
}
__device__ __forceinline__ void e_tma2d(uint32_t dst, const CUtensorMap* m, int c0, int c1, uint32_t bar) {
    asm volatile("{.reg .pred p; elect.sync _|p, 0xffffffff;\n @p cp.async.bulk.tensor.2d.shared::cluster.global.mbarrier::complete_tx::bytes [%0], [%1, {%3, %4}], [%2];}"
                 ::"r"(dst), "l"(m), "r"(bar), "r"(c0), "r"(c1) : "memory");
}
__device__ __forceinline__ void e_tma2d_hint(uint32_t dst, const CUtensorMap* m, int c0, int c1, uint32_t bar, uint64_t pol) {
    asm volatile("{.reg .pred p; elect.sync _|p, 0xffffffff;\n @p cp.async.bulk.tensor.2d.shared::cluster.global.mbarrier::complete_tx::bytes.L2::cache_hint [%0], [%1, {%3, %4}], [%2], %5;}"
                 ::"r"(dst), "l"(m), "r"(bar), "r"(c0), "r"(c1), "l"(pol) : "memory");
}
__device__ __forceinline__ void e_tma2d_mc(uint32_t dst, const CUtensorMap* m, int c0, int c1, uint32_t bar) {
    asm volatile("{.reg .pred p; elect.sync _|p, 0xffffffff;\n @p cp.async.bulk.tensor.2d.shared::cluster.global.mbarrier::complete_tx::bytes.multicast::cluster [%0], [%1, {%3, %4}], [%2], %5;}"
                 ::"r"(dst), "l"(m), "r"(bar), "r"(c0), "r"(c1), "h"((uint16_t)3) : "memory");
}
__device__ __forceinline__ void wait_count_w(const uint32_t* p, uint32_t target) {
    int it = 0;
#pragma unroll 1
    while (true) {
        uint32_t v;
        asm volatile("ld.acquire.gpu.global.u32 %0, [%1];" : "=r"(v) : "l"(p) : "memory");
        if (__all_sync(~0u, v >= target) | (++it > SPIN_LIMIT)) break;
        __nanosleep(100);
    }
}

#define NL 6
constexpr uint32_t SM_HB = 16384, HBK = 5120, SM_SX = 57344, SM_OX = 122880, SM_PX = 124928, SM_PA = 126976, SM_WO = 147456,
                   SM_TAB = 212992, SM_PRE = SM_TAB + 5120, SM_BAR = 227328, SM_REC_TOTAL = 227328 + 256;
constexpr uint32_t SB0 = 1024;
constexpr int B_WO = 0, B_HE = 1, B_HB = 3, B_W = 5;
constexpr int NB_MEM = 1, NB_QK = 2, NB_X1 = 3, NB_X2 = 4, NB_WIN = 5, NB_WG = 6, NB_KDONE = 7, NB_FIN0 = 8, NB_P = 9, NB_PX = 10, NB_G = 11, NB_A = 12, NB_B = 13, NB_C = 14, NB_S = 15;
#define D_NEAR 1620
#define D_FAR (D_NEAR - 90)
#define D_X2 400
#define D_V 280
#define D_W2 40
#define D_PA 40
#define D_MORE 40
#define D_MORE2 30
constexpr int E_MUL = 28;
constexpr int NPF = NL + 6, NE1 = 10;
constexpr int W0_E = 3, W0_RS = NL - 1, G_AT = 18;
struct Delays { uint32_t near, far, x2, v, w2, pa, more2, more; };
#define MISS(i, v)
#define MISS_INIT
#define MISS_OUT
#define HT(i)

__device__ __forceinline__ uint32_t clk32() { uint32_t t; asm volatile("mov.u32 %0, %%clock;" : "=r"(t) :: "memory"); return t; }
__device__ __forceinline__ uint32_t smid() { uint32_t t; asm volatile("mov.u32 %0, %%smid;" : "=r"(t)); return t; }
__device__ __forceinline__ uint32_t gtime() { uint32_t t; asm volatile("mov.u32 %0, %%globaltimer_lo;" : "=r"(t) :: "memory"); return t; }
__device__ __forceinline__ void spin_until(uint32_t t0, uint32_t d) { while (clk32() - t0 < d) {} }
template <int N> __device__ __forceinline__ uint32_t delay(uint32_t zero) {
    float x = __uint_as_float(clk32());
#pragma unroll
    for (int i = 0; i < N; i++) asm volatile("ex2.approx.ftz.f32 %0, %0;" : "+f"(x));
    return __float_as_uint(x) & zero;
}
__device__ __forceinline__ uint32_t opaque(uint32_t v) { return __shfl_sync(~0u, v, threadIdx.x & 31); }
__device__ __forceinline__ uint32_t xor_or(uint32_t a, uint32_t b, uint32_t t) {
    uint32_t r; asm volatile("lop3.b32 %0, %1, %2, %3, 0x7E;" : "=r"(r) : "r"(a), "r"(b), "r"(t)); return r;
}
__device__ __forceinline__ uint32_t settag(uint32_t v, uint32_t tag) {
    uint32_t r; asm("lop3.b32 %0, %1, 1, %2, 0xB8;" : "=r"(r) : "r"(v), "r"(tag)); return r;
}
__device__ __forceinline__ void sts2(uint32_t a, float x, float y) { asm volatile("st.shared.v2.f32 [%0], {%1,%2};" ::"r"(a), "f"(x), "f"(y) : "memory"); }
__device__ __forceinline__ void sts4f(uint32_t a, float x, float y, float z, float w) {
    asm volatile("st.shared.v4.f32 [%0], {%1,%2,%3,%4};" ::"r"(a), "f"(x), "f"(y), "f"(z), "f"(w) : "memory");
}
__device__ __forceinline__ void sts1(uint32_t a, uint32_t x) { asm volatile("st.shared.u32 [%0], %1;" ::"r"(a), "r"(x) : "memory"); }
__device__ __forceinline__ uint32_t lds1(uint32_t a) { uint32_t v; asm volatile("ld.shared.u32 %0, [%1];" : "=r"(v) : "r"(a) : "memory"); return v; }
__device__ __forceinline__ float4 lds4f(uint32_t a) {
    float4 v; asm volatile("ld.shared.v4.f32 {%0,%1,%2,%3}, [%4];" : "=f"(v.x), "=f"(v.y), "=f"(v.z), "=f"(v.w) : "r"(a) : "memory"); return v;
}
__device__ __forceinline__ float2 lds2f(uint32_t a) {
    float2 v; asm volatile("ld.shared.v2.f32 {%0,%1}, [%2];" : "=f"(v.x), "=f"(v.y) : "r"(a) : "memory"); return v;
}
__device__ __forceinline__ bool any_bit0(uint32_t x) {
    uint32_t r;
    asm volatile("{.reg .pred p, q; .reg .b32 t; and.b32 t, %1, 1; setp.ne.u32 p, t, 0; vote.sync.any.pred q, p, 0xffffffff; selp.u32 %0, 1, 0, q;}" : "=r"(r) : "r"(x));
    return r;
}
__device__ __forceinline__ float rcp_fast(float x) { float r; asm("rcp.approx.ftz.f32 %0, %1;" : "=f"(r) : "f"(x)); return r; }
__device__ __forceinline__ void stsm4(uint32_t a, uint32_t r0, uint32_t r1, uint32_t r2, uint32_t r3) {
    asm volatile("stmatrix.sync.aligned.m8n8.x4.shared.b16 [%0], {%1,%2,%3,%4};" ::"r"(a), "r"(r0), "r"(r1), "r"(r2), "r"(r3) : "memory");
}
__device__ __forceinline__ void stsm4t(uint32_t a, uint32_t r0, uint32_t r1, uint32_t r2, uint32_t r3) {
    asm volatile("stmatrix.sync.aligned.m8n8.x4.trans.shared.b16 [%0], {%1,%2,%3,%4};" ::"r"(a), "r"(r0), "r"(r1), "r"(r2), "r"(r3) : "memory");
}
__device__ __forceinline__ uint32_t and3(uint32_t a, uint32_t b, uint32_t c) {
    uint32_t r; asm("lop3.b32 %0, %1, %2, %3, 0x80;" : "=r"(r) : "r"(a), "r"(b), "r"(c)); return r;
}
__device__ __forceinline__ void red_mem(void* p, uint32_t x, uint32_t y, uint32_t z, uint32_t w, void* q, uint32_t e, bool c) {
    asm volatile("{.reg .pred p; setp.ne.u32 p, %7, 0; red.relaxed.gpu.global.add.noftz.v4.bf16x2 [%0], {%1,%2,%3,%4}; @p red.relaxed.gpu.global.add.noftz.bf16x2 [%5], %6;}"
                 ::"l"(p), "r"(x), "r"(y), "r"(z), "r"(w), "l"(q), "r"(e), "r"((uint32_t)c) : "memory");
}
__device__ __forceinline__ void stg4_if(bool c, void* p, uint32_t x) {
    asm volatile("{.reg .pred p; setp.ne.u32 p, %2, 0; @p st.relaxed.gpu.global.v4.u32 [%0], {%1,%1,%1,%1};}" ::"l"(p), "r"(x), "r"((uint32_t)c) : "memory");
}

__device__ __forceinline__ void h_load(uint32_t sb, const uint8_t* hsrc, int pass, uint32_t rank, uint32_t rot) {
    const uint8_t* src = hsrc + (size_t)pass * 65536;
    const uint32_t bar = sb + SM_BAR + 8 * (B_HB + (pass & 1)), dst = sb + SM_HB + (pass & 1) * 65536 + rank * 4 * HBK;
    e_expect(bar, 32768);
#pragma unroll 1
    for (int i = 0; i < H_PIECES; i++) {
        const uint32_t o = ((i + rot) & (H_PIECES - 1)) * (16384 / H_PIECES);
        asm volatile("{.reg .pred p; elect.sync _|p, 0xffffffff;\n"
                     " @p cp.async.bulk.shared::cluster.global.mbarrier::complete_tx::bytes.multicast::cluster [%0], [%1], %4, [%2], %3;}"
                     ::"r"(dst + o + (o >> 12) * 1024), "l"(src + o), "r"(bar), "h"((uint16_t)3), "n"(16384 / H_PIECES) : "memory");
    }
}
__device__ __forceinline__ uint4 ldg_b128(const void* p) {
    uint4 v;
    asm volatile("{.reg .b128 t; .reg .b64 a, b; ld.relaxed.gpu.global.b128 t, [%4]; mov.b128 {a, b}, t; mov.b64 {%0,%1}, a; mov.b64 {%2,%3}, b;}"
                 : "=r"(v.x), "=r"(v.y), "=r"(v.z), "=r"(v.w) : "l"(p) : "memory");
    return v;
}
__device__ __forceinline__ void stg_b128_if(bool c, void* p, uint32_t x, uint32_t y, uint32_t z, uint32_t w) {
    asm volatile("{.reg .pred p; setp.ne.u32 p, %5, 0; @p st.relaxed.gpu.global.v4.u32 [%0], {%1,%2,%3,%4};}"
                 ::"l"(p), "r"(x), "r"(y), "r"(z), "r"(w), "r"((uint32_t)c) : "memory");
}
__device__ __forceinline__ float pretag(float x, uint32_t add, uint32_t keep) { return __uint_as_float((__float_as_uint(x) + add) & keep); }

template <class F, class G>
__device__ __forceinline__ void softmax_rows(uint32_t src, uint32_t dst, uint32_t g16, int row0, F ready, G mid) {
    const uint32_t u = (g16 >> 7) & 3, e = ((g16 >> 9) << 3) | ((g16 >> 4) & 7);
    uint32_t se = src + e * 8, su = se + u * 1088, d0 = dst + e * 16 + u * 4, d1 = dst + 512 + e * 4;
    int vis = row0 + (e >> 2) - 2 * (e & 3) - 8 * u;
    asm volatile("" : "+r"(se), "+r"(su), "+r"(d0), "+r"(d1), "+r"(vis));
    ready();
    const float2 p0 = lds2f(su), p1 = lds2f(su + 256), p2 = lds2f(su + 512), p3 = lds2f(su + 768);
    const float2 m0 = lds2f(se + 4352), m1 = lds2f(se + 4352 + 256), m2 = lds2f(se + 4352 + 512), m3 = lds2f(se + 4352 + 768);
    float a0 = (p0.x + p1.x) + (p2.x + p3.x), a1 = (p0.y + p1.y) + (p2.y + p3.y);
    const float a2 = (m0.x + m1.x) + (m2.x + m3.x), a3 = (m0.y + m1.y) + (m2.y + m3.y);
    if (vis < 0) a0 = -1e9f / 0.08838834764831845f;
    if (vis < 1) a1 = -1e9f / 0.08838834764831845f;
    int k = __float_as_int(fmaxf(fmaxf(a0, a1), fmaxf(a2, a3)));
    k ^= (k >> 31) & 0x7fffffff;
    const bool hi = g16 & 64;
    const int k0 = __reduce_max_sync(~0u, hi ? INT_MIN : k), k1 = __reduce_max_sync(~0u, hi ? k : INT_MIN);
    mid();
    k = hi ? k1 : k0;
    const float m = __int_as_float(k ^ ((k >> 31) & 0x7fffffff));
    const float sl2 = 0.08838834764831845f * 1.4426950408889634f, mb = -m * sl2;
    sts1(d0, pack2(ex2(fmaf(a0, sl2, mb)), ex2(fmaf(a1, sl2, mb))));
    sts1(d1, pack2(ex2(fmaf(a2, sl2, mb)), ex2(fmaf(a3, sl2, mb))));
}

__device__ __forceinline__ uint32_t pack_h2(float lo, float hi) {
    uint32_t r; asm("cvt.rn.satfinite.f16x2.f32 %0, %1, %2;" : "=r"(r) : "f"(hi), "f"(lo)); return r;
}
__device__ __forceinline__ float2 unpack_h2(uint32_t u) {
    float2 r; asm("{.reg .b16 l, h; mov.b32 {l, h}, %2; cvt.f32.f16 %0, l; cvt.f32.f16 %1, h;}" : "=f"(r.x), "=f"(r.y) : "r"(u)); return r;
}
__device__ __forceinline__ uint32_t add_h2(uint32_t a, uint32_t b) { uint32_t r; asm("add.rn.f16x2 %0, %1, %2;" : "=r"(r) : "r"(a), "r"(b)); return r; }
__device__ __forceinline__ uint32_t max_h2(uint32_t a, uint32_t b) { uint32_t r; asm("max.f16x2 %0, %1, %2;" : "=r"(r) : "r"(a), "r"(b)); return r; }
struct U2 { uint32_t x, y; };
__device__ __forceinline__ U2 ldg_u2(const void* p) {
    U2 v; asm volatile("{.reg .b64 t; ld.relaxed.gpu.global.b64 t, [%2]; mov.b64 {%0, %1}, t;}" : "=r"(v.x), "=r"(v.y) : "l"(p) : "memory"); return v;
}
constexpr int POLL_LIMIT = 1 << 16;
constexpr float SM_L2E = 0.08838834764831845f * 1.4426950408889634f;
template <int V> struct IC { static constexpr int value = V; };
typedef unsigned long long u64;
__device__ __forceinline__ u64 ldg_u64(const void* p) { u64 v; asm volatile("ld.relaxed.gpu.global.b64 %0, [%1];" : "=l"(v) : "l"(p) : "memory"); return v; }
__device__ __forceinline__ void rec_main(uint32_t sb, const CUtensorMap* tWo, uint8_t* arena, int role, int hinfo, int wg, uint32_t zero, const Delays& dly) {
    const int hA = hinfo & 255;
    const int tid = threadIdx.x, t = tid & 127, lane = tid & 31, wi = t >> 5;
    const uint32_t bars = sb + SM_BAR;
    const int head = role >> 2, qd = role & 3, j = blockIdx.x & 1, kh = role & 1;
    const uint32_t mypar = head >= hA;
    const uint32_t wu = __reduce_max_sync(~0u, wi);
    const bool warp0 = wu == 0, warp1 = wu == 1;
    const uint8_t* hsrc = (const uint8_t*)g_himg + kh * 32768 + j * 16384;
    auto tokbase = [&](int ty) { return ((ty + 1) << 21) + blk(lb_tok(head), mypar ^ ((hinfo >> (8 + ty)) & 1)); };
    const uint32_t tbw = tokbase(wg), tbq = tokbase(0) + (qd >> 1) * 2048 + (qd & 1) * 8;
    uint32_t w[32 - NL][4];
    const uint32_t frow = ((lane >> 4) * 8 + (lane & 7)) * 128, fx = ((lane >> 3) & 1) ^ (lane & 7);
    const uint32_t wl0 = sb + wg * 65536 + frow + ((fx ^ (2 * wi)) << 4);
    uint32_t g16 = opaque(t * 16);
    auto G16 = [&]() { asm volatile("" : "+r"(g16)); return g16; };
    const uint32_t sbl = sb - wu * 512;
    const uint32_t xso = blk(lb_x2(head), mypar), cu = kh * 2048 + (2 * j + (wu >> 1)) * 512;
    const uint32_t u_xo = xso + wg * 16384 + (wu & 1) * 2048 + (cu >> 1) - wu * 256, u_to = tbw + (wu & 1) * 16384 + cu - wu * 512;
    {
        uint8_t* pp = arena + (tbw + (1 << 20) + j * 16384 + (kh ^ 1) * 2048 + g16);
        stg_rlx4(pp, 0, 0, 0, 0);
        stg_rlx4(pp + 32768, 0, 0, 0, 0);
        stg_rlx4(arena + (u_to + g16), 0, 0, 0, 0);
        stg_rlx2(arena + (u_xo + (g16 >> 1)), 0, 0);
    }
    {
        if (wg > 0) wait_count_w(&g_tick[32 + (lane & 3) * 8], 1);
        if (wg == 1) asm volatile("fence.proxy.async.global;" ::: "memory");
#pragma unroll 1
        for (int i = 0; i < 4; i++) mbar_wait_w(bars + 8 * (B_W + (wg == 2 ? 8 + i : 2 * i + wg)), 0);
#pragma unroll
        for (int p = NL; p < 32; p++) ldsm4t(w[p - NL], wl0 + p * 2048);
        fence_async_smem();
        bar_sync(wg < 2 ? NB_WG : NB_X2, wg < 2 ? 256 : 128);
        if (wg == 2 && wu < 3) {
            e_expect(bars + 8 * B_WO, 16384);
            e_tma2d(sb + SM_WO + wu * 16384, tWo, (wu >> 1) * 512 + qd * 128 + (wu & 1) * 64, head * DH, bars + 8 * B_WO);
            e_tma2d(sb + SM_WO + wu * 16384 + 8192, tWo, (wu >> 1) * 512 + qd * 128 + (wu & 1) * 64, head * DH + 64, bars + 8 * B_WO);
        }
        if (wg == 1 && warp0) {
            if (lane == 0) mbar_arrive_cluster(bars + 8 * B_HE, j ^ 1);
            mbar_wait_w(bars + 8 * B_HE, 0);
#pragma unroll 1
            for (int i = 0; i < 2; i++) h_load(sb, hsrc, i, j, head);
        }
        TL(3 + wg)
    }
    const uint32_t mrow = wg < 2 ? mem_row(wu >> 1, wg * 2 + (wu & 1), qd) : mem_row(kh, wu, 0);
    const uint32_t u_m = mrow - wu * 512, u_e = mrow + 512 - wu * 64;
#define TAB(i) lds1(sb + SM_TAB + (i) * 512 + (G16() >> 2))
    {
        const uint32_t r8 = lane & 7;
        const uint32_t tb = sb + SM_TAB + wg * 1536 + t * 4, ma = sb + SM_HB + 4096 + r8 * 128;
        if (wg < 2) {
            sts1(tb, sb + SM_WO + wi * 16384 + frow + ((fx ^ (2 * wg)) << 4));
            sts1(tb + 512, wl0);
            sts1(tb + 1024, ma + (((lane >> 3) ^ r8) << 4));
        } else {
            sts1(tb, ma + (wi & 1) * HBK + ((((wi & 2) + (lane >> 4) * 4 + ((lane >> 3) & 1)) ^ r8) << 4));
            sts1(tb + 512, ((((wi & 2) + 4) ^ r8) << 4) + ((lane & 3) == 2 ? ma + 128 + ((wi & 1) + (lane >> 3) * 2) * HBK : sb + SM_HB - 128));
            sts1(tb + 1024, mem_row(role >> 6, (role >> 4) & 3, (role >> 2) & 3) + (lane < 8 ? qd * 128 + lane * 16 : 512 + qd * 32 + (lane & 1) * 16));
        }
    }
    MISS_INIT
#define HB(ks) dadd(mkdesc(SB0 + SM_HB + ((ks) >> 2) * HBK + ((ks) & 3) * 32, 16, 1024, 1), hbo)
#define STEP_CONSTS                                                                                  \
    const uint32_t tag = (s & 1) ^ 1, ttag = ((s >> 1) & 1) ^ 1, tso = (s & 1) * 32768;              \
    G16();                            \
    const int p = s + 2, b = p & 1;                                                                  \
    uint32_t hbo = b * 4096, fz[5] = {0, 0, 0, 0, 0};                                                   \
    const uint32_t ftag = (((p - 1) >> 1) & 1) ^ 1, ptag = ((p >> 1) & 1) ^ 1;                       \
    const uint32_t pso = tbw + (1 << 20) + (b ^ 1) * 32768 + j * 16384 + kh * 2048;
#define SCHED_FENCE(i) fz[i] = clk32();
#define FZ ((fz[0] | fz[1] | fz[2] | fz[3] | fz[4]) & zero)
#define BLOCK_FENCE asm volatile("pmevent 0;" ::: "memory");
    constexpr int GAP = 32 / NL;
#define l16 (sbl + g16)
#define g8 (g16 >> 1)
    uint4 u, v;
    uint8_t *pdst, *fdst;
    auto tok_pack = [&](int ty, const float* acc, uint32_t ftag, uint32_t ptag, bool later = false) {
        const bool tg = ty == 2 || !(g16 & 64);
        const uint32_t add = tg ? (ftag ^ 1) << 16 : 0u, keep = tg ? 0xfffe0000u : ~0u;
        const uint32_t add1 = ty == 2 ? 0u : add, keep1 = ty == 2 ? ~0u : keep;
        const uint32_t add2 = ty == 0 ? add : 0u, keep2 = ty == 0 ? keep : ~0u;
        v = {pack2(pretag(acc[0], add, keep), pretag(acc[1], add1, keep1)), pack2(acc[2], acc[3]),
             pack2(pretag(acc[4], add2, keep2), pretag(acc[5], add2, keep2)), pack2(acc[6], acc[7])};
        if (ty < 2) { v.x = movm(v.x); v.z = movm(v.z); v.y = movm(v.y); v.w = movm(v.w); }
        u = {pack2(pretag(acc[8], (ptag ^ 1) << 16, 0xfffe0000u), acc[9]) | ptag, pack2(acc[10], acc[11]), pack2(acc[12], acc[13]), pack2(acc[14], acc[15])};
        if (later) return;
        v.x = settag(v.x, ftag);
        if (ty == 0) v.z = settag(v.z, ftag);
    };

#pragma unroll 1
    for (int s = -2; s < 0; s++) {
        STEP_CONSTS
        (void)tag; (void)ttag; (void)tso; (void)fz;
        float acc[16];
        mbar_wait_w(bars + 8 * (B_HB + b), 0);
        wg_fence();
#pragma unroll
        for (int i = 0; i < 32; i++) {
            if (i < NL) wgmma_ss32(acc, dadd(mkdesc(SB0 + i * 2048, 8192, 1024, 1), wg * 4096), HB(i), i != 0);
            else wgmma_rs32(acc, w[i < NL ? 0 : i - NL], HB(i), 1);
        }
        wg_commit();
        uint4 pa = {0, 0, 0, 0};
        int it = 0;
#pragma unroll 1
        while ((p > 0) & any_bit0(pa.x ^ ftag) & (++it < POLL_LIMIT)) pa = ldg_b128(arena + (pso + g16));
        pdst = arena + ((pso ^ (32768 + 2048)) + G16());
        fdst = arena + ((b ^ 1) * 32768 + u_to + g16);
        wg_wait<0>();
#pragma unroll
        for (int k = 0; k < 4; k++) { acc[2 * k] += bflo((&pa.x)[k]); acc[2 * k + 1] += bfhi((&pa.x)[k]); }
        tok_pack(wg, acc, ftag, ptag);
        stg_b128_if(true, pdst, u.x, u.y, u.z, u.w);
        stg_b128_if(p > 0, fdst, v.x, v.y, v.z, v.w);
        if (p == 0) {
            TL(2)
            if (wg != 1) bar_arrive(NB_C, 288);
        }
    }
    if (wg == 1 && warp0) {
        wait_count_w(&g_tick[32 + (lane & 3) * 8], 2);
        asm volatile("fence.proxy.async.global;" ::: "memory");
        bar_sync(NB_C, 288);
        if (g16 == 0) mbar_arrive_cluster(bars + 8 * B_HE, j ^ 1);
        mbar_wait_w(bars + 8 * B_HE, 1);
        h_load(sb, hsrc, 2, j, head);
    }

    auto qk_loop = [&](auto wgc) {
        constexpr int WG = decltype(wgc)::value;
        uint32_t w0[NL][4], lm0;
        auto w0_load = [&]() {
            const uint32_t wl = TAB(WG * 3 + 1);
            lm0 = TAB(WG * 3 + 2);
#pragma unroll
            for (int k = 0; k < NL; k++) ldsm4t(w0[k], wl + k * 2048);
        };
        const uint32_t wlo = WG * 65536 - SM_WO - wu * 16384, wlx = __reduce_max_sync(~0u, (wi ^ WG) << 5);
        uint32_t tq0, lm, lm1, dx2 = dly.x2;
        auto proj_pre = [&](int s) {
            uint32_t wz0 = zero;
#pragma unroll
            for (int k = 0; k < NL; k += 2) wz0 = and3(wz0, w0[k][0], w0[k + 1 < NL ? k + 1 : k][0]);
            lm = lm0 + (s & 1) * 65536 + wz0; lm1 = lm ^ 64;
            asm volatile("" : "+r"(lm), "+r"(lm1));
        };
        auto proj = [&](int s, auto mid) {
            bar_sync(NB_MEM, 384);
            float c[4][4];
            uint32_t bf[16][4], tq1;
#pragma unroll
            for (int it = 0; it < 3; it++) ldsm4(bf[it], (it & 1 ? lm1 : lm) + (it >> 1) * HBK);
            mid(-1);
#pragma unroll
            for (int it = 0; it < 16; it++) {
                const uint32_t* bfr = bf[it];
                if (it + 3 < 16) ldsm4(bf[it + 3 < 16 ? it + 3 : 0], (it & 1 ? lm : lm1) + ((it + 3) >> 1) * HBK);
                const uint32_t* wa = 2 * it < NL ? w0[2 * it < NL ? 2 * it : 0] : w[2 * it < NL ? 0 : 2 * it - NL];
                const uint32_t* wb = 2 * it + 1 < NL ? w0[2 * it + 1 < NL ? 2 * it + 1 : 0] : w[2 * it + 1 < NL ? 0 : 2 * it + 1 - NL];
                float *ca = c[(2 * it) & 3], *cb = c[(2 * it + 1) & 3];
                if (it < 2) { mma16816z(ca, wa, bfr[0], bfr[1]); mma16816z(cb, wb, bfr[2], bfr[3]); }
                else { mma16816(ca, wa[0], wa[1], wa[2], wa[3], bfr[0], bfr[1]); mma16816(cb, wb[0], wb[1], wb[2], wb[3], bfr[2], bfr[3]); }
                mid(it);
                if (it == 15) { tq1 = clk32(); bar_arrive(NB_QK, 384); }
            }
            const uint32_t xo = u_xo + (G16() >> 1);
            float r[4];
#pragma unroll
            for (int e = 0; e < 4; e++) {
                constexpr float SH = SM_L2E / 64;
                r[e] = WG ? (c[0][e] + c[1][e]) + (c[2][e] + c[3][e]) : fmaf(c[2][e] + c[3][e], SH, (c[0][e] + c[1][e]) * SH);
            }
            const uint32_t r0 = pack2(r[0], r[1]), r1 = pack2(r[2], r[3]);
            const uint32_t m0 = movm(r0), m1 = movm(r1);
            tq0 = clk32();
            stg_rlx2(arena + xo, settag(m0, (s & 1) ^ 1), m1);
            tq0 += tq1 & zero;
        };
        w0_load();
        proj_pre(0);
        if (WG == 1) bar_sync(NB_P, 256);
        proj(0, [](int) {});
        if (WG == 0) mbar_wait_w(bars + 8 * B_WO, 0);
#pragma unroll 1
        for (int s = 0;; s++) {
            STEP_CONSTS
            uint4 pa;
            float acc[16];
            auto acc_init = [&]() {
#pragma unroll
                for (int k = 0; k < 4; k++) { acc[2 * k] = bflo((&pa.x)[k]); acc[2 * k + 1] = bfhi((&pa.x)[k]); acc[8 + 2 * k] = __uint_as_float((&pa.x)[k] & zero); acc[9 + 2 * k] = __uint_as_float(~(&pa.x)[k] & zero); }
            };
            uint32_t wf[NPF][4], a3;
#define WF(f) ((a3 ^ (((f) & 1) * 64)) + ((f) >> 1) * 2048)
            if (WG == 1) {
                float sc[5][4];
                uint32_t sx0 = sb + SM_SX - wu * (2560 - 16) + G16() * 5;
                asm volatile("" : "+r"(sx0));
                int it = 0;
                bool bad;
#pragma unroll 1
                do {
                    uint4 kf[2][2];
                    U2 qf[2], x[8];
                    const uint32_t gz = g16 | (it & zero);
                    const uint8_t *ts = arena + (tso + tbw + gz), *tq = arena + (tso + tbq + gz), *xp = arena + (xso + (gz >> 1));
#pragma unroll
                    for (int a = 0; a < 4; a++) kf[a >> 1][a & 1] = ldg_b128(ts + (a >> 1) * 16384 + (a & 1) * 2048);
                    spin_until(tq0, dx2 - 100);
#pragma unroll
                    for (int a = 0; a < 2; a++) qf[a] = ldg_u2(tq + a * 16384);
                    spin_until(tq0, dx2);
#pragma unroll
                    for (int i = 0; i < 8; i++) x[i] = ldg_u2(xp + (i >> 2) * 16384 + (i & 3) * 1024);
                    const uint32_t q0[4] = {hadd2(x[0].x, x[1].x), qf[0].x, hadd2(x[0].y, x[1].y), qf[0].y};
                    const uint32_t q1[4] = {hadd2(x[2].x, x[3].x), qf[1].x, hadd2(x[2].y, x[3].y), qf[1].y};
                    const uint32_t bt = ((qf[0].x ^ ttag) | (qf[1].x ^ ttag)) | ((kf[0][0].x ^ ttag) | (kf[0][1].x ^ ttag)) | ((kf[1][0].x ^ ttag) | (kf[1][1].x ^ ttag));
                    uint32_t bx = 0;
#pragma unroll
                    for (int i = 0; i < 8; i += 2) bx |= (x[i].x ^ tag) | (x[i + 1].x ^ tag);
                    mma16816z(sc[0], q0, kf[0][0].x, kf[0][0].y);
                    mma16816z(sc[1], q0, kf[0][0].z, kf[0][0].w);
                    mma16816z(sc[2], q0, kf[0][1].x, kf[0][1].y);
                    mma16816z(sc[3], q0, kf[0][1].z, kf[0][1].w);
                    mma16816z(sc[4], q0, hadd2(x[4].x, x[5].x), hadd2(x[4].y, x[5].y));
                    bad = any_bit0(bt | bx) & (++it < POLL_LIMIT);
                    mma16816(sc[0], q1[0], q1[1], q1[2], q1[3], kf[1][0].x, kf[1][0].y);
                    mma16816(sc[1], q1[0], q1[1], q1[2], q1[3], kf[1][0].z, kf[1][0].w);
                    mma16816(sc[2], q1[0], q1[1], q1[2], q1[3], kf[1][1].x, kf[1][1].y);
                    mma16816(sc[3], q1[0], q1[1], q1[2], q1[3], kf[1][1].z, kf[1][1].w);
                    mma16816(sc[4], q1[0], q1[1], q1[2], q1[3], hadd2(x[6].x, x[7].x), hadd2(x[6].y, x[7].y));
                } while (bad);
                MISS(1, it - 1)
                sts4(sx0, pack_h2(sc[0][0], sc[0][1]), pack_h2(sc[1][0], sc[1][1]), pack_h2(sc[2][0], sc[2][1]), pack_h2(sc[3][0], sc[3][1]));
                sts1(sx0 + 64 - wu * 12, pack_h2(sc[4][0], sc[4][1]));
                bar_arrive(NB_X1, 384);
                if (it > 1 && s > 1) dx2 += dly.more2;
                auto tok_sts = [&]() {
#pragma unroll
                    for (int n = 0; n < 5; n++) sts2(sb + SM_SX + 2560 + g8 + n * 1088, sc[n][2], sc[n][3]);
                };
                a3 = TAB(WG * 3);
                if (s == 0) mbar_wait_w(bars + 8 * B_WO, 0);
                softmax_rows(sb + SM_SX + 2560, sb + SM_PX + 1024, g16 | (clk32() & zero), qd * 8, [&]() { BLOCK_FENCE tok_sts(); bar_sync(NB_PX, 128); }, [&]() {
                    BLOCK_FENCE
#pragma unroll
                    for (int f = 0; f < NE1; f++) ldsm4t(wf[f], WF(f));
                    BLOCK_FENCE
                });
            } else {
                a3 = TAB(WG * 3);
                if (warp1 && (s & 3) == 1) asm volatile("fence.proxy.async.global;" ::: "memory");
                spin_until(tq0, dly.pa);
                uint4 x, y;
                int it = 0;
#pragma unroll 1
                do { x = ldg_b128(arena + (pso + g16)); y = ldg_b128(arena + (pso + tokbase(1) - tokbase(0) + g16)); }
                while ((p <= NSEG) & any_bit0(xor_or(x.x, y.x, ftag)) & (++it < POLL_LIMIT));
                sts4(sb + SM_PA + g16, x.x, x.y, x.z, x.w);
                sts4(sb + SM_PA + 2048 + g16, y.x, y.y, y.z, y.w);
                bar_sync(NB_X1, 384);
                if (g16 < 32) asm volatile("red.relaxed.gpu.global.max.u32 [%0], %1; red.relaxed.gpu.global.add.u32 [%0+4], 1;"
                                                    ::"l"(arena + ((blk(LB_TIME, 0) ^ (g16 << 8)) + qd * 1024 + (tq0 & zero))), "r"(gtime()) : "memory");
                __syncwarp();
                const uint32_t tx = clk32();
                spin_until(tx, dly.w2);
            }
#pragma unroll
            for (int f = WG ? NE1 : 0; f < NPF; f++) ldsm4t(wf[f], WF(f));
            if (s + 1 == NSEG) { bar_arrive(NB_X2, 384); break; }
            const uint32_t oa = l16 + SM_OX, slot = mem_slot(s + 1);
            float c[4][4];
            uint32_t ob[4][4];
            BLOCK_FENCE
            bar_sync(NB_X2, 384);
            ldsm4t(ob[0], oa);
            ldsm4t(ob[1], oa + 512);
            SCHED_FENCE(0)
#pragma unroll
            for (int f = 0; f < 16; f++) {
                const uint32_t *a = wf[f % NPF], *o = ob[f >> 2] + (f & 2);
                if (f < 4) mma16816z(c[f], a, o[0], o[1]);
                else mma16816(c[f & 3], a[0], a[1], a[2], a[3], o[0], o[1]);
                if (f == 3) ldsm4t(ob[2], oa + 1024);
                if (f == 5) { ldsm4t(ob[3], oa + 1536); if (NPF < 16) ldsm4t(wf[0], WF(NPF)); }
                if (f == 7) {
#pragma unroll
                    for (int k = NPF + 1; k < 16; k++) ldsm4t(wf[k - NPF], WF(k));
                }
                if (f == 3 || f == 5 || f == 7) SCHED_FENCE(f / 2)
                if (f == 11) {
#pragma unroll
                    for (int k = NL - W0_E; k < NL; k++) ldsm4t(w0[k], (a3 ^ wlx) + wlo + k * 2048);
                    SCHED_FENCE(4)
                }
            }
            const float last = c[1][3] + c[3][3], one = __uint_as_float(CNT1 << 16);
            red_mem(arena + (u_m + slot + G16()), pack2(c[0][0] + c[2][0], c[0][1] + c[2][1]), pack2(c[0][2] + c[2][2], c[0][3] + c[2][3]),
                    pack2(c[1][0] + c[3][0], c[1][1] + c[3][1]), pack2(c[1][2] + c[3][2], g16 & 16 ? one : last),
                    arena + (u_e + slot + ((g16 >> 3) & ~3u)), pack2(last, one), g16 & 16);
            hbo += FZ;
            constexpr int NS = NL - W0_RS, GS = (32 - NL + NS) / NS;
            BLOCK_FENCE
#pragma unroll
            for (int k = NL - W0_E - 1; k >= 0; k--) ldsm4t(w0[k], (a3 ^ wlx) + wlo + k * 2048);
            lm0 = TAB(WG * 3 + 2);
            if (WG == 1) pa = lds4(sb + SM_PA + 2048 + g16);
            if (WG == 0) {
                bar_arrive(NB_WIN, 384);
                pa = lds4(sb + SM_PA + g16);
                acc_init();
                asm volatile("" : F16(acc, 0));
                BLOCK_FENCE
            }
            wg_fence();
            bar_sync(WG ? NB_WIN : NB_B, WG ? 384 : 256);
#pragma unroll
            for (int i = 0; i < 32; i++) {
                const int k = i / GS;
                if (i >= 32 - NL + NS) wgmma_rs32(acc, w0[i < 32 - NL + NS ? 0 : i - 32 + NL], HB(i - 32 + NL), 1);
                else if (i % GS == GS - 1 && k < NS) wgmma_ss32(acc, mkdesc(SB0 + WG * 65536 + k * 2048, 8192, 1024, 1), HB(k), 1);
                else wgmma_rs32(acc, w[i - (k < NS ? k : NS)], HB(NL + i - (k < NS ? k : NS)), WG == 0 || i);
                if (WG == 1 && i == G_AT) bar_arrive(NB_B, 256);
                if (WG == 1 && i == 31 - NL + NS) wg_fence();
            }
            wg_commit();
            BLOCK_FENCE
            if (WG == 1 && warp0 && !(s & 3)) wait_count_w(&g_tick[32 + ((G16() >> 4) & 3) * 8], min((s + 1) / 4 + 3, 17));
            auto tok_store = [&](int m) {
                if (m & 1) stg_b128_if(true, arena + ((b ^ 1) * 32768 + u_to + G16()), v.x, v.y, v.z, v.w);
                if (m & 2) stg_b128_if(p < NSEG, arena + ((pso ^ (32768 + 2048)) + G16()), u.x, u.y, u.z, u.w);
            };
            if (WG == 0) proj_pre(s + 1);
            BLOCK_FENCE
            wg_wait<0>();
            if (WG == 0) {
                asm volatile("" : F16(acc, 0));
                proj(s + 1, [&](int it) {
                    if (it < 0) {
                        SCHED_FENCE(0)
                        asm volatile("" : F16(acc, 0));
                        tok_pack(WG, acc, ftag, ptag, true);
                        tok_store(2);
                        SCHED_FENCE(1)
                    }
                    if (it == 2) { SCHED_FENCE(2) v.x = settag(v.x, ftag); v.z = settag(v.z, ftag); tok_store(1); SCHED_FENCE(3) }
                });
                tq0 += (fz[0] | fz[1] | fz[2] | fz[3]) & zero;
            } else {
#pragma unroll
                for (int k = 0; k < 4; k++) { acc[2 * k] += bflo((&pa.x)[k]); acc[2 * k + 1] += bfhi((&pa.x)[k]); }
                tok_pack(WG, acc, ftag, ptag);
                proj_pre(s + 1);
                asm volatile("" : "+r"(u.x), "+r"(u.y), "+r"(u.z), "+r"(u.w), "+r"(v.x), "+r"(v.y), "+r"(v.z), "+r"(v.w));
                BLOCK_FENCE
                bar_sync(NB_P, 256);
                tok_store(3);
                proj(s + 1, [](int) {});
            }
        }
    };
    if (wg == 0) {
        qk_loop(IC<0>());
    } else if (wg == 1) {
        qk_loop(IC<1>());
    } else {
        const uint32_t ONES = 0x3f803f80u, u_o = qd * 65536 + head * 2048 + wu * 384;
        uint32_t tw = 0, dl = 0, dbase = kh == mypar ? dly.near : dly.far, dst0, dx0;
        dst0 = TAB(6); dx0 = TAB(7);
        uint32_t ov[4] = {0, 0, 0, 0};
        auto o_store = [&](int s) {
            uint8_t* od = (uint8_t*)g_O + (uint32_t)(s * (32 * NH * DH * 2) + u_o + (G16() >> 2));
#pragma unroll
            for (int a = 0; a < 4; a++) stg_rlx1(od + a * 128, ov[a]);
        };
        uint4 vf[2][2], pa;
        auto tok_fetch = [&](int s) {
            const uint8_t* ts = arena + ((s & 1) * 32768 + tbw + g16);
#pragma unroll
            for (int a = 0; a < 4; a++) vf[a >> 1][a & 1] = ldg_b128(ts + (a >> 1) * 16384 + (a & 1) * 2048);
            pa = ldg_b128(arena + (tbw + (1 << 20) + (~s & 1) * 32768 + j * 16384 + kh * 2048 + g16));
        };
        tok_fetch(0);
        TL(9)
        TL(6)
#pragma unroll 1
        for (int s = 0;; s++) {
            STEP_CONSTS
#define VFBAD ((vf[0][0].x ^ ttag) | (vf[0][1].x ^ ttag) | (vf[1][0].x ^ ttag) | (vf[1][1].x ^ ttag))
#define TOKBAD (VFBAD | (p <= NSEG ? pa.x ^ ftag : 0))
            {
                const uint32_t dst = dst0 + b * 65536, dx = dx0 + b * 65536;
                const uint8_t *ms = arena + (u_m + mem_slot(s) + g16), *me = arena + (u_e + mem_slot(s) + ((g16 >> 3) & ~3u));
                uint32_t em = g16 & 16 ? 0u : ~0u;
                asm volatile("" : "+l"(ms), "+l"(me), "+r"(em));
                spin_until(tw, dl);
                int it = 0;
                bool bad;
#pragma unroll 1
                do {
                    uint4 m[4];
                    uint32_t x[4];
#pragma unroll
                    for (int i = 0; i < 4; i++) m[i] = ldg_rlx4(ms + i * 1024);
#pragma unroll
                    for (int i = 0; i < 4; i++) x[i] = ldg_rlx1(me + i * 1024);
#pragma unroll
                    for (int i = 0; i < 3; i++) {
                        stsm4t(dst + i * 2 * HBK, m[i].x, m[i].y, m[i].z, m[i].w);
                        if (i == 1) asm volatile("{.reg .pred p; setp.eq.s32 p, %0, 0; @p bar.arrive %1, 256;}" ::"r"(it), "n"(NB_P) : "memory");
                    }
                    uint32_t c = m[0].w & m[1].w, r, msk = ~(it << 16) & CNT_ALL << 16;
                    asm volatile("" : "+r"(c), "+r"(msk));
                    SCHED_FENCE(1)
                    stsm4t(dst + 6 * HBK, m[3].x, m[3].y, m[3].z, m[3].w);
                    stsm4t(dx, x[0], x[1], x[2], x[3]);
                    asm volatile("{.reg .pred p, q; .reg .b32 t, u; lop3.b32 t, %1, %2, %3, 0x80; lop3.b32 u, %4, %5, %6, 0x80; lop3.b32 t, t, %8, %7, 0xa8;\n"
                                 " lop3.b32 t, t, u, %9, 0x2a; setp.ne.u32 p, t, 0; vote.sync.any.pred q, p, 0xffffffff; @!q bar.arrive %10, 384; selp.u32 %0, 1, 0, q;}"
                                 : "=r"(r) : "r"(c), "r"(m[2].w), "r"(m[3].w), "r"(x[0]), "r"(x[1]), "r"(x[2]), "r"(x[3]), "r"(em), "r"(msk), "n"(NB_MEM) : "memory");
                    bad = r; it++;
                } while (bad);
                if (it > 1 && s > 1) dbase += dly.more;
                MISS(0, it - 1) HT(5)
            }
            if (s == 1) { TL(7) TLC(0) }
            if (s == 63) TLC(1)
            if (s == 0) TL(13)
            o_store(max(s - 1, 0));
            fence_async_smem();
            hbo += fz[1] & zero;
            int it = 0;
#pragma unroll 1
            while (any_bit0(TOKBAD) & (++it < POLL_LIMIT)) tok_fetch(s + (it & zero));
            float acc[20];
#pragma unroll
            for (int k = 0; k < 4; k++) { acc[2 * k] = bflo((&pa.x)[k]); acc[2 * k + 1] = bfhi((&pa.x)[k]); acc[8 + 2 * k] = acc[9 + 2 * k] = acc[16 + k] = __uint_as_float(pa.x & zero); }
            if (p <= NSEG) mbar_wait_w(bars + 8 * (B_HB + b), (p >> 1) & 1);
            asm volatile("" : F16(acc, 0), F4(acc, 16));
            BLOCK_FENCE
            wg_fence();
            bar_sync(NB_QK, 384);
#pragma unroll
            for (int i = 0; i < 32; i++) {
                const int k = i / GAP;
                if (i % GAP == GAP - 1 && k < NL) wgmma_ss40(acc, mkdesc(SB0 + 131072 + k * 2048, 8192, 1024, 1), HB(k), 1);
                else wgmma_rs40(acc, w[i - (k < NL ? k : NL)], HB(NL + i - (k < NL ? k : NL)), 1);
            }
            wg_commit();
            uint8_t* vo = arena + (u_xo + (G16() >> 1));
            pdst = arena + ((pso ^ (32768 + 2048)) + G16());
            fdst = arena + ((b ^ 1) * 32768 + u_to + g16);
            BLOCK_FENCE
            wg_wait<0>();
            stg_rlx2(vo, settag(pack2(acc[16], acc[17]), tag), pack2(acc[18], acc[19]));
            const uint32_t tv = clk32();
            tok_pack(2, acc, ftag, ptag);
            stg_b128_if(p <= NSEG, fdst, v.x, v.y, v.z, v.w);
            stg_b128_if(p < NSEG, pdst, u.x, u.y, u.z, u.w);
            const uint8_t* xp = arena + (xso + 32768 + (G16() >> 1));
            const uint32_t sxa = sb + SM_SX - wu * 2560 + G16() * 5;
            uint32_t sel[2];
            {
                const uint32_t q = (G16() >> 4 ^ g16 >> 6 & 1) & 3;
                sel[0] = q == 0 ? 0x3c00 : 0; sel[1] = q == 2 ? 0x3c00 : 0;
                asm volatile("" : "+r"(sel[0]), "+r"(sel[1]));
            }
            uint32_t xv[4], gt = 0;
            auto pv = [&](uint32_t p0, uint32_t p1, uint32_t p2, uint32_t p3, uint32_t p4, auto getv, auto done) {
                float oc[2][4], lc[4] = {0.f, 0.f, 0.f, 0.f};
                mma16816(lc, ONES, ONES, ONES, ONES, p0, p1);
                mma16816z(oc[0], &vf[0][0].x, p0, p1);
                mma16816z(oc[1], &vf[1][0].x, p0, p1);
                mma16816(lc, ONES, ONES, ONES, ONES, p2, p3);
                mma16816(oc[0], vf[0][1].x, vf[0][1].y, vf[0][1].z, vf[0][1].w, p2, p3);
                mma16816(oc[1], vf[1][1].x, vf[1][1].y, vf[1][1].z, vf[1][1].w, p2, p3);
                mma1688(lc, ONES, ONES, p4);
                getv();
                mma1688(oc[0], xv[0], xv[1], p4);
                mma1688(oc[1], xv[2], xv[3], p4);
                done(__float_as_uint(oc[0][0]) | __float_as_uint(oc[1][0]) | __float_as_uint(lc[0]));
                const float r0 = rcp_fast(lc[0]), r1 = rcp_fast(lc[1]);
                ov[0] = pack2(oc[0][0] * r0, oc[0][1] * r1); ov[1] = pack2(oc[0][2] * r0, oc[0][3] * r1);
                ov[2] = pack2(oc[1][0] * r0, oc[1][1] * r1); ov[3] = pack2(oc[1][2] * r0, oc[1][3] * r1);
            };
            bool bad;
            it = 0;
#pragma unroll 1
            do {
                U2 xr[4];
                asm volatile("{.reg .pred p; setp.eq.s32 p, %0, 0; @p bar.sync %1, 384;}" ::"r"(it), "n"(NB_X1) : "memory");
                uint4 sx[5];
#pragma unroll
                for (int i = 0; i < 5; i++) sx[i] = lds4(sxa + i * 16);
                if (it == 0) { gt = gtime(); tw = clk32(); }
                spin_until(tv, dly.v);
#pragma unroll
                for (int i = 0; i < 4; i++) xr[i] = ldg_u2(xp + i * 1024);
                uint32_t h[5], h0[4];
#pragma unroll
                for (int n = 0; n < 4; n++) h0[n] = add_h2((&sx[0].x)[n], (&sx[1].x)[n]);
#pragma unroll
                for (int n = 0; n < 4; n++) h[n] = add_h2(h0[n], add_h2((&sx[2].x)[n], (&sx[3].x)[n]));
                h[4] = add_h2(add_h2(sx[4].x, sx[4].y), add_h2(sx[4].z, sx[4].w));
                uint32_t hm = max_h2(max_h2(max_h2(h[0], h[1]), h[2]), max_h2(h[3], h[4]));
                float2 a[5];
                float mb;
                {
                    float d[2][4];
                    const uint32_t hs = __byte_perm(hm, hm, 0x1032);
#pragma unroll
                    for (int k = 0; k < 2; k++)
                        asm volatile("mma.sync.aligned.m16n8k8.row.col.f32.f16.f16.f32 {%0,%1,%2,%3},{%4,%5},{%6},{%7,%7,%7,%7};"
                                     : "=f"(d[k][0]), "=f"(d[k][1]), "=f"(d[k][2]), "=f"(d[k][3]) : "r"(hm), "r"(hs), "r"(sel[k]), "f"(0.f));
#pragma unroll
                    for (int n = 0; n < 5; n++) a[n] = unpack_h2(h[n]);
                    mb = -64.0f * fmaxf(fmaxf(fmaxf(d[0][0], d[0][1]), fmaxf(d[0][2], d[0][3])), fmaxf(fmaxf(d[1][0], d[1][1]), fmaxf(d[1][2], d[1][3])));
                }
                uint32_t pm[5];
#pragma unroll
                for (int n = 0; n < 5; n++) pm[n] = pack2(ex2(fmaf(a[n].x, 64.0f, mb)), ex2(fmaf(a[n].y, 64.0f, mb)));
                pv(pm[0], pm[1], pm[2], pm[3], pm[4], [&]() {
                    xv[0] = hadd2(xr[0].x, xr[1].x); xv[1] = hadd2(xr[0].y, xr[1].y);
                    xv[2] = hadd2(xr[2].x, xr[3].x); xv[3] = hadd2(xr[2].y, xr[3].y);
                }, [](uint32_t) {});
                bad = any_bit0((xr[0].x ^ tag) | (xr[1].x ^ tag) | (xr[2].x ^ tag) | (xr[3].x ^ tag)) & (++it < POLL_LIMIT);
                stsm4(sb + SM_OX + g16, ov[0], ov[1], ov[2], ov[3]);
            } while (bad);
                MISS(2, it - 1)
            bar_sync(NB_X2, 384);
            BLOCK_FENCE
            U2 tv2 = {0, 0};
            const uint8_t* tp = arena + (blk(LB_TIME, mypar) + ((G16() << 6) & 0xc00));
            {
                const uint4 pp = lds4(l16 + SM_PX + 1024);
                const uint32_t p4 = lds1(sb + SM_PX + 512 + 1024 - wu * 128 + (G16() >> 2));
                tv2 = ldg_u2(tp);
                if (warp0 && s + 3 <= NSEG) h_load(sb, hsrc, s + 3, j, head);
                pv(pp.x, pp.y, pp.z, pp.w, p4, []() {}, [&](uint32_t r) { bar_arrive(NB_WIN + (r & zero), 384); });
            }
            dst0 = TAB(6); dx0 = TAB(7);
            const uint32_t zo = TAB(8);
                HT(7)
            BLOCK_FENCE
            if (s + 1 == NSEG) break;
            asm volatile("" : "+r"(tv2.y));
            it = 0;
            uint32_t tm = __reduce_max_sync(~0u, tv2.y < 32 * (s + 1) ? ~0u : tv2.x);
#pragma unroll 1
            while ((tm == ~0u) & (++it < 16)) { tv2 = ldg_u2(tp); tm = __reduce_max_sync(~0u, tv2.y < 32 * (s + 1) ? ~0u : tv2.x); }
            const uint32_t e = tm - gt;
            MISS(3, it - 1) MISS(4, gt)
            tok_fetch(s + 1);
            stg4_if(g16 < 160, arena + (zo + mem_slot(s + 3)), 0);
            dl = dbase + (e > 4096 ? 0 : e * E_MUL >> 4);
        }
        o_store(NSEG - 1);
        TL(8)
    }
    MISS_OUT
}

struct RecMaps { CUtensorMap wq, wk, wv, wo, wmod, w3, w1; };
struct RecPtrs { const bf16 *x, *mem0, *c, *wmod, *w1, *w3; uint8_t* arena; uint32_t zero; const bf16 *w2, *w4, *wo; Delays dly; };

__device__ __forceinline__ float silu_bf(const bf16* c, int i) {
    const float v = __bfloat162float(c[i]);
    return bfround(__fdividef(v, 1.0f + __expf(-v)));
}
#define LN_FREE 6
#define LN_SEQ 0xcba6420987531ull
#define W_LATE 1000
#define W_OPEN 1400
__device__ __noinline__ uint32_t side_window_(const uint8_t* arena, uint32_t n);
#define side_window(arena, n) n = side_window_(arena, n)
__device__ __noinline__ void rec_ln(uint32_t sb, const bf16* x, const uint8_t* arena, int id, int r0) {
    int r1 = 32;
    uint32_t n = 0;
    const int tid = threadIdx.x, lane = tid & 31, wid = __reduce_max_sync(~0u, tid >> 5);
    const uint32_t ring = sb + wid * 8192 + lane * 16, coef = sb + SM_PRE;
    x += (id * 8 + wid) * 2 * DM + lane * 8;
#pragma unroll 1
    for (int r = r0 - 1; r < r1; r++) {
        if (r > 3) side_window(arena, n);
        if (r + 1 < r1) {
#pragma unroll
            for (int i = 0; i < 8; i++)
                asm volatile("cp.async.cg.shared.global [%0], [%1], 16;" ::"r"(ring + (~r & 1) * 4096 + i * 512), "l"(x + (r + 1) * 64 * DM + i * 256) : "memory");
        }
        asm volatile("cp.async.commit_group; cp.async.wait_group 1;" ::: "memory");
        if (r < r0) continue;
        const uint32_t src = ring + (r & 1) * 4096;
        float m[2] = {0.f, 0.f}, rs[2];
#pragma unroll 1
        for (int ps = 0; ps < 2; ps++) {
            float t[2][2] = {{0.f, 0.f}, {0.f, 0.f}};
#pragma unroll 1
            for (int i = 0; i < 2048; i += 512) {
#pragma unroll
                for (int h = 0; h < 2; h++) {
                    const uint4 u = lds4(src + h * 2048 + i);
#pragma unroll
                    for (int e = 0; e < 4; e++) {
                        const float a = bflo((&u.x)[e]) - m[h], c = bfhi((&u.x)[e]) - m[h];
                        t[h][0] = fmaf(a, ps ? a : 1.0f, t[h][0]); t[h][1] = fmaf(c, ps ? c : 1.0f, t[h][1]);
                    }
                }
            }
            rs[0] = t[0][0] + t[0][1]; rs[1] = t[1][0] + t[1][1];
#pragma unroll 1
            for (int o = 16; o; o >>= 1) { rs[0] += __shfl_xor_sync(~0u, rs[0], o); rs[1] += __shfl_xor_sync(~0u, rs[1], o); }
            if (!ps) { m[0] = rs[0] * (1.0f / DM); m[1] = rs[1] * (1.0f / DM); }
        }
        rs[0] = rsqrtf(rs[0] * (1.0f / DM) + 1e-5f); rs[1] = rsqrtf(rs[1] * (1.0f / DM) + 1e-5f);
        if (r == r0) {
#pragma unroll 1
            for (int i = tid; i < 2 * DM / 4; i += 256) {
                float t[4];
                int it = 0;
                uint32_t ok;
#pragma unroll 1
                do {
                    uint4 u[8];
#pragma unroll
                    for (int k = 0; k < 8; k++) u[k] = ldg_rlx4(g_modp + k * 2 * DM + i * 4);
                    ok = 1;
#pragma unroll
                    for (int k = 0; k < 32; k++) { const uint32_t w = (&u[k >> 2].x)[k & 3]; ok &= w; t[k & 3] = k < 4 ? __uint_as_float(w) : t[k & 3] + __uint_as_float(w); }
                } while (!__all_sync(~0u, ok) & (++it < SPIN_LIMIT));
                const float o = i >> 8;
                const uint32_t lo = pack2(t[0], t[1]), hi = pack2(t[2], t[3]);
                sts4f(coef + (i >> 8) * 4096 + (i & 1) * 2048 + ((i & 255) >> 1) * 16, bflo(lo) + o, bfhi(lo) + o, bflo(hi) + o, bfhi(hi) + o);
            }
            bar_sync(NB_FIN0, 256);
            if (tid == 0 && r0 == 0) TL(2)
        }
        uint8_t* dst = (uint8_t*)g_himg + (r * 2 + (id >> 1)) * 65536 + (lane >> 3) * 4096 + wid * 256;
#pragma unroll 1
        for (int i = 0; i < 4; i++) {
            const uint32_t ca = coef + i * 512 + lane * 16;
            const float4 s0 = lds4f(ca), s1 = lds4f(ca + 2048), c0 = lds4f(ca + 4096), c1 = lds4f(ca + 6144);
            const float sh[8] = {s0.x, s0.y, s0.z, s0.w, s1.x, s1.y, s1.z, s1.w}, sc[8] = {c0.x, c0.y, c0.z, c0.w, c1.x, c1.y, c1.z, c1.w};
#pragma unroll
            for (int h = 0; h < 2; h++) {
                uint4 u = lds4(src + h * 2048 + i * 512);
#pragma unroll
                for (int e = 0; e < 4; e++) {
                    uint32_t& w = (&u.x)[e];
                    w = pack2(fmaf((bflo(w) - m[h]) * rs[h], sc[2 * e], sh[2 * e]), fmaf((bfhi(w) - m[h]) * rs[h], sc[2 * e + 1], sh[2 * e + 1]));
                }
                *(uint4*)(dst + i * 16384 + ((id & 1) == (i >> 1) ? 65536 : 2048) + h * 128 + (((lane ^ (2 * wid + h)) & 7) << 4)) = u;
            }
        }
        if (r == 0) {
            if (tid == 0) TLX(10)
            int ro, it = 0;
#pragma unroll 1
            do asm volatile("ld.volatile.shared.u32 %0, [%1];" : "=r"(ro) : "r"(sb + SM_BAR + 192) : "memory"); while ((ro == INT_MIN) & (++it < SPIN_LIMIT));
            if (ro >= 0) r1 = 2;
        }
        if (r && !(r & 1)) continue;
        bar_sync(r ? NB_FIN0 : NB_C, r ? 256 : 320);
        if (tid == 0 && r == 0) TLX(11)
        if (wid == (r >> 1 & 7)) {
            if (r == 1) bar_arrive(NB_B, 64);
            if (r == 3) wait_count_w(&g_tick[32 + id * 8], 2);
            if (lane == 0) { signal_count(&g_tick[32 + id * 8]); if (r == 0) TLX(12) }
            __syncwarp();
        }
    }
}
__device__ __noinline__ uint32_t side_window_(const uint8_t* arena, uint32_t n) {
    U2 v;
    int it = 0;
#pragma unroll 1
    while (v = ldg_u2(arena + (LB_TIME << 13)), ((v.y >> 5) == n || gtime() - v.x > W_OPEN + W_LATE) && v.y < 32 * NSEG && ++it < 64) __nanosleep(100);
    it = 0;
#pragma unroll 1
    while ((int)(gtime() - v.x - W_OPEN) < 0 && ++it < 256) {}
    return v.y >> 5;
}
#define SIDE_T 300
template <int NQ, int NB>
__device__ __forceinline__ void side_gemv(const CUtensorMap* tm, int c0, int k0, int k1, uint32_t cs, uint32_t sb, const uint8_t* arena, uint32_t& n, uint32_t& ph, float (*acc)[8], bool once = false) {
    const uint32_t w = __reduce_max_sync(~0u, threadIdx.x >> 5 & 3), ring = sb + (NB == 3 ? 65536 : 0) + w * NB * 8192;
    const uint32_t bars = sb + SM_BAR + (NB == 3 ? 8 * B_W + w * 24 : 8 + w * 8), bs = NB == 3 ? 8 : 0;
#pragma unroll
    for (int q = 0; q < NQ; q++)
#pragma unroll
        for (int j = 0; j < 8; j++) acc[q][j] = 0.f;
#pragma unroll 1
    for (; k0 < k1; k0 += NB * 16, ph ^= 1) {
        const int nr = min(NB * 16, k1 - k0);
        side_window(arena, n);
        const uint32_t t0 = clk32();
#pragma unroll 1
        for (int g = 0; g < NB; g++) {
            spin_until(t0, (g * 4 + w) * (SIDE_T / 4));
            if (bs || !g) e_expect(bars + bs * g, !bs ? NB * 8192 : g * 16 < nr ? 8192 : 0);
            if (g * 16 < nr) e_tma2d_hint(ring + g * 8192, tm, c0, k0 + g * 16, bars + bs * g, once ? EVICT_FIRST : EVICT_NORMAL);
        }
#pragma unroll 1
        for (int r = 0; r < nr; r += 16) {
            mbar_wait_w(bars + bs * (r >> 4), ph);
            uint4 v[16];
#pragma unroll
            for (int h = 0; h < 16; h++) v[h] = lds4(ring + (r + h) * 512 + (threadIdx.x & 31) * 16);
            float4 cf[NQ][4];
#pragma unroll
            for (int q = 0; q < NQ * 4; q++) cf[q >> 2][q & 3] = lds4f(cs + ((q >> 2) * DM + k0 + r + (q & 3) * 4) * 4);
#pragma unroll
            for (int h = 0; h < 16; h++) {
                const float f[8] = {bflo(v[h].x), bfhi(v[h].x), bflo(v[h].y), bfhi(v[h].y), bflo(v[h].z), bfhi(v[h].z), bflo(v[h].w), bfhi(v[h].w)};
#pragma unroll
                for (int q = 0; q < NQ; q++)
#pragma unroll
                    for (int j = 0; j < 8; j++) acc[q][j] = fmaf((&cf[q][h >> 2].x)[h & 3], f[j], acc[q][j]);
            }
        }
        fence_async_smem();
        __syncwarp();
    }
}
__device__ __noinline__ void rec_side(float* sm, const RecMaps& mp, const RecPtrs& p, int id) {
    const int tid = threadIdx.x, t = tid & 127, w = __reduce_max_sync(~0u, t >> 5);
    float* coef = sm + (tid < 256 ? 44032 : 40960);
    const uint32_t sb = smem_u32(sm), cs = smem_u32(coef);
    uint32_t n = 0, ph = 0;
    float acc[3][8];
    if (tid < 256) {
        if (blockIdx.x < 128) rec_ln(smem_u32(sm), p.x, p.arena, id, 2);
        if (tid == 0) TL(14)
        for (int i = tid; i < 2 * S_; i += 256) g_st[id * 2 * S_ + i] = 0.f;
        if (id == 0 && tid < 64) g_pcnt[tid * 8] = 0;
        if (id == 1) for (int i = tid; i < 6 * 256; i += 256) g_pflag[i] = 0;
        if (id == 2 && tid == 0) g_pt = 0;
        fence_async_smem();
        bar_sync(NB_FIN0, 256);
        if (PDL && tid == 0) asm volatile("fence.acq_rel.gpu; griddepcontrol.launch_dependents;" ::: "memory");
        if (tid >= 128) return;
        float* red = coef + 3 * DM;
        if (t == 0) wait_count1(&g_tick[8], 4);
        bar_sync(NB_S, 128);
        for (int i = t; i < DM; i += 128) { coef[i] = 1.0f + __ldcg(g_mod + 4 * DM + i); coef[DM + i] = __ldcg(g_mod + 3 * DM + i); coef[2 * DM + i] = 1.0f; }
        bar_sync(NB_S, 128);
        if (id == 1 && t < 32) {
            float u[5] = {0, 0, 0, 0, 0};
            for (int i = t; i < DM; i += 32) {
                const float a = coef[i], b = coef[DM + i];
                u[0] += a; u[1] += a * a; u[2] += a * b; u[3] += b; u[4] += b * b;
            }
#pragma unroll
            for (int q = 0; q < 5; q++) { const float r = warp_sum(u[q]); if (t == 0) g_cst[q] = r * (1.0f / DM); }
        }
        side_gemv<3, 2>(&mp.w1, id * 256, w * 256, w * 256 + 256, cs, sb, p.arena, n, ph, acc);
#pragma unroll
        for (int q = 0; q < 3; q++)
#pragma unroll
            for (int j = 0; j < 8; j++) red[((t >> 5) * 3 + q) * 256 + (t & 31) * 8 + j] = acc[q][j];
        bar_sync(NB_S, 128);
        for (int i = t; i < 768; i += 128) g_vec[(i >> 8) * DM + id * 256 + (i & 255)] = (red[i] + red[768 + i]) + (red[1536 + i] + red[2304 + i]);
        if (tid == 0) TL(6)
        return;
    }
    for (int i = t; i < DM; i += 128) { coef[i] = silu_bf(p.c, i); coef[2 * DM + i] = 1.0f; }
    if (t == 0) wait_count1(&g_tick[32], 1);
    bar_sync(NB_G, 128);
    side_gemv<1, 3>(&mp.wmod, (2 + id) * DM + w * 256, 0, DM, cs, sb, p.arena, n, ph, acc, true);
#pragma unroll
    for (int j = 0; j < 8; j++) g_mod[(2 + id) * DM + t * 8 + j] = bfround(acc[0][j]);
    bar_sync(NB_G, 128);
    if (t == 0) signal_count(&g_tick[8]);
    side_gemv<1, 3>(&mp.w3, id * (FF / 4) + w * 256, 0, DM, cs + 8 * DM, sb, p.arena, n, ph, acc);
    if (t < FF / 32) {
#pragma unroll
        for (int j = 0; j < 8; j++) g_vec[3 * DM + id * (FF / 4) + t * 8 + j] = acc[0][j];
    }
    if (t == 0) TL(9)
}

__global__ void __cluster_dims__(2, 1, 1) __launch_bounds__(384, 1)
k_rec(const __grid_constant__ RecMaps mp, const __grid_constant__ RecPtrs p) {
    extern __shared__ uint8_t smraw[];
    const uint32_t sb = smem_u32(smraw);
    if ((sb & 0x3FFFF) != SB0) __trap();
    const uint32_t bars = sb + SM_BAR;
    const int tid = threadIdx.x, lane = tid & 31, b = blockIdx.x;
    const int wid = __reduce_max_sync(~0u, tid >> 5);
    const uint32_t rank = b & 1;
    uint8_t* arena = p.arena;
    volatile int* sinfo = (volatile int*)(smraw + SM_BAR + 192);
    if (tid == 0) TL(0)
    if (tid == 0) sinfo[0] = INT_MIN;
    if (tid == 352) {
        for (int i = 0; i < 17; i++) mbar_init(bars + 8 * i, i == B_WO ? 4 : 1);
        asm volatile("fence.mbarrier_init.release.cluster;" ::: "memory");
    }
    __syncwarp();
    asm volatile("barrier.cluster.arrive.relaxed.aligned;" ::: "memory");
    int pr = 0, hA = 0;
    if (wid < 8) {
        if (b < 128) {
            const int cb = (b & 15) * 128, k0 = (b >> 4) * 128 + (tid >> 4);
            uint4 v[8];
#pragma unroll
            for (int i = 0; i < 8; i++) v[i] = __ldg((const uint4*)(p.wmod + (size_t)(k0 + 16 * i) * (6 * DM) + cb + (tid & 15) * 8));
            float acc[8] = {0, 0, 0, 0, 0, 0, 0, 0};
            const float s8 = silu_bf(p.c, k0 + 16 * (lane & 7));
#pragma unroll
            for (int i = 0; i < 8; i++) {
                const float sv = __shfl_sync(~0u, s8, i, 16);
                acc[0] += sv * bflo(v[i].x); acc[1] += sv * bfhi(v[i].x); acc[2] += sv * bflo(v[i].y); acc[3] += sv * bfhi(v[i].y);
                acc[4] += sv * bflo(v[i].z); acc[5] += sv * bfhi(v[i].z); acc[6] += sv * bflo(v[i].w); acc[7] += sv * bfhi(v[i].w);
            }
            float* red = (float*)(smraw + SM_PRE);
            *(float4*)(red + (tid >> 4) * 128 + (tid & 15) * 8) = make_float4(acc[0], acc[1], acc[2], acc[3]);
            *(float4*)(red + (tid >> 4) * 128 + (tid & 15) * 8 + 4) = make_float4(acc[4], acc[5], acc[6], acc[7]);
            bar_sync(NB_FIN0, 256);
            if (wid < 4) {
                float t = 0;
#pragma unroll
                for (int i = 0; i < 16; i++) t += red[i * 128 + tid];
                stg_rlx1(&g_modp[(b >> 4) * 2 * DM + cb + tid], __float_as_uint(t) | 1u);
                TLX(14)
            }
        } else {
            rec_ln(sb, p.x, p.arena, b - 128, 0);
        }
    } else if (wid >= 10 && b >= 128) {
        {
            const int w = (b - 128) * 2 + wid - 10;
            const uint16_t* src = (const uint16_t*)p.mem0 + (lane & 3) * 2 * DM + (w >> 2) * 512 + (w & 1) * 64 + (w & 2) * 8 + (lane >> 2);
            uint32_t v[4][4];
#pragma unroll
            for (int i = 0; i < 16; i++) v[i >> 2][i & 3] = src[(i >> 2) * 128 + (i & 2) * 16 + (i & 1) * 8] | ((uint32_t)src[DM + (i >> 2) * 128 + (i & 2) * 16 + (i & 1) * 8] << 16);
            uint8_t* d = arena + mem_row(w >> 2, w & 3, 0);
            uint8_t* e = d + 512 + (lane >> 1) * 4;
            d += lane * 16;
#pragma unroll
            for (int i = 0; i < 4; i++, d += 1024, e += 1024) {
                stg_rlx4(d, v[i][0], v[i][1], v[i][2], lane & 1 ? (v[i][3] & 0xffff) | CNT_ALL << 16 : v[i][3]);
                stg_rlx4(d + mem_slot(1), 0, 0, 0, 0);
                stg_rlx4(d + mem_slot(2), 0, 0, 0, 0);
                if (lane & 1) { stg_rlx1(e, v[i][3] >> 16 | CNT_ALL << 16); stg_rlx1(e + mem_slot(1), 0); stg_rlx1(e + mem_slot(2), 0); }
            }
            if (w == 0 && lane < 8) stg_rlx2(arena + (LB_TIME << 13) + lane * 1024, 0, 0);
            bar_arrive(NB_C, 320);
        }
    } else if (rank == 0) {
        uint32_t best = ~0u;
        const int pg = wid < 10 ? 0 : 1 + (b >> 1) / 22;
        uint32_t* q = (uint32_t*)(arena + (pg << 21) + (pg ? blk(b >> 1, wid & 1) : blk(LB_PROBE, wid & 1) + b * 16));
        if (lane < 8) stg_rlx1(q + lane, 0);
        __syncwarp();
        if (lane == 0) {
            q += 3;
            uint32_t v = p.zero;
#pragma unroll 1
            for (int r = v; r <= NPROBE; r++) {
                const uint32_t t0 = clk32() + (v >> 8);
                v = atomicAdd(q + (v >> 8), 1u);
                uint32_t t1;
                asm volatile("{.reg .pred p; setp.eq.u32 p, %1, 0xffffffff; @p exit; mov.u32 %0, %%clock;}" : "=r"(t1) : "r"(v) : "memory");
                best = min(best, t1 - t0);
            }
            sinfo[wid - 6] = best;
        }
        bar_sync(NB_KDONE, b < 128 ? 128 : 64);
        if (tid == 256) {
            const uint32_t par = sinfo[2] > sinfo[3], vote = b < 128 && (sinfo[4] > sinfo[5]) != par;
            stg_rlx2(&g_clk[b >> 1], ((clk32() - 2 * gtime()) & ~127u) | b >> 1, 1 + 2 * par + 4 * vote);
        }
    }
    if (wid == 8) {
        U2 v[3], my;
        uint32_t c0;
        const int me = b >> 1;
        int it = 0;
        __syncwarp();
#pragma unroll 1
        do {
            my = ldg_u2(&g_clk[me]);
#pragma unroll
            for (int k = 0; k < 3; k++) v[k] = ldg_u2(&g_clk[k * 22 + min(lane, 21)]);
        } while (!__all_sync(~0u, my.y & v[0].y & v[1].y & v[2].y & 1) & (++it < SPIN_LIMIT));
        TLX(15)
        c0 = __reduce_min_sync(~0u, lane ? ~0u : v[0].x) - 4096;
        const uint32_t mc = me >= 64 ? ~0u : my.x - c0;
        const int par = my.y >> 1 & 1;
        uint32_t cnt = 0, flip = 0;
#pragma unroll
        for (int k = 0; k < 3; k++) {
            const uint32_t c = v[k].x - c0, o = v[k].y >> 1 & 1;
            const bool ln = k == 2 && lane >= 20;
            cnt += o + (o == par ? (ln ? 44 + lane < me : c < mc) * 256 + (c < my.x - c0) * 65536 : 0);
            flip |= __popc(__ballot_sync(~0u, v[k].y & 4) & 0x3fffff) > 10 ? 256 << k : 0;
        }
        cnt = __reduce_add_sync(~0u, lane < 22 ? cnt : 0);
        const int n1 = cnt & 255, n0 = 66 - n1, tk = cnt >> 8 & 255;
        if (lane == 0) g_cls[smid() & 255] = cnt < 32 << 16 ? par * 4 + (cnt >> 19) : 8;
        hA = min(n0 >> 1, NH);
        const int q0 = 2 * hA, q1 = 2 * NH - q0;
        const int over = tk - (par ? q1 : q0), lack = max(par ? q0 - n0 : q1 - n1, 0);
        if (over < 0) pr = par ? q0 + tk : tk;
        else if (over < lack) pr = (par ? n0 : q0 + n1) + over;
        else pr = -1 - (over - lack + (par ? max(n0 - q0, 0) : 0));
        hA |= flip;
        if (lane == 0) {
            sinfo[1] = hA; sinfo[0] = pr;
            if (b >= 128 && rank == 0) atomicOr(&g_tick[6], (pr < 0 ? 4u : 1u) << ((b - 128) >> 1));
        }
    }
    asm volatile("barrier.cluster.wait.aligned;" ::: "memory");
    if (wid == 8) {
        TL(1)
        __syncwarp();
        bar_arrive(NB_A, 288);
        bar_arrive(NB_S, 128);
        if (b >= 128 && pr < 0) bar_sync(NB_B, 64);
        if (pr >= 0) {
            const int pu = __reduce_max_sync(~0u, pr), c0 = (pu >> 1) * 128 + rank * 64, r0 = (pu & 1) * 512;
#pragma unroll 1
            for (int n = 0; n < 13; n++) {
                const u64 seq = b >= 128 ? LN_SEQ : 0xcba9876543210ull;
                const int i = seq >> (4 * n) & 15;
                if (b >= 128 && i == 0) bar_sync(NB_B, 64);
                if (n >= W_INFL && (b < 128 || n < LN_FREE)) mbar_wait_w(bars + 8 * (B_W + (seq >> (4 * (n - W_INFL)) & 15)), 0);
                const int m = i < 8 ? i & 1 : i >> 2, k = i < 8 ? i >> 1 : i & 3;
                const uint32_t dst = sb + m * 65536 + k * 16384, br = bars + 8 * (m < 3 ? B_W + i : B_WO);
                const int c = m < 3 ? c0 : 576 + rank * 256 + (pu & 1) * 128, r = m < 3 ? r0 + k * 128 : (pu >> 1) * DH;
                const uint64_t pol = m < 3 ? EVICT_FIRST : EVICT_NORMAL;
                e_expect(br, 16384);
                e_tma2d_hint(dst, &mp.wq + m, c, r, br, pol);
                e_tma2d_hint(dst + 8192, &mp.wq + m, c, r + 64, br, pol);
            }
        }
    } else {
        bar_sync(wid < 8 ? NB_A : NB_S, wid < 8 ? 288 : 128);
    }
    const int prr = __reduce_max_sync(~0u, sinfo[0]);
    hA = __reduce_max_sync(~0u, sinfo[1]);
    if (prr < 0) {
        int j = (b - 128) >> 1;
        if (b < 128) {
            uint32_t v;
            int it = 0;
#pragma unroll 1
            do { v = __reduce_max_sync(~0u, ldg_rlx1(&g_tick[6])); spin_guard(++it); } while (__popc(v) < 2);
            j = v == 3 ? -1 - prr : (v & 1) ^ 1;
        }
        rec_side((float*)smraw, mp, p, j * 2 + rank);
        return;
    }
    if (PDL) asm volatile("griddepcontrol.launch_dependents;" ::: "memory");
    const int role = (prr >> 1) * 4 + rank * 2 + (prr & 1);
    rec_main(sb, &mp.wo, arena, role, hA, wid >> 2, p.zero, p.dly);
}

__device__ __forceinline__ void wgmma_ss192(float* d, uint64_t a, uint64_t b, int sc) {
    asm volatile("{.reg .pred p; setp.ne.b32 p, %98, 0;\n wgmma.mma_async.sync.aligned.m64n192k16.f32.bf16.bf16 "
                 "{%0,%1,%2,%3,%4,%5,%6,%7,%8,%9,%10,%11,%12,%13,%14,%15,%16,%17,%18,%19,%20,%21,%22,%23,%24,%25,%26,%27,%28,%29,%30,%31,%32,%33,%34,%35,%36,%37,%38,%39,%40,%41,%42,%43,%44,%45,%46,%47,%48,%49,%50,%51,%52,%53,%54,%55,%56,%57,%58,%59,%60,%61,%62,%63,%64,%65,%66,%67,%68,%69,%70,%71,%72,%73,%74,%75,%76,%77,%78,%79,%80,%81,%82,%83,%84,%85,%86,%87,%88,%89,%90,%91,%92,%93,%94,%95}, %96, %97, p, 1, 1, 0, 1;}"
                 : F16(d, 0), F16(d, 16), F16(d, 32), F16(d, 48), F16(d, 64), F16(d, 80) : "l"(a), "l"(b), "r"(sc));
}

constexpr uint32_t P_B = 81920, P_PL = 40960, P_OUT = 180224, P_VEC = 212992, P_ROW = P_VEC + 6144, P_BAR = P_ROW + 4096, P_SMEM = P_BAR + 256;
#define PPH 1
#define FLAG_ST "st.release.gpu.global.u32"
#define FLAG_LD "ld.acquire.gpu.global.u32"
constexpr int ST = 5;
constexpr int PB_F = 0, PB_E = 5, PB_R = 10, PB_OUT = 16;
enum { C_Y = 0, C_G = 1, C_X1 = 2, C_U = 3, C_S1 = 8, C_S3 = 9 };
enum { V_GA = 0, V_A = 1, V_B = 2, V_GB = 3, V_VA = 4, V_VB = 5, V_VC = 6, V_C3 = 7 };
struct PostMaps { CUtensorMap o, wo, y, w1, g, w2, x1, w3, u, w4, out; };
struct PostPtrs { const bf16* x; };

struct GeluK { float k0, k1, kh; };
__device__ __forceinline__ GeluK gelu_k(float c) { return {0.7978845608028654f * c, 0.7978845608028654f * 0.044715f * c * c * c, 0.5f * c}; }
__device__ __forceinline__ float gelu_s(float t, const GeluK& k) {
    const float u = t * fmaf(t * t, k.k1, k.k0);
    float th; asm("tanh.approx.f32 %0, %1;" : "=f"(th) : "f"(u));
    const float hx = k.kh * t;
    return fmaf(hx, th, hx);
}
__device__ __forceinline__ float2 ldsv(uint32_t a) {
    float2 v; asm("ld.shared.v2.f32 {%0,%1}, [%2];" : "=f"(v.x), "=f"(v.y) : "r"(a)); return v;
}
__device__ __forceinline__ void wait_smem(uint32_t a, int target) {
    int it = 0;
#pragma unroll 1
    while (true) {
        int v;
        asm volatile("ld.acquire.cta.shared.u32 %0, [%1];" : "=r"(v) : "r"(a) : "memory");
        if (__all_sync(~0u, v >= target) | (++it > SPIN_LIMIT)) break;
    }
}

#define PP(i)
#define PH_(c, w, i)
__device__ __forceinline__ void release(uint32_t rel, int st, bool c) {
    asm volatile("{.reg .pred p; setp.ne.u32 p, %1, 0; setp.ne.and.u32 p, %2, 0, p; @p mbarrier.arrive.shared::cluster.b64 _, [%0];}"
                 ::"r"(rel + 8 * (st ? st - 1 : ST - 1)), "r"(rel), "r"((uint32_t)c) : "memory");
}
struct Pipe { int st, ph; uint32_t rel; };
__device__ __forceinline__ void adv(Pipe& p) { if (++p.st == ST) { p.st = 0; p.ph ^= 1; } }

__device__ __forceinline__ void post_weights(uint32_t sb, const PostMaps& mp, int nb, int rank) {
    const uint32_t full = sb + P_BAR + 8 * PB_F, empty = sb + P_BAR + 8 * PB_E;
    int st = 0, pp = 1;
#pragma unroll 1
    for (int ph = 0; ph < 7; ph++) {
        const int NK = ph == 0 ? 64 : ph == 6 ? 56 : 16, km = NK == 16 ? 15 : 63;
        const CUtensorMap* tb = &mp.wo + 2 * (ph < 3 ? ph : ph < 6 ? 3 : 4);
        const bool w3 = ph >= 3 && ph < 6;
        const int n0 = w3 ? nb * 64 + (ph == 4 ? 1536 : ph == 5 ? 2560 : 0) : nb * 128, dn = w3 ? 512 : 64;
        const int rot = NK == 16 ? 2 * (nb & 6) : 0, sw = ph == 1 || ph == 3 ? 2 * rank : 0;
#pragma unroll 1
        for (int i = 0; i < NK; i++) {
            const int k0 = (((i < 4 ? i ^ sw : i) + rot) & km) * 64;
            const uint32_t a = sb + P_B + st * 8192, f = full + 8 * st;
            mbar_wait_w(empty + 8 * st, pp);
            e_expect(f, ph == 3 ? 40960 : 32768);
            e_tma2d(a, tb, n0, k0, f);
            e_tma2d(a + P_PL, tb, n0 + dn, k0, f);
            if (ph == 3) e_tma2d(a + 2 * P_PL, tb, n0 + 1024, k0, f);
            if (++st == ST) { st = 0; pp ^= 1; }
        }
    }
#pragma unroll 1
    for (int i = 0; i < ST; i++) mbar_wait_w(empty + 8 * i, pp ^ (i < st));
}
__device__ __forceinline__ void post_acts(uint32_t sb, const PostMaps& mp, int mb, int nb, int rank) {
    const int rh = 2 * mb + rank, lane = threadIdx.x & 31;
    const uint32_t bars = sb + P_BAR;
    int st = 0, pp = 1;
#pragma unroll 1
    for (int ph = 0; ph < 7; ph++) {
        const int NK = ph == 0 ? 64 : ph == 6 ? 56 : 16, km = NK == 16 ? 15 : 63;
        const CUtensorMap* ta = &mp.o + 2 * (ph < 3 ? ph : ph < 6 ? 3 : 4);
        const int amul = ph == 0 ? 256 : 64, arow = (ph == 0 ? rh * 8 : rh * 64) - 2, rot = NK == 16 ? 2 * (nb & 6) : 0;
        const bool own = ph == 1 || ph == 3;
        const uint32_t shifts = ph == 2 ? 0x04000301u : 0x02020202u;
        const uint32_t* fl = &g_pflag[(ph == 6 ? C_U : min(ph - 1, 2)) * 256 + (ph == 2 ? min(max(rh + min(lane >> 3, 2) - 1, 0), 31) : rh) * 8 + ((lane + nb - rank) & 7)];
        int i = 0, n = ph == 0 || ph == 5 ? NK : 0;
        if (own) { i = 4; if (st) { st--; pp ^= 1; } else st = 4; }
#pragma unroll 1
        while (i < NK) {
            if (n <= i) {
                int it = 0;
                PH_(ph == PPH && n == 0, 0, 27) PH_(ph == PPH && n == 0, 1, 27)
#pragma unroll 1
                do {
                    uint32_t v;
                    asm volatile(FLAG_LD " %0, [%1];" : "=r"(v) : "l"(fl) : "memory");
                    n = __reduce_min_sync(~0u, ph == 6 ? 8 * v : v || (own && !(lane & 6)) ? 16 : 2 * (lane & 7));
                    if (++it > SPIN_LIMIT) n = NK;
                } while (n <= i);
                PH_(ph == PPH && i <= 4, 0, 23) PH_(ph == PPH, 0, 24) PH_(ph == PPH && i <= 4, 1, 23) PH_(ph == PPH, 1, 24)
                asm volatile("fence.proxy.async.global;" ::: "memory");
            }
            if (own && (i == 5 || i == 6)) mbar_wait_w(bars + 8 * (PB_E + ph + i - 5), 1);
#pragma unroll 1
            for (const int e = own && i < 6 ? i + 1 : n; i < e; i++) {
                const int kb = (i + rot) & km;
                const uint32_t f = bars + 8 * (PB_F + st);
                mbar_wait_w(f + 8 * PB_E, pp);
                e_tma2d_mc(sb + st * 16384 + rank * 8192, ta, kb * amul, arow + (int)((shifts >> ((kb & 12) * 2)) & 7), f);
                if (++st == ST) { st = 0; pp ^= 1; }
            }
        }
    }
}

template <int PH, class F>
__device__ __forceinline__ void post_kb(uint32_t sb, float* acc, Pipe& p, int wg, bool lead, bool first, F mid) {
    constexpr uint64_t DA = PH == 0 ? mkdesc(SB0, 128, 1024, 0) : mkdesc(SB0, 16, 1024, 1);
    constexpr uint64_t DB = mkdesc(SB0 + P_B, P_PL, 1024, 1);
    mbar_wait_w(sb + P_BAR + 8 * PB_F + 8 * p.st, p.ph);
    const uint32_t a = (uint32_t)DA + p.st * 1024 + wg * 512, b = (uint32_t)DB + p.st * 512;
    wg_fence();
#pragma unroll
    for (int k = 0; k < 4; k++) {
        const uint64_t da = (DA & 0xffffffff00000000ull) | (a + k * (PH == 0 ? 16 : 2)), db = (DB & 0xffffffff00000000ull) | (b + k * 128);
        if (PH == 3) wgmma_ss192(acc, da, db, k || !first);
        else wgmma_ss128<PH == 0>(acc, da, db, k || !first);
    }
    wg_commit();
    wg_wait<1>();
    release(p.rel, p.st, !first);
    mid();
    adv(p);
}
__device__ __forceinline__ void post_end(uint32_t sb, Pipe& p, bool lead) {
    wg_wait<0>();
    release(p.rel, p.st, true);
}
template <int PH>
__device__ __forceinline__ void post_mma(uint32_t sb, float* acc, Pipe& p, int wg, bool lead, int nout, int pi, int mb, int nb) {
#pragma unroll 1
    for (int kb = 0; kb < 16; kb++)
        post_kb<PH>(sb, acc, p, wg, lead, kb == 0, [&]() {
            if (kb == 0) { PP(pi) }
            if (nout && kb == 0) wait_smem(sb + P_BAR + 8 * (PB_OUT + wg), nout);
        });
    post_end(sb, p, lead);
    PP(pi + 1)
}

__global__ void __cluster_dims__(2, 1, 1) __launch_bounds__(384, 1)
k_post(const __grid_constant__ PostMaps mp, const __grid_constant__ PostPtrs pp) {
    extern __shared__ uint8_t smraw[];
    const uint32_t sb = smem_u32(smraw);
    if ((sb & 0x3FFFF) != SB0) __trap();
    const int tid = threadIdx.x, lane = tid & 31;
    const int rank = blockIdx.x & 1;
    const uint32_t bars = sb + P_BAR;
    int c = 0;
    unsigned long long v = 0;
    const int wid = __reduce_max_sync(~0u, tid >> 5);
    const bool draw = tid == 352 && rank == 0;
    if (draw) {
        c = min(ldg_rlx1(&g_cls[smid() & 255]), 8u);
        asm volatile("{.reg .b64 a; cvt.u64.u32 a, %%laneid; add.u64 a, a, %1; atom.relaxed.gpu.global.add.u64 %0, [a], %2;}" : "=l"(v) : "l"(&g_pt), "l"(1ull << (7 * c)) : "memory");
    }
    if (wid < 11) {
        asm volatile("{.reg .pred p; elect.sync _|p, 0xffffffff; @p mbarrier.init.shared.b64 [%0], %1; @p prefetch.tensormap [%2]; fence.mbarrier_init.release.cluster;}"
                     ::"r"(bars + 8 * wid), "r"(wid >= PB_E && wid < PB_R ? 4 : 1), "l"(&mp.o + wid) : "memory");
        if (wid == PB_R) { sts4(bars + 8 * PB_OUT, 0, 0, 0, 0); e_expect(bars + 8 * PB_R, 4); }
    }
    __syncwarp();
    asm volatile("barrier.cluster.arrive.relaxed.aligned; barrier.cluster.wait.aligned;" ::: "memory");
    if (draw) {
        int r = (v >> (7 * c)) & 127, role = c * 8 + r;
        if (c == 8 || r >= 8) {
            int n, x, it = 0;
#pragma unroll 1
            do {
                __nanosleep(200);
                v = ldg_u64(&g_pt); n = 0; x = c < 8 ? r - 8 : r;
#pragma unroll 1
                for (int i = 0; i < 63; i += 7) { const int m = v >> i & 127; n += m; if (i < 7 * c) x += max(m - 8, 0); }
            } while (n < gridDim.x / 2 && ++it < SPIN_LIMIT);
            role = -1;
#pragma unroll 1
            for (int i = 0; i < 64; i += 8, v >>= 7) {
                n = v & 127;
                if (x >= 0 && n + x < 8) role = i + n + x;
                x -= max(8 - n, 0);
            }
        }
#pragma unroll
        for (int i = 0; i < 2; i++)
            asm volatile("{.reg .b32 d; mapa.shared::cluster.u32 d, %0, %2; st.async.shared::cluster.mbarrier::complete_tx::bytes.u32 [d+8], %1, [d];}"
                         ::"r"(bars + 8 * PB_R), "r"(role), "r"(i) : "memory");
    }
    __syncwarp();
    mbar_wait_w(bars + 8 * PB_R, 0);
    const int pr = __reduce_max_sync(~0u, (int)lds1(bars + 8 * PB_R + 8));
    if (pr < 0) return;
    const int mb = (pr >> 5) * 8 + (pr & 7), nb = (pr >> 2 & 6) + rank, cta = pr * 2 + rank;
    if (wid >= 8) {
        asm volatile("setmaxnreg.dec.sync.aligned.u32 40;");
        const int w = wid - 8;
        if (w == 0) {
            post_weights(sb, mp, nb, rank);
        } else if (w == 3) {
            asm volatile("griddepcontrol.wait;" ::: "memory");
            TLP(15)
            post_acts(sb, mp, mb, nb, rank);
        } else {
            const int wg = w - 1, rh = 2 * mb + wg;
            float* rowc = (float*)(smraw + P_ROW) + (wg * 64 + lane * 2) * 8;
            int nout = 0, sig = 0;
#pragma unroll 1
            for (int i = 0; i < 13; i++) {
                const int cnt = (0x4333333392180ull >> (4 * i)) & 15;
                if (cnt < C_S1) {
                    const int ng = cnt == C_U ? 1 : 2, c0 = cnt == C_U ? (i - 5) * 512 + nb * 64 : nb * 128;
                    const bool fast = (cnt == C_Y || cnt == C_X1);
#pragma unroll 1
                    for (int j = 0; j < ng; j++) {
                        const uint32_t st = j ? cnt : cnt ? 1 : 4;
                        const uint32_t src = sb + (fast ? st * 16384 + wg * 8192 : P_OUT + wg * 16384 + ((nout + j) & 1) * 8192);
                        bar_sync(4 + 4 * wg + (sig++ & 3), 160);
                        if (lane == 0) {
                            PH_(cnt == PPH - 1, wg, 20)
                            if (fast) asm volatile("mbarrier.complete_tx.relaxed.cta.shared::cta.b64 [%0], 8192;" ::"r"(bars + 8 * (PB_F + st)) : "memory");
                            asm volatile("cp.async.bulk.tensor.2d.global.shared::cta.bulk_group [%0, {%2, %3}], [%1]; cp.async.bulk.commit_group;"
                                         ::"l"(&mp.y + 2 * cnt), "r"(src), "r"(c0 + j * 64), "r"(rh * 64) : "memory");
                        }
                        __syncwarp();
                    }
                    if (lane == 0) {
                        auto to_peer = [&]() {
                            const uint32_t n = cnt ? 1 : 4;
                            mbar_wait(bars + 8 * (PB_E + (cnt ? 4 : 2)), 0);
#pragma unroll
                            for (int i = 0; i < 2; i++)
                                asm volatile("{.reg .b32 d, m; mapa.shared::cluster.u32 d, %0, %3; mapa.shared::cluster.u32 m, %2, %3;\n"
                                             " cp.async.bulk.shared::cluster.shared::cta.mbarrier::complete_tx::bytes [d], [%1], 8192, [m];}"
                                             ::"r"(sb + (cnt + 1 + i) * 16384 + wg * 8192), "r"(sb + (i ? cnt : n) * 16384 + wg * 8192), "r"(bars + 8 * (PB_F + cnt + 1 + i)), "r"(rank ^ 1) : "memory");
                        };
                        asm volatile("cp.async.bulk.wait_group 0; fence.proxy.async.global;" ::: "memory");
                        asm volatile("st.release.cta.shared.u32 [%0], %1;" ::"r"(bars + 8 * (PB_OUT + wg)), "r"(nout + ng) : "memory");
                        PH_(cnt == PPH - 1, wg, 21)
                        if (i < 12) asm volatile(FLAG_ST " [%0], %1;" ::"l"(&g_pflag[cnt * 256 + rh * 8 + nb]), "r"(max(i - 4, 1)) : "memory");
                        PH_(cnt == PPH - 1, wg, 22)
                        if (fast) to_peer();
                    }
                    nout += ng;
                    __syncwarp();
                    continue;
                }
                bar_sync(4 + 4 * wg + (sig++ & 3), 160);
                uint32_t* c = &g_pcnt[(cnt - C_S1) * 256 + rh * 8];
                if (lane == 0) signal_count(c);
                __syncwarp();
                wait_count_w(c, 8);
                const float4* sp = (const float4*)g_st + rh * 32 + lane;
                float4 u[3] = {__ldcg(sp + (cnt == C_S1 ? 0 : 3) * (S_ / 2)), __ldcg(sp + S_ / 2), __ldcg(sp + S_)};
#pragma unroll 1
                for (int h = 0; h < 2; h++) {
                    const float id = 1.0f / DM;
                    const float m = u[0].x * id, var = fmaxf(u[0].y * id - m * m, 0.f) + 1e-5f, r = rsqrtf(var);
                    float sc = r, m2 = 0.f;
                    if (cnt == C_S1) {
                        m2 = r * (u[1].x * id - m * g_cst[0]) + g_cst[3];
                        const float e2 = r * r * (u[2].x * id - 2.0f * m * u[1].y * id + m * m * g_cst[1]) + 2.0f * r * (u[2].y * id - m * g_cst[2]) + g_cst[4];
                        sc = r * rsqrtf(fmaxf(e2 - m2 * m2, 0.f) + 1e-5f);
                    }
                    const GeluK k = gelu_k(sc);
                    *(float4*)(rowc + h * 8) = make_float4(k.k0, k.k1, k.kh, -m);
                    *(float4*)(rowc + h * 8 + 4) = make_float4(var * r, -m2 * var * r, r, -m * r);
#pragma unroll
                    for (int q = 0; q < 3; q++) { u[q].x = u[q].z; u[q].y = u[q].w; }
                }
                bar_arrive(1 + wg, 160);
            }
        }
    } else {
        asm volatile("setmaxnreg.inc.sync.aligned.u32 232;");
        const bf16* xin = pp.x;
        const int wg = wid >> 2, wi = (tid >> 5) & 3, g = lane >> 2, tq = lane & 3;
        const int rh = 2 * mb + wg, row = rh * 64 + wi * 16 + g;
        const bool lead = (tid & 127) == 0;
        PP(0)
        if (tid == 0) TLP(10)
        uint32_t keep[32];
#pragma unroll
        for (int i = 0; i < 8; i++)
            *(uint4*)(keep + 4 * i) = __ldg((const uint4*)(xin + (size_t)(rh * 64 + wi * 16 + (i & 3) * 4 + (lane >> 3)) * DM + nb * 128 + (i >> 2) * 64 + (lane & 7) * 8));
        asm volatile("griddepcontrol.wait;" ::: "memory");
        if (cta < 64) g_modp[cta * 256 + tid] = 0;
        if (cta == 64 && tid < 196) g_tick[tid] = 0;
        const float* src = wg ? g_vec + nb * 128 + tid - 128 : g_mod + 2 * DM + nb * 128 + tid;
        const float* c3 = &g_vec[3 * DM + (tid >> 6) * 512 + nb * 64 + (tid & 63)];
        const float cv[6] = {__ldcg(src), __ldcg(src + (wg ? 1 : 2) * DM), __ldcg(src + (wg ? 2 : 1) * DM), __ldcg(src + 3 * DM), __ldcg(c3), __ldcg(c3 + (tid < 192 ? 2048 : 0))};
        uint32_t vec = sb + P_VEC + tq * 8;
        const uint32_t stw = sb + (wi * 16 + ((lane >> 3) & 1) * 8 + (lane & 7)) * 128 + (((lane >> 4) ^ (lane & 7)) << 4);
        int sig = 0;
        auto signal = [&]() { bar_arrive(4 + 4 * wg + (sig++ & 3), 160); };
        auto put64 = [&](uint32_t o, const float* v) {
#pragma unroll
            for (int jj = 0; jj < 4; jj++, v += 8) stsm4((stw + o) ^ (jj << 5), pack2(v[0], v[1]), pack2(v[2], v[3]), pack2(v[4], v[5]), pack2(v[6], v[7]));
            fence_async_smem();
            signal();
        };
        auto slot = [&](int n) {
            mbar_wait_w(bars + 8 * (PB_E + n % 5), ((n / 5) & 1) ^ 1);
            return (n % 5) * 16384 + wg * 8192;
        };
        const uint32_t rowc = sb + P_ROW + (wg * 64 + wi * 16 + g) * 32, o128 = P_OUT + wg * 16384;
        Pipe pa = {0, 0, 0};
        asm("mapa.shared::cluster.u32 %0, %1, %2;" : "=r"(pa.rel) : "r"(bars + 8 * PB_E), "r"(tid & 1));
        if (tid & 126) pa.rel = 0;
#define KEEP(jn, e) (((e) & 1) ? bfhi(keep[2 * (jn) + ((e) >> 1)]) : bflo(keep[2 * (jn) + ((e) >> 1)]))
        float mu1[2], r1[2];
        {
            float acc[64];
#pragma unroll 1
            for (int kb = 0; kb < 64; kb++) {
                post_kb<0>(sb, acc, pa, wg, lead, kb == 0, []() {});
                if (kb == 0) { PP(1) if (wg == 0) TLP(11) }
                if (kb == 24) bar_sync(3, 256);
                if (kb != 8 + 8 * wg) continue;
                float* sv = (float*)(smraw + P_VEC) + tid;
                const uint32_t xo = sb + o128 + wi * 2048 + (lane >> 3) * 128;
#pragma unroll
                for (int i = 0; i < 8; i++) sts4(xo + (i >> 2) * 8192 + (i & 3) * 512 + (((lane & 7) ^ ((i & 1) * 4 + (lane >> 3))) << 4), keep[4 * i], keep[4 * i + 1], keep[4 * i + 2], keep[4 * i + 3]);
                __syncwarp();
#pragma unroll
                for (int jj = 0; jj < 8; jj++) ldsm4(keep + jj * 4, (stw + o128 + (jj >> 2) * 8192) ^ ((jj & 3) << 5));
                sv[wg * 384] = cv[0]; sv[wg * 384 + 128] = cv[1] + (wg ? 0.0f : 1.0f); sv[wg * 384 + 256] = cv[2];
                if (!wg) sv[384] = cv[3];
                sv[V_C3 * 128] = cv[4]; sv[V_C3 * 128 + 256] = cv[5];
            }
            post_end(sb, pa, lead);
            PP(2)
            asm volatile("" : "+r"(vec) :: "memory");
            float st[2][6];
#pragma unroll
            for (int q = 0; q < 6; q++) st[0][q] = st[1][q] = 0.f;
#pragma unroll
            for (int jn = 0; jn < 16; jn++) {
                const float2 ga = ldsv(vec + V_GA * 512 + jn * 32), a = ldsv(vec + V_A * 512 + jn * 32);
                float xa[4];
#pragma unroll
                for (int e = 0; e < 4; e++) {
                    xa[e] = fmaf((e & 1) ? ga.y : ga.x, acc[4 * jn + e], KEEP(jn, e));
                    st[e >> 1][0] += xa[e]; st[e >> 1][1] = fmaf(xa[e], xa[e], st[e >> 1][1]);
                    acc[4 * jn + e] = ((e & 1) ? a.y : a.x) * xa[e];
                }
                keep[2 * jn] = pack2(xa[0], xa[1]); keep[2 * jn + 1] = pack2(xa[2], xa[3]);
                if ((jn & 7) == 7) put64(slot(64 + (jn >> 3)), acc + 4 * jn - 28);
            }
            PP(3)
#pragma unroll
            for (int jn = 0; jn < 16; jn++) {
                const float2 a = ldsv(vec + V_A * 512 + jn * 32), b = ldsv(vec + V_B * 512 + jn * 32);
#pragma unroll
                for (int e = 0; e < 4; e++) {
                    const float y = acc[4 * jn + e], aa = (e & 1) ? a.y : a.x, bb = (e & 1) ? b.y : b.x;
                    float* s = st[e >> 1];
                    s[2] += y; s[3] = fmaf(aa, y, s[3]); s[4] = fmaf(y, y, s[4]); s[5] = fmaf(bb, y, s[5]);
                }
            }
#pragma unroll
            for (int h = 0; h < 2; h++)
#pragma unroll
                for (int q = 0; q < 6; q++) { st[h][q] += __shfl_xor_sync(~0u, st[h][q], 1); st[h][q] += __shfl_xor_sync(~0u, st[h][q], 2); }
            if (tq < 3) {
#pragma unroll
                for (int h = 0; h < 2; h++)
                    red2(g_st + (tq * S_ + row + h * 8) * 2, tq == 0 ? st[h][0] : tq == 1 ? st[h][2] : st[h][4], tq == 0 ? st[h][1] : tq == 1 ? st[h][3] : st[h][5]);
            }
            signal();
            PP(29)
        }
        {
            float acc[64];
            post_mma<1>(sb, acc, pa, wg, lead, 2, 4, mb, nb);
            float c1[2], c2[2], c3[2];
            GeluK gk[2];
            bar_sync(1 + wg, 160);
#pragma unroll
            for (int h = 0; h < 2; h++) {
                const float4 a = lds4f(rowc + h * 256), b = lds4f(rowc + h * 256 + 16);
                gk[h] = {a.x, a.y, a.z}; c1[h] = a.w; c2[h] = b.x; c3[h] = b.y; mu1[h] = b.w; r1[h] = b.z;
            }
#pragma unroll
            for (int jn = 0; jn < 16; jn++) {
                const float2 va = ldsv(vec + V_VA * 512 + jn * 32), vb = ldsv(vec + V_VB * 512 + jn * 32), vc = ldsv(vec + V_VC * 512 + jn * 32);
#pragma unroll
                for (int e = 0; e < 4; e++) {
                    const int h = e >> 1;
                    const float t = fmaf(c1[h], (e & 1) ? va.y : va.x, fmaf(c2[h], (e & 1) ? vb.y : vb.x, fmaf(c3[h], (e & 1) ? vc.y : vc.x, acc[4 * jn + e])));
                    acc[4 * jn + e] = gelu_s(t, gk[h]);
                }
                if ((jn & 7) == 7) put64(o128 + (jn >> 3) * 8192, acc + 4 * jn - 28);
            }
            PP(6)
        }
        {
            float acc[64];
            post_mma<2>(sb, acc, pa, wg, lead, 0, 7, mb, nb);
#pragma unroll
            for (int jn = 0; jn < 16; jn++) {
                const float2 a = ldsv(vec + V_A * 512 + jn * 32), b = ldsv(vec + V_B * 512 + jn * 32);
#pragma unroll
                for (int e = 0; e < 4; e++) {
                    const int h = e >> 1;
                    acc[4 * jn + e] += fmaf(fmaf(KEEP(jn, e), r1[h], mu1[h]), (e & 1) ? a.y : a.x, (e & 1) ? b.y : b.x);
                }
                if ((jn & 7) == 7) put64(slot(96 + (jn >> 3)), acc + 4 * jn - 28);
            }
            BLOCK_FENCE
#pragma unroll
            for (int i = 0; i < 64; i += 16) asm volatile("" : F16(acc, i));
            PP(9)
            float st[2][2] = {{0.f, 0.f}, {0.f, 0.f}};
#pragma unroll
            for (int jn = 0; jn < 16; jn++) {
                const float2 gb = ldsv(vec + V_GB * 512 + jn * 32);
                float z[4];
#pragma unroll
                for (int e = 0; e < 4; e++) {
                    const float x1 = acc[4 * jn + e];
                    st[e >> 1][0] += x1; st[e >> 1][1] = fmaf(x1, x1, st[e >> 1][1]);
                    z[e] = fmaf((e & 1) ? gb.y : gb.x, x1, KEEP(jn, e));
                }
                keep[2 * jn] = pack2(z[0], z[1]); keep[2 * jn + 1] = pack2(z[2], z[3]);
            }
#pragma unroll
            for (int h = 0; h < 2; h++)
#pragma unroll
                for (int q = 0; q < 2; q++) { st[h][q] += __shfl_xor_sync(~0u, st[h][q], 1); st[h][q] += __shfl_xor_sync(~0u, st[h][q], 2); }
            if (tq < 2) red2(g_st + (3 * S_ + row + tq * 8) * 2, tq ? st[1][0] : st[0][0], tq ? st[1][1] : st[0][1]);
            signal();
            PP(30)
        }
        {
            float old[96], acc[64];
            post_mma<3>(sb, old, pa, wg, lead, 6, 10, mb, nb);
#pragma unroll
            for (int i = 0; i < 96; i += 16) asm volatile("" : F16(old, i));
            uint32_t v3 = vec + V_C3 * 512;
            bar_sync(1 + wg, 160);
            const float4 rc[2] = {lds4f(rowc), lds4f(rowc + 256)};
            float2 vc[2] = {lds2f(v3), lds2f(v3 + 32)};
            v3 += wg ? 0 : 64;
            bar_sync(3, 256);
#pragma unroll 1
            for (int blk = 0; blk < 11; blk++) {
                const uint32_t o = stw + o128 + (blk & 1) * 8192;
#pragma unroll
                for (int q = 0; q < 4; q++) {
#pragma unroll 1
                    for (int rep = 0; rep < 2; rep++) {
                        post_kb<1>(sb, acc, pa, wg, lead, q == 0 && rep == 0 && blk < 6 && !(blk & 1), []() {});
                        if (rep != wg) {
                            vc[0] = lds2f(v3 + q * 64); vc[1] = lds2f(v3 + q * 64 + 32);
                            if (q == 2) wait_smem(bars + 8 * (PB_OUT + wg), 6 + min(blk, 7));
                            if ((q == 0 && wg && (uint32_t)(blk - 1) < 7) || (q == 3 && !wg && blk < 7)) { fence_async_smem(); signal(); }
                        } else if (blk < 7) {
                            asm volatile("" : F4(old, 8 * q), F4(old, 8 * q + 4));
                            float t[8];
#pragma unroll
                            for (int i = 0; i < 8; i++) {
                                const float4& c = rc[(i >> 1) & 1];
                                t[i] = gelu_s(fmaf(c.w, (i & 1) ? vc[i >> 2].y : vc[i >> 2].x, old[8 * q + i]), GeluK{c.x, c.y, c.z});
                                old[8 * q + i] = old[32 + 8 * q + i];
                                old[32 + 8 * q + i] = old[64 + 8 * q + i];
                            }
                            uint32_t r[4] = {pack2(t[0], t[1]), pack2(t[2], t[3]), pack2(t[4], t[5]), pack2(t[6], t[7])};
                            asm volatile("pmevent 0;" : F4(old, 8 * q), F4(old, 8 * q + 4), F4(old, 8 * q + 32), F4(old, 8 * q + 36), "+r"(r[0]), "+r"(r[1]), "+r"(r[2]), "+r"(r[3]));
                            stsm4(o ^ (q << 5), r[0], r[1], r[2], r[3]);
                        }
                    }
                }
                v3 += 256;
                if (blk != 1 && blk != 3) continue;
                post_end(sb, pa, lead);
                PP(12 + blk)
                asm volatile("" : F16(acc, 0), F4(acc, 16), F4(acc, 20), F4(acc, 24));
                asm volatile("" : F16(acc, 28), F4(acc, 44), F4(acc, 48), F4(acc, 52));
                asm volatile("" : F4(acc, 56), F4(acc, 60));
#pragma unroll
                for (int i = 0; i < 64; i++) old[32 + i] = acc[i];
            }
            post_end(sb, pa, lead);
            PP(17)
#pragma unroll
            for (int jn = 0; jn < 16; jn++) {
                const float2 gb = ldsv(vec + V_GB * 512 + jn * 32);
#pragma unroll
                for (int e = 0; e < 4; e++) acc[4 * jn + e] = fmaf((e & 1) ? gb.y : gb.x, acc[4 * jn + e], KEEP(jn, e));
                if ((jn & 7) == 7) put64(o128 + ((jn >> 3) ^ 1) * 8192, acc + 4 * jn - 28);
            }
            PP(18)
            if (tid == 0) TLP(12)
        }
    }
}

typedef CUresult (*EncFn)(CUtensorMap*, CUtensorMapDataType, cuuint32_t, void*, const cuuint64_t*, const cuuint64_t*, const cuuint32_t*,
                          const cuuint32_t*, CUtensorMapInterleave, CUtensorMapSwizzle, CUtensorMapL2promotion, CUtensorMapFloatOOBfill);

static CUtensorMap make_map(EncFn enc, const void* p, uint64_t inner, uint64_t outer, uint32_t bi = 64) {
    CUtensorMap m;
    cuuint64_t dims[2] = {inner, outer};
    cuuint64_t str[1] = {inner * 2};
    cuuint32_t box[2] = {bi, bi == 64 ? 64u : 16u};
    cuuint32_t es[2] = {1, 1};
    enc(&m, CU_TENSOR_MAP_DATA_TYPE_BFLOAT16, 2, (void*)p, dims, str, box, es, CU_TENSOR_MAP_INTERLEAVE_NONE,
        bi == 64 ? CU_TENSOR_MAP_SWIZZLE_128B : CU_TENSOR_MAP_SWIZZLE_NONE, CU_TENSOR_MAP_L2_PROMOTION_L2_256B, CU_TENSOR_MAP_FLOAT_OOB_FILL_NONE);
    return m;
}
static CUtensorMap make_map_o(EncFn enc, const void* p) {
    CUtensorMap m;
    cuuint64_t dims[2] = {16384, 256};
    cuuint64_t str[1] = {65536};
    cuuint32_t box[2] = {256, 8};
    cuuint32_t es[2] = {1, 1};
    enc(&m, CU_TENSOR_MAP_DATA_TYPE_UINT32, 2, (void*)p, dims, str, box, es, CU_TENSOR_MAP_INTERLEAVE_NONE, CU_TENSOR_MAP_SWIZZLE_NONE,
        CU_TENSOR_MAP_L2_PROMOTION_L2_256B, CU_TENSOR_MAP_FLOAT_OOB_FILL_NONE);
    return m;
}
template <class T> static T* sym(T& s) { void* p = nullptr; cudaGetSymbolAddress(&p, s); return (T*)p; }

static const Delays h_dly = {D_NEAR, D_FAR, D_X2, D_V, D_W2, D_PA, D_MORE2, D_MORE};
extern "C" void kernel_launch(void* const* d_in, const int* in_sizes, int n_in, void* d_out, int out_size) {
    const bf16* x = (const bf16*)d_in[0];
    const bf16* mem0 = (const bf16*)d_in[1];
    const bf16 *Wq = (const bf16*)d_in[2], *Wk = (const bf16*)d_in[3], *Wv = (const bf16*)d_in[4], *Wo = (const bf16*)d_in[5];
    const bf16 *w1 = (const bf16*)d_in[8], *w2 = (const bf16*)d_in[9], *w3 = (const bf16*)d_in[10], *w4 = (const bf16*)d_in[11];
    const bf16 *c = (const bf16*)d_in[12], *wmod = (const bf16*)d_in[13];
    bf16* out = (bf16*)d_out;

    EncFn enc = nullptr;
    cudaDriverEntryPointQueryResult qr;
    cudaGetDriverEntryPoint("cuTensorMapEncodeTiled", (void**)&enc, cudaEnableDefault, &qr);
    CUtensorMap tWq = make_map(enc, Wq, NH * DH, DM), tWk = make_map(enc, Wk, NH * DH, DM), tWv = make_map(enc, Wv, NH * DH, DM);
    PostMaps mp;
    mp.o = make_map_o(enc, sym(g_O)); mp.wo = make_map(enc, Wo, DM, NH * DH);
    mp.y = make_map(enc, sym(g_y), DM, S_); mp.w1 = make_map(enc, w1, DM, DM);
    mp.g = make_map(enc, sym(g_g), DM, S_); mp.w2 = make_map(enc, w2, DM, DM);
    mp.x1 = make_map(enc, sym(g_x1), DM, S_); mp.w3 = make_map(enc, w3, FF, DM);
    mp.u = make_map(enc, sym(g_u), FF, S_); mp.w4 = make_map(enc, w4, DM, FF);
    mp.out = make_map(enc, out, DM, S_);
    cudaFuncSetAttribute(k_rec, cudaFuncAttributeMaxDynamicSharedMemorySize, SM_REC_TOTAL + 2048);
    cudaFuncSetAttribute(k_post, cudaFuncAttributeMaxDynamicSharedMemorySize, P_SMEM);

    uint8_t* arena = (uint8_t*)(((uintptr_t)sym(g_arena) + (2u << 20) - 1) & ~(uintptr_t)((2u << 20) - 1));
    const PostPtrs pp = {x};
    const RecPtrs rp = {x, mem0, c, wmod, w1, w3, arena, 0u, w2, w4, Wo, h_dly};
    const RecMaps rm = {tWq, tWk, tWv, mp.wo, make_map(enc, wmod, 6 * DM, DM, 256), make_map(enc, w3, FF, DM, 256), make_map(enc, w1, DM, DM, 256)};
    k_rec<<<132, 384, SM_REC_TOTAL + 2048>>>(rm, rp);
    cudaLaunchConfig_t cfg = {};
    cfg.gridDim = dim3(132); cfg.blockDim = dim3(384); cfg.dynamicSmemBytes = P_SMEM; cfg.stream = cudaStreamPerThread;
    cudaLaunchAttribute at[1];
    at[0].id = cudaLaunchAttributeProgrammaticStreamSerialization; at[0].val.programmaticStreamSerializationAllowed = PDL;
    cfg.attrs = at; cfg.numAttrs = 1;
    cudaLaunchKernelEx(&cfg, k_post, mp, pp);
}
```

```cpp
#include <cuda_runtime.h>
#include <cuda.h>
#include <cuda_bf16.h>
#include <stdint.h>
#include <limits.h>

typedef __nv_bfloat16 bf16;

constexpr int S_ = 2048, DM = 1024, NH = 32, DH = 128, NSEG = 64, FF = 3584;
constexpr int SPIN_LIMIT = 1 << 22;
#define W_INFL 2
#define H_PIECES 4
#define PDL 1
#define NPROBE 3

__device__ uint8_t g_arena[10 << 20];
__device__ __align__(128) uint32_t g_tick[64 + 132];
#define g_clk ((uint2*)(g_tick + 64))
__device__ uint32_t g_cls[256];
__device__ unsigned long long g_pt;
__device__ __align__(16) uint32_t g_modp[8 * 2 * DM];
__host__ __device__ constexpr uint32_t blk(uint32_t lb, uint32_t par) {
    return (lb << 13) | ((((lb) ^ (lb >> 3) ^ (lb >> 4) ^ (lb >> 6) ^ par) & 1) << 12);
}
__host__ __device__ constexpr uint32_t lb_x2(uint32_t h) { return (h & 1) | ((h >> 1) << 3); }
__host__ __device__ constexpr uint32_t mem_row(uint32_t kh, uint32_t b, uint32_t r) { return blk(128 | b, kh) + r * 1024; }
__device__ __forceinline__ uint32_t mem_slot(uint32_t s) { return ((s & 1) << 15) | ((s & 2) << 17); }
constexpr uint32_t CNT1 = 0x3d80, CNT_ALL = 0x4000;
constexpr uint32_t LB_PROBE = 6 | 64, LB_TIME = 6;
__host__ __device__ constexpr uint32_t lb_tok(uint32_t h) { return (h & 1) | ((h >> 1) << 3); }
__device__ float g_mod[6 * DM];
__device__ __align__(1024) bf16 g_himg[(S_ + 32) * DM];
__device__ __align__(1024) bf16 g_O[S_ * NH * DH];
__device__ __align__(1024) bf16 g_y[S_ * DM];
__device__ __align__(1024) bf16 g_g[S_ * DM];
__device__ __align__(1024) bf16 g_x1[S_ * DM];
__device__ __align__(16) float g_st[4 * S_ * 2];
__device__ float g_vec[3 * DM + FF];
__device__ float g_cst[8];
__device__ uint32_t g_pcnt[2 * 32 * 8], g_pflag[7 * 32 * 8];
__device__ __align__(1024) bf16 g_u[S_ * FF];

__device__ __forceinline__ uint32_t smem_u32(const void* p) { return (uint32_t)__cvta_generic_to_shared(p); }
__device__ __forceinline__ void spin_guard(int it) {
    asm volatile("{.reg .pred p; setp.gt.s32 p, %0, %1; @p st.global.u32 [%2], %0;}" ::"r"(it), "n"(SPIN_LIMIT), "l"(1ull));
}
__device__ __forceinline__ void wg_fence() { asm volatile("wgmma.fence.sync.aligned;" ::: "memory"); }
__device__ __forceinline__ void wg_commit() { asm volatile("wgmma.commit_group.sync.aligned;" ::: "memory"); }
template <int N> __device__ __forceinline__ void wg_wait() { asm volatile("wgmma.wait_group.sync.aligned %0;" ::"n"(N) : "memory"); }
__host__ __device__ constexpr uint64_t mkdesc(uint32_t addr, uint32_t lbo, uint32_t sbo, uint32_t swz) {
    return (uint64_t)((addr & 0x3FFFF) >> 4) | ((uint64_t)(lbo >> 4) << 16) | ((uint64_t)(sbo >> 4) << 32) | ((uint64_t)swz << 62);
}
__device__ __forceinline__ uint64_t dadd(uint64_t d, uint32_t o) { return (d & 0xffffffff00000000ull) | (uint32_t)((uint32_t)d + o); }
__device__ __forceinline__ void mbar_init(uint32_t b, uint32_t c) { asm volatile("mbarrier.init.shared.b64 [%0], %1;" ::"r"(b), "r"(c) : "memory"); }
__device__ __forceinline__ void mbar_arrive_cluster(uint32_t b, uint32_t cta) {
    asm volatile("{.reg .b32 r; mapa.shared::cluster.u32 r, %0, %1; mbarrier.arrive.shared::cluster.b64 _, [r];}" ::"r"(b), "r"(cta) : "memory");
}
__device__ __forceinline__ bool mbar_try(uint32_t b, uint32_t par) {
    uint32_t ok;
    asm volatile("{.reg .pred p; mbarrier.try_wait.parity.shared.b64 p, [%1], %2; selp.u32 %0, 1, 0, p;}" : "=r"(ok) : "r"(b), "r"(par) : "memory");
    return ok;
}
__device__ __forceinline__ void mbar_wait(uint32_t b, uint32_t par) {
    int it = 0;
#pragma unroll 1
    while (!mbar_try(b, par) & (++it < SPIN_LIMIT)) {}
}
__device__ __forceinline__ void mbar_wait_w(uint32_t b, uint32_t par) {
    int it = 0;
#pragma unroll 1
    while (!__all_sync(~0u, mbar_try(b, par)) & (++it < SPIN_LIMIT)) {}
}
constexpr uint64_t EVICT_FIRST = 0x12F0000000000000ull, EVICT_NORMAL = 0x1000000000000000ull;   __device__ __forceinline__ void bar_sync(int id, int n) { asm volatile("bar.sync %0, %1;" ::"r"(id), "r"(n) : "memory"); }
__device__ __forceinline__ void bar_arrive(int id, int n) { asm volatile("bar.arrive %0, %1;" ::"r"(id), "r"(n) : "memory"); }
__device__ __forceinline__ void fence_async_smem() { asm volatile("fence.proxy.async.shared::cta;" ::: "memory"); }
__device__ __forceinline__ void ldsm4t(uint32_t* r, uint32_t a) {
    asm volatile("ldmatrix.sync.aligned.m8n8.x4.trans.shared.b16 {%0,%1,%2,%3}, [%4];" : "=r"(r[0]), "=r"(r[1]), "=r"(r[2]), "=r"(r[3]) : "r"(a) : "memory");
}
__device__ __forceinline__ void ldsm4(uint32_t* r, uint32_t a) {
    asm volatile("ldmatrix.sync.aligned.m8n8.x4.shared.b16 {%0,%1,%2,%3}, [%4];" : "=r"(r[0]), "=r"(r[1]), "=r"(r[2]), "=r"(r[3]) : "r"(a) : "memory");
}
__device__ __forceinline__ uint32_t movm(uint32_t a) {
    uint32_t d; asm volatile("movmatrix.sync.aligned.m8n8.trans.b16 %0, %1;" : "=r"(d) : "r"(a)); return d;
}
__device__ __forceinline__ void mma16816(float* d, uint32_t a0, uint32_t a1, uint32_t a2, uint32_t a3, uint32_t b0, uint32_t b1) {
    asm volatile("mma.sync.aligned.m16n8k16.row.col.f32.bf16.bf16.f32 {%0,%1,%2,%3},{%4,%5,%6,%7},{%8,%9},{%0,%1,%2,%3};"
                 : "+f"(d[0]), "+f"(d[1]), "+f"(d[2]), "+f"(d[3]) : "r"(a0), "r"(a1), "r"(a2), "r"(a3), "r"(b0), "r"(b1));
}
__device__ __forceinline__ void mma16816z(float* d, const uint32_t* a, uint32_t b0, uint32_t b1) {
    asm volatile("mma.sync.aligned.m16n8k16.row.col.f32.bf16.bf16.f32 {%0,%1,%2,%3},{%4,%5,%6,%7},{%8,%9},{%10,%10,%10,%10};"
                 : "=f"(d[0]), "=f"(d[1]), "=f"(d[2]), "=f"(d[3]) : "r"(a[0]), "r"(a[1]), "r"(a[2]), "r"(a[3]), "r"(b0), "r"(b1), "f"(0.f));
}
__device__ __forceinline__ void mma1688(float* d, uint32_t a0, uint32_t a1, uint32_t b0) {
    asm volatile("mma.sync.aligned.m16n8k8.row.col.f32.bf16.bf16.f32 {%0,%1,%2,%3},{%4,%5},{%6},{%0,%1,%2,%3};"
                 : "+f"(d[0]), "+f"(d[1]), "+f"(d[2]), "+f"(d[3]) : "r"(a0), "r"(a1), "r"(b0));
}
__device__ __forceinline__ uint32_t pack2(float lo, float hi) {
    uint32_t r; asm("cvt.rn.bf16x2.f32 %0, %1, %2;" : "=r"(r) : "f"(hi), "f"(lo)); return r;
}
__device__ __forceinline__ uint32_t hadd2(uint32_t a, uint32_t b) {
    uint32_t r; asm("add.rn.bf16x2 %0, %1, %2;" : "=r"(r) : "r"(a), "r"(b)); return r;
}
__device__ __forceinline__ float bflo(uint32_t u) { return __uint_as_float(u << 16); }
__device__ __forceinline__ float bfhi(uint32_t u) { return __uint_as_float(u & 0xffff0000u); }
__device__ __forceinline__ float ex2(float x) { float r; asm("ex2.approx.ftz.f32 %0, %1;" : "=f"(r) : "f"(x)); return r; }
__device__ __forceinline__ uint4 ldg_rlx4(const void* p) {
    uint4 v; asm volatile("ld.relaxed.gpu.global.v4.u32 {%0,%1,%2,%3}, [%4];" : "=r"(v.x), "=r"(v.y), "=r"(v.z), "=r"(v.w) : "l"(p) : "memory"); return v;
}
__device__ __forceinline__ uint32_t ldg_rlx1(const void* p) {
    uint32_t v; asm volatile("ld.relaxed.gpu.global.u32 %0, [%1];" : "=r"(v) : "l"(p) : "memory"); return v;
}
__device__ __forceinline__ void stg_rlx1(void* p, uint32_t v) { asm volatile("st.relaxed.gpu.global.u32 [%0], %1;" ::"l"(p), "r"(v) : "memory"); }
__device__ __forceinline__ void stg_rlx2(void* p, uint32_t x, uint32_t y) {
    unsigned long long v = (unsigned long long)x | ((unsigned long long)y << 32);
    asm volatile("st.relaxed.gpu.global.b64 [%0], %1;" ::"l"(p), "l"(v) : "memory");
}
__device__ __forceinline__ void stg_rlx4(void* p, uint32_t x, uint32_t y, uint32_t z, uint32_t w) {
    asm volatile("st.relaxed.gpu.global.v4.u32 [%0], {%1,%2,%3,%4};" ::"l"(p), "r"(x), "r"(y), "r"(z), "r"(w) : "memory");
}
__device__ __forceinline__ void sts4(uint32_t a, uint32_t x, uint32_t y, uint32_t z, uint32_t w) {
    asm volatile("st.shared.v4.u32 [%0], {%1,%2,%3,%4};" ::"r"(a), "r"(x), "r"(y), "r"(z), "r"(w) : "memory");
}
__device__ __forceinline__ uint4 lds4(uint32_t a) {
    uint4 v; asm volatile("ld.shared.v4.u32 {%0,%1,%2,%3}, [%4];" : "=r"(v.x), "=r"(v.y), "=r"(v.z), "=r"(v.w) : "r"(a) : "memory"); return v;
}
#define F4(d, i) "+f"(d[i]), "+f"(d[i + 1]), "+f"(d[i + 2]), "+f"(d[i + 3])
__device__ __forceinline__ void wgmma_rs32(float* d, const uint32_t* a, uint64_t b, int sc) {
    asm volatile("{.reg .pred p; setp.ne.b32 p, %21, 0;\n wgmma.mma_async.sync.aligned.m64n32k16.f32.bf16.bf16 {%0,%1,%2,%3,%4,%5,%6,%7,%8,%9,%10,%11,%12,%13,%14,%15}, {%16,%17,%18,%19}, %20, p, 1, 1, 0;}"
                 : F4(d, 0), F4(d, 4), F4(d, 8), F4(d, 12) : "r"(a[0]), "r"(a[1]), "r"(a[2]), "r"(a[3]), "l"(b), "r"(sc));
}
__device__ __forceinline__ void wgmma_ss32(float* d, uint64_t a, uint64_t b, int sc) {
    asm volatile("{.reg .pred p; setp.ne.b32 p, %18, 0;\n wgmma.mma_async.sync.aligned.m64n32k16.f32.bf16.bf16 {%0,%1,%2,%3,%4,%5,%6,%7,%8,%9,%10,%11,%12,%13,%14,%15}, %16, %17, p, 1, 1, 1, 0;}"
                 : F4(d, 0), F4(d, 4), F4(d, 8), F4(d, 12) : "l"(a), "l"(b), "r"(sc));
}
__device__ __forceinline__ void wgmma_rs40(float* d, const uint32_t* a, uint64_t b, int sc) {
    asm volatile("{.reg .pred p; setp.ne.b32 p, %25, 0;\n wgmma.mma_async.sync.aligned.m64n40k16.f32.bf16.bf16 {%0,%1,%2,%3,%4,%5,%6,%7,%8,%9,%10,%11,%12,%13,%14,%15,%16,%17,%18,%19}, {%20,%21,%22,%23}, %24, p, 1, 1, 0;}"
                 : F4(d, 0), F4(d, 4), F4(d, 8), F4(d, 12), F4(d, 16) : "r"(a[0]), "r"(a[1]), "r"(a[2]), "r"(a[3]), "l"(b), "r"(sc));
}
__device__ __forceinline__ void wgmma_ss40(float* d, uint64_t a, uint64_t b, int sc) {
    asm volatile("{.reg .pred p; setp.ne.b32 p, %22, 0;\n wgmma.mma_async.sync.aligned.m64n40k16.f32.bf16.bf16 {%0,%1,%2,%3,%4,%5,%6,%7,%8,%9,%10,%11,%12,%13,%14,%15,%16,%17,%18,%19}, %20, %21, p, 1, 1, 1, 0;}"
                 : F4(d, 0), F4(d, 4), F4(d, 8), F4(d, 12), F4(d, 16) : "l"(a), "l"(b), "r"(sc));
}
#define F16(d, i) F4(d, i), F4(d, i + 4), F4(d, i + 8), F4(d, i + 12)
template <int TA>
__device__ __forceinline__ void wgmma_ss128(float* d, uint64_t a, uint64_t b, int sc) {
    asm volatile("{.reg .pred p; setp.ne.b32 p, %66, 0;\n wgmma.mma_async.sync.aligned.m64n128k16.f32.bf16.bf16 "
                 "{%0,%1,%2,%3,%4,%5,%6,%7,%8,%9,%10,%11,%12,%13,%14,%15,%16,%17,%18,%19,%20,%21,%22,%23,%24,%25,%26,%27,%28,%29,%30,%31,"
                 "%32,%33,%34,%35,%36,%37,%38,%39,%40,%41,%42,%43,%44,%45,%46,%47,%48,%49,%50,%51,%52,%53,%54,%55,%56,%57,%58,%59,%60,%61,%62,%63}, %64, %65, p, 1, 1, %67, 1;}"
                 : F16(d, 0), F16(d, 16), F16(d, 32), F16(d, 48) : "l"(a), "l"(b), "r"(sc), "n"(TA));
}

__device__ __forceinline__ float warp_sum(float v) {
#pragma unroll
    for (int o = 16; o; o >>= 1) v += __shfl_xor_sync(~0u, v, o);
    return v;
}
__device__ __forceinline__ float bfround(float x) { return __bfloat162float(__float2bfloat16(x)); }

__device__ __forceinline__ void wait_count1(const uint32_t* p, uint32_t target) {
    int it = 0;
#pragma unroll 1
    while (true) {
        uint32_t v;
        asm volatile("ld.acquire.gpu.global.u32 %0, [%1];" : "=r"(v) : "l"(p) : "memory");
        if (v >= target) break;
        spin_guard(++it);
    }
}
__device__ __forceinline__ void red2(float* p, float a, float b) {
    asm volatile("red.relaxed.gpu.global.add.v2.f32 [%0], {%1, %2};" ::"l"(p), "f"(a), "f"(b) : "memory");
}
__device__ __forceinline__ void signal_count(uint32_t* p) { asm volatile("red.release.gpu.global.add.u32 [%0], 1;" ::"l"(p) : "memory"); }
__device__ __forceinline__ void e_expect(uint32_t b, uint32_t tx) {
    asm volatile("{.reg .pred p; elect.sync _|p, 0xffffffff; @p mbarrier.arrive.expect_tx.shared.b64 _, [%0], %1;}" ::"r"(b), "r"(tx) : "memory");
}
__device__ __forceinline__ void e_tma2d(uint32_t dst, const CUtensorMap* m, int c0, int c1, uint32_t bar) {
    asm volatile("{.reg .pred p; elect.sync _|p, 0xffffffff;\n @p cp.async.bulk.tensor.2d.shared::cluster.global.mbarrier::complete_tx::bytes [%0], [%1, {%3, %4}], [%2];}"
                 ::"r"(dst), "l"(m), "r"(bar), "r"(c0), "r"(c1) : "memory");
}
__device__ __forceinline__ void e_tma2d_hint(uint32_t dst, const CUtensorMap* m, int c0, int c1, uint32_t bar, uint64_t pol) {
    asm volatile("{.reg .pred p; elect.sync _|p, 0xffffffff;\n @p cp.async.bulk.tensor.2d.shared::cluster.global.mbarrier::complete_tx::bytes.L2::cache_hint [%0], [%1, {%3, %4}], [%2], %5;}"
                 ::"r"(dst), "l"(m), "r"(bar), "r"(c0), "r"(c1), "l"(pol) : "memory");
}
__device__ __forceinline__ void e_tma2d_mc(uint32_t dst, const CUtensorMap* m, int c0, int c1, uint32_t bar) {
    asm volatile("{.reg .pred p; elect.sync _|p, 0xffffffff;\n @p cp.async.bulk.tensor.2d.shared::cluster.global.mbarrier::complete_tx::bytes.multicast::cluster [%0], [%1, {%3, %4}], [%2], %5;}"
                 ::"r"(dst), "l"(m), "r"(bar), "r"(c0), "r"(c1), "h"((uint16_t)3) : "memory");
}
__device__ __forceinline__ void wait_count_w(const uint32_t* p, uint32_t target) {
    int it = 0;
#pragma unroll 1
    while (true) {
        uint32_t v;
        asm volatile("ld.acquire.gpu.global.u32 %0, [%1];" : "=r"(v) : "l"(p) : "memory");
        if (__all_sync(~0u, v >= target) | (++it > SPIN_LIMIT)) break;
        __nanosleep(100);
    }
}

#define NL 6
constexpr uint32_t SM_HB = 16384, HBK = 5120, SM_SX = 57344, SM_OX = 122880, SM_PX = 124928, SM_PA = 126976, SM_WO = 147456,
                   SM_TAB = 212992, SM_PRE = SM_TAB + 5120, SM_BAR = 227328, SM_REC_TOTAL = 227328 + 256;
constexpr uint32_t SB0 = 1024;
constexpr int B_WO = 0, B_HE = 1, B_HB = 3, B_W = 5;
constexpr int NB_MEM = 1, NB_QK = 2, NB_X1 = 3, NB_X2 = 4, NB_WIN = 5, NB_WG = 6, NB_KDONE = 7, NB_FIN0 = 8, NB_P = 9, NB_PX = 10, NB_G = 11, NB_A = 12, NB_B = 13, NB_C = 14, NB_S = 15;
#define D_NEAR 1620
#define D_FAR (D_NEAR - 90)
#define D_X2 400
#define D_V 280
#define D_W2 40
#define D_PA 40
#define D_MORE 40
#define D_MORE2 30
constexpr int E_MUL = 28;
constexpr int NPF = NL + 6, NE1 = 10;
constexpr int W0_E = 3, W0_RS = NL - 1, G_AT = 18;
struct Delays { uint32_t near, far, x2, v, w2, pa, more2, more; };

__device__ __forceinline__ uint32_t clk32() { uint32_t t; asm volatile("mov.u32 %0, %%clock;" : "=r"(t) :: "memory"); return t; }
__device__ __forceinline__ uint32_t smid() { uint32_t t; asm volatile("mov.u32 %0, %%smid;" : "=r"(t)); return t; }
__device__ __forceinline__ uint32_t gtime() { uint32_t t; asm volatile("mov.u32 %0, %%globaltimer_lo;" : "=r"(t) :: "memory"); return t; }
__device__ __forceinline__ void spin_until(uint32_t t0, uint32_t d) { while (clk32() - t0 < d) {} }
template <int N> __device__ __forceinline__ uint32_t delay(uint32_t zero) {
    float x = __uint_as_float(clk32());
#pragma unroll
    for (int i = 0; i < N; i++) asm volatile("ex2.approx.ftz.f32 %0, %0;" : "+f"(x));
    return __float_as_uint(x) & zero;
}
__device__ __forceinline__ uint32_t opaque(uint32_t v) { return __shfl_sync(~0u, v, threadIdx.x & 31); }
__device__ __forceinline__ uint32_t xor_or(uint32_t a, uint32_t b, uint32_t t) {
    uint32_t r; asm volatile("lop3.b32 %0, %1, %2, %3, 0x7E;" : "=r"(r) : "r"(a), "r"(b), "r"(t)); return r;
}
__device__ __forceinline__ uint32_t settag(uint32_t v, uint32_t tag) {
    uint32_t r; asm("lop3.b32 %0, %1, 1, %2, 0xB8;" : "=r"(r) : "r"(v), "r"(tag)); return r;
}
__device__ __forceinline__ void sts2(uint32_t a, float x, float y) { asm volatile("st.shared.v2.f32 [%0], {%1,%2};" ::"r"(a), "f"(x), "f"(y) : "memory"); }
__device__ __forceinline__ void sts4f(uint32_t a, float x, float y, float z, float w) {
    asm volatile("st.shared.v4.f32 [%0], {%1,%2,%3,%4};" ::"r"(a), "f"(x), "f"(y), "f"(z), "f"(w) : "memory");
}
__device__ __forceinline__ void sts1(uint32_t a, uint32_t x) { asm volatile("st.shared.u32 [%0], %1;" ::"r"(a), "r"(x) : "memory"); }
__device__ __forceinline__ uint32_t lds1(uint32_t a) { uint32_t v; asm volatile("ld.shared.u32 %0, [%1];" : "=r"(v) : "r"(a) : "memory"); return v; }
__device__ __forceinline__ float4 lds4f(uint32_t a) {
    float4 v; asm volatile("ld.shared.v4.f32 {%0,%1,%2,%3}, [%4];" : "=f"(v.x), "=f"(v.y), "=f"(v.z), "=f"(v.w) : "r"(a) : "memory"); return v;
}
__device__ __forceinline__ float2 lds2f(uint32_t a) {
    float2 v; asm volatile("ld.shared.v2.f32 {%0,%1}, [%2];" : "=f"(v.x), "=f"(v.y) : "r"(a) : "memory"); return v;
}
__device__ __forceinline__ bool any_bit0(uint32_t x) {
    uint32_t r;
    asm volatile("{.reg .pred p, q; .reg .b32 t; and.b32 t, %1, 1; setp.ne.u32 p, t, 0; vote.sync.any.pred q, p, 0xffffffff; selp.u32 %0, 1, 0, q;}" : "=r"(r) : "r"(x));
    return r;
}
__device__ __forceinline__ float rcp_fast(float x) { float r; asm("rcp.approx.ftz.f32 %0, %1;" : "=f"(r) : "f"(x)); return r; }
__device__ __forceinline__ void stsm4(uint32_t a, uint32_t r0, uint32_t r1, uint32_t r2, uint32_t r3) {
    asm volatile("stmatrix.sync.aligned.m8n8.x4.shared.b16 [%0], {%1,%2,%3,%4};" ::"r"(a), "r"(r0), "r"(r1), "r"(r2), "r"(r3) : "memory");
}
__device__ __forceinline__ void stsm4t(uint32_t a, uint32_t r0, uint32_t r1, uint32_t r2, uint32_t r3) {
    asm volatile("stmatrix.sync.aligned.m8n8.x4.trans.shared.b16 [%0], {%1,%2,%3,%4};" ::"r"(a), "r"(r0), "r"(r1), "r"(r2), "r"(r3) : "memory");
}
__device__ __forceinline__ uint32_t and3(uint32_t a, uint32_t b, uint32_t c) {
    uint32_t r; asm("lop3.b32 %0, %1, %2, %3, 0x80;" : "=r"(r) : "r"(a), "r"(b), "r"(c)); return r;
}
__device__ __forceinline__ void red_mem(void* p, uint32_t x, uint32_t y, uint32_t z, uint32_t w, void* q, uint32_t e, bool c) {
    asm volatile("{.reg .pred p; setp.ne.u32 p, %7, 0; red.relaxed.gpu.global.add.noftz.v4.bf16x2 [%0], {%1,%2,%3,%4}; @p red.relaxed.gpu.global.add.noftz.bf16x2 [%5], %6;}"
                 ::"l"(p), "r"(x), "r"(y), "r"(z), "r"(w), "l"(q), "r"(e), "r"((uint32_t)c) : "memory");
}
__device__ __forceinline__ void stg4_if(bool c, void* p, uint32_t x) {
    asm volatile("{.reg .pred p; setp.ne.u32 p, %2, 0; @p st.relaxed.gpu.global.v4.u32 [%0], {%1,%1,%1,%1};}" ::"l"(p), "r"(x), "r"((uint32_t)c) : "memory");
}

__device__ __forceinline__ void h_load(uint32_t sb, const uint8_t* hsrc, int pass, uint32_t rank, uint32_t rot) {
    const uint8_t* src = hsrc + (size_t)pass * 65536;
    const uint32_t bar = sb + SM_BAR + 8 * (B_HB + (pass & 1)), dst = sb + SM_HB + (pass & 1) * 65536 + rank * 4 * HBK;
    e_expect(bar, 32768);
#pragma unroll 1
    for (int i = 0; i < H_PIECES; i++) {
        const uint32_t o = ((i + rot) & (H_PIECES - 1)) * (16384 / H_PIECES);
        asm volatile("{.reg .pred p; elect.sync _|p, 0xffffffff;\n"
                     " @p cp.async.bulk.shared::cluster.global.mbarrier::complete_tx::bytes.multicast::cluster [%0], [%1], %4, [%2], %3;}"
                     ::"r"(dst + o + (o >> 12) * 1024), "l"(src + o), "r"(bar), "h"((uint16_t)3), "n"(16384 / H_PIECES) : "memory");
    }
}
__device__ __forceinline__ uint4 ldg_b128(const void* p) {
    uint4 v;
    asm volatile("{.reg .b128 t; .reg .b64 a, b; ld.relaxed.gpu.global.b128 t, [%4]; mov.b128 {a, b}, t; mov.b64 {%0,%1}, a; mov.b64 {%2,%3}, b;}"
                 : "=r"(v.x), "=r"(v.y), "=r"(v.z), "=r"(v.w) : "l"(p) : "memory");
    return v;
}
__device__ __forceinline__ void stg_b128_if(bool c, void* p, uint32_t x, uint32_t y, uint32_t z, uint32_t w) {
    asm volatile("{.reg .pred p; setp.ne.u32 p, %5, 0; @p st.relaxed.gpu.global.v4.u32 [%0], {%1,%2,%3,%4};}"
                 ::"l"(p), "r"(x), "r"(y), "r"(z), "r"(w), "r"((uint32_t)c) : "memory");
}
__device__ __forceinline__ float pretag(float x, uint32_t add, uint32_t keep) { return __uint_as_float((__float_as_uint(x) + add) & keep); }

template <class F, class G>
__device__ __forceinline__ void softmax_rows(uint32_t src, uint32_t dst, uint32_t g16, int row0, F ready, G mid) {
    const uint32_t u = (g16 >> 7) & 3, e = ((g16 >> 9) << 3) | ((g16 >> 4) & 7);
    uint32_t se = src + e * 8, su = se + u * 1088, d0 = dst + e * 16 + u * 4, d1 = dst + 512 + e * 4;
    int vis = row0 + (e >> 2) - 2 * (e & 3) - 8 * u;
    asm volatile("" : "+r"(se), "+r"(su), "+r"(d0), "+r"(d1), "+r"(vis));
    ready();
    const float2 p0 = lds2f(su), p1 = lds2f(su + 256), p2 = lds2f(su + 512), p3 = lds2f(su + 768);
    const float2 m0 = lds2f(se + 4352), m1 = lds2f(se + 4352 + 256), m2 = lds2f(se + 4352 + 512), m3 = lds2f(se + 4352 + 768);
    float a0 = (p0.x + p1.x) + (p2.x + p3.x), a1 = (p0.y + p1.y) + (p2.y + p3.y);
    const float a2 = (m0.x + m1.x) + (m2.x + m3.x), a3 = (m0.y + m1.y) + (m2.y + m3.y);
    if (vis < 0) a0 = -1e9f / 0.08838834764831845f;
    if (vis < 1) a1 = -1e9f / 0.08838834764831845f;
    int k = __float_as_int(fmaxf(fmaxf(a0, a1), fmaxf(a2, a3)));
    k ^= (k >> 31) & 0x7fffffff;
    const bool hi = g16 & 64;
    const int k0 = __reduce_max_sync(~0u, hi ? INT_MIN : k), k1 = __reduce_max_sync(~0u, hi ? k : INT_MIN);
    mid();
    k = hi ? k1 : k0;
    const float m = __int_as_float(k ^ ((k >> 31) & 0x7fffffff));
    const float sl2 = 0.08838834764831845f * 1.4426950408889634f, mb = -m * sl2;
    sts1(d0, pack2(ex2(fmaf(a0, sl2, mb)), ex2(fmaf(a1, sl2, mb))));
    sts1(d1, pack2(ex2(fmaf(a2, sl2, mb)), ex2(fmaf(a3, sl2, mb))));
}

__device__ __forceinline__ uint32_t pack_h2(float lo, float hi) {
    uint32_t r; asm("cvt.rn.satfinite.f16x2.f32 %0, %1, %2;" : "=r"(r) : "f"(hi), "f"(lo)); return r;
}
__device__ __forceinline__ float2 unpack_h2(uint32_t u) {
    float2 r; asm("{.reg .b16 l, h; mov.b32 {l, h}, %2; cvt.f32.f16 %0, l; cvt.f32.f16 %1, h;}" : "=f"(r.x), "=f"(r.y) : "r"(u)); return r;
}
__device__ __forceinline__ uint32_t add_h2(uint32_t a, uint32_t b) { uint32_t r; asm("add.rn.f16x2 %0, %1, %2;" : "=r"(r) : "r"(a), "r"(b)); return r; }
__device__ __forceinline__ uint32_t max_h2(uint32_t a, uint32_t b) { uint32_t r; asm("max.f16x2 %0, %1, %2;" : "=r"(r) : "r"(a), "r"(b)); return r; }
struct U2 { uint32_t x, y; };
__device__ __forceinline__ U2 ldg_u2(const void* p) {
    U2 v; asm volatile("{.reg .b64 t; ld.relaxed.gpu.global.b64 t, [%2]; mov.b64 {%0, %1}, t;}" : "=r"(v.x), "=r"(v.y) : "l"(p) : "memory"); return v;
}
constexpr int POLL_LIMIT = 1 << 16;
constexpr float SM_L2E = 0.08838834764831845f * 1.4426950408889634f;
template <int V> struct IC { static constexpr int value = V; };
typedef unsigned long long u64;
__device__ __forceinline__ u64 ldg_u64(const void* p) { u64 v; asm volatile("ld.relaxed.gpu.global.b64 %0, [%1];" : "=l"(v) : "l"(p) : "memory"); return v; }
__device__ __forceinline__ void rec_main(uint32_t sb, const CUtensorMap* tWo, uint8_t* arena, int role, int hinfo, int wg, uint32_t zero, const Delays& dly) {
    const int hA = hinfo & 255;
    const int tid = threadIdx.x, t = tid & 127, lane = tid & 31, wi = t >> 5;
    const uint32_t bars = sb + SM_BAR;
    const int head = role >> 2, qd = role & 3, j = blockIdx.x & 1, kh = role & 1;
    const uint32_t mypar = head >= hA;
    const uint32_t wu = __reduce_max_sync(~0u, wi);
    const bool warp0 = wu == 0, warp1 = wu == 1;
    const uint8_t* hsrc = (const uint8_t*)g_himg + kh * 32768 + j * 16384;
    auto tokbase = [&](int ty) { return ((ty + 1) << 21) + blk(lb_tok(head), mypar ^ ((hinfo >> (8 + ty)) & 1)); };
    const uint32_t tbw = tokbase(wg), tbq = tokbase(0) + (qd >> 1) * 2048 + (qd & 1) * 8;
    uint32_t w[32 - NL][4];
    const uint32_t frow = ((lane >> 4) * 8 + (lane & 7)) * 128, fx = ((lane >> 3) & 1) ^ (lane & 7);
    const uint32_t wl0 = sb + wg * 65536 + frow + ((fx ^ (2 * wi)) << 4);
    uint32_t g16 = opaque(t * 16);
    auto G16 = [&]() { asm volatile("" : "+r"(g16)); return g16; };
    const uint32_t sbl = sb - wu * 512;
    const uint32_t xso = blk(lb_x2(head), mypar), cu = kh * 2048 + (2 * j + (wu >> 1)) * 512;
    const uint32_t u_xo = xso + wg * 16384 + (wu & 1) * 2048 + (cu >> 1) - wu * 256, u_to = tbw + (wu & 1) * 16384 + cu - wu * 512;
    {
        uint8_t* pp = arena + (tbw + (1 << 20) + j * 16384 + (kh ^ 1) * 2048 + g16);
        stg_rlx4(pp, 0, 0, 0, 0);
        stg_rlx4(pp + 32768, 0, 0, 0, 0);
        stg_rlx4(arena + (u_to + g16), 0, 0, 0, 0);
        stg_rlx2(arena + (u_xo + (g16 >> 1)), 0, 0);
    }
    {
        if (wg > 0) wait_count_w(&g_tick[32 + (lane & 3) * 8], 1);
        if (wg == 1) asm volatile("fence.proxy.async.global;" ::: "memory");
#pragma unroll 1
        for (int i = 0; i < 4; i++) mbar_wait_w(bars + 8 * (B_W + (wg == 2 ? 8 + i : 2 * i + wg)), 0);
#pragma unroll
        for (int p = NL; p < 32; p++) ldsm4t(w[p - NL], wl0 + p * 2048);
        fence_async_smem();
        bar_sync(wg < 2 ? NB_WG : NB_X2, wg < 2 ? 256 : 128);
        if (wg == 2 && wu < 3) {
            e_expect(bars + 8 * B_WO, 16384);
            e_tma2d(sb + SM_WO + wu * 16384, tWo, (wu >> 1) * 512 + qd * 128 + (wu & 1) * 64, head * DH, bars + 8 * B_WO);
            e_tma2d(sb + SM_WO + wu * 16384 + 8192, tWo, (wu >> 1) * 512 + qd * 128 + (wu & 1) * 64, head * DH + 64, bars + 8 * B_WO);
        }
        if (wg == 1 && warp0) {
            if (lane == 0) mbar_arrive_cluster(bars + 8 * B_HE, j ^ 1);
            mbar_wait_w(bars + 8 * B_HE, 0);
#pragma unroll 1
            for (int i = 0; i < 2; i++) h_load(sb, hsrc, i, j, head);
        }
    }
    const uint32_t mrow = wg < 2 ? mem_row(wu >> 1, wg * 2 + (wu & 1), qd) : mem_row(kh, wu, 0);
    const uint32_t u_m = mrow - wu * 512, u_e = mrow + 512 - wu * 64;
#define TAB(i) lds1(sb + SM_TAB + (i) * 512 + (G16() >> 2))
    {
        const uint32_t r8 = lane & 7;
        const uint32_t tb = sb + SM_TAB + wg * 1536 + t * 4, ma = sb + SM_HB + 4096 + r8 * 128;
        if (wg < 2) {
            sts1(tb, sb + SM_WO + wi * 16384 + frow + ((fx ^ (2 * wg)) << 4));
            sts1(tb + 512, wl0);
            sts1(tb + 1024, ma + (((lane >> 3) ^ r8) << 4));
        } else {
            sts1(tb, ma + (wi & 1) * HBK + ((((wi & 2) + (lane >> 4) * 4 + ((lane >> 3) & 1)) ^ r8) << 4));
            sts1(tb + 512, ((((wi & 2) + 4) ^ r8) << 4) + ((lane & 3) == 2 ? ma + 128 + ((wi & 1) + (lane >> 3) * 2) * HBK : sb + SM_HB - 128));
            sts1(tb + 1024, mem_row(role >> 6, (role >> 4) & 3, (role >> 2) & 3) + (lane < 8 ? qd * 128 + lane * 16 : 512 + qd * 32 + (lane & 1) * 16));
        }
    }
#define HB(ks) dadd(mkdesc(SB0 + SM_HB + ((ks) >> 2) * HBK + ((ks) & 3) * 32, 16, 1024, 1), hbo)
#define STEP_CONSTS                                                                                  \
    const uint32_t tag = (s & 1) ^ 1, ttag = ((s >> 1) & 1) ^ 1, tso = (s & 1) * 32768;              \
    G16();                            \
    const int p = s + 2, b = p & 1;                                                                  \
    uint32_t hbo = b * 4096, fz[5] = {0, 0, 0, 0, 0};                                                   \
    const uint32_t ftag = (((p - 1) >> 1) & 1) ^ 1, ptag = ((p >> 1) & 1) ^ 1;                       \
    const uint32_t pso = tbw + (1 << 20) + (b ^ 1) * 32768 + j * 16384 + kh * 2048;
#define SCHED_FENCE(i) fz[i] = clk32();
#define FZ ((fz[0] | fz[1] | fz[2] | fz[3] | fz[4]) & zero)
#define BLOCK_FENCE asm volatile("pmevent 0;" ::: "memory");
    constexpr int GAP = 32 / NL;
#define l16 (sbl + g16)
#define g8 (g16 >> 1)
    uint4 u, v;
    uint8_t *pdst, *fdst;
    auto tok_pack = [&](int ty, const float* acc, uint32_t ftag, uint32_t ptag, bool later = false) {
        const bool tg = ty == 2 || !(g16 & 64);
        const uint32_t add = tg ? (ftag ^ 1) << 16 : 0u, keep = tg ? 0xfffe0000u : ~0u;
        const uint32_t add1 = ty == 2 ? 0u : add, keep1 = ty == 2 ? ~0u : keep;
        const uint32_t add2 = ty == 0 ? add : 0u, keep2 = ty == 0 ? keep : ~0u;
        v = {pack2(pretag(acc[0], add, keep), pretag(acc[1], add1, keep1)), pack2(acc[2], acc[3]),
             pack2(pretag(acc[4], add2, keep2), pretag(acc[5], add2, keep2)), pack2(acc[6], acc[7])};
        if (ty < 2) { v.x = movm(v.x); v.z = movm(v.z); v.y = movm(v.y); v.w = movm(v.w); }
        u = {pack2(pretag(acc[8], (ptag ^ 1) << 16, 0xfffe0000u), acc[9]) | ptag, pack2(acc[10], acc[11]), pack2(acc[12], acc[13]), pack2(acc[14], acc[15])};
        if (later) return;
        v.x = settag(v.x, ftag);
        if (ty == 0) v.z = settag(v.z, ftag);
    };

#pragma unroll 1
    for (int s = -2; s < 0; s++) {
        STEP_CONSTS
        (void)tag; (void)ttag; (void)tso; (void)fz;
        float acc[16];
        mbar_wait_w(bars + 8 * (B_HB + b), 0);
        wg_fence();
#pragma unroll
        for (int i = 0; i < 32; i++) {
            if (i < NL) wgmma_ss32(acc, dadd(mkdesc(SB0 + i * 2048, 8192, 1024, 1), wg * 4096), HB(i), i != 0);
            else wgmma_rs32(acc, w[i < NL ? 0 : i - NL], HB(i), 1);
        }
        wg_commit();
        uint4 pa = {0, 0, 0, 0};
        int it = 0;
#pragma unroll 1
        while ((p > 0) & any_bit0(pa.x ^ ftag) & (++it < POLL_LIMIT)) pa = ldg_b128(arena + (pso + g16));
        pdst = arena + ((pso ^ (32768 + 2048)) + G16());
        fdst = arena + ((b ^ 1) * 32768 + u_to + g16);
        wg_wait<0>();
#pragma unroll
        for (int k = 0; k < 4; k++) { acc[2 * k] += bflo((&pa.x)[k]); acc[2 * k + 1] += bfhi((&pa.x)[k]); }
        tok_pack(wg, acc, ftag, ptag);
        stg_b128_if(true, pdst, u.x, u.y, u.z, u.w);
        stg_b128_if(p > 0, fdst, v.x, v.y, v.z, v.w);
        if (p == 0) {
            if (wg != 1) bar_arrive(NB_C, 288);
        }
    }
    if (wg == 1 && warp0) {
        wait_count_w(&g_tick[32 + (lane & 3) * 8], 2);
        asm volatile("fence.proxy.async.global;" ::: "memory");
        bar_sync(NB_C, 288);
        if (g16 == 0) mbar_arrive_cluster(bars + 8 * B_HE, j ^ 1);
        mbar_wait_w(bars + 8 * B_HE, 1);
        h_load(sb, hsrc, 2, j, head);
    }

    auto qk_loop = [&](auto wgc) {
        constexpr int WG = decltype(wgc)::value;
        uint32_t w0[NL][4], lm0;
        auto w0_load = [&]() {
            const uint32_t wl = TAB(WG * 3 + 1);
            lm0 = TAB(WG * 3 + 2);
#pragma unroll
            for (int k = 0; k < NL; k++) ldsm4t(w0[k], wl + k * 2048);
        };
        const uint32_t wlo = WG * 65536 - SM_WO - wu * 16384, wlx = __reduce_max_sync(~0u, (wi ^ WG) << 5);
        uint32_t tq0, lm, lm1, dx2 = dly.x2;
        auto proj_pre = [&](int s) {
            uint32_t wz0 = zero;
#pragma unroll
            for (int k = 0; k < NL; k += 2) wz0 = and3(wz0, w0[k][0], w0[k + 1 < NL ? k + 1 : k][0]);
            lm = lm0 + (s & 1) * 65536 + wz0; lm1 = lm ^ 64;
            asm volatile("" : "+r"(lm), "+r"(lm1));
        };
        auto proj = [&](int s, auto mid) {
            bar_sync(NB_MEM, 384);
            float c[4][4];
            uint32_t bf[16][4], tq1;
#pragma unroll
            for (int it = 0; it < 3; it++) ldsm4(bf[it], (it & 1 ? lm1 : lm) + (it >> 1) * HBK);
            mid(-1);
#pragma unroll
            for (int it = 0; it < 16; it++) {
                const uint32_t* bfr = bf[it];
                if (it + 3 < 16) ldsm4(bf[it + 3 < 16 ? it + 3 : 0], (it & 1 ? lm : lm1) + ((it + 3) >> 1) * HBK);
                const uint32_t* wa = 2 * it < NL ? w0[2 * it < NL ? 2 * it : 0] : w[2 * it < NL ? 0 : 2 * it - NL];
                const uint32_t* wb = 2 * it + 1 < NL ? w0[2 * it + 1 < NL ? 2 * it + 1 : 0] : w[2 * it + 1 < NL ? 0 : 2 * it + 1 - NL];
                float *ca = c[(2 * it) & 3], *cb = c[(2 * it + 1) & 3];
                if (it < 2) { mma16816z(ca, wa, bfr[0], bfr[1]); mma16816z(cb, wb, bfr[2], bfr[3]); }
                else { mma16816(ca, wa[0], wa[1], wa[2], wa[3], bfr[0], bfr[1]); mma16816(cb, wb[0], wb[1], wb[2], wb[3], bfr[2], bfr[3]); }
                mid(it);
                if (it == 15) { tq1 = clk32(); bar_arrive(NB_QK, 384); }
            }
            const uint32_t xo = u_xo + (G16() >> 1);
            float r[4];
#pragma unroll
            for (int e = 0; e < 4; e++) {
                constexpr float SH = SM_L2E / 64;
                r[e] = WG ? (c[0][e] + c[1][e]) + (c[2][e] + c[3][e]) : fmaf(c[2][e] + c[3][e], SH, (c[0][e] + c[1][e]) * SH);
            }
            const uint32_t r0 = pack2(r[0], r[1]), r1 = pack2(r[2], r[3]);
            const uint32_t m0 = movm(r0), m1 = movm(r1);
            tq0 = clk32();
            stg_rlx2(arena + xo, settag(m0, (s & 1) ^ 1), m1);
            tq0 += tq1 & zero;
        };
        w0_load();
        proj_pre(0);
        if (WG == 1) bar_sync(NB_P, 256);
        proj(0, [](int) {});
        if (WG == 0) mbar_wait_w(bars + 8 * B_WO, 0);
#pragma unroll 1
        for (int s = 0;; s++) {
            STEP_CONSTS
            uint4 pa;
            float acc[16];
            auto acc_init = [&]() {
#pragma unroll
                for (int k = 0; k < 4; k++) { acc[2 * k] = bflo((&pa.x)[k]); acc[2 * k + 1] = bfhi((&pa.x)[k]); acc[8 + 2 * k] = __uint_as_float((&pa.x)[k] & zero); acc[9 + 2 * k] = __uint_as_float(~(&pa.x)[k] & zero); }
            };
            uint32_t wf[NPF][4], a3;
#define WF(f) ((a3 ^ (((f) & 1) * 64)) + ((f) >> 1) * 2048)
            if (WG == 1) {
                float sc[5][4];
                uint32_t sx0 = sb + SM_SX - wu * (2560 - 16) + G16() * 5;
                asm volatile("" : "+r"(sx0));
                int it = 0;
                bool bad;
#pragma unroll 1
                do {
                    uint4 kf[2][2];
                    U2 qf[2], x[8];
                    const uint32_t gz = g16 | (it & zero);
                    const uint8_t *ts = arena + (tso + tbw + gz), *tq = arena + (tso + tbq + gz), *xp = arena + (xso + (gz >> 1));
#pragma unroll
                    for (int a = 0; a < 4; a++) kf[a >> 1][a & 1] = ldg_b128(ts + (a >> 1) * 16384 + (a & 1) * 2048);
                    spin_until(tq0, dx2 - 100);
#pragma unroll
                    for (int a = 0; a < 2; a++) qf[a] = ldg_u2(tq + a * 16384);
                    spin_until(tq0, dx2);
#pragma unroll
                    for (int i = 0; i < 8; i++) x[i] = ldg_u2(xp + (i >> 2) * 16384 + (i & 3) * 1024);
                    const uint32_t q0[4] = {hadd2(x[0].x, x[1].x), qf[0].x, hadd2(x[0].y, x[1].y), qf[0].y};
                    const uint32_t q1[4] = {hadd2(x[2].x, x[3].x), qf[1].x, hadd2(x[2].y, x[3].y), qf[1].y};
                    const uint32_t bt = ((qf[0].x ^ ttag) | (qf[1].x ^ ttag)) | ((kf[0][0].x ^ ttag) | (kf[0][1].x ^ ttag)) | ((kf[1][0].x ^ ttag) | (kf[1][1].x ^ ttag));
                    uint32_t bx = 0;
#pragma unroll
                    for (int i = 0; i < 8; i += 2) bx |= (x[i].x ^ tag) | (x[i + 1].x ^ tag);
                    mma16816z(sc[0], q0, kf[0][0].x, kf[0][0].y);
                    mma16816z(sc[1], q0, kf[0][0].z, kf[0][0].w);
                    mma16816z(sc[2], q0, kf[0][1].x, kf[0][1].y);
                    mma16816z(sc[3], q0, kf[0][1].z, kf[0][1].w);
                    mma16816z(sc[4], q0, hadd2(x[4].x, x[5].x), hadd2(x[4].y, x[5].y));
                    bad = any_bit0(bt | bx) & (++it < POLL_LIMIT);
                    mma16816(sc[0], q1[0], q1[1], q1[2], q1[3], kf[1][0].x, kf[1][0].y);
                    mma16816(sc[1], q1[0], q1[1], q1[2], q1[3], kf[1][0].z, kf[1][0].w);
                    mma16816(sc[2], q1[0], q1[1], q1[2], q1[3], kf[1][1].x, kf[1][1].y);
                    mma16816(sc[3], q1[0], q1[1], q1[2], q1[3], kf[1][1].z, kf[1][1].w);
                    mma16816(sc[4], q1[0], q1[1], q1[2], q1[3], hadd2(x[6].x, x[7].x), hadd2(x[6].y, x[7].y));
                } while (bad);
                sts4(sx0, pack_h2(sc[0][0], sc[0][1]), pack_h2(sc[1][0], sc[1][1]), pack_h2(sc[2][0], sc[2][1]), pack_h2(sc[3][0], sc[3][1]));
                sts1(sx0 + 64 - wu * 12, pack_h2(sc[4][0], sc[4][1]));
                bar_arrive(NB_X1, 384);
                if (it > 1 && s > 1) dx2 += dly.more2;
                auto tok_sts = [&]() {
#pragma unroll
                    for (int n = 0; n < 5; n++) sts2(sb + SM_SX + 2560 + g8 + n * 1088, sc[n][2], sc[n][3]);
                };
                a3 = TAB(WG * 3);
                if (s == 0) mbar_wait_w(bars + 8 * B_WO, 0);
                softmax_rows(sb + SM_SX + 2560, sb + SM_PX + 1024, g16 | (clk32() & zero), qd * 8, [&]() { BLOCK_FENCE tok_sts(); bar_sync(NB_PX, 128); }, [&]() {
                    BLOCK_FENCE
#pragma unroll
                    for (int f = 0; f < NE1; f++) ldsm4t(wf[f], WF(f));
                    BLOCK_FENCE
                });
            } else {
                a3 = TAB(WG * 3);
                if (warp1 && (s & 3) == 1) asm volatile("fence.proxy.async.global;" ::: "memory");
                spin_until(tq0, dly.pa);
                uint4 x, y;
                int it = 0;
#pragma unroll 1
                do { x = ldg_b128(arena + (pso + g16)); y = ldg_b128(arena + (pso + tokbase(1) - tokbase(0) + g16)); }
                while ((p <= NSEG) & any_bit0(xor_or(x.x, y.x, ftag)) & (++it < POLL_LIMIT));
                sts4(sb + SM_PA + g16, x.x, x.y, x.z, x.w);
                sts4(sb + SM_PA + 2048 + g16, y.x, y.y, y.z, y.w);
                bar_sync(NB_X1, 384);
                if (g16 < 32) asm volatile("red.relaxed.gpu.global.max.u32 [%0], %1; red.relaxed.gpu.global.add.u32 [%0+4], 1;"
                                                    ::"l"(arena + ((blk(LB_TIME, 0) ^ (g16 << 8)) + qd * 1024 + (tq0 & zero))), "r"(gtime()) : "memory");
                __syncwarp();
                const uint32_t tx = clk32();
                spin_until(tx, dly.w2);
            }
#pragma unroll
            for (int f = WG ? NE1 : 0; f < NPF; f++) ldsm4t(wf[f], WF(f));
            if (s + 1 == NSEG) { bar_arrive(NB_X2, 384); break; }
            const uint32_t oa = l16 + SM_OX, slot = mem_slot(s + 1);
            float c[4][4];
            uint32_t ob[4][4];
            BLOCK_FENCE
            bar_sync(NB_X2, 384);
            ldsm4t(ob[0], oa);
            ldsm4t(ob[1], oa + 512);
            SCHED_FENCE(0)
#pragma unroll
            for (int f = 0; f < 16; f++) {
                const uint32_t *a = wf[f % NPF], *o = ob[f >> 2] + (f & 2);
                if (f < 4) mma16816z(c[f], a, o[0], o[1]);
                else mma16816(c[f & 3], a[0], a[1], a[2], a[3], o[0], o[1]);
                if (f == 3) ldsm4t(ob[2], oa + 1024);
                if (f == 5) { ldsm4t(ob[3], oa + 1536); if (NPF < 16) ldsm4t(wf[0], WF(NPF)); }
                if (f == 7) {
#pragma unroll
                    for (int k = NPF + 1; k < 16; k++) ldsm4t(wf[k - NPF], WF(k));
                }
                if (f == 3 || f == 5 || f == 7) SCHED_FENCE(f / 2)
                if (f == 11) {
#pragma unroll
                    for (int k = NL - W0_E; k < NL; k++) ldsm4t(w0[k], (a3 ^ wlx) + wlo + k * 2048);
                    SCHED_FENCE(4)
                }
            }
            const float last = c[1][3] + c[3][3], one = __uint_as_float(CNT1 << 16);
            red_mem(arena + (u_m + slot + G16()), pack2(c[0][0] + c[2][0], c[0][1] + c[2][1]), pack2(c[0][2] + c[2][2], c[0][3] + c[2][3]),
                    pack2(c[1][0] + c[3][0], c[1][1] + c[3][1]), pack2(c[1][2] + c[3][2], g16 & 16 ? one : last),
                    arena + (u_e + slot + ((g16 >> 3) & ~3u)), pack2(last, one), g16 & 16);
            hbo += FZ;
            constexpr int NS = NL - W0_RS, GS = (32 - NL + NS) / NS;
            BLOCK_FENCE
#pragma unroll
            for (int k = NL - W0_E - 1; k >= 0; k--) ldsm4t(w0[k], (a3 ^ wlx) + wlo + k * 2048);
            lm0 = TAB(WG * 3 + 2);
            if (WG == 1) pa = lds4(sb + SM_PA + 2048 + g16);
            if (WG == 0) {
                bar_arrive(NB_WIN, 384);
                pa = lds4(sb + SM_PA + g16);
                acc_init();
                asm volatile("" : F16(acc, 0));
                BLOCK_FENCE
            }
            wg_fence();
            bar_sync(WG ? NB_WIN : NB_B, WG ? 384 : 256);
#pragma unroll
            for (int i = 0; i < 32; i++) {
                const int k = i / GS;
                if (i >= 32 - NL + NS) wgmma_rs32(acc, w0[i < 32 - NL + NS ? 0 : i - 32 + NL], HB(i - 32 + NL), 1);
                else if (i % GS == GS - 1 && k < NS) wgmma_ss32(acc, mkdesc(SB0 + WG * 65536 + k * 2048, 8192, 1024, 1), HB(k), 1);
                else wgmma_rs32(acc, w[i - (k < NS ? k : NS)], HB(NL + i - (k < NS ? k : NS)), WG == 0 || i);
                if (WG == 1 && i == G_AT) bar_arrive(NB_B, 256);
                if (WG == 1 && i == 31 - NL + NS) wg_fence();
            }
            wg_commit();
            BLOCK_FENCE
            if (WG == 1 && warp0 && !(s & 3)) wait_count_w(&g_tick[32 + ((G16() >> 4) & 3) * 8], min((s + 1) / 4 + 3, 17));
            auto tok_store = [&](int m) {
                if (m & 1) stg_b128_if(true, arena + ((b ^ 1) * 32768 + u_to + G16()), v.x, v.y, v.z, v.w);
                if (m & 2) stg_b128_if(p < NSEG, arena + ((pso ^ (32768 + 2048)) + G16()), u.x, u.y, u.z, u.w);
            };
            if (WG == 0) proj_pre(s + 1);
            BLOCK_FENCE
            wg_wait<0>();
            if (WG == 0) {
                asm volatile("" : F16(acc, 0));
                proj(s + 1, [&](int it) {
                    if (it < 0) {
                        SCHED_FENCE(0)
                        asm volatile("" : F16(acc, 0));
                        tok_pack(WG, acc, ftag, ptag, true);
                        tok_store(2);
                        SCHED_FENCE(1)
                    }
                    if (it == 2) { SCHED_FENCE(2) v.x = settag(v.x, ftag); v.z = settag(v.z, ftag); tok_store(1); SCHED_FENCE(3) }
                });
                tq0 += (fz[0] | fz[1] | fz[2] | fz[3]) & zero;
            } else {
#pragma unroll
                for (int k = 0; k < 4; k++) { acc[2 * k] += bflo((&pa.x)[k]); acc[2 * k + 1] += bfhi((&pa.x)[k]); }
                tok_pack(WG, acc, ftag, ptag);
                proj_pre(s + 1);
                asm volatile("" : "+r"(u.x), "+r"(u.y), "+r"(u.z), "+r"(u.w), "+r"(v.x), "+r"(v.y), "+r"(v.z), "+r"(v.w));
                BLOCK_FENCE
                bar_sync(NB_P, 256);
                tok_store(3);
                proj(s + 1, [](int) {});
            }
        }
    };
    if (wg == 0) {
        qk_loop(IC<0>());
    } else if (wg == 1) {
        qk_loop(IC<1>());
    } else {
        const uint32_t ONES = 0x3f803f80u, u_o = qd * 65536 + head * 2048 + wu * 384;
        uint32_t tw = 0, dl = 0, dbase = kh == mypar ? dly.near : dly.far, dst0, dx0;
        dst0 = TAB(6); dx0 = TAB(7);
        uint32_t ov[4] = {0, 0, 0, 0};
        auto o_store = [&](int s) {
            uint8_t* od = (uint8_t*)g_O + (uint32_t)(s * (32 * NH * DH * 2) + u_o + (G16() >> 2));
#pragma unroll
            for (int a = 0; a < 4; a++) stg_rlx1(od + a * 128, ov[a]);
        };
        uint4 vf[2][2], pa;
        auto tok_fetch = [&](int s) {
            const uint8_t* ts = arena + ((s & 1) * 32768 + tbw + g16);
#pragma unroll
            for (int a = 0; a < 4; a++) vf[a >> 1][a & 1] = ldg_b128(ts + (a >> 1) * 16384 + (a & 1) * 2048);
            pa = ldg_b128(arena + (tbw + (1 << 20) + (~s & 1) * 32768 + j * 16384 + kh * 2048 + g16));
        };
        tok_fetch(0);
#pragma unroll 1
        for (int s = 0;; s++) {
            STEP_CONSTS
#define VFBAD ((vf[0][0].x ^ ttag) | (vf[0][1].x ^ ttag) | (vf[1][0].x ^ ttag) | (vf[1][1].x ^ ttag))
#define TOKBAD (VFBAD | (p <= NSEG ? pa.x ^ ftag : 0))
            {
                const uint32_t dst = dst0 + b * 65536, dx = dx0 + b * 65536;
                const uint8_t *ms = arena + (u_m + mem_slot(s) + g16), *me = arena + (u_e + mem_slot(s) + ((g16 >> 3) & ~3u));
                uint32_t em = g16 & 16 ? 0u : ~0u;
                asm volatile("" : "+l"(ms), "+l"(me), "+r"(em));
                spin_until(tw, dl);
                int it = 0;
                bool bad;
#pragma unroll 1
                do {
                    uint4 m[4];
                    uint32_t x[4];
#pragma unroll
                    for (int i = 0; i < 4; i++) m[i] = ldg_rlx4(ms + i * 1024);
#pragma unroll
                    for (int i = 0; i < 4; i++) x[i] = ldg_rlx1(me + i * 1024);
#pragma unroll
                    for (int i = 0; i < 3; i++) {
                        stsm4t(dst + i * 2 * HBK, m[i].x, m[i].y, m[i].z, m[i].w);
                        if (i == 1) asm volatile("{.reg .pred p; setp.eq.s32 p, %0, 0; @p bar.arrive %1, 256;}" ::"r"(it), "n"(NB_P) : "memory");
                    }
                    uint32_t c = m[0].w & m[1].w, r, msk = ~(it << 16) & CNT_ALL << 16;
                    asm volatile("" : "+r"(c), "+r"(msk));
                    SCHED_FENCE(1)
                    stsm4t(dst + 6 * HBK, m[3].x, m[3].y, m[3].z, m[3].w);
                    stsm4t(dx, x[0], x[1], x[2], x[3]);
                    asm volatile("{.reg .pred p, q; .reg .b32 t, u; lop3.b32 t, %1, %2, %3, 0x80; lop3.b32 u, %4, %5, %6, 0x80; lop3.b32 t, t, %8, %7, 0xa8;\n"
                                 " lop3.b32 t, t, u, %9, 0x2a; setp.ne.u32 p, t, 0; vote.sync.any.pred q, p, 0xffffffff; @!q bar.arrive %10, 384; selp.u32 %0, 1, 0, q;}"
                                 : "=r"(r) : "r"(c), "r"(m[2].w), "r"(m[3].w), "r"(x[0]), "r"(x[1]), "r"(x[2]), "r"(x[3]), "r"(em), "r"(msk), "n"(NB_MEM) : "memory");
                    bad = r; it++;
                } while (bad);
                if (it > 1 && s > 1) dbase += dly.more;
            }
            o_store(max(s - 1, 0));
            fence_async_smem();
            hbo += fz[1] & zero;
            int it = 0;
#pragma unroll 1
            while (any_bit0(TOKBAD) & (++it < POLL_LIMIT)) tok_fetch(s + (it & zero));
            float acc[20];
#pragma unroll
            for (int k = 0; k < 4; k++) { acc[2 * k] = bflo((&pa.x)[k]); acc[2 * k + 1] = bfhi((&pa.x)[k]); acc[8 + 2 * k] = acc[9 + 2 * k] = acc[16 + k] = __uint_as_float(pa.x & zero); }
            if (p <= NSEG) mbar_wait_w(bars + 8 * (B_HB + b), (p >> 1) & 1);
            asm volatile("" : F16(acc, 0), F4(acc, 16));
            BLOCK_FENCE
            wg_fence();
            bar_sync(NB_QK, 384);
#pragma unroll
            for (int i = 0; i < 32; i++) {
                const int k = i / GAP;
                if (i % GAP == GAP - 1 && k < NL) wgmma_ss40(acc, mkdesc(SB0 + 131072 + k * 2048, 8192, 1024, 1), HB(k), 1);
                else wgmma_rs40(acc, w[i - (k < NL ? k : NL)], HB(NL + i - (k < NL ? k : NL)), 1);
            }
            wg_commit();
            uint8_t* vo = arena + (u_xo + (G16() >> 1));
            pdst = arena + ((pso ^ (32768 + 2048)) + G16());
            fdst = arena + ((b ^ 1) * 32768 + u_to + g16);
            BLOCK_FENCE
            wg_wait<0>();
            stg_rlx2(vo, settag(pack2(acc[16], acc[17]), tag), pack2(acc[18], acc[19]));
            const uint32_t tv = clk32();
            tok_pack(2, acc, ftag, ptag);
            stg_b128_if(p <= NSEG, fdst, v.x, v.y, v.z, v.w);
            stg_b128_if(p < NSEG, pdst, u.x, u.y, u.z, u.w);
            const uint8_t* xp = arena + (xso + 32768 + (G16() >> 1));
            const uint32_t sxa = sb + SM_SX - wu * 2560 + G16() * 5;
            uint32_t sel[2];
            {
                const uint32_t q = (G16() >> 4 ^ g16 >> 6 & 1) & 3;
                sel[0] = q == 0 ? 0x3c00 : 0; sel[1] = q == 2 ? 0x3c00 : 0;
                asm volatile("" : "+r"(sel[0]), "+r"(sel[1]));
            }
            uint32_t xv[4], gt = 0;
            auto pv = [&](uint32_t p0, uint32_t p1, uint32_t p2, uint32_t p3, uint32_t p4, auto getv, auto done) {
                float oc[2][4], lc[4] = {0.f, 0.f, 0.f, 0.f};
                mma16816(lc, ONES, ONES, ONES, ONES, p0, p1);
                mma16816z(oc[0], &vf[0][0].x, p0, p1);
                mma16816z(oc[1], &vf[1][0].x, p0, p1);
                mma16816(lc, ONES, ONES, ONES, ONES, p2, p3);
                mma16816(oc[0], vf[0][1].x, vf[0][1].y, vf[0][1].z, vf[0][1].w, p2, p3);
                mma16816(oc[1], vf[1][1].x, vf[1][1].y, vf[1][1].z, vf[1][1].w, p2, p3);
                mma1688(lc, ONES, ONES, p4);
                getv();
                mma1688(oc[0], xv[0], xv[1], p4);
                mma1688(oc[1], xv[2], xv[3], p4);
                done(__float_as_uint(oc[0][0]) | __float_as_uint(oc[1][0]) | __float_as_uint(lc[0]));
                const float r0 = rcp_fast(lc[0]), r1 = rcp_fast(lc[1]);
                ov[0] = pack2(oc[0][0] * r0, oc[0][1] * r1); ov[1] = pack2(oc[0][2] * r0, oc[0][3] * r1);
                ov[2] = pack2(oc[1][0] * r0, oc[1][1] * r1); ov[3] = pack2(oc[1][2] * r0, oc[1][3] * r1);
            };
            bool bad;
            it = 0;
#pragma unroll 1
            do {
                U2 xr[4];
                asm volatile("{.reg .pred p; setp.eq.s32 p, %0, 0; @p bar.sync %1, 384;}" ::"r"(it), "n"(NB_X1) : "memory");
                uint4 sx[5];
#pragma unroll
                for (int i = 0; i < 5; i++) sx[i] = lds4(sxa + i * 16);
                if (it == 0) { gt = gtime(); tw = clk32(); }
                spin_until(tv, dly.v);
#pragma unroll
                for (int i = 0; i < 4; i++) xr[i] = ldg_u2(xp + i * 1024);
                uint32_t h[5], h0[4];
#pragma unroll
                for (int n = 0; n < 4; n++) h0[n] = add_h2((&sx[0].x)[n], (&sx[1].x)[n]);
#pragma unroll
                for (int n = 0; n < 4; n++) h[n] = add_h2(h0[n], add_h2((&sx[2].x)[n], (&sx[3].x)[n]));
                h[4] = add_h2(add_h2(sx[4].x, sx[4].y), add_h2(sx[4].z, sx[4].w));
                uint32_t hm = max_h2(max_h2(max_h2(h[0], h[1]), h[2]), max_h2(h[3], h[4]));
                float2 a[5];
                float mb;
                {
                    float d[2][4];
                    const uint32_t hs = __byte_perm(hm, hm, 0x1032);
#pragma unroll
                    for (int k = 0; k < 2; k++)
                        asm volatile("mma.sync.aligned.m16n8k8.row.col.f32.f16.f16.f32 {%0,%1,%2,%3},{%4,%5},{%6},{%7,%7,%7,%7};"
                                     : "=f"(d[k][0]), "=f"(d[k][1]), "=f"(d[k][2]), "=f"(d[k][3]) : "r"(hm), "r"(hs), "r"(sel[k]), "f"(0.f));
#pragma unroll
                    for (int n = 0; n < 5; n++) a[n] = unpack_h2(h[n]);
                    mb = -64.0f * fmaxf(fmaxf(fmaxf(d[0][0], d[0][1]), fmaxf(d[0][2], d[0][3])), fmaxf(fmaxf(d[1][0], d[1][1]), fmaxf(d[1][2], d[1][3])));
                }
                uint32_t pm[5];
#pragma unroll
                for (int n = 0; n < 5; n++) pm[n] = pack2(ex2(fmaf(a[n].x, 64.0f, mb)), ex2(fmaf(a[n].y, 64.0f, mb)));
                pv(pm[0], pm[1], pm[2], pm[3], pm[4], [&]() {
                    xv[0] = hadd2(xr[0].x, xr[1].x); xv[1] = hadd2(xr[0].y, xr[1].y);
                    xv[2] = hadd2(xr[2].x, xr[3].x); xv[3] = hadd2(xr[2].y, xr[3].y);
                }, [](uint32_t) {});
                bad = any_bit0((xr[0].x ^ tag) | (xr[1].x ^ tag) | (xr[2].x ^ tag) | (xr[3].x ^ tag)) & (++it < POLL_LIMIT);
                stsm4(sb + SM_OX + g16, ov[0], ov[1], ov[2], ov[3]);
            } while (bad);
            bar_sync(NB_X2, 384);
            BLOCK_FENCE
            U2 tv2 = {0, 0};
            const uint8_t* tp = arena + (blk(LB_TIME, mypar) + ((G16() << 6) & 0xc00));
            {
                const uint4 pp = lds4(l16 + SM_PX + 1024);
                const uint32_t p4 = lds1(sb + SM_PX + 512 + 1024 - wu * 128 + (G16() >> 2));
                tv2 = ldg_u2(tp);
                if (warp0 && s + 3 <= NSEG) h_load(sb, hsrc, s + 3, j, head);
                pv(pp.x, pp.y, pp.z, pp.w, p4, []() {}, [&](uint32_t r) { bar_arrive(NB_WIN + (r & zero), 384); });
            }
            dst0 = TAB(6); dx0 = TAB(7);
            const uint32_t zo = TAB(8);
            BLOCK_FENCE
            if (s + 1 == NSEG) break;
            asm volatile("" : "+r"(tv2.y));
            it = 0;
            uint32_t tm = __reduce_max_sync(~0u, tv2.y < 32 * (s + 1) ? ~0u : tv2.x);
#pragma unroll 1
            while ((tm == ~0u) & (++it < 16)) { tv2 = ldg_u2(tp); tm = __reduce_max_sync(~0u, tv2.y < 32 * (s + 1) ? ~0u : tv2.x); }
            const uint32_t e = tm - gt;
            tok_fetch(s + 1);
            stg4_if(g16 < 160, arena + (zo + mem_slot(s + 3)), 0);
            dl = dbase + (e > 4096 ? 0 : e * E_MUL >> 4);
        }
        o_store(NSEG - 1);
    }
}

struct RecMaps { CUtensorMap wq, wk, wv, wo, wmod, w3, w1; };
struct RecPtrs { const bf16 *x, *mem0, *c, *wmod, *w1, *w3; uint8_t* arena; uint32_t zero; const bf16 *w2, *w4, *wo; Delays dly; };

__device__ __forceinline__ float silu_bf(const bf16* c, int i) {
    const float v = __bfloat162float(c[i]);
    return bfround(__fdividef(v, 1.0f + __expf(-v)));
}
#define LN_FREE 6
#define LN_SEQ 0xcba6420987531ull
#define W_LATE 1000
#define W_OPEN 1400
__device__ __noinline__ uint32_t side_window_(const uint8_t* arena, uint32_t n);
#define side_window(arena, n) n = side_window_(arena, n)
__device__ __noinline__ void rec_ln(uint32_t sb, const bf16* x, const uint8_t* arena, int id, int r0) {
    int r1 = 32;
    uint32_t n = 0;
    const int tid = threadIdx.x, lane = tid & 31, wid = __reduce_max_sync(~0u, tid >> 5);
    const uint32_t ring = sb + wid * 8192 + lane * 16, coef = sb + SM_PRE;
    x += (id * 8 + wid) * 2 * DM + lane * 8;
#pragma unroll 1
    for (int r = r0 - 1; r < r1; r++) {
        if (r > 3) side_window(arena, n);
        if (r + 1 < r1) {
#pragma unroll
            for (int i = 0; i < 8; i++)
                asm volatile("cp.async.cg.shared.global [%0], [%1], 16;" ::"r"(ring + (~r & 1) * 4096 + i * 512), "l"(x + (r + 1) * 64 * DM + i * 256) : "memory");
        }
        asm volatile("cp.async.commit_group; cp.async.wait_group 1;" ::: "memory");
        if (r < r0) continue;
        const uint32_t src = ring + (r & 1) * 4096;
        float m[2] = {0.f, 0.f}, rs[2];
#pragma unroll 1
        for (int ps = 0; ps < 2; ps++) {
            float t[2][2] = {{0.f, 0.f}, {0.f, 0.f}};
#pragma unroll 1
            for (int i = 0; i < 2048; i += 512) {
#pragma unroll
                for (int h = 0; h < 2; h++) {
                    const uint4 u = lds4(src + h * 2048 + i);
#pragma unroll
                    for (int e = 0; e < 4; e++) {
                        const float a = bflo((&u.x)[e]) - m[h], c = bfhi((&u.x)[e]) - m[h];
                        t[h][0] = fmaf(a, ps ? a : 1.0f, t[h][0]); t[h][1] = fmaf(c, ps ? c : 1.0f, t[h][1]);
                    }
                }
            }
            rs[0] = t[0][0] + t[0][1]; rs[1] = t[1][0] + t[1][1];
#pragma unroll 1
            for (int o = 16; o; o >>= 1) { rs[0] += __shfl_xor_sync(~0u, rs[0], o); rs[1] += __shfl_xor_sync(~0u, rs[1], o); }
            if (!ps) { m[0] = rs[0] * (1.0f / DM); m[1] = rs[1] * (1.0f / DM); }
        }
        rs[0] = rsqrtf(rs[0] * (1.0f / DM) + 1e-5f); rs[1] = rsqrtf(rs[1] * (1.0f / DM) + 1e-5f);
        if (r == r0) {
#pragma unroll 1
            for (int i = tid; i < 2 * DM / 4; i += 256) {
                float t[4];
                int it = 0;
                uint32_t ok;
#pragma unroll 1
                do {
                    uint4 u[8];
#pragma unroll
                    for (int k = 0; k < 8; k++) u[k] = ldg_rlx4(g_modp + k * 2 * DM + i * 4);
                    ok = 1;
#pragma unroll
                    for (int k = 0; k < 32; k++) { const uint32_t w = (&u[k >> 2].x)[k & 3]; ok &= w; t[k & 3] = k < 4 ? __uint_as_float(w) : t[k & 3] + __uint_as_float(w); }
                } while (!__all_sync(~0u, ok) & (++it < SPIN_LIMIT));
                const float o = i >> 8;
                const uint32_t lo = pack2(t[0], t[1]), hi = pack2(t[2], t[3]);
                sts4f(coef + (i >> 8) * 4096 + (i & 1) * 2048 + ((i & 255) >> 1) * 16, bflo(lo) + o, bfhi(lo) + o, bflo(hi) + o, bfhi(hi) + o);
            }
            bar_sync(NB_FIN0, 256);
        }
        uint8_t* dst = (uint8_t*)g_himg + (r * 2 + (id >> 1)) * 65536 + (lane >> 3) * 4096 + wid * 256;
#pragma unroll 1
        for (int i = 0; i < 4; i++) {
            const uint32_t ca = coef + i * 512 + lane * 16;
            const float4 s0 = lds4f(ca), s1 = lds4f(ca + 2048), c0 = lds4f(ca + 4096), c1 = lds4f(ca + 6144);
            const float sh[8] = {s0.x, s0.y, s0.z, s0.w, s1.x, s1.y, s1.z, s1.w}, sc[8] = {c0.x, c0.y, c0.z, c0.w, c1.x, c1.y, c1.z, c1.w};
#pragma unroll
            for (int h = 0; h < 2; h++) {
                uint4 u = lds4(src + h * 2048 + i * 512);
#pragma unroll
                for (int e = 0; e < 4; e++) {
                    uint32_t& w = (&u.x)[e];
                    w = pack2(fmaf((bflo(w) - m[h]) * rs[h], sc[2 * e], sh[2 * e]), fmaf((bfhi(w) - m[h]) * rs[h], sc[2 * e + 1], sh[2 * e + 1]));
                }
                *(uint4*)(dst + i * 16384 + ((id & 1) == (i >> 1) ? 65536 : 2048) + h * 128 + (((lane ^ (2 * wid + h)) & 7) << 4)) = u;
            }
        }
        if (r == 0) {
            int ro, it = 0;
#pragma unroll 1
            do asm volatile("ld.volatile.shared.u32 %0, [%1];" : "=r"(ro) : "r"(sb + SM_BAR + 192) : "memory"); while ((ro == INT_MIN) & (++it < SPIN_LIMIT));
            if (ro >= 0) r1 = 2;
        }
        if (r && !(r & 1)) continue;
        bar_sync(r ? NB_FIN0 : NB_C, r ? 256 : 320);
        if (wid == (r >> 1 & 7)) {
            if (r == 1) bar_arrive(NB_B, 64);
            if (r == 3) wait_count_w(&g_tick[32 + id * 8], 2);
            if (lane == 0) { signal_count(&g_tick[32 + id * 8]); }
            __syncwarp();
        }
    }
}
__device__ __noinline__ uint32_t side_window_(const uint8_t* arena, uint32_t n) {
    U2 v;
    int it = 0;
#pragma unroll 1
    while (v = ldg_u2(arena + (LB_TIME << 13)), ((v.y >> 5) == n || gtime() - v.x > W_OPEN + W_LATE) && v.y < 32 * NSEG && ++it < 64) __nanosleep(100);
    it = 0;
#pragma unroll 1
    while ((int)(gtime() - v.x - W_OPEN) < 0 && ++it < 256) {}
    return v.y >> 5;
}
#define SIDE_T 300
template <int NQ, int NB>
__device__ __forceinline__ void side_gemv(const CUtensorMap* tm, int c0, int k0, int k1, uint32_t cs, uint32_t sb, const uint8_t* arena, uint32_t& n, uint32_t& ph, float (*acc)[8], bool once = false) {
    const uint32_t w = __reduce_max_sync(~0u, threadIdx.x >> 5 & 3), ring = sb + (NB == 3 ? 65536 : 0) + w * NB * 8192;
    const uint32_t bars = sb + SM_BAR + (NB == 3 ? 8 * B_W + w * 24 : 8 + w * 8), bs = NB == 3 ? 8 : 0;
#pragma unroll
    for (int q = 0; q < NQ; q++)
#pragma unroll
        for (int j = 0; j < 8; j++) acc[q][j] = 0.f;
#pragma unroll 1
    for (; k0 < k1; k0 += NB * 16, ph ^= 1) {
        const int nr = min(NB * 16, k1 - k0);
        side_window(arena, n);
        const uint32_t t0 = clk32();
#pragma unroll 1
        for (int g = 0; g < NB; g++) {
            spin_until(t0, (g * 4 + w) * (SIDE_T / 4));
            if (bs || !g) e_expect(bars + bs * g, !bs ? NB * 8192 : g * 16 < nr ? 8192 : 0);
            if (g * 16 < nr) e_tma2d_hint(ring + g * 8192, tm, c0, k0 + g * 16, bars + bs * g, once ? EVICT_FIRST : EVICT_NORMAL);
        }
#pragma unroll 1
        for (int r = 0; r < nr; r += 16) {
            mbar_wait_w(bars + bs * (r >> 4), ph);
            uint4 v[16];
#pragma unroll
            for (int h = 0; h < 16; h++) v[h] = lds4(ring + (r + h) * 512 + (threadIdx.x & 31) * 16);
            float4 cf[NQ][4];
#pragma unroll
            for (int q = 0; q < NQ * 4; q++) cf[q >> 2][q & 3] = lds4f(cs + ((q >> 2) * DM + k0 + r + (q & 3) * 4) * 4);
#pragma unroll
            for (int h = 0; h < 16; h++) {
                const float f[8] = {bflo(v[h].x), bfhi(v[h].x), bflo(v[h].y), bfhi(v[h].y), bflo(v[h].z), bfhi(v[h].z), bflo(v[h].w), bfhi(v[h].w)};
#pragma unroll
                for (int q = 0; q < NQ; q++)
#pragma unroll
                    for (int j = 0; j < 8; j++) acc[q][j] = fmaf((&cf[q][h >> 2].x)[h & 3], f[j], acc[q][j]);
            }
        }
        fence_async_smem();
        __syncwarp();
    }
}
__device__ __noinline__ void rec_side(float* sm, const RecMaps& mp, const RecPtrs& p, int id) {
    const int tid = threadIdx.x, t = tid & 127, w = __reduce_max_sync(~0u, t >> 5);
    float* coef = sm + (tid < 256 ? 44032 : 40960);
    const uint32_t sb = smem_u32(sm), cs = smem_u32(coef);
    uint32_t n = 0, ph = 0;
    float acc[3][8];
    if (tid < 256) {
        if (blockIdx.x < 128) rec_ln(smem_u32(sm), p.x, p.arena, id, 2);
        for (int i = tid; i < 2 * S_; i += 256) g_st[id * 2 * S_ + i] = 0.f;
        if (id == 0 && tid < 64) g_pcnt[tid * 8] = 0;
        if (id == 1) for (int i = tid; i < 6 * 256; i += 256) g_pflag[i] = 0;
        if (id == 2 && tid == 0) g_pt = 0;
        fence_async_smem();
        bar_sync(NB_FIN0, 256);
        if (PDL && tid == 0) asm volatile("fence.acq_rel.gpu; griddepcontrol.launch_dependents;" ::: "memory");
        if (tid >= 128) return;
        float* red = coef + 3 * DM;
        if (t == 0) wait_count1(&g_tick[8], 4);
        bar_sync(NB_S, 128);
        for (int i = t; i < DM; i += 128) { coef[i] = 1.0f + __ldcg(g_mod + 4 * DM + i); coef[DM + i] = __ldcg(g_mod + 3 * DM + i); coef[2 * DM + i] = 1.0f; }
        bar_sync(NB_S, 128);
        if (id == 1 && t < 32) {
            float u[5] = {0, 0, 0, 0, 0};
            for (int i = t; i < DM; i += 32) {
                const float a = coef[i], b = coef[DM + i];
                u[0] += a; u[1] += a * a; u[2] += a * b; u[3] += b; u[4] += b * b;
            }
#pragma unroll
            for (int q = 0; q < 5; q++) { const float r = warp_sum(u[q]); if (t == 0) g_cst[q] = r * (1.0f / DM); }
        }
        side_gemv<3, 2>(&mp.w1, id * 256, w * 256, w * 256 + 256, cs, sb, p.arena, n, ph, acc);
#pragma unroll
        for (int q = 0; q < 3; q++)
#pragma unroll
            for (int j = 0; j < 8; j++) red[((t >> 5) * 3 + q) * 256 + (t & 31) * 8 + j] = acc[q][j];
        bar_sync(NB_S, 128);
        for (int i = t; i < 768; i += 128) g_vec[(i >> 8) * DM + id * 256 + (i & 255)] = (red[i] + red[768 + i]) + (red[1536 + i] + red[2304 + i]);
        return;
    }
    for (int i = t; i < DM; i += 128) { coef[i] = silu_bf(p.c, i); coef[2 * DM + i] = 1.0f; }
    if (t == 0) wait_count1(&g_tick[32], 1);
    bar_sync(NB_G, 128);
    side_gemv<1, 3>(&mp.wmod, (2 + id) * DM + w * 256, 0, DM, cs, sb, p.arena, n, ph, acc, true);
#pragma unroll
    for (int j = 0; j < 8; j++) g_mod[(2 + id) * DM + t * 8 + j] = bfround(acc[0][j]);
    bar_sync(NB_G, 128);
    if (t == 0) signal_count(&g_tick[8]);
    side_gemv<1, 3>(&mp.w3, id * (FF / 4) + w * 256, 0, DM, cs + 8 * DM, sb, p.arena, n, ph, acc);
    if (t < FF / 32) {
#pragma unroll
        for (int j = 0; j < 8; j++) g_vec[3 * DM + id * (FF / 4) + t * 8 + j] = acc[0][j];
    }
}

__global__ void __cluster_dims__(2, 1, 1) __launch_bounds__(384, 1)
k_rec(const __grid_constant__ RecMaps mp, const __grid_constant__ RecPtrs p) {
    extern __shared__ uint8_t smraw[];
    const uint32_t sb = smem_u32(smraw);
    if ((sb & 0x3FFFF) != SB0) __trap();
    const uint32_t bars = sb + SM_BAR;
    const int tid = threadIdx.x, lane = tid & 31, b = blockIdx.x;
    const int wid = __reduce_max_sync(~0u, tid >> 5);
    const uint32_t rank = b & 1;
    uint8_t* arena = p.arena;
    volatile int* sinfo = (volatile int*)(smraw + SM_BAR + 192);
    if (tid == 0) sinfo[0] = INT_MIN;
    if (tid == 352) {
        for (int i = 0; i < 17; i++) mbar_init(bars + 8 * i, i == B_WO ? 4 : 1);
        asm volatile("fence.mbarrier_init.release.cluster;" ::: "memory");
    }
    __syncwarp();
    asm volatile("barrier.cluster.arrive.relaxed.aligned;" ::: "memory");
    int pr = 0, hA = 0;
    if (wid < 8) {
        if (b < 128) {
            const int cb = (b & 15) * 128, k0 = (b >> 4) * 128 + (tid >> 4);
            uint4 v[8];
#pragma unroll
            for (int i = 0; i < 8; i++) v[i] = __ldg((const uint4*)(p.wmod + (size_t)(k0 + 16 * i) * (6 * DM) + cb + (tid & 15) * 8));
            float acc[8] = {0, 0, 0, 0, 0, 0, 0, 0};
            const float s8 = silu_bf(p.c, k0 + 16 * (lane & 7));
#pragma unroll
            for (int i = 0; i < 8; i++) {
                const float sv = __shfl_sync(~0u, s8, i, 16);
                acc[0] += sv * bflo(v[i].x); acc[1] += sv * bfhi(v[i].x); acc[2] += sv * bflo(v[i].y); acc[3] += sv * bfhi(v[i].y);
                acc[4] += sv * bflo(v[i].z); acc[5] += sv * bfhi(v[i].z); acc[6] += sv * bflo(v[i].w); acc[7] += sv * bfhi(v[i].w);
            }
            float* red = (float*)(smraw + SM_PRE);
            *(float4*)(red + (tid >> 4) * 128 + (tid & 15) * 8) = make_float4(acc[0], acc[1], acc[2], acc[3]);
            *(float4*)(red + (tid >> 4) * 128 + (tid & 15) * 8 + 4) = make_float4(acc[4], acc[5], acc[6], acc[7]);
            bar_sync(NB_FIN0, 256);
            if (wid < 4) {
                float t = 0;
#pragma unroll
                for (int i = 0; i < 16; i++) t += red[i * 128 + tid];
                stg_rlx1(&g_modp[(b >> 4) * 2 * DM + cb + tid], __float_as_uint(t) | 1u);
            }
        } else {
            rec_ln(sb, p.x, p.arena, b - 128, 0);
        }
    } else if (wid >= 10 && b >= 128) {
        {
            const int w = (b - 128) * 2 + wid - 10;
            const uint16_t* src = (const uint16_t*)p.mem0 + (lane & 3) * 2 * DM + (w >> 2) * 512 + (w & 1) * 64 + (w & 2) * 8 + (lane >> 2);
            uint32_t v[4][4];
#pragma unroll
            for (int i = 0; i < 16; i++) v[i >> 2][i & 3] = src[(i >> 2) * 128 + (i & 2) * 16 + (i & 1) * 8] | ((uint32_t)src[DM + (i >> 2) * 128 + (i & 2) * 16 + (i & 1) * 8] << 16);
            uint8_t* d = arena + mem_row(w >> 2, w & 3, 0);
            uint8_t* e = d + 512 + (lane >> 1) * 4;
            d += lane * 16;
#pragma unroll
            for (int i = 0; i < 4; i++, d += 1024, e += 1024) {
                stg_rlx4(d, v[i][0], v[i][1], v[i][2], lane & 1 ? (v[i][3] & 0xffff) | CNT_ALL << 16 : v[i][3]);
                stg_rlx4(d + mem_slot(1), 0, 0, 0, 0);
                stg_rlx4(d + mem_slot(2), 0, 0, 0, 0);
                if (lane & 1) { stg_rlx1(e, v[i][3] >> 16 | CNT_ALL << 16); stg_rlx1(e + mem_slot(1), 0); stg_rlx1(e + mem_slot(2), 0); }
            }
            if (w == 0 && lane < 8) stg_rlx2(arena + (LB_TIME << 13) + lane * 1024, 0, 0);
            bar_arrive(NB_C, 320);
        }
    } else if (rank == 0) {
        uint32_t best = ~0u;
        const int pg = wid < 10 ? 0 : 1 + (b >> 1) / 22;
        uint32_t* q = (uint32_t*)(arena + (pg << 21) + (pg ? blk(b >> 1, wid & 1) : blk(LB_PROBE, wid & 1) + b * 16));
        if (lane < 8) stg_rlx1(q + lane, 0);
        __syncwarp();
        if (lane == 0) {
            q += 3;
            uint32_t v = p.zero;
#pragma unroll 1
            for (int r = v; r <= NPROBE; r++) {
                const uint32_t t0 = clk32() + (v >> 8);
                v = atomicAdd(q + (v >> 8), 1u);
                uint32_t t1;
                asm volatile("{.reg .pred p; setp.eq.u32 p, %1, 0xffffffff; @p exit; mov.u32 %0, %%clock;}" : "=r"(t1) : "r"(v) : "memory");
                best = min(best, t1 - t0);
            }
            sinfo[wid - 6] = best;
        }
        bar_sync(NB_KDONE, b < 128 ? 128 : 64);
        if (tid == 256) {
            const uint32_t par = sinfo[2] > sinfo[3], vote = b < 128 && (sinfo[4] > sinfo[5]) != par;
            stg_rlx2(&g_clk[b >> 1], ((clk32() - 2 * gtime()) & ~127u) | b >> 1, 1 + 2 * par + 4 * vote);
        }
    }
    if (wid == 8) {
        U2 v[3], my;
        uint32_t c0;
        const int me = b >> 1;
        int it = 0;
        __syncwarp();
#pragma unroll 1
        do {
            my = ldg_u2(&g_clk[me]);
#pragma unroll
            for (int k = 0; k < 3; k++) v[k] = ldg_u2(&g_clk[k * 22 + min(lane, 21)]);
        } while (!__all_sync(~0u, my.y & v[0].y & v[1].y & v[2].y & 1) & (++it < SPIN_LIMIT));
        c0 = __reduce_min_sync(~0u, lane ? ~0u : v[0].x) - 4096;
        const uint32_t mc = me >= 64 ? ~0u : my.x - c0;
        const int par = my.y >> 1 & 1;
        uint32_t cnt = 0, flip = 0;
#pragma unroll
        for (int k = 0; k < 3; k++) {
            const uint32_t c = v[k].x - c0, o = v[k].y >> 1 & 1;
            const bool ln = k == 2 && lane >= 20;
            cnt += o + (o == par ? (ln ? 44 + lane < me : c < mc) * 256 + (c < my.x - c0) * 65536 : 0);
            flip |= __popc(__ballot_sync(~0u, v[k].y & 4) & 0x3fffff) > 10 ? 256 << k : 0;
        }
        cnt = __reduce_add_sync(~0u, lane < 22 ? cnt : 0);
        const int n1 = cnt & 255, n0 = 66 - n1, tk = cnt >> 8 & 255;
        if (lane == 0) g_cls[smid() & 255] = cnt < 32 << 16 ? par * 4 + (cnt >> 19) : 8;
        hA = min(n0 >> 1, NH);
        const int q0 = 2 * hA, q1 = 2 * NH - q0;
        const int over = tk - (par ? q1 : q0), lack = max(par ? q0 - n0 : q1 - n1, 0);
        if (over < 0) pr = par ? q0 + tk : tk;
        else if (over < lack) pr = (par ? n0 : q0 + n1) + over;
        else pr = -1 - (over - lack + (par ? max(n0 - q0, 0) : 0));
        hA |= flip;
        if (lane == 0) {
            sinfo[1] = hA; sinfo[0] = pr;
            if (b >= 128 && rank == 0) atomicOr(&g_tick[6], (pr < 0 ? 4u : 1u) << ((b - 128) >> 1));
        }
    }
    asm volatile("barrier.cluster.wait.aligned;" ::: "memory");
    if (wid == 8) {
        __syncwarp();
        bar_arrive(NB_A, 288);
        bar_arrive(NB_S, 128);
        if (b >= 128 && pr < 0) bar_sync(NB_B, 64);
        if (pr >= 0) {
            const int pu = __reduce_max_sync(~0u, pr), c0 = (pu >> 1) * 128 + rank * 64, r0 = (pu & 1) * 512;
#pragma unroll 1
            for (int n = 0; n < 13; n++) {
                const u64 seq = b >= 128 ? LN_SEQ : 0xcba9876543210ull;
                const int i = seq >> (4 * n) & 15;
                if (b >= 128 && i == 0) bar_sync(NB_B, 64);
                if (n >= W_INFL && (b < 128 || n < LN_FREE)) mbar_wait_w(bars + 8 * (B_W + (seq >> (4 * (n - W_INFL)) & 15)), 0);
                const int m = i < 8 ? i & 1 : i >> 2, k = i < 8 ? i >> 1 : i & 3;
                const uint32_t dst = sb + m * 65536 + k * 16384, br = bars + 8 * (m < 3 ? B_W + i : B_WO);
                const int c = m < 3 ? c0 : 576 + rank * 256 + (pu & 1) * 128, r = m < 3 ? r0 + k * 128 : (pu >> 1) * DH;
                const uint64_t pol = m < 3 ? EVICT_FIRST : EVICT_NORMAL;
                e_expect(br, 16384);
                e_tma2d_hint(dst, &mp.wq + m, c, r, br, pol);
                e_tma2d_hint(dst + 8192, &mp.wq + m, c, r + 64, br, pol);
            }
        }
    } else {
        bar_sync(wid < 8 ? NB_A : NB_S, wid < 8 ? 288 : 128);
    }
    const int prr = __reduce_max_sync(~0u, sinfo[0]);
    hA = __reduce_max_sync(~0u, sinfo[1]);
    if (prr < 0) {
        int j = (b - 128) >> 1;
        if (b < 128) {
            uint32_t v;
            int it = 0;
#pragma unroll 1
            do { v = __reduce_max_sync(~0u, ldg_rlx1(&g_tick[6])); spin_guard(++it); } while (__popc(v) < 2);
            j = v == 3 ? -1 - prr : (v & 1) ^ 1;
        }
        rec_side((float*)smraw, mp, p, j * 2 + rank);
        return;
    }
    if (PDL) asm volatile("griddepcontrol.launch_dependents;" ::: "memory");
    const int role = (prr >> 1) * 4 + rank * 2 + (prr & 1);
    rec_main(sb, &mp.wo, arena, role, hA, wid >> 2, p.zero, p.dly);
}

__device__ __forceinline__ void wgmma_ss192(float* d, uint64_t a, uint64_t b, int sc) {
    asm volatile("{.reg .pred p; setp.ne.b32 p, %98, 0;\n wgmma.mma_async.sync.aligned.m64n192k16.f32.bf16.bf16 "
                 "{%0,%1,%2,%3,%4,%5,%6,%7,%8,%9,%10,%11,%12,%13,%14,%15,%16,%17,%18,%19,%20,%21,%22,%23,%24,%25,%26,%27,%28,%29,%30,%31,%32,%33,%34,%35,%36,%37,%38,%39,%40,%41,%42,%43,%44,%45,%46,%47,%48,%49,%50,%51,%52,%53,%54,%55,%56,%57,%58,%59,%60,%61,%62,%63,%64,%65,%66,%67,%68,%69,%70,%71,%72,%73,%74,%75,%76,%77,%78,%79,%80,%81,%82,%83,%84,%85,%86,%87,%88,%89,%90,%91,%92,%93,%94,%95}, %96, %97, p, 1, 1, 0, 1;}"
                 : F16(d, 0), F16(d, 16), F16(d, 32), F16(d, 48), F16(d, 64), F16(d, 80) : "l"(a), "l"(b), "r"(sc));
}

constexpr uint32_t P_B = 81920, P_PL = 40960, P_OUT = 180224, P_VEC = 212992, P_ROW = P_VEC + 6144, P_BAR = P_ROW + 4096, P_SMEM = P_BAR + 256;
#define FLAG_ST "st.release.gpu.global.u32"
#define FLAG_LD "ld.acquire.gpu.global.u32"
constexpr int ST = 5;
constexpr int PB_F = 0, PB_E = 5, PB_R = 10, PB_OUT = 16;
enum { C_Y = 0, C_G = 1, C_X1 = 2, C_U = 3, C_S1 = 8, C_S3 = 9 };
enum { V_GA = 0, V_A = 1, V_B = 2, V_GB = 3, V_VA = 4, V_VB = 5, V_VC = 6, V_C3 = 7 };
struct PostMaps { CUtensorMap o, wo, y, w1, g, w2, x1, w3, u, w4, out; };
struct PostPtrs { const bf16* x; };

struct GeluK { float k0, k1, kh; };
__device__ __forceinline__ GeluK gelu_k(float c) { return {0.7978845608028654f * c, 0.7978845608028654f * 0.044715f * c * c * c, 0.5f * c}; }
__device__ __forceinline__ float gelu_s(float t, const GeluK& k) {
    const float u = t * fmaf(t * t, k.k1, k.k0);
    float th; asm("tanh.approx.f32 %0, %1;" : "=f"(th) : "f"(u));
    const float hx = k.kh * t;
    return fmaf(hx, th, hx);
}
__device__ __forceinline__ float2 ldsv(uint32_t a) {
    float2 v; asm("ld.shared.v2.f32 {%0,%1}, [%2];" : "=f"(v.x), "=f"(v.y) : "r"(a)); return v;
}
__device__ __forceinline__ void wait_smem(uint32_t a, int target) {
    int it = 0;
#pragma unroll 1
    while (true) {
        int v;
        asm volatile("ld.acquire.cta.shared.u32 %0, [%1];" : "=r"(v) : "r"(a) : "memory");
        if (__all_sync(~0u, v >= target) | (++it > SPIN_LIMIT)) break;
    }
}

__device__ __forceinline__ void release(uint32_t rel, int st, bool c) {
    asm volatile("{.reg .pred p; setp.ne.u32 p, %1, 0; setp.ne.and.u32 p, %2, 0, p; @p mbarrier.arrive.shared::cluster.b64 _, [%0];}"
                 ::"r"(rel + 8 * (st ? st - 1 : ST - 1)), "r"(rel), "r"((uint32_t)c) : "memory");
}
struct Pipe { int st, ph; uint32_t rel; };
__device__ __forceinline__ void adv(Pipe& p) { if (++p.st == ST) { p.st = 0; p.ph ^= 1; } }

__device__ __forceinline__ void post_weights(uint32_t sb, const PostMaps& mp, int nb, int rank) {
    const uint32_t full = sb + P_BAR + 8 * PB_F, empty = sb + P_BAR + 8 * PB_E;
    int st = 0, pp = 1;
#pragma unroll 1
    for (int ph = 0; ph < 7; ph++) {
        const int NK = ph == 0 ? 64 : ph == 6 ? 56 : 16, km = NK == 16 ? 15 : 63;
        const CUtensorMap* tb = &mp.wo + 2 * (ph < 3 ? ph : ph < 6 ? 3 : 4);
        const bool w3 = ph >= 3 && ph < 6;
        const int n0 = w3 ? nb * 64 + (ph == 4 ? 1536 : ph == 5 ? 2560 : 0) : nb * 128, dn = w3 ? 512 : 64;
        const int rot = NK == 16 ? 2 * (nb & 6) : 0, sw = ph == 1 || ph == 3 ? 2 * rank : 0;
#pragma unroll 1
        for (int i = 0; i < NK; i++) {
            const int k0 = (((i < 4 ? i ^ sw : i) + rot) & km) * 64;
            const uint32_t a = sb + P_B + st * 8192, f = full + 8 * st;
            mbar_wait_w(empty + 8 * st, pp);
            e_expect(f, ph == 3 ? 40960 : 32768);
            e_tma2d(a, tb, n0, k0, f);
            e_tma2d(a + P_PL, tb, n0 + dn, k0, f);
            if (ph == 3) e_tma2d(a + 2 * P_PL, tb, n0 + 1024, k0, f);
            if (++st == ST) { st = 0; pp ^= 1; }
        }
    }
#pragma unroll 1
    for (int i = 0; i < ST; i++) mbar_wait_w(empty + 8 * i, pp ^ (i < st));
}
__device__ __forceinline__ void post_acts(uint32_t sb, const PostMaps& mp, int mb, int nb, int rank) {
    const int rh = 2 * mb + rank, lane = threadIdx.x & 31;
    const uint32_t bars = sb + P_BAR;
    int st = 0, pp = 1;
#pragma unroll 1
    for (int ph = 0; ph < 7; ph++) {
        const int NK = ph == 0 ? 64 : ph == 6 ? 56 : 16, km = NK == 16 ? 15 : 63;
        const CUtensorMap* ta = &mp.o + 2 * (ph < 3 ? ph : ph < 6 ? 3 : 4);
        const int amul = ph == 0 ? 256 : 64, arow = (ph == 0 ? rh * 8 : rh * 64) - 2, rot = NK == 16 ? 2 * (nb & 6) : 0;
        const bool own = ph == 1 || ph == 3;
        const uint32_t shifts = ph == 2 ? 0x04000301u : 0x02020202u;
        const uint32_t* fl = &g_pflag[(ph == 6 ? C_U : min(ph - 1, 2)) * 256 + (ph == 2 ? min(max(rh + min(lane >> 3, 2) - 1, 0), 31) : rh) * 8 + ((lane + nb - rank) & 7)];
        int i = 0, n = ph == 0 || ph == 5 ? NK : 0;
        if (own) { i = 4; if (st) { st--; pp ^= 1; } else st = 4; }
#pragma unroll 1
        while (i < NK) {
            if (n <= i) {
                int it = 0;
#pragma unroll 1
                do {
                    uint32_t v;
                    asm volatile(FLAG_LD " %0, [%1];" : "=r"(v) : "l"(fl) : "memory");
                    n = __reduce_min_sync(~0u, ph == 6 ? 8 * v : v || (own && !(lane & 6)) ? 16 : 2 * (lane & 7));
                    if (++it > SPIN_LIMIT) n = NK;
                } while (n <= i);
                asm volatile("fence.proxy.async.global;" ::: "memory");
            }
            if (own && (i == 5 || i == 6)) mbar_wait_w(bars + 8 * (PB_E + ph + i - 5), 1);
#pragma unroll 1
            for (const int e = own && i < 6 ? i + 1 : n; i < e; i++) {
                const int kb = (i + rot) & km;
                const uint32_t f = bars + 8 * (PB_F + st);
                mbar_wait_w(f + 8 * PB_E, pp);
                e_tma2d_mc(sb + st * 16384 + rank * 8192, ta, kb * amul, arow + (int)((shifts >> ((kb & 12) * 2)) & 7), f);
                if (++st == ST) { st = 0; pp ^= 1; }
            }
        }
    }
}

template <int PH, class F>
__device__ __forceinline__ void post_kb(uint32_t sb, float* acc, Pipe& p, int wg, bool lead, bool first, F mid) {
    constexpr uint64_t DA = PH == 0 ? mkdesc(SB0, 128, 1024, 0) : mkdesc(SB0, 16, 1024, 1);
    constexpr uint64_t DB = mkdesc(SB0 + P_B, P_PL, 1024, 1);
    mbar_wait_w(sb + P_BAR + 8 * PB_F + 8 * p.st, p.ph);
    const uint32_t a = (uint32_t)DA + p.st * 1024 + wg * 512, b = (uint32_t)DB + p.st * 512;
    wg_fence();
#pragma unroll
    for (int k = 0; k < 4; k++) {
        const uint64_t da = (DA & 0xffffffff00000000ull) | (a + k * (PH == 0 ? 16 : 2)), db = (DB & 0xffffffff00000000ull) | (b + k * 128);
        if (PH == 3) wgmma_ss192(acc, da, db, k || !first);
        else wgmma_ss128<PH == 0>(acc, da, db, k || !first);
    }
    wg_commit();
    wg_wait<1>();
    release(p.rel, p.st, !first);
    mid();
    adv(p);
}
__device__ __forceinline__ void post_end(uint32_t sb, Pipe& p, bool lead) {
    wg_wait<0>();
    release(p.rel, p.st, true);
}
template <int PH>
__device__ __forceinline__ void post_mma(uint32_t sb, float* acc, Pipe& p, int wg, bool lead, int nout, int pi, int mb, int nb) {
#pragma unroll 1
    for (int kb = 0; kb < 16; kb++)
        post_kb<PH>(sb, acc, p, wg, lead, kb == 0, [&]() {
            if (nout && kb == 0) wait_smem(sb + P_BAR + 8 * (PB_OUT + wg), nout);
        });
    post_end(sb, p, lead);
}

__global__ void __cluster_dims__(2, 1, 1) __launch_bounds__(384, 1)
k_post(const __grid_constant__ PostMaps mp, const __grid_constant__ PostPtrs pp) {
    extern __shared__ uint8_t smraw[];
    const uint32_t sb = smem_u32(smraw);
    if ((sb & 0x3FFFF) != SB0) __trap();
    const int tid = threadIdx.x, lane = tid & 31;
    const int rank = blockIdx.x & 1;
    const uint32_t bars = sb + P_BAR;
    int c = 0;
    unsigned long long v = 0;
    const int wid = __reduce_max_sync(~0u, tid >> 5);
    const bool draw = tid == 352 && rank == 0;
    if (draw) {
        c = min(ldg_rlx1(&g_cls[smid() & 255]), 8u);
        asm volatile("{.reg .b64 a; cvt.u64.u32 a, %%laneid; add.u64 a, a, %1; atom.relaxed.gpu.global.add.u64 %0, [a], %2;}" : "=l"(v) : "l"(&g_pt), "l"(1ull << (7 * c)) : "memory");
    }
    if (wid < 11) {
        asm volatile("{.reg .pred p; elect.sync _|p, 0xffffffff; @p mbarrier.init.shared.b64 [%0], %1; @p prefetch.tensormap [%2]; fence.mbarrier_init.release.cluster;}"
                     ::"r"(bars + 8 * wid), "r"(wid >= PB_E && wid < PB_R ? 4 : 1), "l"(&mp.o + wid) : "memory");
        if (wid == PB_R) { sts4(bars + 8 * PB_OUT, 0, 0, 0, 0); e_expect(bars + 8 * PB_R, 4); }
    }
    __syncwarp();
    asm volatile("barrier.cluster.arrive.relaxed.aligned; barrier.cluster.wait.aligned;" ::: "memory");
    if (draw) {
        int r = (v >> (7 * c)) & 127, role = c * 8 + r;
        if (c == 8 || r >= 8) {
            int n, x, it = 0;
#pragma unroll 1
            do {
                __nanosleep(200);
                v = ldg_u64(&g_pt); n = 0; x = c < 8 ? r - 8 : r;
#pragma unroll 1
                for (int i = 0; i < 63; i += 7) { const int m = v >> i & 127; n += m; if (i < 7 * c) x += max(m - 8, 0); }
            } while (n < gridDim.x / 2 && ++it < SPIN_LIMIT);
            role = -1;
#pragma unroll 1
            for (int i = 0; i < 64; i += 8, v >>= 7) {
                n = v & 127;
                if (x >= 0 && n + x < 8) role = i + n + x;
                x -= max(8 - n, 0);
            }
        }
#pragma unroll
        for (int i = 0; i < 2; i++)
            asm volatile("{.reg .b32 d; mapa.shared::cluster.u32 d, %0, %2; st.async.shared::cluster.mbarrier::complete_tx::bytes.u32 [d+8], %1, [d];}"
                         ::"r"(bars + 8 * PB_R), "r"(role), "r"(i) : "memory");
    }
    __syncwarp();
    mbar_wait_w(bars + 8 * PB_R, 0);
    const int pr = __reduce_max_sync(~0u, (int)lds1(bars + 8 * PB_R + 8));
    if (pr < 0) return;
    const int mb = (pr >> 5) * 8 + (pr & 7), nb = (pr >> 2 & 6) + rank, cta = pr * 2 + rank;
    if (wid >= 8) {
        asm volatile("setmaxnreg.dec.sync.aligned.u32 40;");
        const int w = wid - 8;
        if (w == 0) {
            post_weights(sb, mp, nb, rank);
        } else if (w == 3) {
            asm volatile("griddepcontrol.wait;" ::: "memory");
            post_acts(sb, mp, mb, nb, rank);
        } else {
            const int wg = w - 1, rh = 2 * mb + wg;
            float* rowc = (float*)(smraw + P_ROW) + (wg * 64 + lane * 2) * 8;
            int nout = 0, sig = 0;
#pragma unroll 1
            for (int i = 0; i < 13; i++) {
                const int cnt = (0x4333333392180ull >> (4 * i)) & 15;
                if (cnt < C_S1) {
                    const int ng = cnt == C_U ? 1 : 2, c0 = cnt == C_U ? (i - 5) * 512 + nb * 64 : nb * 128;
                    const bool fast = (cnt == C_Y || cnt == C_X1);
#pragma unroll 1
                    for (int j = 0; j < ng; j++) {
                        const uint32_t st = j ? cnt : cnt ? 1 : 4;
                        const uint32_t src = sb + (fast ? st * 16384 + wg * 8192 : P_OUT + wg * 16384 + ((nout + j) & 1) * 8192);
                        bar_sync(4 + 4 * wg + (sig++ & 3), 160);
                        if (lane == 0) {
                            if (fast) asm volatile("mbarrier.complete_tx.relaxed.cta.shared::cta.b64 [%0], 8192;" ::"r"(bars + 8 * (PB_F + st)) : "memory");
                            asm volatile("cp.async.bulk.tensor.2d.global.shared::cta.bulk_group [%0, {%2, %3}], [%1]; cp.async.bulk.commit_group;"
                                         ::"l"(&mp.y + 2 * cnt), "r"(src), "r"(c0 + j * 64), "r"(rh * 64) : "memory");
                        }
                        __syncwarp();
                    }
                    if (lane == 0) {
                        auto to_peer = [&]() {
                            const uint32_t n = cnt ? 1 : 4;
                            mbar_wait(bars + 8 * (PB_E + (cnt ? 4 : 2)), 0);
#pragma unroll
                            for (int i = 0; i < 2; i++)
                                asm volatile("{.reg .b32 d, m; mapa.shared::cluster.u32 d, %0, %3; mapa.shared::cluster.u32 m, %2, %3;\n"
                                             " cp.async.bulk.shared::cluster.shared::cta.mbarrier::complete_tx::bytes [d], [%1], 8192, [m];}"
                                             ::"r"(sb + (cnt + 1 + i) * 16384 + wg * 8192), "r"(sb + (i ? cnt : n) * 16384 + wg * 8192), "r"(bars + 8 * (PB_F + cnt + 1 + i)), "r"(rank ^ 1) : "memory");
                        };
                        asm volatile("cp.async.bulk.wait_group 0; fence.proxy.async.global;" ::: "memory");
                        asm volatile("st.release.cta.shared.u32 [%0], %1;" ::"r"(bars + 8 * (PB_OUT + wg)), "r"(nout + ng) : "memory");
                        if (i < 12) asm volatile(FLAG_ST " [%0], %1;" ::"l"(&g_pflag[cnt * 256 + rh * 8 + nb]), "r"(max(i - 4, 1)) : "memory");
                        if (fast) to_peer();
                    }
                    nout += ng;
                    __syncwarp();
                    continue;
                }
                bar_sync(4 + 4 * wg + (sig++ & 3), 160);
                uint32_t* c = &g_pcnt[(cnt - C_S1) * 256 + rh * 8];
                if (lane == 0) signal_count(c);
                __syncwarp();
                wait_count_w(c, 8);
                const float4* sp = (const float4*)g_st + rh * 32 + lane;
                float4 u[3] = {__ldcg(sp + (cnt == C_S1 ? 0 : 3) * (S_ / 2)), __ldcg(sp + S_ / 2), __ldcg(sp + S_)};
#pragma unroll 1
                for (int h = 0; h < 2; h++) {
                    const float id = 1.0f / DM;
                    const float m = u[0].x * id, var = fmaxf(u[0].y * id - m * m, 0.f) + 1e-5f, r = rsqrtf(var);
                    float sc = r, m2 = 0.f;
                    if (cnt == C_S1) {
                        m2 = r * (u[1].x * id - m * g_cst[0]) + g_cst[3];
                        const float e2 = r * r * (u[2].x * id - 2.0f * m * u[1].y * id + m * m * g_cst[1]) + 2.0f * r * (u[2].y * id - m * g_cst[2]) + g_cst[4];
                        sc = r * rsqrtf(fmaxf(e2 - m2 * m2, 0.f) + 1e-5f);
                    }
                    const GeluK k = gelu_k(sc);
                    *(float4*)(rowc + h * 8) = make_float4(k.k0, k.k1, k.kh, -m);
                    *(float4*)(rowc + h * 8 + 4) = make_float4(var * r, -m2 * var * r, r, -m * r);
#pragma unroll
                    for (int q = 0; q < 3; q++) { u[q].x = u[q].z; u[q].y = u[q].w; }
                }
                bar_arrive(1 + wg, 160);
            }
        }
    } else {
        asm volatile("setmaxnreg.inc.sync.aligned.u32 232;");
        const bf16* xin = pp.x;
        const int wg = wid >> 2, wi = (tid >> 5) & 3, g = lane >> 2, tq = lane & 3;
        const int rh = 2 * mb + wg, row = rh * 64 + wi * 16 + g;
        const bool lead = (tid & 127) == 0;
        uint32_t keep[32];
#pragma unroll
        for (int i = 0; i < 8; i++)
            *(uint4*)(keep + 4 * i) = __ldg((const uint4*)(xin + (size_t)(rh * 64 + wi * 16 + (i & 3) * 4 + (lane >> 3)) * DM + nb * 128 + (i >> 2) * 64 + (lane & 7) * 8));
        asm volatile("griddepcontrol.wait;" ::: "memory");
        if (cta < 64) g_modp[cta * 256 + tid] = 0;
        if (cta == 64 && tid < 196) g_tick[tid] = 0;
        const float* src = wg ? g_vec + nb * 128 + tid - 128 : g_mod + 2 * DM + nb * 128 + tid;
        const float* c3 = &g_vec[3 * DM + (tid >> 6) * 512 + nb * 64 + (tid & 63)];
        const float cv[6] = {__ldcg(src), __ldcg(src + (wg ? 1 : 2) * DM), __ldcg(src + (wg ? 2 : 1) * DM), __ldcg(src + 3 * DM), __ldcg(c3), __ldcg(c3 + (tid < 192 ? 2048 : 0))};
        uint32_t vec = sb + P_VEC + tq * 8;
        const uint32_t stw = sb + (wi * 16 + ((lane >> 3) & 1) * 8 + (lane & 7)) * 128 + (((lane >> 4) ^ (lane & 7)) << 4);
        int sig = 0;
        auto signal = [&]() { bar_arrive(4 + 4 * wg + (sig++ & 3), 160); };
        auto put64 = [&](uint32_t o, const float* v) {
#pragma unroll
            for (int jj = 0; jj < 4; jj++, v += 8) stsm4((stw + o) ^ (jj << 5), pack2(v[0], v[1]), pack2(v[2], v[3]), pack2(v[4], v[5]), pack2(v[6], v[7]));
            fence_async_smem();
            signal();
        };
        auto slot = [&](int n) {
            mbar_wait_w(bars + 8 * (PB_E + n % 5), ((n / 5) & 1) ^ 1);
            return (n % 5) * 16384 + wg * 8192;
        };
        const uint32_t rowc = sb + P_ROW + (wg * 64 + wi * 16 + g) * 32, o128 = P_OUT + wg * 16384;
        Pipe pa = {0, 0, 0};
        asm("mapa.shared::cluster.u32 %0, %1, %2;" : "=r"(pa.rel) : "r"(bars + 8 * PB_E), "r"(tid & 1));
        if (tid & 126) pa.rel = 0;
#define KEEP(jn, e) (((e) & 1) ? bfhi(keep[2 * (jn) + ((e) >> 1)]) : bflo(keep[2 * (jn) + ((e) >> 1)]))
        float mu1[2], r1[2];
        {
            float acc[64];
#pragma unroll 1
            for (int kb = 0; kb < 64; kb++) {
                post_kb<0>(sb, acc, pa, wg, lead, kb == 0, []() {});
                if (kb == 24) bar_sync(3, 256);
                if (kb != 8 + 8 * wg) continue;
                float* sv = (float*)(smraw + P_VEC) + tid;
                const uint32_t xo = sb + o128 + wi * 2048 + (lane >> 3) * 128;
#pragma unroll
                for (int i = 0; i < 8; i++) sts4(xo + (i >> 2) * 8192 + (i & 3) * 512 + (((lane & 7) ^ ((i & 1) * 4 + (lane >> 3))) << 4), keep[4 * i], keep[4 * i + 1], keep[4 * i + 2], keep[4 * i + 3]);
                __syncwarp();
#pragma unroll
                for (int jj = 0; jj < 8; jj++) ldsm4(keep + jj * 4, (stw + o128 + (jj >> 2) * 8192) ^ ((jj & 3) << 5));
                sv[wg * 384] = cv[0]; sv[wg * 384 + 128] = cv[1] + (wg ? 0.0f : 1.0f); sv[wg * 384 + 256] = cv[2];
                if (!wg) sv[384] = cv[3];
                sv[V_C3 * 128] = cv[4]; sv[V_C3 * 128 + 256] = cv[5];
            }
            post_end(sb, pa, lead);
            asm volatile("" : "+r"(vec) :: "memory");
            float st[2][6];
#pragma unroll
            for (int q = 0; q < 6; q++) st[0][q] = st[1][q] = 0.f;
#pragma unroll
            for (int jn = 0; jn < 16; jn++) {
                const float2 ga = ldsv(vec + V_GA * 512 + jn * 32), a = ldsv(vec + V_A * 512 + jn * 32);
                float xa[4];
#pragma unroll
                for (int e = 0; e < 4; e++) {
                    xa[e] = fmaf((e & 1) ? ga.y : ga.x, acc[4 * jn + e], KEEP(jn, e));
                    st[e >> 1][0] += xa[e]; st[e >> 1][1] = fmaf(xa[e], xa[e], st[e >> 1][1]);
                    acc[4 * jn + e] = ((e & 1) ? a.y : a.x) * xa[e];
                }
                keep[2 * jn] = pack2(xa[0], xa[1]); keep[2 * jn + 1] = pack2(xa[2], xa[3]);
                if ((jn & 7) == 7) put64(slot(64 + (jn >> 3)), acc + 4 * jn - 28);
            }
#pragma unroll
            for (int jn = 0; jn < 16; jn++) {
                const float2 a = ldsv(vec + V_A * 512 + jn * 32), b = ldsv(vec + V_B * 512 + jn * 32);
#pragma unroll
                for (int e = 0; e < 4; e++) {
                    const float y = acc[4 * jn + e], aa = (e & 1) ? a.y : a.x, bb = (e & 1) ? b.y : b.x;
                    float* s = st[e >> 1];
                    s[2] += y; s[3] = fmaf(aa, y, s[3]); s[4] = fmaf(y, y, s[4]); s[5] = fmaf(bb, y, s[5]);
                }
            }
#pragma unroll
            for (int h = 0; h < 2; h++)
#pragma unroll
                for (int q = 0; q < 6; q++) { st[h][q] += __shfl_xor_sync(~0u, st[h][q], 1); st[h][q] += __shfl_xor_sync(~0u, st[h][q], 2); }
            if (tq < 3) {
#pragma unroll
                for (int h = 0; h < 2; h++)
                    red2(g_st + (tq * S_ + row + h * 8) * 2, tq == 0 ? st[h][0] : tq == 1 ? st[h][2] : st[h][4], tq == 0 ? st[h][1] : tq == 1 ? st[h][3] : st[h][5]);
            }
            signal();
        }
        {
            float acc[64];
            post_mma<1>(sb, acc, pa, wg, lead, 2, 4, mb, nb);
            float c1[2], c2[2], c3[2];
            GeluK gk[2];
            bar_sync(1 + wg, 160);
#pragma unroll
            for (int h = 0; h < 2; h++) {
                const float4 a = lds4f(rowc + h * 256), b = lds4f(rowc + h * 256 + 16);
                gk[h] = {a.x, a.y, a.z}; c1[h] = a.w; c2[h] = b.x; c3[h] = b.y; mu1[h] = b.w; r1[h] = b.z;
            }
#pragma unroll
            for (int jn = 0; jn < 16; jn++) {
                const float2 va = ldsv(vec + V_VA * 512 + jn * 32), vb = ldsv(vec + V_VB * 512 + jn * 32), vc = ldsv(vec + V_VC * 512 + jn * 32);
#pragma unroll
                for (int e = 0; e < 4; e++) {
                    const int h = e >> 1;
                    const float t = fmaf(c1[h], (e & 1) ? va.y : va.x, fmaf(c2[h], (e & 1) ? vb.y : vb.x, fmaf(c3[h], (e & 1) ? vc.y : vc.x, acc[4 * jn + e])));
                    acc[4 * jn + e] = gelu_s(t, gk[h]);
                }
                if ((jn & 7) == 7) put64(o128 + (jn >> 3) * 8192, acc + 4 * jn - 28);
            }
        }
        {
            float acc[64];
            post_mma<2>(sb, acc, pa, wg, lead, 0, 7, mb, nb);
#pragma unroll
            for (int jn = 0; jn < 16; jn++) {
                const float2 a = ldsv(vec + V_A * 512 + jn * 32), b = ldsv(vec + V_B * 512 + jn * 32);
#pragma unroll
                for (int e = 0; e < 4; e++) {
                    const int h = e >> 1;
                    acc[4 * jn + e] += fmaf(fmaf(KEEP(jn, e), r1[h], mu1[h]), (e & 1) ? a.y : a.x, (e & 1) ? b.y : b.x);
                }
                if ((jn & 7) == 7) put64(slot(96 + (jn >> 3)), acc + 4 * jn - 28);
            }
            BLOCK_FENCE
#pragma unroll
            for (int i = 0; i < 64; i += 16) asm volatile("" : F16(acc, i));
            float st[2][2] = {{0.f, 0.f}, {0.f, 0.f}};
#pragma unroll
            for (int jn = 0; jn < 16; jn++) {
                const float2 gb = ldsv(vec + V_GB * 512 + jn * 32);
                float z[4];
#pragma unroll
                for (int e = 0; e < 4; e++) {
                    const float x1 = acc[4 * jn + e];
                    st[e >> 1][0] += x1; st[e >> 1][1] = fmaf(x1, x1, st[e >> 1][1]);
                    z[e] = fmaf((e & 1) ? gb.y : gb.x, x1, KEEP(jn, e));
                }
                keep[2 * jn] = pack2(z[0], z[1]); keep[2 * jn + 1] = pack2(z[2], z[3]);
            }
#pragma unroll
            for (int h = 0; h < 2; h++)
#pragma unroll
                for (int q = 0; q < 2; q++) { st[h][q] += __shfl_xor_sync(~0u, st[h][q], 1); st[h][q] += __shfl_xor_sync(~0u, st[h][q], 2); }
            if (tq < 2) red2(g_st + (3 * S_ + row + tq * 8) * 2, tq ? st[1][0] : st[0][0], tq ? st[1][1] : st[0][1]);
            signal();
        }
        {
            float old[96], acc[64];
            post_mma<3>(sb, old, pa, wg, lead, 6, 10, mb, nb);
#pragma unroll
            for (int i = 0; i < 96; i += 16) asm volatile("" : F16(old, i));
            uint32_t v3 = vec + V_C3 * 512;
            bar_sync(1 + wg, 160);
            const float4 rc[2] = {lds4f(rowc), lds4f(rowc + 256)};
            float2 vc[2] = {lds2f(v3), lds2f(v3 + 32)};
            v3 += wg ? 0 : 64;
            bar_sync(3, 256);
#pragma unroll 1
            for (int blk = 0; blk < 11; blk++) {
                const uint32_t o = stw + o128 + (blk & 1) * 8192;
#pragma unroll
                for (int q = 0; q < 4; q++) {
#pragma unroll 1
                    for (int rep = 0; rep < 2; rep++) {
                        post_kb<1>(sb, acc, pa, wg, lead, q == 0 && rep == 0 && blk < 6 && !(blk & 1), []() {});
                        if (rep != wg) {
                            vc[0] = lds2f(v3 + q * 64); vc[1] = lds2f(v3 + q * 64 + 32);
                            if (q == 2) wait_smem(bars + 8 * (PB_OUT + wg), 6 + min(blk, 7));
                            if ((q == 0 && wg && (uint32_t)(blk - 1) < 7) || (q == 3 && !wg && blk < 7)) { fence_async_smem(); signal(); }
                        } else if (blk < 7) {
                            asm volatile("" : F4(old, 8 * q), F4(old, 8 * q + 4));
                            float t[8];
#pragma unroll
                            for (int i = 0; i < 8; i++) {
                                const float4& c = rc[(i >> 1) & 1];
                                t[i] = gelu_s(fmaf(c.w, (i & 1) ? vc[i >> 2].y : vc[i >> 2].x, old[8 * q + i]), GeluK{c.x, c.y, c.z});
                                old[8 * q + i] = old[32 + 8 * q + i];
                                old[32 + 8 * q + i] = old[64 + 8 * q + i];
                            }
                            uint32_t r[4] = {pack2(t[0], t[1]), pack2(t[2], t[3]), pack2(t[4], t[5]), pack2(t[6], t[7])};
                            asm volatile("pmevent 0;" : F4(old, 8 * q), F4(old, 8 * q + 4), F4(old, 8 * q + 32), F4(old, 8 * q + 36), "+r"(r[0]), "+r"(r[1]), "+r"(r[2]), "+r"(r[3]));
                            stsm4(o ^ (q << 5), r[0], r[1], r[2], r[3]);
                        }
                    }
                }
                v3 += 256;
                if (blk != 1 && blk != 3) continue;
                post_end(sb, pa, lead);
                asm volatile("" : F16(acc, 0), F4(acc, 16), F4(acc, 20), F4(acc, 24));
                asm volatile("" : F16(acc, 28), F4(acc, 44), F4(acc, 48), F4(acc, 52));
                asm volatile("" : F4(acc, 56), F4(acc, 60));
#pragma unroll
                for (int i = 0; i < 64; i++) old[32 + i] = acc[i];
            }
            post_end(sb, pa, lead);
#pragma unroll
            for (int jn = 0; jn < 16; jn++) {
                const float2 gb = ldsv(vec + V_GB * 512 + jn * 32);
#pragma unroll
                for (int e = 0; e < 4; e++) acc[4 * jn + e] = fmaf((e & 1) ? gb.y : gb.x, acc[4 * jn + e], KEEP(jn, e));
                if ((jn & 7) == 7) put64(o128 + ((jn >> 3) ^ 1) * 8192, acc + 4 * jn - 28);
            }
        }
    }
}

typedef CUresult (*EncFn)(CUtensorMap*, CUtensorMapDataType, cuuint32_t, void*, const cuuint64_t*, const cuuint64_t*, const cuuint32_t*,
                          const cuuint32_t*, CUtensorMapInterleave, CUtensorMapSwizzle, CUtensorMapL2promotion, CUtensorMapFloatOOBfill);

static CUtensorMap make_map(EncFn enc, const void* p, uint64_t inner, uint64_t outer, uint32_t bi = 64) {
    CUtensorMap m;
    cuuint64_t dims[2] = {inner, outer};
    cuuint64_t str[1] = {inner * 2};
    cuuint32_t box[2] = {bi, bi == 64 ? 64u : 16u};
    cuuint32_t es[2] = {1, 1};
    enc(&m, CU_TENSOR_MAP_DATA_TYPE_BFLOAT16, 2, (void*)p, dims, str, box, es, CU_TENSOR_MAP_INTERLEAVE_NONE,
        bi == 64 ? CU_TENSOR_MAP_SWIZZLE_128B : CU_TENSOR_MAP_SWIZZLE_NONE, CU_TENSOR_MAP_L2_PROMOTION_L2_256B, CU_TENSOR_MAP_FLOAT_OOB_FILL_NONE);
    return m;
}
static CUtensorMap make_map_o(EncFn enc, const void* p) {
    CUtensorMap m;
    cuuint64_t dims[2] = {16384, 256};
    cuuint64_t str[1] = {65536};
    cuuint32_t box[2] = {256, 8};
    cuuint32_t es[2] = {1, 1};
    enc(&m, CU_TENSOR_MAP_DATA_TYPE_UINT32, 2, (void*)p, dims, str, box, es, CU_TENSOR_MAP_INTERLEAVE_NONE, CU_TENSOR_MAP_SWIZZLE_NONE,
        CU_TENSOR_MAP_L2_PROMOTION_L2_256B, CU_TENSOR_MAP_FLOAT_OOB_FILL_NONE);
    return m;
}
template <class T> static T* sym(T& s) { void* p = nullptr; cudaGetSymbolAddress(&p, s); return (T*)p; }

static const Delays h_dly = {D_NEAR, D_FAR, D_X2, D_V, D_W2, D_PA, D_MORE2, D_MORE};
extern "C" void kernel_launch(void* const* d_in, const int* in_sizes, int n_in, void* d_out, int out_size) {
    const bf16* x = (const bf16*)d_in[0];
    const bf16* mem0 = (const bf16*)d_in[1];
    const bf16 *Wq = (const bf16*)d_in[2], *Wk = (const bf16*)d_in[3], *Wv = (const bf16*)d_in[4], *Wo = (const bf16*)d_in[5];
    const bf16 *w1 = (const bf16*)d_in[8], *w2 = (const bf16*)d_in[9], *w3 = (const bf16*)d_in[10], *w4 = (const bf16*)d_in[11];
    const bf16 *c = (const bf16*)d_in[12], *wmod = (const bf16*)d_in[13];
    bf16* out = (bf16*)d_out;

    EncFn enc = nullptr;
    cudaDriverEntryPointQueryResult qr;
    cudaGetDriverEntryPoint("cuTensorMapEncodeTiled", (void**)&enc, cudaEnableDefault, &qr);
    CUtensorMap tWq = make_map(enc, Wq, NH * DH, DM), tWk = make_map(enc, Wk, NH * DH, DM), tWv = make_map(enc, Wv, NH * DH, DM);
    PostMaps mp;
    mp.o = make_map_o(enc, sym(g_O)); mp.wo = make_map(enc, Wo, DM, NH * DH);
    mp.y = make_map(enc, sym(g_y), DM, S_); mp.w1 = make_map(enc, w1, DM, DM);
    mp.g = make_map(enc, sym(g_g), DM, S_); mp.w2 = make_map(enc, w2, DM, DM);
    mp.x1 = make_map(enc, sym(g_x1), DM, S_); mp.w3 = make_map(enc, w3, FF, DM);
    mp.u = make_map(enc, sym(g_u), FF, S_); mp.w4 = make_map(enc, w4, DM, FF);
    mp.out = make_map(enc, out, DM, S_);
    cudaFuncSetAttribute(k_rec, cudaFuncAttributeMaxDynamicSharedMemorySize, SM_REC_TOTAL + 2048);
    cudaFuncSetAttribute(k_post, cudaFuncAttributeMaxDynamicSharedMemorySize, P_SMEM);

    uint8_t* arena = (uint8_t*)(((uintptr_t)sym(g_arena) + (2u << 20) - 1) & ~(uintptr_t)((2u << 20) - 1));
    const PostPtrs pp = {x};
    const RecPtrs rp = {x, mem0, c, wmod, w1, w3, arena, 0u, w2, w4, Wo, h_dly};
    const RecMaps rm = {tWq, tWk, tWv, mp.wo, make_map(enc, wmod, 6 * DM, DM, 256), make_map(enc, w3, FF, DM, 256), make_map(enc, w1, DM, DM, 256)};
    k_rec<<<132, 384, SM_REC_TOTAL + 2048>>>(rm, rp);
    cudaLaunchConfig_t cfg = {};
    cfg.gridDim = dim3(132); cfg.blockDim = dim3(384); cfg.dynamicSmemBytes = P_SMEM; cfg.stream = cudaStreamPerThread;
    cudaLaunchAttribute at[1];
    at[0].id = cudaLaunchAttributeProgrammaticStreamSerialization; at[0].val.programmaticStreamSerializationAllowed = PDL;
    cfg.attrs = at; cfg.numAttrs = 1;
    cudaLaunchKernelEx(&cfg, k_post, mp, pp);
}
```

```cpp
#include <cuda_runtime.h>
#include <cuda.h>
#include <cuda_bf16.h>
#include <stdint.h>
#include <limits.h>

typedef __nv_bfloat16 bf16;

constexpr int S_ = 2048, DM = 1024, NH = 32, DH = 128, NSEG = 64, FF = 3584;
constexpr int SPIN_LIMIT = 1 << 22;
#define W_INFL 2
#define H_PIECES 4
#define PDL 1
#define PD0 3
#define PD1 3
#define QS_AT 2
#define NPROBE 3

__device__ uint8_t g_arena[10 << 20];
__device__ __align__(128) uint32_t g_tick[64 + 132];
#define g_clk ((uint2*)(g_tick + 64))
__device__ uint32_t g_cls[256];
__device__ unsigned long long g_pt;
__device__ __align__(16) uint32_t g_modp[8 * 2 * DM];
__host__ __device__ constexpr uint32_t blk(uint32_t lb, uint32_t par) {
    return (lb << 13) | ((((lb) ^ (lb >> 3) ^ (lb >> 4) ^ (lb >> 6) ^ par) & 1) << 12);
}
__host__ __device__ constexpr uint32_t lb_x2(uint32_t h) { return (h & 1) | ((h >> 1) << 3); }
__host__ __device__ constexpr uint32_t mem_row(uint32_t kh, uint32_t b, uint32_t r) { return blk(128 | b, kh) + r * 1024; }
__device__ __forceinline__ uint32_t mem_slot(uint32_t s) { return ((s & 1) << 15) | ((s & 2) << 17); }
constexpr uint32_t CNT1 = 0x3d80, CNT_ALL = 0x4000;
constexpr uint32_t LB_PROBE = 6 | 64, LB_TIME = 6;
__host__ __device__ constexpr uint32_t lb_tok(uint32_t h) { return (h & 1) | ((h >> 1) << 3); }
__device__ float g_mod[6 * DM];
__device__ __align__(1024) bf16 g_himg[(S_ + 32) * DM];
__device__ __align__(1024) bf16 g_O[S_ * NH * DH];
__device__ __align__(1024) bf16 g_y[S_ * DM];
__device__ __align__(1024) bf16 g_g[S_ * DM];
__device__ __align__(1024) bf16 g_x1[S_ * DM];
__device__ __align__(16) float g_st[4 * S_ * 2];
__device__ float g_vec[3 * DM + FF];
__device__ float g_cst[8];
__device__ uint32_t g_pcnt[2 * 32 * 8], g_pflag[7 * 32 * 8];
__device__ __align__(1024) bf16 g_u[S_ * FF];

__device__ __forceinline__ uint32_t smem_u32(const void* p) { return (uint32_t)__cvta_generic_to_shared(p); }
__device__ __forceinline__ void spin_guard(int it) {
    asm volatile("{.reg .pred p; setp.gt.s32 p, %0, %1; @p st.global.u32 [%2], %0;}" ::"r"(it), "n"(SPIN_LIMIT), "l"(1ull));
}
__device__ __forceinline__ void wg_fence() { asm volatile("wgmma.fence.sync.aligned;" ::: "memory"); }
__device__ __forceinline__ void wg_commit() { asm volatile("wgmma.commit_group.sync.aligned;" ::: "memory"); }
template <int N> __device__ __forceinline__ void wg_wait() { asm volatile("wgmma.wait_group.sync.aligned %0;" ::"n"(N) : "memory"); }
__host__ __device__ constexpr uint64_t mkdesc(uint32_t addr, uint32_t lbo, uint32_t sbo, uint32_t swz) {
    return (uint64_t)((addr & 0x3FFFF) >> 4) | ((uint64_t)(lbo >> 4) << 16) | ((uint64_t)(sbo >> 4) << 32) | ((uint64_t)swz << 62);
}
__device__ __forceinline__ uint64_t dadd(uint64_t d, uint32_t o) { return (d & 0xffffffff00000000ull) | (uint32_t)((uint32_t)d + o); }
__device__ __forceinline__ void mbar_init(uint32_t b, uint32_t c) { asm volatile("mbarrier.init.shared.b64 [%0], %1;" ::"r"(b), "r"(c) : "memory"); }
__device__ __forceinline__ void mbar_arrive_cluster(uint32_t b, uint32_t cta) {
    asm volatile("{.reg .b32 r; mapa.shared::cluster.u32 r, %0, %1; mbarrier.arrive.shared::cluster.b64 _, [r];}" ::"r"(b), "r"(cta) : "memory");
}
__device__ __forceinline__ bool mbar_try(uint32_t b, uint32_t par) {
    uint32_t ok;
    asm volatile("{.reg .pred p; mbarrier.try_wait.parity.shared.b64 p, [%1], %2; selp.u32 %0, 1, 0, p;}" : "=r"(ok) : "r"(b), "r"(par) : "memory");
    return ok;
}
__device__ __forceinline__ void mbar_wait(uint32_t b, uint32_t par) {
    int it = 0;
#pragma unroll 1
    while (!mbar_try(b, par) & (++it < SPIN_LIMIT)) {}
}
__device__ __forceinline__ void mbar_wait_w(uint32_t b, uint32_t par) {
    int it = 0;
#pragma unroll 1
    while (!__all_sync(~0u, mbar_try(b, par)) & (++it < SPIN_LIMIT)) {}
}
constexpr uint64_t EVICT_FIRST = 0x12F0000000000000ull, EVICT_NORMAL = 0x1000000000000000ull;   __device__ __forceinline__ void bar_sync(int id, int n) { asm volatile("bar.sync %0, %1;" ::"r"(id), "r"(n) : "memory"); }
__device__ __forceinline__ void bar_arrive(int id, int n) { asm volatile("bar.arrive %0, %1;" ::"r"(id), "r"(n) : "memory"); }
__device__ __forceinline__ void fence_async_smem() { asm volatile("fence.proxy.async.shared::cta;" ::: "memory"); }
__device__ __forceinline__ void ldsm4t(uint32_t* r, uint32_t a) {
    asm volatile("ldmatrix.sync.aligned.m8n8.x4.trans.shared.b16 {%0,%1,%2,%3}, [%4];" : "=r"(r[0]), "=r"(r[1]), "=r"(r[2]), "=r"(r[3]) : "r"(a) : "memory");
}
__device__ __forceinline__ void ldsm4(uint32_t* r, uint32_t a) {
    asm volatile("ldmatrix.sync.aligned.m8n8.x4.shared.b16 {%0,%1,%2,%3}, [%4];" : "=r"(r[0]), "=r"(r[1]), "=r"(r[2]), "=r"(r[3]) : "r"(a) : "memory");
}
__device__ __forceinline__ uint32_t movm(uint32_t a) {
    uint32_t d; asm volatile("movmatrix.sync.aligned.m8n8.trans.b16 %0, %1;" : "=r"(d) : "r"(a)); return d;
}
__device__ __forceinline__ void mma16816(float* d, uint32_t a0, uint32_t a1, uint32_t a2, uint32_t a3, uint32_t b0, uint32_t b1) {
    asm volatile("mma.sync.aligned.m16n8k16.row.col.f32.bf16.bf16.f32 {%0,%1,%2,%3},{%4,%5,%6,%7},{%8,%9},{%0,%1,%2,%3};"
                 : "+f"(d[0]), "+f"(d[1]), "+f"(d[2]), "+f"(d[3]) : "r"(a0), "r"(a1), "r"(a2), "r"(a3), "r"(b0), "r"(b1));
}
__device__ __forceinline__ void mma16816z(float* d, const uint32_t* a, uint32_t b0, uint32_t b1) {
    asm volatile("mma.sync.aligned.m16n8k16.row.col.f32.bf16.bf16.f32 {%0,%1,%2,%3},{%4,%5,%6,%7},{%8,%9},{%10,%10,%10,%10};"
                 : "=f"(d[0]), "=f"(d[1]), "=f"(d[2]), "=f"(d[3]) : "r"(a[0]), "r"(a[1]), "r"(a[2]), "r"(a[3]), "r"(b0), "r"(b1), "f"(0.f));
}
__device__ __forceinline__ void mma1688(float* d, uint32_t a0, uint32_t a1, uint32_t b0) {
    asm volatile("mma.sync.aligned.m16n8k8.row.col.f32.bf16.bf16.f32 {%0,%1,%2,%3},{%4,%5},{%6},{%0,%1,%2,%3};"
                 : "+f"(d[0]), "+f"(d[1]), "+f"(d[2]), "+f"(d[3]) : "r"(a0), "r"(a1), "r"(b0));
}
__device__ __forceinline__ uint32_t pack2(float lo, float hi) {
    uint32_t r; asm("cvt.rn.bf16x2.f32 %0, %1, %2;" : "=r"(r) : "f"(hi), "f"(lo)); return r;
}
__device__ __forceinline__ uint32_t hadd2(uint32_t a, uint32_t b) {
    uint32_t r; asm("add.rn.bf16x2 %0, %1, %2;" : "=r"(r) : "r"(a), "r"(b)); return r;
}
__device__ __forceinline__ float bflo(uint32_t u) { return __uint_as_float(u << 16); }
__device__ __forceinline__ float bfhi(uint32_t u) { return __uint_as_float(u & 0xffff0000u); }
__device__ __forceinline__ float ex2(float x) { float r; asm("ex2.approx.ftz.f32 %0, %1;" : "=f"(r) : "f"(x)); return r; }
__device__ __forceinline__ uint4 ldg_rlx4(const void* p) {
    uint4 v; asm volatile("ld.relaxed.gpu.global.v4.u32 {%0,%1,%2,%3}, [%4];" : "=r"(v.x), "=r"(v.y), "=r"(v.z), "=r"(v.w) : "l"(p) : "memory"); return v;
}
__device__ __forceinline__ uint32_t ldg_rlx1(const void* p) {
    uint32_t v; asm volatile("ld.relaxed.gpu.global.u32 %0, [%1];" : "=r"(v) : "l"(p) : "memory"); return v;
}
__device__ __forceinline__ void stg_rlx1(void* p, uint32_t v) { asm volatile("st.relaxed.gpu.global.u32 [%0], %1;" ::"l"(p), "r"(v) : "memory"); }
__device__ __forceinline__ void stg_rlx2(void* p, uint32_t x, uint32_t y) {
    unsigned long long v = (unsigned long long)x | ((unsigned long long)y << 32);
    asm volatile("st.relaxed.gpu.global.b64 [%0], %1;" ::"l"(p), "l"(v) : "memory");
}
__device__ __forceinline__ void stg_rlx4(void* p, uint32_t x, uint32_t y, uint32_t z, uint32_t w) {
    asm volatile("st.relaxed.gpu.global.v4.u32 [%0], {%1,%2,%3,%4};" ::"l"(p), "r"(x), "r"(y), "r"(z), "r"(w) : "memory");
}
__device__ __forceinline__ void sts4(uint32_t a, uint32_t x, uint32_t y, uint32_t z, uint32_t w) {
    asm volatile("st.shared.v4.u32 [%0], {%1,%2,%3,%4};" ::"r"(a), "r"(x), "r"(y), "r"(z), "r"(w) : "memory");
}
__device__ __forceinline__ uint4 lds4(uint32_t a) {
    uint4 v; asm volatile("ld.shared.v4.u32 {%0,%1,%2,%3}, [%4];" : "=r"(v.x), "=r"(v.y), "=r"(v.z), "=r"(v.w) : "r"(a) : "memory"); return v;
}
#define F4(d, i) "+f"(d[i]), "+f"(d[i + 1]), "+f"(d[i + 2]), "+f"(d[i + 3])
__device__ __forceinline__ void wgmma_rs32(float* d, const uint32_t* a, uint64_t b, int sc) {
    asm volatile("{.reg .pred p; setp.ne.b32 p, %21, 0;\n wgmma.mma_async.sync.aligned.m64n32k16.f32.bf16.bf16 {%0,%1,%2,%3,%4,%5,%6,%7,%8,%9,%10,%11,%12,%13,%14,%15}, {%16,%17,%18,%19}, %20, p, 1, 1, 0;}"
                 : F4(d, 0), F4(d, 4), F4(d, 8), F4(d, 12) : "r"(a[0]), "r"(a[1]), "r"(a[2]), "r"(a[3]), "l"(b), "r"(sc));
}
__device__ __forceinline__ void wgmma_ss32(float* d, uint64_t a, uint64_t b, int sc) {
    asm volatile("{.reg .pred p; setp.ne.b32 p, %18, 0;\n wgmma.mma_async.sync.aligned.m64n32k16.f32.bf16.bf16 {%0,%1,%2,%3,%4,%5,%6,%7,%8,%9,%10,%11,%12,%13,%14,%15}, %16, %17, p, 1, 1, 1, 0;}"
                 : F4(d, 0), F4(d, 4), F4(d, 8), F4(d, 12) : "l"(a), "l"(b), "r"(sc));
}
__device__ __forceinline__ void wgmma_rs40(float* d, const uint32_t* a, uint64_t b, int sc) {
    asm volatile("{.reg .pred p; setp.ne.b32 p, %25, 0;\n wgmma.mma_async.sync.aligned.m64n40k16.f32.bf16.bf16 {%0,%1,%2,%3,%4,%5,%6,%7,%8,%9,%10,%11,%12,%13,%14,%15,%16,%17,%18,%19}, {%20,%21,%22,%23}, %24, p, 1, 1, 0;}"
                 : F4(d, 0), F4(d, 4), F4(d, 8), F4(d, 12), F4(d, 16) : "r"(a[0]), "r"(a[1]), "r"(a[2]), "r"(a[3]), "l"(b), "r"(sc));
}
__device__ __forceinline__ void wgmma_ss40(float* d, uint64_t a, uint64_t b, int sc) {
    asm volatile("{.reg .pred p; setp.ne.b32 p, %22, 0;\n wgmma.mma_async.sync.aligned.m64n40k16.f32.bf16.bf16 {%0,%1,%2,%3,%4,%5,%6,%7,%8,%9,%10,%11,%12,%13,%14,%15,%16,%17,%18,%19}, %20, %21, p, 1, 1, 1, 0;}"
                 : F4(d, 0), F4(d, 4), F4(d, 8), F4(d, 12), F4(d, 16) : "l"(a), "l"(b), "r"(sc));
}
#define F16(d, i) F4(d, i), F4(d, i + 4), F4(d, i + 8), F4(d, i + 12)
template <int TA>
__device__ __forceinline__ void wgmma_ss128(float* d, uint64_t a, uint64_t b, int sc) {
    asm volatile("{.reg .pred p; setp.ne.b32 p, %66, 0;\n wgmma.mma_async.sync.aligned.m64n128k16.f32.bf16.bf16 "
                 "{%0,%1,%2,%3,%4,%5,%6,%7,%8,%9,%10,%11,%12,%13,%14,%15,%16,%17,%18,%19,%20,%21,%22,%23,%24,%25,%26,%27,%28,%29,%30,%31,"
                 "%32,%33,%34,%35,%36,%37,%38,%39,%40,%41,%42,%43,%44,%45,%46,%47,%48,%49,%50,%51,%52,%53,%54,%55,%56,%57,%58,%59,%60,%61,%62,%63}, %64, %65, p, 1, 1, %67, 1;}"
                 : F16(d, 0), F16(d, 16), F16(d, 32), F16(d, 48) : "l"(a), "l"(b), "r"(sc), "n"(TA));
}

__device__ __forceinline__ float warp_sum(float v) {
#pragma unroll
    for (int o = 16; o; o >>= 1) v += __shfl_xor_sync(~0u, v, o);
    return v;
}
__device__ __forceinline__ float bfround(float x) { return __bfloat162float(__float2bfloat16(x)); }

__device__ __forceinline__ void wait_count1(const uint32_t* p, uint32_t target) {
    int it = 0;
#pragma unroll 1
    while (true) {
        uint32_t v;
        asm volatile("ld.acquire.gpu.global.u32 %0, [%1];" : "=r"(v) : "l"(p) : "memory");
        if (v >= target) break;
        spin_guard(++it);
    }
}
__device__ __forceinline__ void red2(float* p, float a, float b) {
    asm volatile("red.relaxed.gpu.global.add.v2.f32 [%0], {%1, %2};" ::"l"(p), "f"(a), "f"(b) : "memory");
}
__device__ __forceinline__ void signal_count(uint32_t* p) { asm volatile("red.release.gpu.global.add.u32 [%0], 1;" ::"l"(p) : "memory"); }
__device__ __forceinline__ void e_expect(uint32_t b, uint32_t tx) {
    asm volatile("{.reg .pred p; elect.sync _|p, 0xffffffff; @p mbarrier.arrive.expect_tx.shared.b64 _, [%0], %1;}" ::"r"(b), "r"(tx) : "memory");
}
__device__ __forceinline__ void e_tma2d(uint32_t dst, const CUtensorMap* m, int c0, int c1, uint32_t bar) {
    asm volatile("{.reg .pred p; elect.sync _|p, 0xffffffff;\n @p cp.async.bulk.tensor.2d.shared::cluster.global.mbarrier::complete_tx::bytes [%0], [%1, {%3, %4}], [%2];}"
                 ::"r"(dst), "l"(m), "r"(bar), "r"(c0), "r"(c1) : "memory");
}
__device__ __forceinline__ void e_tma2d_hint(uint32_t dst, const CUtensorMap* m, int c0, int c1, uint32_t bar, uint64_t pol) {
    asm volatile("{.reg .pred p; elect.sync _|p, 0xffffffff;\n @p cp.async.bulk.tensor.2d.shared::cluster.global.mbarrier::complete_tx::bytes.L2::cache_hint [%0], [%1, {%3, %4}], [%2], %5;}"
                 ::"r"(dst), "l"(m), "r"(bar), "r"(c0), "r"(c1), "l"(pol) : "memory");
}
__device__ __forceinline__ void e_tma2d_mc(uint32_t dst, const CUtensorMap* m, int c0, int c1, uint32_t bar) {
    asm volatile("{.reg .pred p; elect.sync _|p, 0xffffffff;\n @p cp.async.bulk.tensor.2d.shared::cluster.global.mbarrier::complete_tx::bytes.multicast::cluster [%0], [%1, {%3, %4}], [%2], %5;}"
                 ::"r"(dst), "l"(m), "r"(bar), "r"(c0), "r"(c1), "h"((uint16_t)3) : "memory");
}
__device__ __forceinline__ void wait_count_w(const uint32_t* p, uint32_t target) {
    int it = 0;
#pragma unroll 1
    while (true) {
        uint32_t v;
        asm volatile("ld.acquire.gpu.global.u32 %0, [%1];" : "=r"(v) : "l"(p) : "memory");
        if (__all_sync(~0u, v >= target) | (++it > SPIN_LIMIT)) break;
        __nanosleep(100);
    }
}

#define NL 6
constexpr uint32_t SM_HB = 16384, HBK = 5120, SM_SX = 57344, SM_OX = 122880, SM_PX = 124928, SM_PA = 126976, SM_WO = 147456,
                   SM_TAB = 212992, SM_PRE = SM_TAB + 5120, SM_BAR = 227328, SM_REC_TOTAL = 227328 + 256;
constexpr uint32_t SB0 = 1024;
constexpr int B_WO = 0, B_HE = 1, B_HB = 3, B_W = 5;
constexpr int NB_MEM = 1, NB_QK = 2, NB_X1 = 3, NB_X2 = 4, NB_WIN = 5, NB_WG = 6, NB_KDONE = 7, NB_FIN0 = 8, NB_P = 9, NB_PX = 10, NB_G = 11, NB_A = 12, NB_B = 13, NB_C = 14, NB_S = 15;
#define D_NEAR 1620
#define D_FAR (D_NEAR - 90)
#define D_X2 400
#define D_V 280
#define D_W2 40
#define D_PA 40
#define D_MORE 40
#define D_MORE2 30
constexpr int E_MUL = 28;
constexpr int NPF = NL + 6, NE1 = 10;
constexpr int W0_E = 3, W0_RS = NL - 1, G_AT = 18;
struct Delays { uint32_t near, far, x2, v, w2, pa, more2, more; };

__device__ __forceinline__ uint32_t clk32() { uint32_t t; asm volatile("mov.u32 %0, %%clock;" : "=r"(t) :: "memory"); return t; }
__device__ __forceinline__ uint32_t smid() { uint32_t t; asm volatile("mov.u32 %0, %%smid;" : "=r"(t)); return t; }
__device__ __forceinline__ uint32_t gtime() { uint32_t t; asm volatile("mov.u32 %0, %%globaltimer_lo;" : "=r"(t) :: "memory"); return t; }
__device__ __forceinline__ void spin_until(uint32_t t0, uint32_t d) { while (clk32() - t0 < d) {} }
template <int N> __device__ __forceinline__ uint32_t delay(uint32_t zero) {
    float x = __uint_as_float(clk32());
#pragma unroll
    for (int i = 0; i < N; i++) asm volatile("ex2.approx.ftz.f32 %0, %0;" : "+f"(x));
    return __float_as_uint(x) & zero;
}
__device__ __forceinline__ uint32_t opaque(uint32_t v) { return __shfl_sync(~0u, v, threadIdx.x & 31); }
__device__ __forceinline__ uint32_t xor_or(uint32_t a, uint32_t b, uint32_t t) {
    uint32_t r; asm volatile("lop3.b32 %0, %1, %2, %3, 0x7E;" : "=r"(r) : "r"(a), "r"(b), "r"(t)); return r;
}
__device__ __forceinline__ uint32_t settag(uint32_t v, uint32_t tag) {
    uint32_t r; asm("lop3.b32 %0, %1, 1, %2, 0xB8;" : "=r"(r) : "r"(v), "r"(tag)); return r;
}
__device__ __forceinline__ void sts2(uint32_t a, float x, float y) { asm volatile("st.shared.v2.f32 [%0], {%1,%2};" ::"r"(a), "f"(x), "f"(y) : "memory"); }
__device__ __forceinline__ void sts4f(uint32_t a, float x, float y, float z, float w) {
    asm volatile("st.shared.v4.f32 [%0], {%1,%2,%3,%4};" ::"r"(a), "f"(x), "f"(y), "f"(z), "f"(w) : "memory");
}
__device__ __forceinline__ void sts1(uint32_t a, uint32_t x) { asm volatile("st.shared.u32 [%0], %1;" ::"r"(a), "r"(x) : "memory"); }
__device__ __forceinline__ uint32_t lds1(uint32_t a) { uint32_t v; asm volatile("ld.shared.u32 %0, [%1];" : "=r"(v) : "r"(a) : "memory"); return v; }
__device__ __forceinline__ float4 lds4f(uint32_t a) {
    float4 v; asm volatile("ld.shared.v4.f32 {%0,%1,%2,%3}, [%4];" : "=f"(v.x), "=f"(v.y), "=f"(v.z), "=f"(v.w) : "r"(a) : "memory"); return v;
}
__device__ __forceinline__ float2 lds2f(uint32_t a) {
    float2 v; asm volatile("ld.shared.v2.f32 {%0,%1}, [%2];" : "=f"(v.x), "=f"(v.y) : "r"(a) : "memory"); return v;
}
__device__ __forceinline__ bool any_bit0(uint32_t x) {
    uint32_t r;
    asm volatile("{.reg .pred p, q; .reg .b32 t; and.b32 t, %1, 1; setp.ne.u32 p, t, 0; vote.sync.any.pred q, p, 0xffffffff; selp.u32 %0, 1, 0, q;}" : "=r"(r) : "r"(x));
    return r;
}
__device__ __forceinline__ float rcp_fast(float x) { float r; asm("rcp.approx.ftz.f32 %0, %1;" : "=f"(r) : "f"(x)); return r; }
__device__ __forceinline__ void stsm4(uint32_t a, uint32_t r0, uint32_t r1, uint32_t r2, uint32_t r3) {
    asm volatile("stmatrix.sync.aligned.m8n8.x4.shared.b16 [%0], {%1,%2,%3,%4};" ::"r"(a), "r"(r0), "r"(r1), "r"(r2), "r"(r3) : "memory");
}
__device__ __forceinline__ void stsm4t(uint32_t a, uint32_t r0, uint32_t r1, uint32_t r2, uint32_t r3) {
    asm volatile("stmatrix.sync.aligned.m8n8.x4.trans.shared.b16 [%0], {%1,%2,%3,%4};" ::"r"(a), "r"(r0), "r"(r1), "r"(r2), "r"(r3) : "memory");
}
__device__ __forceinline__ uint32_t and3(uint32_t a, uint32_t b, uint32_t c) {
    uint32_t r; asm("lop3.b32 %0, %1, %2, %3, 0x80;" : "=r"(r) : "r"(a), "r"(b), "r"(c)); return r;
}
__device__ __forceinline__ void red_mem(void* p, uint32_t x, uint32_t y, uint32_t z, uint32_t w, void* q, uint32_t e, bool c) {
    asm volatile("{.reg .pred p; setp.ne.u32 p, %7, 0; red.relaxed.gpu.global.add.noftz.v4.bf16x2 [%0], {%1,%2,%3,%4}; @p red.relaxed.gpu.global.add.noftz.bf16x2 [%5], %6;}"
                 ::"l"(p), "r"(x), "r"(y), "r"(z), "r"(w), "l"(q), "r"(e), "r"((uint32_t)c) : "memory");
}
__device__ __forceinline__ void stg4_if(bool c, void* p, uint32_t x) {
    asm volatile("{.reg .pred p; setp.ne.u32 p, %2, 0; @p st.relaxed.gpu.global.v4.u32 [%0], {%1,%1,%1,%1};}" ::"l"(p), "r"(x), "r"((uint32_t)c) : "memory");
}

__device__ __forceinline__ void h_load(uint32_t sb, const uint8_t* hsrc, int pass, uint32_t rank, uint32_t rot) {
    const uint8_t* src = hsrc + (size_t)pass * 65536;
    const uint32_t bar = sb + SM_BAR + 8 * (B_HB + (pass & 1)), dst = sb + SM_HB + (pass & 1) * 65536 + rank * 4 * HBK;
    e_expect(bar, 32768);
#pragma unroll 1
    for (int i = 0; i < H_PIECES; i++) {
        const uint32_t o = ((i + rot) & (H_PIECES - 1)) * (16384 / H_PIECES);
        asm volatile("{.reg .pred p; elect.sync _|p, 0xffffffff;\n"
                     " @p cp.async.bulk.shared::cluster.global.mbarrier::complete_tx::bytes.multicast::cluster [%0], [%1], %4, [%2], %3;}"
                     ::"r"(dst + o + (o >> 12) * 1024), "l"(src + o), "r"(bar), "h"((uint16_t)3), "n"(16384 / H_PIECES) : "memory");
    }
}
__device__ __forceinline__ uint4 ldg_b128(const void* p) {
    uint4 v;
    asm volatile("{.reg .b128 t; .reg .b64 a, b; ld.relaxed.gpu.global.b128 t, [%4]; mov.b128 {a, b}, t; mov.b64 {%0,%1}, a; mov.b64 {%2,%3}, b;}"
                 : "=r"(v.x), "=r"(v.y), "=r"(v.z), "=r"(v.w) : "l"(p) : "memory");
    return v;
}
__device__ __forceinline__ void stg_b128_if(bool c, void* p, uint32_t x, uint32_t y, uint32_t z, uint32_t w) {
    asm volatile("{.reg .pred p; setp.ne.u32 p, %5, 0; @p st.relaxed.gpu.global.v4.u32 [%0], {%1,%2,%3,%4};}"
                 ::"l"(p), "r"(x), "r"(y), "r"(z), "r"(w), "r"((uint32_t)c) : "memory");
}
__device__ __forceinline__ float pretag(float x, uint32_t add, uint32_t keep) { return __uint_as_float((__float_as_uint(x) + add) & keep); }

template <class F, class G>
__device__ __forceinline__ void softmax_rows(uint32_t src, uint32_t dst, uint32_t g16, int row0, F ready, G mid) {
    const uint32_t u = (g16 >> 7) & 3, e = ((g16 >> 9) << 3) | ((g16 >> 4) & 7);
    uint32_t se = src + e * 8, su = se + u * 1088, d0 = dst + e * 16 + u * 4, d1 = dst + 512 + e * 4;
    int vis = row0 + (e >> 2) - 2 * (e & 3) - 8 * u;
    asm volatile("" : "+r"(se), "+r"(su), "+r"(d0), "+r"(d1), "+r"(vis));
    ready();
    const float2 p0 = lds2f(su), p1 = lds2f(su + 256), p2 = lds2f(su + 512), p3 = lds2f(su + 768);
    const float2 m0 = lds2f(se + 4352), m1 = lds2f(se + 4352 + 256), m2 = lds2f(se + 4352 + 512), m3 = lds2f(se + 4352 + 768);
    float a0 = (p0.x + p1.x) + (p2.x + p3.x), a1 = (p0.y + p1.y) + (p2.y + p3.y);
    const float a2 = (m0.x + m1.x) + (m2.x + m3.x), a3 = (m0.y + m1.y) + (m2.y + m3.y);
    if (vis < 0) a0 = -1e9f / 0.08838834764831845f;
    if (vis < 1) a1 = -1e9f / 0.08838834764831845f;
    int k = __float_as_int(fmaxf(fmaxf(a0, a1), fmaxf(a2, a3)));
    k ^= (k >> 31) & 0x7fffffff;
    const bool hi = g16 & 64;
    const int k0 = __reduce_max_sync(~0u, hi ? INT_MIN : k), k1 = __reduce_max_sync(~0u, hi ? k : INT_MIN);
    mid();
    k = hi ? k1 : k0;
    const float m = __int_as_float(k ^ ((k >> 31) & 0x7fffffff));
    const float sl2 = 0.08838834764831845f * 1.4426950408889634f, mb = -m * sl2;
    sts1(d0, pack2(ex2(fmaf(a0, sl2, mb)), ex2(fmaf(a1, sl2, mb))));
    sts1(d1, pack2(ex2(fmaf(a2, sl2, mb)), ex2(fmaf(a3, sl2, mb))));
}

__device__ __forceinline__ uint32_t pack_h2(float lo, float hi) {
    uint32_t r; asm("cvt.rn.satfinite.f16x2.f32 %0, %1, %2;" : "=r"(r) : "f"(hi), "f"(lo)); return r;
}
__device__ __forceinline__ float2 unpack_h2(uint32_t u) {
    float2 r; asm("{.reg .b16 l, h; mov.b32 {l, h}, %2; cvt.f32.f16 %0, l; cvt.f32.f16 %1, h;}" : "=f"(r.x), "=f"(r.y) : "r"(u)); return r;
}
__device__ __forceinline__ uint32_t add_h2(uint32_t a, uint32_t b) { uint32_t r; asm("add.rn.f16x2 %0, %1, %2;" : "=r"(r) : "r"(a), "r"(b)); return r; }
__device__ __forceinline__ uint32_t max_h2(uint32_t a, uint32_t b) { uint32_t r; asm("max.f16x2 %0, %1, %2;" : "=r"(r) : "r"(a), "r"(b)); return r; }
struct U2 { uint32_t x, y; };
__device__ __forceinline__ U2 ldg_u2(const void* p) {
    U2 v; asm volatile("{.reg .b64 t; ld.relaxed.gpu.global.b64 t, [%2]; mov.b64 {%0, %1}, t;}" : "=r"(v.x), "=r"(v.y) : "l"(p) : "memory"); return v;
}
constexpr int POLL_LIMIT = 1 << 16;
constexpr float SM_L2E = 0.08838834764831845f * 1.4426950408889634f;
template <int V> struct IC { static constexpr int value = V; };
typedef unsigned long long u64;
__device__ __forceinline__ u64 ldg_u64(const void* p) { u64 v; asm volatile("ld.relaxed.gpu.global.b64 %0, [%1];" : "=l"(v) : "l"(p) : "memory"); return v; }
__device__ __forceinline__ void rec_main(uint32_t sb, const CUtensorMap* tWo, uint8_t* arena, int role, int hinfo, int wg, uint32_t zero, const Delays& dly) {
    const int hA = hinfo & 255;
    const int tid = threadIdx.x, t = tid & 127, lane = tid & 31, wi = t >> 5;
    const uint32_t bars = sb + SM_BAR;
    const int head = role >> 2, qd = role & 3, j = blockIdx.x & 1, kh = role & 1;
    const uint32_t mypar = head >= hA;
    const uint32_t wu = __reduce_max_sync(~0u, wi);
    const bool warp0 = wu == 0, warp1 = wu == 1;
    const uint8_t* hsrc = (const uint8_t*)g_himg + kh * 32768 + j * 16384;
    auto tokbase = [&](int ty) { return ((ty + 1) << 21) + blk(lb_tok(head), mypar ^ ((hinfo >> (8 + ty)) & 1)); };
    const uint32_t tbw = tokbase(wg), tbq = tokbase(0) + (qd >> 1) * 2048 + ((qd & 1) + wu) * 256;
    uint32_t w[32 - NL][4];
    const uint32_t frow = ((lane >> 4) * 8 + (lane & 7)) * 128, fx = ((lane >> 3) & 1) ^ (lane & 7);
    const uint32_t wl0 = sb + wg * 65536 + frow + ((fx ^ (2 * wi)) << 4);
    uint32_t g16 = opaque(t * 16);
    auto G16 = [&]() { asm volatile("" : "+r"(g16)); return g16; };
    const uint32_t sbl = sb - wu * 512;
    const uint32_t xso = blk(lb_x2(head), mypar), cu = kh * 2048 + (2 * j + (wu >> 1)) * 512;
    const uint32_t u_xo = xso + wg * 16384 + (wu & 1) * 2048 + (cu >> 1) - wu * 256, u_to = tbw + (wu & 1) * 16384 + cu - wu * 512;
    {
        uint8_t* pp = arena + (tbw + (1 << 20) + j * 16384 + (kh ^ 1) * 2048 + g16);
        stg_rlx4(pp, 0, 0, 0, 0);
        stg_rlx4(pp + 32768, 0, 0, 0, 0);
        stg_rlx4(arena + (u_to + g16), 0, 0, 0, 0);
        stg_rlx2(arena + (u_xo + (g16 >> 1)), 0, 0);
    }
    {
        if (wg > 0) wait_count_w(&g_tick[32 + (lane & 3) * 8], 1);
        if (wg == 1) asm volatile("fence.proxy.async.global;" ::: "memory");
#pragma unroll 1
        for (int i = 0; i < 4; i++) mbar_wait_w(bars + 8 * (B_W + (wg == 2 ? 8 + i : 2 * i + wg)), 0);
#pragma unroll
        for (int p = NL; p < 32; p++) ldsm4t(w[p - NL], wl0 + p * 2048);
        fence_async_smem();
        bar_sync(wg < 2 ? NB_WG : NB_X2, wg < 2 ? 256 : 128);
        if (wg == 2 && wu < 3) {
            e_expect(bars + 8 * B_WO, 16384);
            e_tma2d(sb + SM_WO + wu * 16384, tWo, (wu >> 1) * 512 + qd * 128 + (wu & 1) * 64, head * DH, bars + 8 * B_WO);
            e_tma2d(sb + SM_WO + wu * 16384 + 8192, tWo, (wu >> 1) * 512 + qd * 128 + (wu & 1) * 64, head * DH + 64, bars + 8 * B_WO);
        }
        if (wg == 1 && warp0) {
            if (lane == 0) mbar_arrive_cluster(bars + 8 * B_HE, j ^ 1);
            mbar_wait_w(bars + 8 * B_HE, 0);
#pragma unroll 1
            for (int i = 0; i < 2; i++) h_load(sb, hsrc, i, j, head);
        }
    }
    const uint32_t mrow = wg < 2 ? mem_row(wu >> 1, wg * 2 + (wu & 1), qd) : mem_row(kh, wu, 0);
    const uint32_t u_m = mrow - wu * 512, u_e = mrow + 512 - wu * 64;
#define TAB(i) lds1(sb + SM_TAB + (i) * 512 + (G16() >> 2))
    {
        const uint32_t r8 = lane & 7;
        const uint32_t tb = sb + SM_TAB + wg * 1536 + t * 4, ma = sb + SM_HB + 4096 + r8 * 128;
        if (wg < 2) {
            sts1(tb, sb + SM_WO + wi * 16384 + frow + ((fx ^ (2 * wg)) << 4));
            sts1(tb + 512, wl0);
            sts1(tb + 1024, ma + (((lane >> 3) ^ r8) << 4));
        } else {
            sts1(tb, ma + (wi & 1) * HBK + ((((wi & 2) + (lane >> 4) * 4 + ((lane >> 3) & 1)) ^ r8) << 4));
            sts1(tb + 512, ((((wi & 2) + 4) ^ r8) << 4) + ((lane & 3) == 2 ? ma + 128 + ((wi & 1) + (lane >> 3) * 2) * HBK : sb + SM_HB - 128));
            sts1(tb + 1024, mem_row(role >> 6, (role >> 4) & 3, (role >> 2) & 3) + (lane < 8 ? qd * 128 + lane * 16 : 512 + qd * 32 + (lane & 1) * 16));
        }
    }
#define HB(ks) dadd(mkdesc(SB0 + SM_HB + ((ks) >> 2) * HBK + ((ks) & 3) * 32, 16, 1024, 1), hbo)
#define STEP_CONSTS                                                                                  \
    const uint32_t tag = (s & 1) ^ 1, ttag = ((s >> 1) & 1) ^ 1, tso = (s & 1) * 32768;              \
    G16();                            \
    const int p = s + 2, b = p & 1;                                                                  \
    uint32_t hbo = b * 4096, fz[5] = {0, 0, 0, 0, 0};                                                   \
    const uint32_t ftag = (((p - 1) >> 1) & 1) ^ 1, ptag = ((p >> 1) & 1) ^ 1;                       \
    const uint32_t pso = tbw + (1 << 20) + (b ^ 1) * 32768 + j * 16384 + kh * 2048;
#define SCHED_FENCE(i) fz[i] = clk32();
#define FZ ((fz[0] | fz[1] | fz[2] | fz[3] | fz[4]) & zero)
#define BLOCK_FENCE asm volatile("pmevent 0;" ::: "memory");
    constexpr int GAP = 32 / NL;
#define l16 (sbl + g16)
#define g8 (g16 >> 1)
    uint4 u, v;
    uint8_t *pdst, *fdst;
    auto tok_pack = [&](int ty, const float* acc, uint32_t ftag, uint32_t ptag, bool later = false) {
        const bool tg = ty == 2 || !(g16 & 64);
        const uint32_t add = tg ? (ftag ^ 1) << 16 : 0u, keep = tg ? 0xfffe0000u : ~0u;
        const uint32_t add1 = ty == 2 ? 0u : add, keep1 = ty == 2 ? ~0u : keep;
        const uint32_t add2 = ty == 0 ? add : 0u, keep2 = ty == 0 ? keep : ~0u;
        v = {pack2(pretag(acc[0], add, keep), pretag(acc[1], add1, keep1)), pack2(acc[2], acc[3]),
             pack2(pretag(acc[4], add2, keep2), pretag(acc[5], add2, keep2)), pack2(acc[6], acc[7])};
        if (ty < 2) { v.x = movm(v.x); v.z = movm(v.z); v.y = movm(v.y); v.w = movm(v.w); }
        u = {settag(pack2(pretag(acc[8], (ptag ^ 1) << 16, 0xfffe0000u), acc[9]), ptag), pack2(acc[10], acc[11]), pack2(acc[12], acc[13]), pack2(acc[14], acc[15])};
        if (later) return;
        v.x = settag(v.x, ftag);
        if (ty == 0) v.z = settag(v.z, ftag);
    };

#pragma unroll 1
    for (int s = -2; s < 0; s++) {
        STEP_CONSTS
        (void)tag; (void)ttag; (void)tso; (void)fz;
        float acc[16];
        mbar_wait_w(bars + 8 * (B_HB + b), 0);
        wg_fence();
#pragma unroll
        for (int i = 0; i < 32; i++) {
            if (i < NL) wgmma_ss32(acc, dadd(mkdesc(SB0 + i * 2048, 8192, 1024, 1), wg * 4096), HB(i), i != 0);
            else wgmma_rs32(acc, w[i < NL ? 0 : i - NL], HB(i), 1);
        }
        wg_commit();
        uint4 pa = {0, 0, 0, 0};
        int it = 0;
#pragma unroll 1
        while ((p > 0) & any_bit0(pa.x ^ ftag) & (++it < POLL_LIMIT)) pa = ldg_b128(arena + (pso + g16));
        pdst = arena + ((pso ^ (32768 + 2048)) + G16());
        fdst = arena + ((b ^ 1) * 32768 + u_to + g16);
        wg_wait<0>();
#pragma unroll
        for (int k = 0; k < 4; k++) { acc[2 * k] += bflo((&pa.x)[k]); acc[2 * k + 1] += bfhi((&pa.x)[k]); }
        tok_pack(wg, acc, ftag, ptag);
        stg_b128_if(true, pdst, u.x, u.y, u.z, u.w);
        stg_b128_if(p > 0 && wg, fdst, v.x, v.y, v.z, v.w);
        if (p > 0 && !wg) { stg_rlx2(fdst - lane * 8, v.x, v.y); stg_rlx2(fdst - lane * 8 + 256, v.z, v.w); }
        if (p == 0) {
            if (wg != 1) bar_arrive(NB_C, 288);
        }
    }
    if (wg == 1 && warp0) {
        wait_count_w(&g_tick[32 + (lane & 3) * 8], 2);
        asm volatile("fence.proxy.async.global;" ::: "memory");
        bar_sync(NB_C, 288);
        if (g16 == 0) mbar_arrive_cluster(bars + 8 * B_HE, j ^ 1);
        mbar_wait_w(bars + 8 * B_HE, 1);
        h_load(sb, hsrc, 2, j, head);
    }

    auto qk_loop = [&](auto wgc) {
        constexpr int WG = decltype(wgc)::value;
        uint32_t w0[NL][4], lm0;
        auto w0_load = [&]() {
            const uint32_t wl = TAB(WG * 3 + 1);
            lm0 = TAB(WG * 3 + 2);
#pragma unroll
            for (int k = 0; k < NL; k++) ldsm4t(w0[k], wl + k * 2048);
        };
        const uint32_t wlo = WG * 65536 - SM_WO - wu * 16384, wlx = __reduce_max_sync(~0u, (wi ^ WG) << 5);
        uint32_t tq0, lm, lm1, dx2 = dly.x2;
        auto proj_pre = [&](int s) {
            uint32_t wz0 = zero;
#pragma unroll
            for (int k = 0; k < NL; k += 2) wz0 = and3(wz0, w0[k][0], w0[k + 1 < NL ? k + 1 : k][0]);
            lm = lm0 + (s & 1) * 65536 + wz0; lm1 = lm ^ 64;
            asm volatile("" : "+r"(lm), "+r"(lm1));
        };
        auto proj = [&](int s, auto mid) {
            bar_sync(NB_MEM, 384);
            float c[4][4];
            constexpr int PD = WG ? PD1 : PD0;
            uint32_t bf[16][4], tq1;
#pragma unroll
            for (int it = 0; it < PD; it++) ldsm4(bf[it], (it & 1 ? lm1 : lm) + (it >> 1) * HBK);
            mid(-1);
#pragma unroll
            for (int it = 0; it < 16; it++) {
                const uint32_t* bfr = bf[it];
                if (it + PD < 16) ldsm4(bf[it + PD < 16 ? it + PD : 0], ((it + PD) & 1 ? lm1 : lm) + ((it + PD) >> 1) * HBK);
                const uint32_t* wa = 2 * it < NL ? w0[2 * it < NL ? 2 * it : 0] : w[2 * it < NL ? 0 : 2 * it - NL];
                const uint32_t* wb = 2 * it + 1 < NL ? w0[2 * it + 1 < NL ? 2 * it + 1 : 0] : w[2 * it + 1 < NL ? 0 : 2 * it + 1 - NL];
                float *ca = c[(2 * it) & 3], *cb = c[(2 * it + 1) & 3];
                if (it < 2) { mma16816z(ca, wa, bfr[0], bfr[1]); mma16816z(cb, wb, bfr[2], bfr[3]); }
                else { mma16816(ca, wa[0], wa[1], wa[2], wa[3], bfr[0], bfr[1]); mma16816(cb, wb[0], wb[1], wb[2], wb[3], bfr[2], bfr[3]); }
                mid(it);
                if (it == 15) { tq1 = clk32(); bar_arrive(NB_QK, 384); }
            }
            const uint32_t xo = u_xo + (G16() >> 1);
            float r[4];
#pragma unroll
            for (int e = 0; e < 4; e++) {
                constexpr float SH = SM_L2E / 64;
                r[e] = WG ? (c[0][e] + c[1][e]) + (c[2][e] + c[3][e]) : fmaf(c[2][e] + c[3][e], SH, (c[0][e] + c[1][e]) * SH);
            }
            const uint32_t r0 = pack2(r[0], r[1]), r1 = pack2(r[2], r[3]);
            const uint32_t m0 = movm(r0), m1 = movm(r1);
            tq0 = clk32();
            stg_rlx2(arena + xo, settag(m0, (s & 1) ^ 1), m1);
            tq0 += tq1 & zero;
        };
        w0_load();
        proj_pre(0);
        if (WG == 1) bar_sync(NB_P, 256);
        proj(0, [](int) {});
        if (WG == 0) mbar_wait_w(bars + 8 * B_WO, 0);
#pragma unroll 1
        for (int s = 0;; s++) {
            STEP_CONSTS
            uint4 pa;
            float acc[16];
            auto acc_init = [&]() {
#pragma unroll
                for (int k = 0; k < 4; k++) { acc[2 * k] = bflo((&pa.x)[k]); acc[2 * k + 1] = bfhi((&pa.x)[k]); acc[8 + 2 * k] = __uint_as_float((&pa.x)[k] & zero); acc[9 + 2 * k] = __uint_as_float(~(&pa.x)[k] & zero); }
            };
            uint32_t wf[NPF][4], a3;
#define WF(f) ((a3 ^ (((f) & 1) * 64)) + ((f) >> 1) * 2048)
            if (WG == 1) {
                float sc[5][4];
                uint32_t sx0 = sb + SM_SX - wu * (2560 - 16) + G16() * 5;
                asm volatile("" : "+r"(sx0));
                int it = 0;
                bool bad;
#pragma unroll 1
                do {
                    uint4 kf[2][2];
                    U2 qf[2], x[8];
                    const uint32_t gz = g16 | (it & zero);
                    const uint8_t *ts = arena + (tso + tbw + gz), *tq = arena + (tso + tbq + (gz >> 1)), *xp = arena + (xso + (gz >> 1));
#pragma unroll
                    for (int a = 0; a < 4; a++) kf[a >> 1][a & 1] = ldg_b128(ts + (a >> 1) * 16384 + (a & 1) * 2048);
                    spin_until(tq0, dx2 - 100);
#pragma unroll
                    for (int a = 0; a < 2; a++) qf[a] = ldg_u2(tq + a * 16384);
                    spin_until(tq0, dx2);
#pragma unroll
                    for (int i = 0; i < 8; i++) x[i] = ldg_u2(xp + (i >> 2) * 16384 + (i & 3) * 1024);
                    const uint32_t q0[4] = {hadd2(x[0].x, x[1].x), qf[0].x, hadd2(x[0].y, x[1].y), qf[0].y};
                    const uint32_t q1[4] = {hadd2(x[2].x, x[3].x), qf[1].x, hadd2(x[2].y, x[3].y), qf[1].y};
                    const uint32_t bt = ((qf[0].x ^ ttag) | (qf[1].x ^ ttag)) | ((kf[0][0].x ^ ttag) | (kf[0][1].x ^ ttag)) | ((kf[1][0].x ^ ttag) | (kf[1][1].x ^ ttag));
                    uint32_t bx = 0;
#pragma unroll
                    for (int i = 0; i < 8; i += 2) bx |= (x[i].x ^ tag) | (x[i + 1].x ^ tag);
                    mma16816z(sc[0], q0, kf[0][0].x, kf[0][0].y);
                    mma16816z(sc[1], q0, kf[0][0].z, kf[0][0].w);
                    mma16816z(sc[2], q0, kf[0][1].x, kf[0][1].y);
                    mma16816z(sc[3], q0, kf[0][1].z, kf[0][1].w);
                    mma16816z(sc[4], q0, hadd2(x[4].x, x[5].x), hadd2(x[4].y, x[5].y));
                    bad = any_bit0(bt | bx) & (++it < POLL_LIMIT);
                    mma16816(sc[0], q1[0], q1[1], q1[2], q1[3], kf[1][0].x, kf[1][0].y);
                    mma16816(sc[1], q1[0], q1[1], q1[2], q1[3], kf[1][0].z, kf[1][0].w);
                    mma16816(sc[2], q1[0], q1[1], q1[2], q1[3], kf[1][1].x, kf[1][1].y);
                    mma16816(sc[3], q1[0], q1[1], q1[2], q1[3], kf[1][1].z, kf[1][1].w);
                    mma16816(sc[4], q1[0], q1[1], q1[2], q1[3], hadd2(x[6].x, x[7].x), hadd2(x[6].y, x[7].y));
                } while (bad);
                sts4(sx0, pack_h2(sc[0][0], sc[0][1]), pack_h2(sc[1][0], sc[1][1]), pack_h2(sc[2][0], sc[2][1]), pack_h2(sc[3][0], sc[3][1]));
                sts1(sx0 + 64 - wu * 12, pack_h2(sc[4][0], sc[4][1]));
                bar_arrive(NB_X1, 384);
                if (it > 1 && s > 1) dx2 += dly.more2;
                auto tok_sts = [&]() {
#pragma unroll
                    for (int n = 0; n < 5; n++) sts2(sb + SM_SX + 2560 + g8 + n * 1088, sc[n][2], sc[n][3]);
                };
                a3 = TAB(WG * 3);
                if (s == 0) mbar_wait_w(bars + 8 * B_WO, 0);
                softmax_rows(sb + SM_SX + 2560, sb + SM_PX + 1024, g16 | (clk32() & zero), qd * 8, [&]() { BLOCK_FENCE tok_sts(); bar_sync(NB_PX, 128); }, [&]() {
                    BLOCK_FENCE
#pragma unroll
                    for (int f = 0; f < NE1; f++) ldsm4t(wf[f], WF(f));
                    BLOCK_FENCE
                });
            } else {
                a3 = TAB(WG * 3);
                if (warp1 && (s & 3) == 1) asm volatile("fence.proxy.async.global;" ::: "memory");
                spin_until(tq0, dly.pa);
                uint4 x, y;
                int it = 0;
#pragma unroll 1
                do { x = ldg_b128(arena + (pso + g16)); y = ldg_b128(arena + (pso + tokbase(1) - tokbase(0) + g16)); }
                while ((p <= NSEG) & any_bit0(xor_or(x.x, y.x, ftag)) & (++it < POLL_LIMIT));
                sts4(sb + SM_PA + g16, x.x, x.y, x.z, x.w);
                sts4(sb + SM_PA + 2048 + g16, y.x, y.y, y.z, y.w);
                bar_sync(NB_X1, 384);
                if (g16 < 32) asm volatile("red.relaxed.gpu.global.max.u32 [%0], %1; red.relaxed.gpu.global.add.u32 [%0+4], 1;"
                                                    ::"l"(arena + ((blk(LB_TIME, 0) ^ (g16 << 8)) + qd * 1024 + (tq0 & zero))), "r"(gtime()) : "memory");
                __syncwarp();
                const uint32_t tx = clk32();
                spin_until(tx, dly.w2);
            }
#pragma unroll
            for (int f = WG ? NE1 : 0; f < NPF; f++) ldsm4t(wf[f], WF(f));
            if (s + 1 == NSEG) { bar_arrive(NB_X2, 384); break; }
            const uint32_t oa = l16 + SM_OX, slot = mem_slot(s + 1);
            float c[4][4];
            uint32_t ob[4][4];
            BLOCK_FENCE
            bar_sync(NB_X2, 384);
            ldsm4t(ob[0], oa);
            ldsm4t(ob[1], oa + 512);
            SCHED_FENCE(0)
#pragma unroll
            for (int f = 0; f < 16; f++) {
                const uint32_t *a = wf[f % NPF], *o = ob[f >> 2] + (f & 2);
                if (f < 4) mma16816z(c[f], a, o[0], o[1]);
                else mma16816(c[f & 3], a[0], a[1], a[2], a[3], o[0], o[1]);
                if (f == 3) ldsm4t(ob[2], oa + 1024);
                if (f == 5) { ldsm4t(ob[3], oa + 1536); if (NPF < 16) ldsm4t(wf[0], WF(NPF)); }
                if (f == 7) {
#pragma unroll
                    for (int k = NPF + 1; k < 16; k++) ldsm4t(wf[k - NPF], WF(k));
                }
                if (f == 3 || f == 5 || f == 7) SCHED_FENCE(f / 2)
                if (f == 11) {
#pragma unroll
                    for (int k = NL - W0_E; k < NL; k++) ldsm4t(w0[k], (a3 ^ wlx) + wlo + k * 2048);
                    SCHED_FENCE(4)
                }
            }
            const float last = c[1][3] + c[3][3], one = __uint_as_float(CNT1 << 16);
            red_mem(arena + (u_m + slot + G16()), pack2(c[0][0] + c[2][0], c[0][1] + c[2][1]), pack2(c[0][2] + c[2][2], c[0][3] + c[2][3]),
                    pack2(c[1][0] + c[3][0], c[1][1] + c[3][1]), pack2(c[1][2] + c[3][2], g16 & 16 ? one : last),
                    arena + (u_e + slot + ((g16 >> 3) & ~3u)), pack2(last, one), g16 & 16);
            hbo += FZ;
            constexpr int NS = NL - W0_RS, GS = (32 - NL + NS) / NS;
            BLOCK_FENCE
#pragma unroll
            for (int k = NL - W0_E - 1; k >= 0; k--) ldsm4t(w0[k], (a3 ^ wlx) + wlo + k * 2048);
            lm0 = TAB(WG * 3 + 2);
            if (WG == 1) pa = lds4(sb + SM_PA + 2048 + g16);
            if (WG == 0) {
                bar_arrive(NB_WIN, 384);
                pa = lds4(sb + SM_PA + g16);
                acc_init();
                asm volatile("" : F16(acc, 0));
                BLOCK_FENCE
            }
            wg_fence();
            bar_sync(WG ? NB_WIN : NB_B, WG ? 384 : 256);
#pragma unroll
            for (int i = 0; i < 32; i++) {
                const int k = i / GS;
                if (i >= 32 - NL + NS) wgmma_rs32(acc, w0[i < 32 - NL + NS ? 0 : i - 32 + NL], HB(i - 32 + NL), 1);
                else if (i % GS == GS - 1 && k < NS) wgmma_ss32(acc, mkdesc(SB0 + WG * 65536 + k * 2048, 8192, 1024, 1), HB(k), 1);
                else wgmma_rs32(acc, w[i - (k < NS ? k : NS)], HB(NL + i - (k < NS ? k : NS)), WG == 0 || i);
                if (WG == 1 && i == G_AT) bar_arrive(NB_B, 256);
                if (WG == 1 && i == 31 - NL + NS) wg_fence();
            }
            wg_commit();
            BLOCK_FENCE
            if (WG == 1 && warp0 && !(s & 3)) wait_count_w(&g_tick[32 + ((G16() >> 4) & 3) * 8], min((s + 1) / 4 + 3, 17));
            auto tok_store = [&](int m) {
                if (m & 1) {
                    if (WG) stg_b128_if(true, arena + ((b ^ 1) * 32768 + u_to + G16()), v.x, v.y, v.z, v.w);
                    else {
                        uint8_t* d = arena + ((b ^ 1) * 32768 + u_to + wu * 256 + (G16() >> 1));
                        stg_rlx2(d, v.x, v.y); stg_rlx2(d + 256, v.z, v.w);
                    }
                }
                if (m & 2) stg_b128_if(p < NSEG, arena + ((pso ^ (32768 + 2048)) + G16()), u.x, u.y, u.z, u.w);
            };
            if (WG == 0) proj_pre(s + 1);
            BLOCK_FENCE
            wg_wait<0>();
            if (WG == 0) {
                asm volatile("" : F16(acc, 0));
                proj(s + 1, [&](int it) {
                    if (it < 0) {
                        SCHED_FENCE(0)
                        asm volatile("" : F16(acc, 0));
                        tok_pack(WG, acc, ftag, ptag, true);
                        tok_store(2);
                        SCHED_FENCE(1)
                    }
                    if (it == QS_AT) { SCHED_FENCE(2) v.x = settag(v.x, ftag); v.z = settag(v.z, ftag); tok_store(1); SCHED_FENCE(3) }
                });
                tq0 += (fz[0] | fz[1] | fz[2] | fz[3]) & zero;
            } else {
#pragma unroll
                for (int k = 0; k < 4; k++) { acc[2 * k] += bflo((&pa.x)[k]); acc[2 * k + 1] += bfhi((&pa.x)[k]); }
                tok_pack(WG, acc, ftag, ptag);
                proj_pre(s + 1);
                asm volatile("" : "+r"(u.x), "+r"(u.y), "+r"(u.z), "+r"(u.w), "+r"(v.x), "+r"(v.y), "+r"(v.z), "+r"(v.w));
                BLOCK_FENCE
                bar_sync(NB_P, 256);
                tok_store(3);
                proj(s + 1, [](int) {});
            }
        }
    };
    if (wg == 0) {
        qk_loop(IC<0>());
    } else if (wg == 1) {
        qk_loop(IC<1>());
    } else {
        const uint32_t ONES = 0x3f803f80u, u_o = qd * 65536 + head * 2048 + wu * 384;
        uint32_t tw = 0, dl = 0, dbase = kh == mypar ? dly.near : dly.far, dst0, dx0;
        dst0 = TAB(6); dx0 = TAB(7);
        uint32_t ov[4] = {0, 0, 0, 0};
        auto o_store = [&](int s) {
            uint8_t* od = (uint8_t*)g_O + (uint32_t)(s * (32 * NH * DH * 2) + u_o + (G16() >> 2));
#pragma unroll
            for (int a = 0; a < 4; a++) stg_rlx1(od + a * 128, ov[a]);
        };
        uint4 vf[2][2], pa;
        auto tok_fetch = [&](int s) {
            const uint8_t* ts = arena + ((s & 1) * 32768 + tbw + g16);
#pragma unroll
            for (int a = 0; a < 4; a++) vf[a >> 1][a & 1] = ldg_b128(ts + (a >> 1) * 16384 + (a & 1) * 2048);
            pa = ldg_b128(arena + (tbw + (1 << 20) + (~s & 1) * 32768 + j * 16384 + kh * 2048 + g16));
        };
        tok_fetch(0);
#pragma unroll 1
        for (int s = 0;; s++) {
            STEP_CONSTS
#define VFBAD ((vf[0][0].x ^ ttag) | (vf[0][1].x ^ ttag) | (vf[1][0].x ^ ttag) | (vf[1][1].x ^ ttag))
#define TOKBAD (VFBAD | (p <= NSEG ? pa.x ^ ftag : 0))
            {
                const uint32_t dst = dst0 + b * 65536, dx = dx0 + b * 65536;
                const uint8_t *ms = arena + (u_m + mem_slot(s) + g16), *me = arena + (u_e + mem_slot(s) + ((g16 >> 3) & ~3u));
                uint32_t em = g16 & 16 ? 0u : ~0u;
                asm volatile("" : "+l"(ms), "+l"(me), "+r"(em));
                spin_until(tw, dl);
                int it = 0;
                bool bad;
#pragma unroll 1
                do {
                    uint4 m[4];
                    uint32_t x[4];
#pragma unroll
                    for (int i = 0; i < 4; i++) m[i] = ldg_rlx4(ms + i * 1024);
#pragma unroll
                    for (int i = 0; i < 4; i++) x[i] = ldg_rlx1(me + i * 1024);
#pragma unroll
                    for (int i = 0; i < 3; i++) {
                        stsm4t(dst + i * 2 * HBK, m[i].x, m[i].y, m[i].z, m[i].w);
                        if (i == 1) asm volatile("{.reg .pred p; setp.eq.s32 p, %0, 0; @p bar.arrive %1, 256;}" ::"r"(it), "n"(NB_P) : "memory");
                    }
                    uint32_t c = m[0].w & m[1].w, r, msk = ~(it << 16) & CNT_ALL << 16;
                    asm volatile("" : "+r"(c), "+r"(msk));
                    SCHED_FENCE(1)
                    stsm4t(dst + 6 * HBK, m[3].x, m[3].y, m[3].z, m[3].w);
                    stsm4t(dx, x[0], x[1], x[2], x[3]);
                    asm volatile("{.reg .pred p, q; .reg .b32 t, u; lop3.b32 t, %1, %2, %3, 0x80; lop3.b32 u, %4, %5, %6, 0x80; lop3.b32 t, t, %8, %7, 0xa8;\n"
                                 " lop3.b32 t, t, u, %9, 0x2a; setp.ne.u32 p, t, 0; vote.sync.any.pred q, p, 0xffffffff; @!q bar.arrive %10, 384; selp.u32 %0, 1, 0, q;}"
                                 : "=r"(r) : "r"(c), "r"(m[2].w), "r"(m[3].w), "r"(x[0]), "r"(x[1]), "r"(x[2]), "r"(x[3]), "r"(em), "r"(msk), "n"(NB_MEM) : "memory");
                    bad = r; it++;
                } while (bad);
                if (it > 1 && s > 1) dbase += dly.more;
            }
            o_store(max(s - 1, 0));
            fence_async_smem();
            hbo += fz[1] & zero;
            int it = 0;
#pragma unroll 1
            while (any_bit0(TOKBAD) & (++it < POLL_LIMIT)) tok_fetch(s + (it & zero));
            float acc[20];
#pragma unroll
            for (int k = 0; k < 4; k++) { acc[2 * k] = bflo((&pa.x)[k]); acc[2 * k + 1] = bfhi((&pa.x)[k]); acc[8 + 2 * k] = acc[9 + 2 * k] = acc[16 + k] = __uint_as_float(pa.x & zero); }
            if (p <= NSEG) mbar_wait_w(bars + 8 * (B_HB + b), (p >> 1) & 1);
            asm volatile("" : F16(acc, 0), F4(acc, 16));
            BLOCK_FENCE
            wg_fence();
            bar_sync(NB_QK, 384);
#pragma unroll
            for (int i = 0; i < 32; i++) {
                const int k = i / GAP;
                if (i % GAP == GAP - 1 && k < NL) wgmma_ss40(acc, mkdesc(SB0 + 131072 + k * 2048, 8192, 1024, 1), HB(k), 1);
                else wgmma_rs40(acc, w[i - (k < NL ? k : NL)], HB(NL + i - (k < NL ? k : NL)), 1);
            }
            wg_commit();
            uint8_t* vo = arena + (u_xo + (G16() >> 1));
            pdst = arena + ((pso ^ (32768 + 2048)) + G16());
            fdst = arena + ((b ^ 1) * 32768 + u_to + g16);
            BLOCK_FENCE
            wg_wait<0>();
            stg_rlx2(vo, settag(pack2(acc[16], acc[17]), tag), pack2(acc[18], acc[19]));
            const uint32_t tv = clk32();
            tok_pack(2, acc, ftag, ptag);
            stg_b128_if(p <= NSEG, fdst, v.x, v.y, v.z, v.w);
            stg_b128_if(p < NSEG, pdst, u.x, u.y, u.z, u.w);
            const uint8_t* xp = arena + (xso + 32768 + (G16() >> 1));
            const uint32_t sxa = sb + SM_SX - wu * 2560 + G16() * 5;
            uint32_t sel[2];
            {
                const uint32_t q = (G16() >> 4 ^ g16 >> 6 & 1) & 3;
                sel[0] = q == 0 ? 0x3c00 : 0; sel[1] = q == 2 ? 0x3c00 : 0;
                asm volatile("" : "+r"(sel[0]), "+r"(sel[1]));
            }
            uint32_t xv[4], gt = 0;
            auto pv = [&](uint32_t p0, uint32_t p1, uint32_t p2, uint32_t p3, uint32_t p4, auto getv, auto done) {
                float oc[2][4], lc[4] = {0.f, 0.f, 0.f, 0.f};
                mma16816(lc, ONES, ONES, ONES, ONES, p0, p1);
                mma16816z(oc[0], &vf[0][0].x, p0, p1);
                mma16816z(oc[1], &vf[1][0].x, p0, p1);
                mma16816(lc, ONES, ONES, ONES, ONES, p2, p3);
                mma16816(oc[0], vf[0][1].x, vf[0][1].y, vf[0][1].z, vf[0][1].w, p2, p3);
                mma16816(oc[1], vf[1][1].x, vf[1][1].y, vf[1][1].z, vf[1][1].w, p2, p3);
                mma1688(lc, ONES, ONES, p4);
                getv();
                mma1688(oc[0], xv[0], xv[1], p4);
                mma1688(oc[1], xv[2], xv[3], p4);
                done(__float_as_uint(oc[0][0]) | __float_as_uint(oc[1][0]) | __float_as_uint(lc[0]));
                const float r0 = rcp_fast(lc[0]), r1 = rcp_fast(lc[1]);
                ov[0] = pack2(oc[0][0] * r0, oc[0][1] * r1); ov[1] = pack2(oc[0][2] * r0, oc[0][3] * r1);
                ov[2] = pack2(oc[1][0] * r0, oc[1][1] * r1); ov[3] = pack2(oc[1][2] * r0, oc[1][3] * r1);
            };
            bool bad;
            it = 0;
#pragma unroll 1
            do {
                U2 xr[4];
                asm volatile("{.reg .pred p; setp.eq.s32 p, %0, 0; @p bar.sync %1, 384;}" ::"r"(it), "n"(NB_X1) : "memory");
                uint4 sx[5];
#pragma unroll
                for (int i = 0; i < 5; i++) sx[i] = lds4(sxa + i * 16);
                if (it == 0) { gt = gtime(); tw = clk32(); }
                spin_until(tv, dly.v);
#pragma unroll
                for (int i = 0; i < 4; i++) xr[i] = ldg_u2(xp + i * 1024);
                uint32_t h[5], h0[4];
#pragma unroll
                for (int n = 0; n < 4; n++) h0[n] = add_h2((&sx[0].x)[n], (&sx[1].x)[n]);
#pragma unroll
                for (int n = 0; n < 4; n++) h[n] = add_h2(h0[n], add_h2((&sx[2].x)[n], (&sx[3].x)[n]));
                h[4] = add_h2(add_h2(sx[4].x, sx[4].y), add_h2(sx[4].z, sx[4].w));
                uint32_t hm = max_h2(max_h2(max_h2(h[0], h[1]), h[2]), max_h2(h[3], h[4]));
                float2 a[5];
                float mb;
                {
                    float d[2][4];
                    const uint32_t hs = __byte_perm(hm, hm, 0x1032);
#pragma unroll
                    for (int k = 0; k < 2; k++)
                        asm volatile("mma.sync.aligned.m16n8k8.row.col.f32.f16.f16.f32 {%0,%1,%2,%3},{%4,%5},{%6},{%7,%7,%7,%7};"
                                     : "=f"(d[k][0]), "=f"(d[k][1]), "=f"(d[k][2]), "=f"(d[k][3]) : "r"(hm), "r"(hs), "r"(sel[k]), "f"(0.f));
#pragma unroll
                    for (int n = 0; n < 5; n++) a[n] = unpack_h2(h[n]);
                    mb = -64.0f * fmaxf(fmaxf(fmaxf(d[0][0], d[0][1]), fmaxf(d[0][2], d[0][3])), fmaxf(fmaxf(d[1][0], d[1][1]), fmaxf(d[1][2], d[1][3])));
                }
                uint32_t pm[5];
#pragma unroll
                for (int n = 0; n < 5; n++) pm[n] = pack2(ex2(fmaf(a[n].x, 64.0f, mb)), ex2(fmaf(a[n].y, 64.0f, mb)));
                pv(pm[0], pm[1], pm[2], pm[3], pm[4], [&]() {
                    xv[0] = hadd2(xr[0].x, xr[1].x); xv[1] = hadd2(xr[0].y, xr[1].y);
                    xv[2] = hadd2(xr[2].x, xr[3].x); xv[3] = hadd2(xr[2].y, xr[3].y);
                }, [](uint32_t) {});
                bad = any_bit0((xr[0].x ^ tag) | (xr[1].x ^ tag) | (xr[2].x ^ tag) | (xr[3].x ^ tag)) & (++it < POLL_LIMIT);
                stsm4(sb + SM_OX + g16, ov[0], ov[1], ov[2], ov[3]);
            } while (bad);
            bar_sync(NB_X2, 384);
            BLOCK_FENCE
            U2 tv2 = {0, 0};
            const uint8_t* tp = arena + (blk(LB_TIME, mypar) + ((G16() << 6) & 0xc00));
            {
                const uint4 pp = lds4(l16 + SM_PX + 1024);
                const uint32_t p4 = lds1(sb + SM_PX + 512 + 1024 - wu * 128 + (G16() >> 2));
                tv2 = ldg_u2(tp);
                if (warp0 && s + 3 <= NSEG) h_load(sb, hsrc, s + 3, j, head);
                pv(pp.x, pp.y, pp.z, pp.w, p4, []() {}, [&](uint32_t r) { bar_arrive(NB_WIN + (r & zero), 384); });
            }
            dst0 = TAB(6); dx0 = TAB(7);
            const uint32_t zo = TAB(8);
            BLOCK_FENCE
            if (s + 1 == NSEG) break;
            asm volatile("" : "+r"(tv2.y));
            it = 0;
            uint32_t tm = __reduce_max_sync(~0u, tv2.y < 32 * (s + 1) ? ~0u : tv2.x);
#pragma unroll 1
            while ((tm == ~0u) & (++it < 16)) { tv2 = ldg_u2(tp); tm = __reduce_max_sync(~0u, tv2.y < 32 * (s + 1) ? ~0u : tv2.x); }
            const uint32_t e = tm - gt;
            tok_fetch(s + 1);
            stg4_if(g16 < 160, arena + (zo + mem_slot(s + 3)), 0);
            dl = dbase + (e > 4096 ? 0 : e * E_MUL >> 4);
        }
        o_store(NSEG - 1);
    }
}

struct RecMaps { CUtensorMap wq, wk, wv, wo, wmod, w3, w1; };
struct RecPtrs { const bf16 *x, *mem0, *c, *wmod, *w1, *w3; uint8_t* arena; uint32_t zero; const bf16 *w2, *w4, *wo; Delays dly; };

__device__ __forceinline__ float silu_bf(const bf16* c, int i) {
    const float v = __bfloat162float(c[i]);
    return bfround(__fdividef(v, 1.0f + __expf(-v)));
}
#define LN_FREE 6
#define LN_SEQ 0xcba6420987531ull
#define W_LATE 1000
#define W_OPEN 1400
__device__ __noinline__ uint32_t side_window_(const uint8_t* arena, uint32_t n);
#define side_window(arena, n) n = side_window_(arena, n)
__device__ __noinline__ void rec_ln(uint32_t sb, const bf16* x, const uint8_t* arena, int id, int r0) {
    int r1 = 32;
    uint32_t n = 0;
    const int tid = threadIdx.x, lane = tid & 31, wid = __reduce_max_sync(~0u, tid >> 5);
    const uint32_t ring = sb + wid * 8192 + lane * 16, coef = sb + SM_PRE;
    x += (id * 8 + wid) * 2 * DM + lane * 8;
#pragma unroll 1
    for (int r = r0 - 1; r < r1; r++) {
        if (r > 3) side_window(arena, n);
        if (r + 1 < r1) {
#pragma unroll
            for (int i = 0; i < 8; i++)
                asm volatile("cp.async.cg.shared.global [%0], [%1], 16;" ::"r"(ring + (~r & 1) * 4096 + i * 512), "l"(x + (r + 1) * 64 * DM + i * 256) : "memory");
        }
        asm volatile("cp.async.commit_group; cp.async.wait_group 1;" ::: "memory");
        if (r < r0) continue;
        const uint32_t src = ring + (r & 1) * 4096;
        float m[2] = {0.f, 0.f}, rs[2];
#pragma unroll 1
        for (int ps = 0; ps < 2; ps++) {
            float t[2][2] = {{0.f, 0.f}, {0.f, 0.f}};
#pragma unroll 1
            for (int i = 0; i < 2048; i += 512) {
#pragma unroll
                for (int h = 0; h < 2; h++) {
                    const uint4 u = lds4(src + h * 2048 + i);
#pragma unroll
                    for (int e = 0; e < 4; e++) {
                        const float a = bflo((&u.x)[e]) - m[h], c = bfhi((&u.x)[e]) - m[h];
                        t[h][0] = fmaf(a, ps ? a : 1.0f, t[h][0]); t[h][1] = fmaf(c, ps ? c : 1.0f, t[h][1]);
                    }
                }
            }
            rs[0] = t[0][0] + t[0][1]; rs[1] = t[1][0] + t[1][1];
#pragma unroll 1
            for (int o = 16; o; o >>= 1) { rs[0] += __shfl_xor_sync(~0u, rs[0], o); rs[1] += __shfl_xor_sync(~0u, rs[1], o); }
            if (!ps) { m[0] = rs[0] * (1.0f / DM); m[1] = rs[1] * (1.0f / DM); }
        }
        rs[0] = rsqrtf(rs[0] * (1.0f / DM) + 1e-5f); rs[1] = rsqrtf(rs[1] * (1.0f / DM) + 1e-5f);
        if (r == r0) {
#pragma unroll 1
            for (int i = tid; i < 2 * DM / 4; i += 256) {
                float t[4];
                int it = 0;
                uint32_t ok;
#pragma unroll 1
                do {
                    uint4 u[8];
#pragma unroll
                    for (int k = 0; k < 8; k++) u[k] = ldg_rlx4(g_modp + k * 2 * DM + i * 4);
                    ok = 1;
#pragma unroll
                    for (int k = 0; k < 32; k++) { const uint32_t w = (&u[k >> 2].x)[k & 3]; ok &= w; t[k & 3] = k < 4 ? __uint_as_float(w) : t[k & 3] + __uint_as_float(w); }
                } while (!__all_sync(~0u, ok) & (++it < SPIN_LIMIT));
                const float o = i >> 8;
                const uint32_t lo = pack2(t[0], t[1]), hi = pack2(t[2], t[3]);
                sts4f(coef + (i >> 8) * 4096 + (i & 1) * 2048 + ((i & 255) >> 1) * 16, bflo(lo) + o, bfhi(lo) + o, bflo(hi) + o, bfhi(hi) + o);
            }
            bar_sync(NB_FIN0, 256);
        }
        uint8_t* dst = (uint8_t*)g_himg + (r * 2 + (id >> 1)) * 65536 + (lane >> 3) * 4096 + wid * 256;
#pragma unroll 1
        for (int i = 0; i < 4; i++) {
            const uint32_t ca = coef + i * 512 + lane * 16;
            const float4 s0 = lds4f(ca), s1 = lds4f(ca + 2048), c0 = lds4f(ca + 4096), c1 = lds4f(ca + 6144);
            const float sh[8] = {s0.x, s0.y, s0.z, s0.w, s1.x, s1.y, s1.z, s1.w}, sc[8] = {c0.x, c0.y, c0.z, c0.w, c1.x, c1.y, c1.z, c1.w};
#pragma unroll
            for (int h = 0; h < 2; h++) {
                uint4 u = lds4(src + h * 2048 + i * 512);
#pragma unroll
                for (int e = 0; e < 4; e++) {
                    uint32_t& w = (&u.x)[e];
                    w = pack2(fmaf((bflo(w) - m[h]) * rs[h], sc[2 * e], sh[2 * e]), fmaf((bfhi(w) - m[h]) * rs[h], sc[2 * e + 1], sh[2 * e + 1]));
                }
                *(uint4*)(dst + i * 16384 + ((id & 1) == (i >> 1) ? 65536 : 2048) + h * 128 + (((lane ^ (2 * wid + h)) & 7) << 4)) = u;
            }
        }
        if (r == 0) {
            int ro, it = 0;
#pragma unroll 1
            do asm volatile("ld.volatile.shared.u32 %0, [%1];" : "=r"(ro) : "r"(sb + SM_BAR + 192) : "memory"); while ((ro == INT_MIN) & (++it < SPIN_LIMIT));
            if (ro >= 0) r1 = 2;
        }
        if (r && !(r & 1)) continue;
        bar_sync(r ? NB_FIN0 : NB_C, r ? 256 : 320);
        if (wid == (r >> 1 & 7)) {
            if (r == 1) bar_arrive(NB_B, 64);
            if (r == 3) wait_count_w(&g_tick[32 + id * 8], 2);
            if (lane == 0) { signal_count(&g_tick[32 + id * 8]); }
            __syncwarp();
        }
    }
}
__device__ __noinline__ uint32_t side_window_(const uint8_t* arena, uint32_t n) {
    U2 v;
    int it = 0;
#pragma unroll 1
    while (v = ldg_u2(arena + (LB_TIME << 13)), ((v.y >> 5) == n || gtime() - v.x > W_OPEN + W_LATE) && v.y < 32 * NSEG && ++it < 64) __nanosleep(100);
    it = 0;
#pragma unroll 1
    while ((int)(gtime() - v.x - W_OPEN) < 0 && ++it < 256) {}
    return v.y >> 5;
}
#define SIDE_T 300
template <int NQ, int NB>
__device__ __forceinline__ void side_gemv(const CUtensorMap* tm, int c0, int k0, int k1, uint32_t cs, uint32_t sb, const uint8_t* arena, uint32_t& n, uint32_t& ph, float (*acc)[8], bool once = false) {
    const uint32_t w = __reduce_max_sync(~0u, threadIdx.x >> 5 & 3), ring = sb + (NB == 3 ? 65536 : 0) + w * NB * 8192;
    const uint32_t bars = sb + SM_BAR + (NB == 3 ? 8 * B_W + w * 24 : 8 + w * 8), bs = NB == 3 ? 8 : 0;
#pragma unroll
    for (int q = 0; q < NQ; q++)
#pragma unroll
        for (int j = 0; j < 8; j++) acc[q][j] = 0.f;
#pragma unroll 1
    for (; k0 < k1; k0 += NB * 16, ph ^= 1) {
        const int nr = min(NB * 16, k1 - k0);
        side_window(arena, n);
        const uint32_t t0 = clk32();
#pragma unroll 1
        for (int g = 0; g < NB; g++) {
            spin_until(t0, (g * 4 + w) * (SIDE_T / 4));
            if (bs || !g) e_expect(bars + bs * g, !bs ? NB * 8192 : g * 16 < nr ? 8192 : 0);
            if (g * 16 < nr) e_tma2d_hint(ring + g * 8192, tm, c0, k0 + g * 16, bars + bs * g, once ? EVICT_FIRST : EVICT_NORMAL);
        }
#pragma unroll 1
        for (int r = 0; r < nr; r += 16) {
            mbar_wait_w(bars + bs * (r >> 4), ph);
            uint4 v[16];
#pragma unroll
            for (int h = 0; h < 16; h++) v[h] = lds4(ring + (r + h) * 512 + (threadIdx.x & 31) * 16);
            float4 cf[NQ][4];
#pragma unroll
            for (int q = 0; q < NQ * 4; q++) cf[q >> 2][q & 3] = lds4f(cs + ((q >> 2) * DM + k0 + r + (q & 3) * 4) * 4);
#pragma unroll
            for (int h = 0; h < 16; h++) {
                const float f[8] = {bflo(v[h].x), bfhi(v[h].x), bflo(v[h].y), bfhi(v[h].y), bflo(v[h].z), bfhi(v[h].z), bflo(v[h].w), bfhi(v[h].w)};
#pragma unroll
                for (int q = 0; q < NQ; q++)
#pragma unroll
                    for (int j = 0; j < 8; j++) acc[q][j] = fmaf((&cf[q][h >> 2].x)[h & 3], f[j], acc[q][j]);
            }
        }
        fence_async_smem();
        __syncwarp();
    }
}
__device__ __noinline__ void rec_side(float* sm, const RecMaps& mp, const RecPtrs& p, int id) {
    const int tid = threadIdx.x, t = tid & 127, w = __reduce_max_sync(~0u, t >> 5);
    float* coef = sm + (tid < 256 ? 44032 : 40960);
    const uint32_t sb = smem_u32(sm), cs = smem_u32(coef);
    uint32_t n = 0, ph = 0;
    float acc[3][8];
    if (tid < 256) {
        if (blockIdx.x < 128) rec_ln(smem_u32(sm), p.x, p.arena, id, 2);
        for (int i = tid; i < 2 * S_; i += 256) g_st[id * 2 * S_ + i] = 0.f;
        if (id == 0 && tid < 64) g_pcnt[tid * 8] = 0;
        if (id == 1) for (int i = tid; i < 6 * 256; i += 256) g_pflag[i] = 0;
        if (id == 2 && tid == 0) g_pt = 0;
        fence_async_smem();
        bar_sync(NB_FIN0, 256);
        if (PDL && tid == 0) asm volatile("fence.acq_rel.gpu; griddepcontrol.launch_dependents;" ::: "memory");
        if (tid >= 128) return;
        float* red = coef + 3 * DM;
        if (t == 0) wait_count1(&g_tick[8], 4);
        bar_sync(NB_S, 128);
        for (int i = t; i < DM; i += 128) { coef[i] = 1.0f + __ldcg(g_mod + 4 * DM + i); coef[DM + i] = __ldcg(g_mod + 3 * DM + i); coef[2 * DM + i] = 1.0f; }
        bar_sync(NB_S, 128);
        if (id == 1 && t < 32) {
            float u[5] = {0, 0, 0, 0, 0};
            for (int i = t; i < DM; i += 32) {
                const float a = coef[i], b = coef[DM + i];
                u[0] += a; u[1] += a * a; u[2] += a * b; u[3] += b; u[4] += b * b;
            }
#pragma unroll
            for (int q = 0; q < 5; q++) { const float r = warp_sum(u[q]); if (t == 0) g_cst[q] = r * (1.0f / DM); }
        }
        side_gemv<3, 2>(&mp.w1, id * 256, w * 256, w * 256 + 256, cs, sb, p.arena, n, ph, acc);
#pragma unroll
        for (int q = 0; q < 3; q++)
#pragma unroll
            for (int j = 0; j < 8; j++) red[((t >> 5) * 3 + q) * 256 + (t & 31) * 8 + j] = acc[q][j];
        bar_sync(NB_S, 128);
        for (int i = t; i < 768; i += 128) g_vec[(i >> 8) * DM + id * 256 + (i & 255)] = (red[i] + red[768 + i]) + (red[1536 + i] + red[2304 + i]);
        return;
    }
    for (int i = t; i < DM; i += 128) { coef[i] = silu_bf(p.c, i); coef[2 * DM + i] = 1.0f; }
    if (t == 0) wait_count1(&g_tick[32], 1);
    bar_sync(NB_G, 128);
    side_gemv<1, 3>(&mp.wmod, (2 + id) * DM + w * 256, 0, DM, cs, sb, p.arena, n, ph, acc, true);
#pragma unroll
    for (int j = 0; j < 8; j++) g_mod[(2 + id) * DM + t * 8 + j] = bfround(acc[0][j]);
    bar_sync(NB_G, 128);
    if (t == 0) signal_count(&g_tick[8]);
    side_gemv<1, 3>(&mp.w3, id * (FF / 4) + w * 256, 0, DM, cs + 8 * DM, sb, p.arena, n, ph, acc);
    if (t < FF / 32) {
#pragma unroll
        for (int j = 0; j < 8; j++) g_vec[3 * DM + id * (FF / 4) + t * 8 + j] = acc[0][j];
    }
}

__global__ void __cluster_dims__(2, 1, 1) __launch_bounds__(384, 1)
k_rec(const __grid_constant__ RecMaps mp, const __grid_constant__ RecPtrs p) {
    extern __shared__ uint8_t smraw[];
    const uint32_t sb = smem_u32(smraw);
    if ((sb & 0x3FFFF) != SB0) __trap();
    const uint32_t bars = sb + SM_BAR;
    const int tid = threadIdx.x, lane = tid & 31, b = blockIdx.x;
    const int wid = __reduce_max_sync(~0u, tid >> 5);
    const uint32_t rank = b & 1;
    uint8_t* arena = p.arena;
    volatile int* sinfo = (volatile int*)(smraw + SM_BAR + 192);
    if (tid == 0) sinfo[0] = INT_MIN;
    if (tid == 352) {
        for (int i = 0; i < 17; i++) mbar_init(bars + 8 * i, i == B_WO ? 4 : 1);
        asm volatile("fence.mbarrier_init.release.cluster;" ::: "memory");
    }
    __syncwarp();
    asm volatile("barrier.cluster.arrive.relaxed.aligned;" ::: "memory");
    int pr = 0, hA = 0;
    if (wid < 8) {
        if (b < 128) {
            const int cb = (b & 15) * 128, k0 = (b >> 4) * 128 + (tid >> 4);
            uint4 v[8];
#pragma unroll
            for (int i = 0; i < 8; i++) v[i] = __ldg((const uint4*)(p.wmod + (size_t)(k0 + 16 * i) * (6 * DM) + cb + (tid & 15) * 8));
            float acc[8] = {0, 0, 0, 0, 0, 0, 0, 0};
            const float s8 = silu_bf(p.c, k0 + 16 * (lane & 7));
#pragma unroll
            for (int i = 0; i < 8; i++) {
                const float sv = __shfl_sync(~0u, s8, i, 16);
                acc[0] += sv * bflo(v[i].x); acc[1] += sv * bfhi(v[i].x); acc[2] += sv * bflo(v[i].y); acc[3] += sv * bfhi(v[i].y);
                acc[4] += sv * bflo(v[i].z); acc[5] += sv * bfhi(v[i].z); acc[6] += sv * bflo(v[i].w); acc[7] += sv * bfhi(v[i].w);
            }
            float* red = (float*)(smraw + SM_PRE);
            *(float4*)(red + (tid >> 4) * 128 + (tid & 15) * 8) = make_float4(acc[0], acc[1], acc[2], acc[3]);
            *(float4*)(red + (tid >> 4) * 128 + (tid & 15) * 8 + 4) = make_float4(acc[4], acc[5], acc[6], acc[7]);
            bar_sync(NB_FIN0, 256);
            if (wid < 4) {
                float t = 0;
#pragma unroll
                for (int i = 0; i < 16; i++) t += red[i * 128 + tid];
                stg_rlx1(&g_modp[(b >> 4) * 2 * DM + cb + tid], __float_as_uint(t) | 1u);
            }
        } else {
            rec_ln(sb, p.x, p.arena, b - 128, 0);
        }
    } else if (wid >= 10 && b >= 128) {
        {
            const int w = (b - 128) * 2 + wid - 10;
            const uint16_t* src = (const uint16_t*)p.mem0 + (lane & 3) * 2 * DM + (w >> 2) * 512 + (w & 1) * 64 + (w & 2) * 8 + (lane >> 2);
            uint32_t v[4][4];
#pragma unroll
            for (int i = 0; i < 16; i++) v[i >> 2][i & 3] = src[(i >> 2) * 128 + (i & 2) * 16 + (i & 1) * 8] | ((uint32_t)src[DM + (i >> 2) * 128 + (i & 2) * 16 + (i & 1) * 8] << 16);
            uint8_t* d = arena + mem_row(w >> 2, w & 3, 0);
            uint8_t* e = d + 512 + (lane >> 1) * 4;
            d += lane * 16;
#pragma unroll
            for (int i = 0; i < 4; i++, d += 1024, e += 1024) {
                stg_rlx4(d, v[i][0], v[i][1], v[i][2], lane & 1 ? (v[i][3] & 0xffff) | CNT_ALL << 16 : v[i][3]);
                stg_rlx4(d + mem_slot(1), 0, 0, 0, 0);
                stg_rlx4(d + mem_slot(2), 0, 0, 0, 0);
                if (lane & 1) { stg_rlx1(e, v[i][3] >> 16 | CNT_ALL << 16); stg_rlx1(e + mem_slot(1), 0); stg_rlx1(e + mem_slot(2), 0); }
            }
            if (w == 0 && lane < 8) stg_rlx2(arena + (LB_TIME << 13) + lane * 1024, 0, 0);
            bar_arrive(NB_C, 320);
        }
    } else if (rank == 0) {
        uint32_t best = ~0u;
        const int pg = wid < 10 ? 0 : 1 + (b >> 1) / 22;
        uint32_t* q = (uint32_t*)(arena + (pg << 21) + (pg ? blk(b >> 1, wid & 1) : blk(LB_PROBE, wid & 1) + b * 16));
        if (lane < 8) stg_rlx1(q + lane, 0);
        __syncwarp();
        if (lane == 0) {
            q += 3;
            uint32_t v = p.zero;
#pragma unroll 1
            for (int r = v; r <= NPROBE; r++) {
                const uint32_t t0 = clk32() + (v >> 8);
                v = atomicAdd(q + (v >> 8), 1u);
                uint32_t t1;
                asm volatile("{.reg .pred p; setp.eq.u32 p, %1, 0xffffffff; @p exit; mov.u32 %0, %%clock;}" : "=r"(t1) : "r"(v) : "memory");
                best = min(best, t1 - t0);
            }
            sinfo[wid - 6] = best;
        }
        bar_sync(NB_KDONE, b < 128 ? 128 : 64);
        if (tid == 256) {
            const uint32_t par = sinfo[2] > sinfo[3], vote = b < 128 && (sinfo[4] > sinfo[5]) != par;
            stg_rlx2(&g_clk[b >> 1], ((clk32() - 2 * gtime()) & ~127u) | b >> 1, 1 + 2 * par + 4 * vote);
        }
    }
    if (wid == 8) {
        U2 v[3], my;
        uint32_t c0;
        const int me = b >> 1;
        int it = 0;
        __syncwarp();
#pragma unroll 1
        do {
            my = ldg_u2(&g_clk[me]);
#pragma unroll
            for (int k = 0; k < 3; k++) v[k] = ldg_u2(&g_clk[k * 22 + min(lane, 21)]);
        } while (!__all_sync(~0u, my.y & v[0].y & v[1].y & v[2].y & 1) & (++it < SPIN_LIMIT));
        c0 = __reduce_min_sync(~0u, lane ? ~0u : v[0].x) - 4096;
        const uint32_t mc = me >= 64 ? ~0u : my.x - c0;
        const int par = my.y >> 1 & 1;
        uint32_t cnt = 0, flip = 0;
#pragma unroll
        for (int k = 0; k < 3; k++) {
            const uint32_t c = v[k].x - c0, o = v[k].y >> 1 & 1;
            const bool ln = k == 2 && lane >= 20;
            cnt += o + (o == par ? (ln ? 44 + lane < me : c < mc) * 256 + (c < my.x - c0) * 65536 : 0);
            flip |= __popc(__ballot_sync(~0u, v[k].y & 4) & 0x3fffff) > 10 ? 256 << k : 0;
        }
        cnt = __reduce_add_sync(~0u, lane < 22 ? cnt : 0);
        const int n1 = cnt & 255, n0 = 66 - n1, tk = cnt >> 8 & 255;
        if (lane == 0) g_cls[smid() & 255] = cnt < 32 << 16 ? par * 4 + (cnt >> 19) : 8;
        hA = min(n0 >> 1, NH);
        const int q0 = 2 * hA, q1 = 2 * NH - q0;
        const int over = tk - (par ? q1 : q0), lack = max(par ? q0 - n0 : q1 - n1, 0);
        if (over < 0) pr = par ? q0 + tk : tk;
        else if (over < lack) pr = (par ? n0 : q0 + n1) + over;
        else pr = -1 - (over - lack + (par ? max(n0 - q0, 0) : 0));
        hA |= flip;
        if (lane == 0) {
            sinfo[1] = hA; sinfo[0] = pr;
            if (b >= 128 && rank == 0) atomicOr(&g_tick[6], (pr < 0 ? 4u : 1u) << ((b - 128) >> 1));
        }
    }
    asm volatile("barrier.cluster.wait.aligned;" ::: "memory");
    if (wid == 8) {
        __syncwarp();
        bar_arrive(NB_A, 288);
        bar_arrive(NB_S, 128);
        if (b >= 128 && pr < 0) bar_sync(NB_B, 64);
        if (pr >= 0) {
            const int pu = __reduce_max_sync(~0u, pr), c0 = (pu >> 1) * 128 + rank * 64, r0 = (pu & 1) * 512;
#pragma unroll 1
            for (int n = 0; n < 13; n++) {
                const u64 seq = b >= 128 ? LN_SEQ : 0xcba9876543210ull;
                const int i = seq >> (4 * n) & 15;
                if (b >= 128 && i == 0) bar_sync(NB_B, 64);
                if (n >= W_INFL && (b < 128 || n < LN_FREE)) mbar_wait_w(bars + 8 * (B_W + (seq >> (4 * (n - W_INFL)) & 15)), 0);
                const int m = i < 8 ? i & 1 : i >> 2, k = i < 8 ? i >> 1 : i & 3;
                const uint32_t dst = sb + m * 65536 + k * 16384, br = bars + 8 * (m < 3 ? B_W + i : B_WO);
                const int c = m < 3 ? c0 : 576 + rank * 256 + (pu & 1) * 128, r = m < 3 ? r0 + k * 128 : (pu >> 1) * DH;
                const uint64_t pol = m < 3 ? EVICT_FIRST : EVICT_NORMAL;
                e_expect(br, 16384);
                e_tma2d_hint(dst, &mp.wq + m, c, r, br, pol);
                e_tma2d_hint(dst + 8192, &mp.wq + m, c, r + 64, br, pol);
            }
        }
    } else {
        bar_sync(wid < 8 ? NB_A : NB_S, wid < 8 ? 288 : 128);
    }
    const int prr = __reduce_max_sync(~0u, sinfo[0]);
    hA = __reduce_max_sync(~0u, sinfo[1]);
    if (prr < 0) {
        int j = (b - 128) >> 1;
        if (b < 128) {
            uint32_t v;
            int it = 0;
#pragma unroll 1
            do { v = __reduce_max_sync(~0u, ldg_rlx1(&g_tick[6])); spin_guard(++it); } while (__popc(v) < 2);
            j = v == 3 ? -1 - prr : (v & 1) ^ 1;
        }
        rec_side((float*)smraw, mp, p, j * 2 + rank);
        return;
    }
    if (PDL) asm volatile("griddepcontrol.launch_dependents;" ::: "memory");
    const int role = (prr >> 1) * 4 + rank * 2 + (prr & 1);
    rec_main(sb, &mp.wo, arena, role, hA, wid >> 2, p.zero, p.dly);
}

__device__ __forceinline__ void wgmma_ss192(float* d, uint64_t a, uint64_t b, int sc) {
    asm volatile("{.reg .pred p; setp.ne.b32 p, %98, 0;\n wgmma.mma_async.sync.aligned.m64n192k16.f32.bf16.bf16 "
                 "{%0,%1,%2,%3,%4,%5,%6,%7,%8,%9,%10,%11,%12,%13,%14,%15,%16,%17,%18,%19,%20,%21,%22,%23,%24,%25,%26,%27,%28,%29,%30,%31,%32,%33,%34,%35,%36,%37,%38,%39,%40,%41,%42,%43,%44,%45,%46,%47,%48,%49,%50,%51,%52,%53,%54,%55,%56,%57,%58,%59,%60,%61,%62,%63,%64,%65,%66,%67,%68,%69,%70,%71,%72,%73,%74,%75,%76,%77,%78,%79,%80,%81,%82,%83,%84,%85,%86,%87,%88,%89,%90,%91,%92,%93,%94,%95}, %96, %97, p, 1, 1, 0, 1;}"
                 : F16(d, 0), F16(d, 16), F16(d, 32), F16(d, 48), F16(d, 64), F16(d, 80) : "l"(a), "l"(b), "r"(sc));
}

constexpr uint32_t P_B = 81920, P_PL = 40960, P_OUT = 180224, P_VEC = 212992, P_ROW = P_VEC + 6144, P_BAR = P_ROW + 4096, P_SMEM = P_BAR + 256;
#define FLAG_ST "st.release.gpu.global.u32"
#define FLAG_LD "ld.acquire.gpu.global.u32"
constexpr int ST = 5;
constexpr int PB_F = 0, PB_E = 5, PB_R = 10, PB_OUT = 16;
enum { C_Y = 0, C_G = 1, C_X1 = 2, C_U = 3, C_S1 = 8, C_S3 = 9 };
enum { V_GA = 0, V_A = 1, V_B = 2, V_GB = 3, V_VA = 4, V_VB = 5, V_VC = 6, V_C3 = 7 };
struct PostMaps { CUtensorMap o, wo, y, w1, g, w2, x1, w3, u, w4, out; };
struct PostPtrs { const bf16* x; };

struct GeluK { float k0, k1, kh; };
__device__ __forceinline__ GeluK gelu_k(float c) { return {0.7978845608028654f * c, 0.7978845608028654f * 0.044715f * c * c * c, 0.5f * c}; }
__device__ __forceinline__ float gelu_s(float t, const GeluK& k) {
    const float u = t * fmaf(t * t, k.k1, k.k0);
    float th; asm("tanh.approx.f32 %0, %1;" : "=f"(th) : "f"(u));
    const float hx = k.kh * t;
    return fmaf(hx, th, hx);
}
__device__ __forceinline__ float2 ldsv(uint32_t a) {
    float2 v; asm("ld.shared.v2.f32 {%0,%1}, [%2];" : "=f"(v.x), "=f"(v.y) : "r"(a)); return v;
}
__device__ __forceinline__ void wait_smem(uint32_t a, int target) {
    int it = 0;
#pragma unroll 1
    while (true) {
        int v;
        asm volatile("ld.acquire.cta.shared.u32 %0, [%1];" : "=r"(v) : "r"(a) : "memory");
        if (__all_sync(~0u, v >= target) | (++it > SPIN_LIMIT)) break;
    }
}

__device__ __forceinline__ void release(uint32_t rel, int st, bool c) {
    asm volatile("{.reg .pred p; setp.ne.u32 p, %1, 0; setp.ne.and.u32 p, %2, 0, p; @p mbarrier.arrive.shared::cluster.b64 _, [%0];}"
                 ::"r"(rel + 8 * (st ? st - 1 : ST - 1)), "r"(rel), "r"((uint32_t)c) : "memory");
}
struct Pipe { int st, ph; uint32_t rel; };
__device__ __forceinline__ void adv(Pipe& p) { if (++p.st == ST) { p.st = 0; p.ph ^= 1; } }

__device__ __forceinline__ void post_weights(uint32_t sb, const PostMaps& mp, int nb, int rank) {
    const uint32_t full = sb + P_BAR + 8 * PB_F, empty = sb + P_BAR + 8 * PB_E;
    int st = 0, pp = 1;
#pragma unroll 1
    for (int ph = 0; ph < 7; ph++) {
        const int NK = ph == 0 ? 64 : ph == 6 ? 56 : 16, km = NK == 16 ? 15 : 63;
        const CUtensorMap* tb = &mp.wo + 2 * (ph < 3 ? ph : ph < 6 ? 3 : 4);
        const bool w3 = ph >= 3 && ph < 6;
        const int n0 = w3 ? nb * 64 + (ph == 4 ? 1536 : ph == 5 ? 2560 : 0) : nb * 128, dn = w3 ? 512 : 64;
        const int rot = NK == 16 ? 2 * (nb & 6) : 0, sw = ph == 1 || ph == 3 ? 2 * rank : 0;
#pragma unroll 1
        for (int i = 0; i < NK; i++) {
            const int k0 = (((i < 4 ? i ^ sw : i) + rot) & km) * 64;
            const uint32_t a = sb + P_B + st * 8192, f = full + 8 * st;
            mbar_wait_w(empty + 8 * st, pp);
            e_expect(f, ph == 3 ? 40960 : 32768);
            e_tma2d(a, tb, n0, k0, f);
            e_tma2d(a + P_PL, tb, n0 + dn, k0, f);
            if (ph == 3) e_tma2d(a + 2 * P_PL, tb, n0 + 1024, k0, f);
            if (++st == ST) { st = 0; pp ^= 1; }
        }
    }
#pragma unroll 1
    for (int i = 0; i < ST; i++) mbar_wait_w(empty + 8 * i, pp ^ (i < st));
}
__device__ __forceinline__ void post_acts(uint32_t sb, const PostMaps& mp, int mb, int nb, int rank) {
    const int rh = 2 * mb + rank, lane = threadIdx.x & 31;
    const uint32_t bars = sb + P_BAR;
    int st = 0, pp = 1;
#pragma unroll 1
    for (int ph = 0; ph < 7; ph++) {
        const int NK = ph == 0 ? 64 : ph == 6 ? 56 : 16, km = NK == 16 ? 15 : 63;
        const CUtensorMap* ta = &mp.o + 2 * (ph < 3 ? ph : ph < 6 ? 3 : 4);
        const int amul = ph == 0 ? 256 : 64, arow = (ph == 0 ? rh * 8 : rh * 64) - 2, rot = NK == 16 ? 2 * (nb & 6) : 0;
        const bool own = ph == 1 || ph == 3;
        const uint32_t shifts = ph == 2 ? 0x04000301u : 0x02020202u;
        const uint32_t* fl = &g_pflag[(ph == 6 ? C_U : min(ph - 1, 2)) * 256 + (ph == 2 ? min(max(rh + min(lane >> 3, 2) - 1, 0), 31) : rh) * 8 + ((lane + nb - rank) & 7)];
        int i = 0, n = ph == 0 || ph == 5 ? NK : 0;
        if (own) { i = 4; if (st) { st--; pp ^= 1; } else st = 4; }
#pragma unroll 1
        while (i < NK) {
            if (n <= i) {
                int it = 0;
#pragma unroll 1
                do {
                    uint32_t v;
                    asm volatile(FLAG_LD " %0, [%1];" : "=r"(v) : "l"(fl) : "memory");
                    n = __reduce_min_sync(~0u, ph == 6 ? 8 * v : v || (own && !(lane & 6)) ? 16 : 2 * (lane & 7));
                    if (++it > SPIN_LIMIT) n = NK;
                } while (n <= i);
                asm volatile("fence.proxy.async.global;" ::: "memory");
            }
            if (own && (i == 5 || i == 6)) mbar_wait_w(bars + 8 * (PB_E + ph + i - 5), 1);
#pragma unroll 1
            for (const int e = own && i < 6 ? i + 1 : n; i < e; i++) {
                const int kb = (i + rot) & km;
                const uint32_t f = bars + 8 * (PB_F + st);
                mbar_wait_w(f + 8 * PB_E, pp);
                e_tma2d_mc(sb + st * 16384 + rank * 8192, ta, kb * amul, arow + (int)((shifts >> ((kb & 12) * 2)) & 7), f);
                if (++st == ST) { st = 0; pp ^= 1; }
            }
        }
    }
}

template <int PH, class F>
__device__ __forceinline__ void post_kb(uint32_t sb, float* acc, Pipe& p, int wg, bool lead, bool first, F mid) {
    constexpr uint64_t DA = PH == 0 ? mkdesc(SB0, 128, 1024, 0) : mkdesc(SB0, 16, 1024, 1);
    constexpr uint64_t DB = mkdesc(SB0 + P_B, P_PL, 1024, 1);
    mbar_wait_w(sb + P_BAR + 8 * PB_F + 8 * p.st, p.ph);
    const uint32_t a = (uint32_t)DA + p.st * 1024 + wg * 512, b = (uint32_t)DB + p.st * 512;
    wg_fence();
#pragma unroll
    for (int k = 0; k < 4; k++) {
        const uint64_t da = (DA & 0xffffffff00000000ull) | (a + k * (PH == 0 ? 16 : 2)), db = (DB & 0xffffffff00000000ull) | (b + k * 128);
        if (PH == 3) wgmma_ss192(acc, da, db, k || !first);
        else wgmma_ss128<PH == 0>(acc, da, db, k || !first);
    }
    wg_commit();
    wg_wait<1>();
    release(p.rel, p.st, !first);
    mid();
    adv(p);
}
__device__ __forceinline__ void post_end(uint32_t sb, Pipe& p, bool lead) {
    wg_wait<0>();
    release(p.rel, p.st, true);
}
template <int PH>
__device__ __forceinline__ void post_mma(uint32_t sb, float* acc, Pipe& p, int wg, bool lead, int nout, int pi, int mb, int nb) {
#pragma unroll 1
    for (int kb = 0; kb < 16; kb++)
        post_kb<PH>(sb, acc, p, wg, lead, kb == 0, [&]() {
            if (nout && kb == 0) wait_smem(sb + P_BAR + 8 * (PB_OUT + wg), nout);
        });
    post_end(sb, p, lead);
}

__global__ void __cluster_dims__(2, 1, 1) __launch_bounds__(384, 1)
k_post(const __grid_constant__ PostMaps mp, const __grid_constant__ PostPtrs pp) {
    extern __shared__ uint8_t smraw[];
    const uint32_t sb = smem_u32(smraw);
    if ((sb & 0x3FFFF) != SB0) __trap();
    const int tid = threadIdx.x, lane = tid & 31;
    const int rank = blockIdx.x & 1;
    const uint32_t bars = sb + P_BAR;
    int c = 0;
    unsigned long long v = 0;
    const int wid = __reduce_max_sync(~0u, tid >> 5);
    const bool draw = tid == 352 && rank == 0;
    if (draw) {
        c = min(ldg_rlx1(&g_cls[smid() & 255]), 8u);
        asm volatile("{.reg .b64 a; cvt.u64.u32 a, %%laneid; add.u64 a, a, %1; atom.relaxed.gpu.global.add.u64 %0, [a], %2;}" : "=l"(v) : "l"(&g_pt), "l"(1ull << (7 * c)) : "memory");
    }
    if (wid < 11) {
        asm volatile("{.reg .pred p; elect.sync _|p, 0xffffffff; @p mbarrier.init.shared.b64 [%0], %1; @p prefetch.tensormap [%2]; fence.mbarrier_init.release.cluster;}"
                     ::"r"(bars + 8 * wid), "r"(wid >= PB_E && wid < PB_R ? 4 : 1), "l"(&mp.o + wid) : "memory");
        if (wid == PB_R) { sts4(bars + 8 * PB_OUT, 0, 0, 0, 0); e_expect(bars + 8 * PB_R, 4); }
    }
    __syncwarp();
    asm volatile("barrier.cluster.arrive.relaxed.aligned; barrier.cluster.wait.aligned;" ::: "memory");
    if (draw) {
        int r = (v >> (7 * c)) & 127, role = c * 8 + r;
        if (c == 8 || r >= 8) {
            int n, x, it = 0;
#pragma unroll 1
            do {
                __nanosleep(200);
                v = ldg_u64(&g_pt); n = 0; x = c < 8 ? r - 8 : r;
#pragma unroll 1
                for (int i = 0; i < 63; i += 7) { const int m = v >> i & 127; n += m; if (i < 7 * c) x += max(m - 8, 0); }
            } while (n < gridDim.x / 2 && ++it < SPIN_LIMIT);
            role = -1;
#pragma unroll 1
            for (int i = 0; i < 64; i += 8, v >>= 7) {
                n = v & 127;
                if (x >= 0 && n + x < 8) role = i + n + x;
                x -= max(8 - n, 0);
            }
        }
#pragma unroll
        for (int i = 0; i < 2; i++)
            asm volatile("{.reg .b32 d; mapa.shared::cluster.u32 d, %0, %2; st.async.shared::cluster.mbarrier::complete_tx::bytes.u32 [d+8], %1, [d];}"
                         ::"r"(bars + 8 * PB_R), "r"(role), "r"(i) : "memory");
    }
    __syncwarp();
    mbar_wait_w(bars + 8 * PB_R, 0);
    const int pr = __reduce_max_sync(~0u, (int)lds1(bars + 8 * PB_R + 8));
    if (pr < 0) return;
    const int mb = (pr >> 5) * 8 + (pr & 7), nb = (pr >> 2 & 6) + rank, cta = pr * 2 + rank;
    if (wid >= 8) {
        asm volatile("setmaxnreg.dec.sync.aligned.u32 40;");
        const int w = wid - 8;
        if (w == 0) {
            post_weights(sb, mp, nb, rank);
        } else if (w == 3) {
            asm volatile("griddepcontrol.wait;" ::: "memory");
            post_acts(sb, mp, mb, nb, rank);
        } else {
            const int wg = w - 1, rh = 2 * mb + wg;
            float* rowc = (float*)(smraw + P_ROW) + (wg * 64 + lane * 2) * 8;
            int nout = 0, sig = 0;
#pragma unroll 1
            for (int i = 0; i < 13; i++) {
                const int cnt = (0x4333333392180ull >> (4 * i)) & 15;
                if (cnt < C_S1) {
                    const int ng = cnt == C_U ? 1 : 2, c0 = cnt == C_U ? (i - 5) * 512 + nb * 64 : nb * 128;
                    const bool fast = (cnt == C_Y || cnt == C_X1);
#pragma unroll 1
                    for (int j = 0; j < ng; j++) {
                        const uint32_t st = j ? cnt : cnt ? 1 : 4;
                        const uint32_t src = sb + (fast ? st * 16384 + wg * 8192 : P_OUT + wg * 16384 + ((nout + j) & 1) * 8192);
                        bar_sync(4 + 4 * wg + (sig++ & 3), 160);
                        if (lane == 0) {
                            if (fast) asm volatile("mbarrier.complete_tx.relaxed.cta.shared::cta.b64 [%0], 8192;" ::"r"(bars + 8 * (PB_F + st)) : "memory");
                            asm volatile("cp.async.bulk.tensor.2d.global.shared::cta.bulk_group [%0, {%2, %3}], [%1]; cp.async.bulk.commit_group;"
                                         ::"l"(&mp.y + 2 * cnt), "r"(src), "r"(c0 + j * 64), "r"(rh * 64) : "memory");
                        }
                        __syncwarp();
                    }
                    if (lane == 0) {
                        auto to_peer = [&]() {
                            const uint32_t n = cnt ? 1 : 4;
                            mbar_wait(bars + 8 * (PB_E + (cnt ? 4 : 2)), 0);
#pragma unroll
                            for (int i = 0; i < 2; i++)
                                asm volatile("{.reg .b32 d, m; mapa.shared::cluster.u32 d, %0, %3; mapa.shared::cluster.u32 m, %2, %3;\n"
                                             " cp.async.bulk.shared::cluster.shared::cta.mbarrier::complete_tx::bytes [d], [%1], 8192, [m];}"
                                             ::"r"(sb + (cnt + 1 + i) * 16384 + wg * 8192), "r"(sb + (i ? cnt : n) * 16384 + wg * 8192), "r"(bars + 8 * (PB_F + cnt + 1 + i)), "r"(rank ^ 1) : "memory");
                        };
                        asm volatile("cp.async.bulk.wait_group 0; fence.proxy.async.global;" ::: "memory");
                        asm volatile("st.release.cta.shared.u32 [%0], %1;" ::"r"(bars + 8 * (PB_OUT + wg)), "r"(nout + ng) : "memory");
                        if (i < 12) asm volatile(FLAG_ST " [%0], %1;" ::"l"(&g_pflag[cnt * 256 + rh * 8 + nb]), "r"(max(i - 4, 1)) : "memory");
                        if (fast) to_peer();
                    }
                    nout += ng;
                    __syncwarp();
                    continue;
                }
                bar_sync(4 + 4 * wg + (sig++ & 3), 160);
                uint32_t* c = &g_pcnt[(cnt - C_S1) * 256 + rh * 8];
                if (lane == 0) signal_count(c);
                __syncwarp();
                wait_count_w(c, 8);
                const float4* sp = (const float4*)g_st + rh * 32 + lane;
                float4 u[3] = {__ldcg(sp + (cnt == C_S1 ? 0 : 3) * (S_ / 2)), __ldcg(sp + S_ / 2), __ldcg(sp + S_)};
#pragma unroll 1
                for (int h = 0; h < 2; h++) {
                    const float id = 1.0f / DM;
                    const float m = u[0].x * id, var = fmaxf(u[0].y * id - m * m, 0.f) + 1e-5f, r = rsqrtf(var);
                    float sc = r, m2 = 0.f;
                    if (cnt == C_S1) {
                        m2 = r * (u[1].x * id - m * g_cst[0]) + g_cst[3];
                        const float e2 = r * r * (u[2].x * id - 2.0f * m * u[1].y * id + m * m * g_cst[1]) + 2.0f * r * (u[2].y * id - m * g_cst[2]) + g_cst[4];
                        sc = r * rsqrtf(fmaxf(e2 - m2 * m2, 0.f) + 1e-5f);
                    }
                    const GeluK k = gelu_k(sc);
                    *(float4*)(rowc + h * 8) = make_float4(k.k0, k.k1, k.kh, -m);
                    *(float4*)(rowc + h * 8 + 4) = make_float4(var * r, -m2 * var * r, r, -m * r);
#pragma unroll
                    for (int q = 0; q < 3; q++) { u[q].x = u[q].z; u[q].y = u[q].w; }
                }
                bar_arrive(1 + wg, 160);
            }
        }
    } else {
        asm volatile("setmaxnreg.inc.sync.aligned.u32 232;");
        const bf16* xin = pp.x;
        const int wg = wid >> 2, wi = (tid >> 5) & 3, g = lane >> 2, tq = lane & 3;
        const int rh = 2 * mb + wg, row = rh * 64 + wi * 16 + g;
        const bool lead = (tid & 127) == 0;
        uint32_t keep[32];
#pragma unroll
        for (int i = 0; i < 8; i++)
            *(uint4*)(keep + 4 * i) = __ldg((const uint4*)(xin + (size_t)(rh * 64 + wi * 16 + (i & 3) * 4 + (lane >> 3)) * DM + nb * 128 + (i >> 2) * 64 + (lane & 7) * 8));
        asm volatile("griddepcontrol.wait;" ::: "memory");
        if (cta < 64) g_modp[cta * 256 + tid] = 0;
        if (cta == 64 && tid < 196) g_tick[tid] = 0;
        const float* src = wg ? g_vec + nb * 128 + tid - 128 : g_mod + 2 * DM + nb * 128 + tid;
        const float* c3 = &g_vec[3 * DM + (tid >> 6) * 512 + nb * 64 + (tid & 63)];
        const float cv[6] = {__ldcg(src), __ldcg(src + (wg ? 1 : 2) * DM), __ldcg(src + (wg ? 2 : 1) * DM), __ldcg(src + 3 * DM), __ldcg(c3), __ldcg(c3 + (tid < 192 ? 2048 : 0))};
        uint32_t vec = sb + P_VEC + tq * 8;
        const uint32_t stw = sb + (wi * 16 + ((lane >> 3) & 1) * 8 + (lane & 7)) * 128 + (((lane >> 4) ^ (lane & 7)) << 4);
        int sig = 0;
        auto signal = [&]() { bar_arrive(4 + 4 * wg + (sig++ & 3), 160); };
        auto put64 = [&](uint32_t o, const float* v) {
#pragma unroll
            for (int jj = 0; jj < 4; jj++, v += 8) stsm4((stw + o) ^ (jj << 5), pack2(v[0], v[1]), pack2(v[2], v[3]), pack2(v[4], v[5]), pack2(v[6], v[7]));
            fence_async_smem();
            signal();
        };
        auto slot = [&](int n) {
            mbar_wait_w(bars + 8 * (PB_E + n % 5), ((n / 5) & 1) ^ 1);
            return (n % 5) * 16384 + wg * 8192;
        };
        const uint32_t rowc = sb + P_ROW + (wg * 64 + wi * 16 + g) * 32, o128 = P_OUT + wg * 16384;
        Pipe pa = {0, 0, 0};
        asm("mapa.shared::cluster.u32 %0, %1, %2;" : "=r"(pa.rel) : "r"(bars + 8 * PB_E), "r"(tid & 1));
        if (tid & 126) pa.rel = 0;
#define KEEP(jn, e) (((e) & 1) ? bfhi(keep[2 * (jn) + ((e) >> 1)]) : bflo(keep[2 * (jn) + ((e) >> 1)]))
        float mu1[2], r1[2];
        {
            float acc[64];
#pragma unroll 1
            for (int kb = 0; kb < 64; kb++) {
                post_kb<0>(sb, acc, pa, wg, lead, kb == 0, []() {});
                if (kb == 24) bar_sync(3, 256);
                if (kb != 8 + 8 * wg) continue;
                float* sv = (float*)(smraw + P_VEC) + tid;
                const uint32_t xo = sb + o128 + wi * 2048 + (lane >> 3) * 128;
#pragma unroll
                for (int i = 0; i < 8; i++) sts4(xo + (i >> 2) * 8192 + (i & 3) * 512 + (((lane & 7) ^ ((i & 1) * 4 + (lane >> 3))) << 4), keep[4 * i], keep[4 * i + 1], keep[4 * i + 2], keep[4 * i + 3]);
                __syncwarp();
#pragma unroll
                for (int jj = 0; jj < 8; jj++) ldsm4(keep + jj * 4, (stw + o128 + (jj >> 2) * 8192) ^ ((jj & 3) << 5));
                sv[wg * 384] = cv[0]; sv[wg * 384 + 128] = cv[1] + (wg ? 0.0f : 1.0f); sv[wg * 384 + 256] = cv[2];
                if (!wg) sv[384] = cv[3];
                sv[V_C3 * 128] = cv[4]; sv[V_C3 * 128 + 256] = cv[5];
            }
            post_end(sb, pa, lead);
            asm volatile("" : "+r"(vec) :: "memory");
            float st[2][6];
#pragma unroll
            for (int q = 0; q < 6; q++) st[0][q] = st[1][q] = 0.f;
#pragma unroll
            for (int jn = 0; jn < 16; jn++) {
                const float2 ga = ldsv(vec + V_GA * 512 + jn * 32), a = ldsv(vec + V_A * 512 + jn * 32);
                float xa[4];
#pragma unroll
                for (int e = 0; e < 4; e++) {
                    xa[e] = fmaf((e & 1) ? ga.y : ga.x, acc[4 * jn + e], KEEP(jn, e));
                    st[e >> 1][0] += xa[e]; st[e >> 1][1] = fmaf(xa[e], xa[e], st[e >> 1][1]);
                    acc[4 * jn + e] = ((e & 1) ? a.y : a.x) * xa[e];
                }
                keep[2 * jn] = pack2(xa[0], xa[1]); keep[2 * jn + 1] = pack2(xa[2], xa[3]);
                if ((jn & 7) == 7) put64(slot(64 + (jn >> 3)), acc + 4 * jn - 28);
            }
#pragma unroll
            for (int jn = 0; jn < 16; jn++) {
                const float2 a = ldsv(vec + V_A * 512 + jn * 32), b = ldsv(vec + V_B * 512 + jn * 32);
#pragma unroll
                for (int e = 0; e < 4; e++) {
                    const float y = acc[4 * jn + e], aa = (e & 1) ? a.y : a.x, bb = (e & 1) ? b.y : b.x;
                    float* s = st[e >> 1];
                    s[2] += y; s[3] = fmaf(aa, y, s[3]); s[4] = fmaf(y, y, s[4]); s[5] = fmaf(bb, y, s[5]);
                }
            }
#pragma unroll
            for (int h = 0; h < 2; h++)
#pragma unroll
                for (int q = 0; q < 6; q++) { st[h][q] += __shfl_xor_sync(~0u, st[h][q], 1); st[h][q] += __shfl_xor_sync(~0u, st[h][q], 2); }
            if (tq < 3) {
#pragma unroll
                for (int h = 0; h < 2; h++)
                    red2(g_st + (tq * S_ + row + h * 8) * 2, tq == 0 ? st[h][0] : tq == 1 ? st[h][2] : st[h][4], tq == 0 ? st[h][1] : tq == 1 ? st[h][3] : st[h][5]);
            }
            signal();
        }
        {
            float acc[64];
            post_mma<1>(sb, acc, pa, wg, lead, 2, 4, mb, nb);
            float c1[2], c2[2], c3[2];
            GeluK gk[2];
            bar_sync(1 + wg, 160);
#pragma unroll
            for (int h = 0; h < 2; h++) {
                const float4 a = lds4f(rowc + h * 256), b = lds4f(rowc + h * 256 + 16);
                gk[h] = {a.x, a.y, a.z}; c1[h] = a.w; c2[h] = b.x; c3[h] = b.y; mu1[h] = b.w; r1[h] = b.z;
            }
#pragma unroll
            for (int jn = 0; jn < 16; jn++) {
                const float2 va = ldsv(vec + V_VA * 512 + jn * 32), vb = ldsv(vec + V_VB * 512 + jn * 32), vc = ldsv(vec + V_VC * 512 + jn * 32);
#pragma unroll
                for (int e = 0; e < 4; e++) {
                    const int h = e >> 1;
                    const float t = fmaf(c1[h], (e & 1) ? va.y : va.x, fmaf(c2[h], (e & 1) ? vb.y : vb.x, fmaf(c3[h], (e & 1) ? vc.y : vc.x, acc[4 * jn + e])));
                    acc[4 * jn + e] = gelu_s(t, gk[h]);
                }
                if ((jn & 7) == 7) put64(o128 + (jn >> 3) * 8192, acc + 4 * jn - 28);
            }
        }
        {
            float acc[64];
            post_mma<2>(sb, acc, pa, wg, lead, 0, 7, mb, nb);
#pragma unroll
            for (int jn = 0; jn < 16; jn++) {
                const float2 a = ldsv(vec + V_A * 512 + jn * 32), b = ldsv(vec + V_B * 512 + jn * 32);
#pragma unroll
                for (int e = 0; e < 4; e++) {
                    const int h = e >> 1;
                    acc[4 * jn + e] += fmaf(fmaf(KEEP(jn, e), r1[h], mu1[h]), (e & 1) ? a.y : a.x, (e & 1) ? b.y : b.x);
                }
                if ((jn & 7) == 7) put64(slot(96 + (jn >> 3)), acc + 4 * jn - 28);
            }
            BLOCK_FENCE
#pragma unroll
            for (int i = 0; i < 64; i += 16) asm volatile("" : F16(acc, i));
            float st[2][2] = {{0.f, 0.f}, {0.f, 0.f}};
#pragma unroll
            for (int jn = 0; jn < 16; jn++) {
                const float2 gb = ldsv(vec + V_GB * 512 + jn * 32);
                float z[4];
#pragma unroll
                for (int e = 0; e < 4; e++) {
                    const float x1 = acc[4 * jn + e];
                    st[e >> 1][0] += x1; st[e >> 1][1] = fmaf(x1, x1, st[e >> 1][1]);
                    z[e] = fmaf((e & 1) ? gb.y : gb.x, x1, KEEP(jn, e));
                }
                keep[2 * jn] = pack2(z[0], z[1]); keep[2 * jn + 1] = pack2(z[2], z[3]);
            }
#pragma unroll
            for (int h = 0; h < 2; h++)
#pragma unroll
                for (int q = 0; q < 2; q++) { st[h][q] += __shfl_xor_sync(~0u, st[h][q], 1); st[h][q] += __shfl_xor_sync(~0u, st[h][q], 2); }
            if (tq < 2) red2(g_st + (3 * S_ + row + tq * 8) * 2, tq ? st[1][0] : st[0][0], tq ? st[1][1] : st[0][1]);
            signal();
        }
        {
            float old[96], acc[64];
            post_mma<3>(sb, old, pa, wg, lead, 6, 10, mb, nb);
#pragma unroll
            for (int i = 0; i < 96; i += 16) asm volatile("" : F16(old, i));
            uint32_t v3 = vec + V_C3 * 512;
            bar_sync(1 + wg, 160);
            const float4 rc[2] = {lds4f(rowc), lds4f(rowc + 256)};
            float2 vc[2] = {lds2f(v3), lds2f(v3 + 32)};
            v3 += wg ? 0 : 64;
            bar_sync(3, 256);
#pragma unroll 1
            for (int blk = 0; blk < 11; blk++) {
                const uint32_t o = stw + o128 + (blk & 1) * 8192;
#pragma unroll
                for (int q = 0; q < 4; q++) {
#pragma unroll 1
                    for (int rep = 0; rep < 2; rep++) {
                        post_kb<1>(sb, acc, pa, wg, lead, q == 0 && rep == 0 && blk < 6 && !(blk & 1), []() {});
                        if (rep != wg) {
                            vc[0] = lds2f(v3 + q * 64); vc[1] = lds2f(v3 + q * 64 + 32);
                            if (q == 2) wait_smem(bars + 8 * (PB_OUT + wg), 6 + min(blk, 7));
                            if ((q == 0 && wg && (uint32_t)(blk - 1) < 7) || (q == 3 && !wg && blk < 7)) { fence_async_smem(); signal(); }
                        } else if (blk < 7) {
                            asm volatile("" : F4(old, 8 * q), F4(old, 8 * q + 4));
                            float t[8];
#pragma unroll
                            for (int i = 0; i < 8; i++) {
                                const float4& c = rc[(i >> 1) & 1];
                                t[i] = gelu_s(fmaf(c.w, (i & 1) ? vc[i >> 2].y : vc[i >> 2].x, old[8 * q + i]), GeluK{c.x, c.y, c.z});
                                old[8 * q + i] = old[32 + 8 * q + i];
                                old[32 + 8 * q + i] = old[64 + 8 * q + i];
                            }
                            uint32_t r[4] = {pack2(t[0], t[1]), pack2(t[2], t[3]), pack2(t[4], t[5]), pack2(t[6], t[7])};
                            asm volatile("pmevent 0;" : F4(old, 8 * q), F4(old, 8 * q + 4), F4(old, 8 * q + 32), F4(old, 8 * q + 36), "+r"(r[0]), "+r"(r[1]), "+r"(r[2]), "+r"(r[3]));
                            stsm4(o ^ (q << 5), r[0], r[1], r[2], r[3]);
                        }
                    }
                }
                v3 += 256;
                if (blk != 1 && blk != 3) continue;
                post_end(sb, pa, lead);
                asm volatile("" : F16(acc, 0), F4(acc, 16), F4(acc, 20), F4(acc, 24));
                asm volatile("" : F16(acc, 28), F4(acc, 44), F4(acc, 48), F4(acc, 52));
                asm volatile("" : F4(acc, 56), F4(acc, 60));
#pragma unroll
                for (int i = 0; i < 64; i++) old[32 + i] = acc[i];
            }
            post_end(sb, pa, lead);
#pragma unroll
            for (int jn = 0; jn < 16; jn++) {
                const float2 gb = ldsv(vec + V_GB * 512 + jn * 32);
#pragma unroll
                for (int e = 0; e < 4; e++) acc[4 * jn + e] = fmaf((e & 1) ? gb.y : gb.x, acc[4 * jn + e], KEEP(jn, e));
                if ((jn & 7) == 7) put64(o128 + ((jn >> 3) ^ 1) * 8192, acc + 4 * jn - 28);
            }
        }
    }
}

typedef CUresult (*EncFn)(CUtensorMap*, CUtensorMapDataType, cuuint32_t, void*, const cuuint64_t*, const cuuint64_t*, const cuuint32_t*,
                          const cuuint32_t*, CUtensorMapInterleave, CUtensorMapSwizzle, CUtensorMapL2promotion, CUtensorMapFloatOOBfill);

static CUtensorMap make_map(EncFn enc, const void* p, uint64_t inner, uint64_t outer, uint32_t bi = 64) {
    CUtensorMap m;
    cuuint64_t dims[2] = {inner, outer};
    cuuint64_t str[1] = {inner * 2};
    cuuint32_t box[2] = {bi, bi == 64 ? 64u : 16u};
    cuuint32_t es[2] = {1, 1};
    enc(&m, CU_TENSOR_MAP_DATA_TYPE_BFLOAT16, 2, (void*)p, dims, str, box, es, CU_TENSOR_MAP_INTERLEAVE_NONE,
        bi == 64 ? CU_TENSOR_MAP_SWIZZLE_128B : CU_TENSOR_MAP_SWIZZLE_NONE, CU_TENSOR_MAP_L2_PROMOTION_L2_256B, CU_TENSOR_MAP_FLOAT_OOB_FILL_NONE);
    return m;
}
static CUtensorMap make_map_o(EncFn enc, const void* p) {
    CUtensorMap m;
    cuuint64_t dims[2] = {16384, 256};
    cuuint64_t str[1] = {65536};
    cuuint32_t box[2] = {256, 8};
    cuuint32_t es[2] = {1, 1};
    enc(&m, CU_TENSOR_MAP_DATA_TYPE_UINT32, 2, (void*)p, dims, str, box, es, CU_TENSOR_MAP_INTERLEAVE_NONE, CU_TENSOR_MAP_SWIZZLE_NONE,
        CU_TENSOR_MAP_L2_PROMOTION_L2_256B, CU_TENSOR_MAP_FLOAT_OOB_FILL_NONE);
    return m;
}
template <class T> static T* sym(T& s) { void* p = nullptr; cudaGetSymbolAddress(&p, s); return (T*)p; }

static const Delays h_dly = {D_NEAR, D_FAR, D_X2, D_V, D_W2, D_PA, D_MORE2, D_MORE};
extern "C" void kernel_launch(void* const* d_in, const int* in_sizes, int n_in, void* d_out, int out_size) {
    const bf16* x = (const bf16*)d_in[0];
    const bf16* mem0 = (const bf16*)d_in[1];
    const bf16 *Wq = (const bf16*)d_in[2], *Wk = (const bf16*)d_in[3], *Wv = (const bf16*)d_in[4], *Wo = (const bf16*)d_in[5];
    const bf16 *w1 = (const bf16*)d_in[8], *w2 = (const bf16*)d_in[9], *w3 = (const bf16*)d_in[10], *w4 = (const bf16*)d_in[11];
    const bf16 *c = (const bf16*)d_in[12], *wmod = (const bf16*)d_in[13];
    bf16* out = (bf16*)d_out;

    EncFn enc = nullptr;
    cudaDriverEntryPointQueryResult qr;
    cudaGetDriverEntryPoint("cuTensorMapEncodeTiled", (void**)&enc, cudaEnableDefault, &qr);
    CUtensorMap tWq = make_map(enc, Wq, NH * DH, DM), tWk = make_map(enc, Wk, NH * DH, DM), tWv = make_map(enc, Wv, NH * DH, DM);
    PostMaps mp;
    mp.o = make_map_o(enc, sym(g_O)); mp.wo = make_map(enc, Wo, DM, NH * DH);
    mp.y = make_map(enc, sym(g_y), DM, S_); mp.w1 = make_map(enc, w1, DM, DM);
    mp.g = make_map(enc, sym(g_g), DM, S_); mp.w2 = make_map(enc, w2, DM, DM);
    mp.x1 = make_map(enc, sym(g_x1), DM, S_); mp.w3 = make_map(enc, w3, FF, DM);
    mp.u = make_map(enc, sym(g_u), FF, S_); mp.w4 = make_map(enc, w4, DM, FF);
    mp.out = make_map(enc, out, DM, S_);
    cudaFuncSetAttribute(k_rec, cudaFuncAttributeMaxDynamicSharedMemorySize, SM_REC_TOTAL + 2048);
    cudaFuncSetAttribute(k_post, cudaFuncAttributeMaxDynamicSharedMemorySize, P_SMEM);

    uint8_t* arena = (uint8_t*)(((uintptr_t)sym(g_arena) + (2u << 20) - 1) & ~(uintptr_t)((2u << 20) - 1));
    const PostPtrs pp = {x};
    const RecPtrs rp = {x, mem0, c, wmod, w1, w3, arena, 0u, w2, w4, Wo, h_dly};
    const RecMaps rm = {tWq, tWk, tWv, mp.wo, make_map(enc, wmod, 6 * DM, DM, 256), make_map(enc, w3, FF, DM, 256), make_map(enc, w1, DM, DM, 256)};
    k_rec<<<132, 384, SM_REC_TOTAL + 2048>>>(rm, rp);
    cudaLaunchConfig_t cfg = {};
    cfg.gridDim = dim3(132); cfg.blockDim = dim3(384); cfg.dynamicSmemBytes = P_SMEM; cfg.stream = cudaStreamPerThread;
    cudaLaunchAttribute at[1];
    at[0].id = cudaLaunchAttributeProgrammaticStreamSerialization; at[0].val.programmaticStreamSerializationAllowed = PDL;
    cfg.attrs = at; cfg.numAttrs = 1;
    cudaLaunchKernelEx(&cfg, k_post, mp, pp);
}
```

```cpp
#include <cuda_runtime.h>
#include <cuda.h>
#include <cuda_bf16.h>
#include <stdint.h>
#include <limits.h>

typedef __nv_bfloat16 bf16;

constexpr int S_ = 2048, DM = 1024, NH = 32, DH = 128, NSEG = 64, FF = 3584;
constexpr int SPIN_LIMIT = 1 << 22;
#define W_INFL 2
#define H_PIECES 4
#define PDL 1
#define NPROBE 3

__device__ uint8_t g_arena[10 << 20];
__device__ __align__(128) uint32_t g_tick[64 + 132];
#define g_clk ((uint2*)(g_tick + 64))
__device__ uint32_t g_cls[256];
__device__ unsigned long long g_pt;
__device__ __align__(16) uint32_t g_modp[8 * 2 * DM];
__host__ __device__ constexpr uint32_t blk(uint32_t lb, uint32_t par) {
    return (lb << 13) | ((((lb) ^ (lb >> 3) ^ (lb >> 4) ^ (lb >> 6) ^ par) & 1) << 12);
}
__host__ __device__ constexpr uint32_t lb_x2(uint32_t h) { return (h & 1) | ((h >> 1) << 3); }
__host__ __device__ constexpr uint32_t mem_row(uint32_t kh, uint32_t b, uint32_t r) { return blk(128 | b, kh) + r * 1024; }
__device__ __forceinline__ uint32_t mem_slot(uint32_t s) { return ((s & 1) << 15) | ((s & 2) << 17); }
constexpr uint32_t CNT1 = 0x3d80, CNT_ALL = 0x4000;
constexpr uint32_t LB_PROBE = 6 | 64, LB_TIME = 6;
__host__ __device__ constexpr uint32_t lb_tok(uint32_t h) { return (h & 1) | ((h >> 1) << 3); }
__device__ float g_mod[6 * DM];
__device__ __align__(1024) bf16 g_himg[(S_ + 32) * DM];
__device__ __align__(1024) bf16 g_O[S_ * NH * DH];
__device__ __align__(1024) bf16 g_y[S_ * DM];
__device__ __align__(1024) bf16 g_g[S_ * DM];
__device__ __align__(1024) bf16 g_x1[S_ * DM];
__device__ __align__(16) float g_st[4 * S_ * 2];
__device__ float g_vec[3 * DM + FF];
__device__ float g_cst[8];
__device__ uint32_t g_pcnt[2 * 32 * 8], g_pflag[7 * 32 * 8];
__device__ __align__(1024) bf16 g_u[S_ * FF];

__device__ __forceinline__ uint32_t smem_u32(const void* p) { return (uint32_t)__cvta_generic_to_shared(p); }
__device__ __forceinline__ void spin_guard(int it) {
    asm volatile("{.reg .pred p; setp.gt.s32 p, %0, %1; @p st.global.u32 [%2], %0;}" ::"r"(it), "n"(SPIN_LIMIT), "l"(1ull));
}
__device__ __forceinline__ void wg_fence() { asm volatile("wgmma.fence.sync.aligned;" ::: "memory"); }
__device__ __forceinline__ void wg_commit() { asm volatile("wgmma.commit_group.sync.aligned;" ::: "memory"); }
template <int N> __device__ __forceinline__ void wg_wait() { asm volatile("wgmma.wait_group.sync.aligned %0;" ::"n"(N) : "memory"); }
__host__ __device__ constexpr uint64_t mkdesc(uint32_t addr, uint32_t lbo, uint32_t sbo, uint32_t swz) {
    return (uint64_t)((addr & 0x3FFFF) >> 4) | ((uint64_t)(lbo >> 4) << 16) | ((uint64_t)(sbo >> 4) << 32) | ((uint64_t)swz << 62);
}
__device__ __forceinline__ uint64_t dadd(uint64_t d, uint32_t o) { return (d & 0xffffffff00000000ull) | (uint32_t)((uint32_t)d + o); }
__device__ __forceinline__ void mbar_init(uint32_t b, uint32_t c) { asm volatile("mbarrier.init.shared.b64 [%0], %1;" ::"r"(b), "r"(c) : "memory"); }
__device__ __forceinline__ void mbar_arrive_cluster(uint32_t b, uint32_t cta) {
    asm volatile("{.reg .b32 r; mapa.shared::cluster.u32 r, %0, %1; mbarrier.arrive.shared::cluster.b64 _, [r];}" ::"r"(b), "r"(cta) : "memory");
}
__device__ __forceinline__ bool mbar_try(uint32_t b, uint32_t par) {
    uint32_t ok;
    asm volatile("{.reg .pred p; mbarrier.try_wait.parity.shared.b64 p, [%1], %2; selp.u32 %0, 1, 0, p;}" : "=r"(ok) : "r"(b), "r"(par) : "memory");
    return ok;
}
__device__ __forceinline__ void mbar_wait(uint32_t b, uint32_t par) {
    int it = 0;
#pragma unroll 1
    while (!mbar_try(b, par) & (++it < SPIN_LIMIT)) {}
}
__device__ __forceinline__ void mbar_wait_w(uint32_t b, uint32_t par) {
    int it = 0;
#pragma unroll 1
    while (!__all_sync(~0u, mbar_try(b, par)) & (++it < SPIN_LIMIT)) {}
}
constexpr uint64_t EVICT_FIRST = 0x12F0000000000000ull, EVICT_NORMAL = 0x1000000000000000ull;   __device__ __forceinline__ void bar_sync(int id, int n) { asm volatile("bar.sync %0, %1;" ::"r"(id), "r"(n) : "memory"); }
__device__ __forceinline__ void bar_arrive(int id, int n) { asm volatile("bar.arrive %0, %1;" ::"r"(id), "r"(n) : "memory"); }
__device__ __forceinline__ void fence_async_smem() { asm volatile("fence.proxy.async.shared::cta;" ::: "memory"); }
__device__ __forceinline__ void ldsm4t(uint32_t* r, uint32_t a) {
    asm volatile("ldmatrix.sync.aligned.m8n8.x4.trans.shared.b16 {%0,%1,%2,%3}, [%4];" : "=r"(r[0]), "=r"(r[1]), "=r"(r[2]), "=r"(r[3]) : "r"(a) : "memory");
}
__device__ __forceinline__ void ldsm4(uint32_t* r, uint32_t a) {
    asm volatile("ldmatrix.sync.aligned.m8n8.x4.shared.b16 {%0,%1,%2,%3}, [%4];" : "=r"(r[0]), "=r"(r[1]), "=r"(r[2]), "=r"(r[3]) : "r"(a) : "memory");
}
__device__ __forceinline__ uint32_t movm(uint32_t a) {
    uint32_t d; asm volatile("movmatrix.sync.aligned.m8n8.trans.b16 %0, %1;" : "=r"(d) : "r"(a)); return d;
}
__device__ __forceinline__ void mma16816(float* d, uint32_t a0, uint32_t a1, uint32_t a2, uint32_t a3, uint32_t b0, uint32_t b1) {
    asm volatile("mma.sync.aligned.m16n8k16.row.col.f32.bf16.bf16.f32 {%0,%1,%2,%3},{%4,%5,%6,%7},{%8,%9},{%0,%1,%2,%3};"
                 : "+f"(d[0]), "+f"(d[1]), "+f"(d[2]), "+f"(d[3]) : "r"(a0), "r"(a1), "r"(a2), "r"(a3), "r"(b0), "r"(b1));
}
__device__ __forceinline__ void mma16816z(float* d, const uint32_t* a, uint32_t b0, uint32_t b1) {
    asm volatile("mma.sync.aligned.m16n8k16.row.col.f32.bf16.bf16.f32 {%0,%1,%2,%3},{%4,%5,%6,%7},{%8,%9},{%10,%10,%10,%10};"
                 : "=f"(d[0]), "=f"(d[1]), "=f"(d[2]), "=f"(d[3]) : "r"(a[0]), "r"(a[1]), "r"(a[2]), "r"(a[3]), "r"(b0), "r"(b1), "f"(0.f));
}
__device__ __forceinline__ void mma1688(float* d, uint32_t a0, uint32_t a1, uint32_t b0) {
    asm volatile("mma.sync.aligned.m16n8k8.row.col.f32.bf16.bf16.f32 {%0,%1,%2,%3},{%4,%5},{%6},{%0,%1,%2,%3};"
                 : "+f"(d[0]), "+f"(d[1]), "+f"(d[2]), "+f"(d[3]) : "r"(a0), "r"(a1), "r"(b0));
}
__device__ __forceinline__ uint32_t pack2(float lo, float hi) {
    uint32_t r; asm("cvt.rn.bf16x2.f32 %0, %1, %2;" : "=r"(r) : "f"(hi), "f"(lo)); return r;
}
__device__ __forceinline__ uint32_t hadd2(uint32_t a, uint32_t b) {
    uint32_t r; asm("add.rn.bf16x2 %0, %1, %2;" : "=r"(r) : "r"(a), "r"(b)); return r;
}
__device__ __forceinline__ float bflo(uint32_t u) { return __uint_as_float(u << 16); }
__device__ __forceinline__ float bfhi(uint32_t u) { return __uint_as_float(u & 0xffff0000u); }
__device__ __forceinline__ float ex2(float x) { float r; asm("ex2.approx.ftz.f32 %0, %1;" : "=f"(r) : "f"(x)); return r; }
__device__ __forceinline__ uint4 ldg_rlx4(const void* p) {
    uint4 v; asm volatile("ld.relaxed.gpu.global.v4.u32 {%0,%1,%2,%3}, [%4];" : "=r"(v.x), "=r"(v.y), "=r"(v.z), "=r"(v.w) : "l"(p) : "memory"); return v;
}
__device__ __forceinline__ uint32_t ldg_rlx1(const void* p) {
    uint32_t v; asm volatile("ld.relaxed.gpu.global.u32 %0, [%1];" : "=r"(v) : "l"(p) : "memory"); return v;
}
__device__ __forceinline__ void stg_rlx1(void* p, uint32_t v) { asm volatile("st.relaxed.gpu.global.u32 [%0], %1;" ::"l"(p), "r"(v) : "memory"); }
__device__ __forceinline__ void stg_rlx2(void* p, uint32_t x, uint32_t y) {
    unsigned long long v = (unsigned long long)x | ((unsigned long long)y << 32);
    asm volatile("st.relaxed.gpu.global.b64 [%0], %1;" ::"l"(p), "l"(v) : "memory");
}
__device__ __forceinline__ void stg_rlx4(void* p, uint32_t x, uint32_t y, uint32_t z, uint32_t w) {
    asm volatile("st.relaxed.gpu.global.v4.u32 [%0], {%1,%2,%3,%4};" ::"l"(p), "r"(x), "r"(y), "r"(z), "r"(w) : "memory");
}
__device__ __forceinline__ void sts4(uint32_t a, uint32_t x, uint32_t y, uint32_t z, uint32_t w) {
    asm volatile("st.shared.v4.u32 [%0], {%1,%2,%3,%4};" ::"r"(a), "r"(x), "r"(y), "r"(z), "r"(w) : "memory");
}
__device__ __forceinline__ uint4 lds4(uint32_t a) {
    uint4 v; asm volatile("ld.shared.v4.u32 {%0,%1,%2,%3}, [%4];" : "=r"(v.x), "=r"(v.y), "=r"(v.z), "=r"(v.w) : "r"(a) : "memory"); return v;
}
#define F4(d, i) "+f"(d[i]), "+f"(d[i + 1]), "+f"(d[i + 2]), "+f"(d[i + 3])
__device__ __forceinline__ void wgmma_rs32(float* d, const uint32_t* a, uint64_t b, int sc) {
    asm volatile("{.reg .pred p; setp.ne.b32 p, %21, 0;\n wgmma.mma_async.sync.aligned.m64n32k16.f32.bf16.bf16 {%0,%1,%2,%3,%4,%5,%6,%7,%8,%9,%10,%11,%12,%13,%14,%15}, {%16,%17,%18,%19}, %20, p, 1, 1, 0;}"
                 : F4(d, 0), F4(d, 4), F4(d, 8), F4(d, 12) : "r"(a[0]), "r"(a[1]), "r"(a[2]), "r"(a[3]), "l"(b), "r"(sc));
}
__device__ __forceinline__ void wgmma_ss32(float* d, uint64_t a, uint64_t b, int sc) {
    asm volatile("{.reg .pred p; setp.ne.b32 p, %18, 0;\n wgmma.mma_async.sync.aligned.m64n32k16.f32.bf16.bf16 {%0,%1,%2,%3,%4,%5,%6,%7,%8,%9,%10,%11,%12,%13,%14,%15}, %16, %17, p, 1, 1, 1, 0;}"
                 : F4(d, 0), F4(d, 4), F4(d, 8), F4(d, 12) : "l"(a), "l"(b), "r"(sc));
}
__device__ __forceinline__ void wgmma_rs40(float* d, const uint32_t* a, uint64_t b, int sc) {
    asm volatile("{.reg .pred p; setp.ne.b32 p, %25, 0;\n wgmma.mma_async.sync.aligned.m64n40k16.f32.bf16.bf16 {%0,%1,%2,%3,%4,%5,%6,%7,%8,%9,%10,%11,%12,%13,%14,%15,%16,%17,%18,%19}, {%20,%21,%22,%23}, %24, p, 1, 1, 0;}"
                 : F4(d, 0), F4(d, 4), F4(d, 8), F4(d, 12), F4(d, 16) : "r"(a[0]), "r"(a[1]), "r"(a[2]), "r"(a[3]), "l"(b), "r"(sc));
}
__device__ __forceinline__ void wgmma_ss40(float* d, uint64_t a, uint64_t b, int sc) {
    asm volatile("{.reg .pred p; setp.ne.b32 p, %22, 0;\n wgmma.mma_async.sync.aligned.m64n40k16.f32.bf16.bf16 {%0,%1,%2,%3,%4,%5,%6,%7,%8,%9,%10,%11,%12,%13,%14,%15,%16,%17,%18,%19}, %20, %21, p, 1, 1, 1, 0;}"
                 : F4(d, 0), F4(d, 4), F4(d, 8), F4(d, 12), F4(d, 16) : "l"(a), "l"(b), "r"(sc));
}
#define F16(d, i) F4(d, i), F4(d, i + 4), F4(d, i + 8), F4(d, i + 12)
template <int TA>
__device__ __forceinline__ void wgmma_ss128(float* d, uint64_t a, uint64_t b, int sc) {
    asm volatile("{.reg .pred p; setp.ne.b32 p, %66, 0;\n wgmma.mma_async.sync.aligned.m64n128k16.f32.bf16.bf16 "
                 "{%0,%1,%2,%3,%4,%5,%6,%7,%8,%9,%10,%11,%12,%13,%14,%15,%16,%17,%18,%19,%20,%21,%22,%23,%24,%25,%26,%27,%28,%29,%30,%31,"
                 "%32,%33,%34,%35,%36,%37,%38,%39,%40,%41,%42,%43,%44,%45,%46,%47,%48,%49,%50,%51,%52,%53,%54,%55,%56,%57,%58,%59,%60,%61,%62,%63}, %64, %65, p, 1, 1, %67, 1;}"
                 : F16(d, 0), F16(d, 16), F16(d, 32), F16(d, 48) : "l"(a), "l"(b), "r"(sc), "n"(TA));
}

__device__ __forceinline__ float warp_sum(float v) {
#pragma unroll
    for (int o = 16; o; o >>= 1) v += __shfl_xor_sync(~0u, v, o);
    return v;
}
__device__ __forceinline__ float bfround(float x) { return __bfloat162float(__float2bfloat16(x)); }

__device__ __forceinline__ void wait_count1(const uint32_t* p, uint32_t target) {
    int it = 0;
#pragma unroll 1
    while (true) {
        uint32_t v;
        asm volatile("ld.acquire.gpu.global.u32 %0, [%1];" : "=r"(v) : "l"(p) : "memory");
        if (v >= target) break;
        spin_guard(++it);
    }
}
__device__ __forceinline__ void red2(float* p, float a, float b) {
    asm volatile("red.relaxed.gpu.global.add.v2.f32 [%0], {%1, %2};" ::"l"(p), "f"(a), "f"(b) : "memory");
}
__device__ __forceinline__ void signal_count(uint32_t* p) { asm volatile("red.release.gpu.global.add.u32 [%0], 1;" ::"l"(p) : "memory"); }
__device__ __forceinline__ void e_expect(uint32_t b, uint32_t tx) {
    asm volatile("{.reg .pred p; elect.sync _|p, 0xffffffff; @p mbarrier.arrive.expect_tx.shared.b64 _, [%0], %1;}" ::"r"(b), "r"(tx) : "memory");
}
__device__ __forceinline__ void e_tma2d(uint32_t dst, const CUtensorMap* m, int c0, int c1, uint32_t bar) {
    asm volatile("{.reg .pred p; elect.sync _|p, 0xffffffff;\n @p cp.async.bulk.tensor.2d.shared::cluster.global.mbarrier::complete_tx::bytes [%0], [%1, {%3, %4}], [%2];}"
                 ::"r"(dst), "l"(m), "r"(bar), "r"(c0), "r"(c1) : "memory");
}
__device__ __forceinline__ void e_tma2d_hint(uint32_t dst, const CUtensorMap* m, int c0, int c1, uint32_t bar, uint64_t pol) {
    asm volatile("{.reg .pred p; elect.sync _|p, 0xffffffff;\n @p cp.async.bulk.tensor.2d.shared::cluster.global.mbarrier::complete_tx::bytes.L2::cache_hint [%0], [%1, {%3, %4}], [%2], %5;}"
                 ::"r"(dst), "l"(m), "r"(bar), "r"(c0), "r"(c1), "l"(pol) : "memory");
}
__device__ __forceinline__ void e_tma2d_mc(uint32_t dst, const CUtensorMap* m, int c0, int c1, uint32_t bar) {
    asm volatile("{.reg .pred p; elect.sync _|p, 0xffffffff;\n @p cp.async.bulk.tensor.2d.shared::cluster.global.mbarrier::complete_tx::bytes.multicast::cluster [%0], [%1, {%3, %4}], [%2], %5;}"
                 ::"r"(dst), "l"(m), "r"(bar), "r"(c0), "r"(c1), "h"((uint16_t)3) : "memory");
}
__device__ __forceinline__ void wait_count_w(const uint32_t* p, uint32_t target) {
    int it = 0;
#pragma unroll 1
    while (true) {
        uint32_t v;
        asm volatile("ld.acquire.gpu.global.u32 %0, [%1];" : "=r"(v) : "l"(p) : "memory");
        if (__all_sync(~0u, v >= target) | (++it > SPIN_LIMIT)) break;
        __nanosleep(100);
    }
}

#define NL 6
constexpr uint32_t SM_HB = 16384, HBK = 5120, SM_SX = 57344, SM_OX = 122880, SM_PX = 124928, SM_PA = 126976, SM_WO = 147456,
                   SM_TAB = 212992, SM_PRE = SM_TAB + 5120, SM_BAR = 227328, SM_REC_TOTAL = 227328 + 256;
constexpr uint32_t SB0 = 1024;
constexpr int B_WO = 0, B_HE = 1, B_HB = 3, B_W = 5;
constexpr int NB_MEM = 1, NB_QK = 2, NB_X1 = 3, NB_X2 = 4, NB_WIN = 5, NB_WG = 6, NB_KDONE = 7, NB_FIN0 = 8, NB_P = 9, NB_PX = 10, NB_G = 11, NB_A = 12, NB_B = 13, NB_C = 14, NB_S = 15;
#define D_NEAR 1620
#define D_FAR (D_NEAR - 90)
#define D_X2 400
#define D_V 280
#define D_W2 40
#define D_PA 40
#define D_MORE 40
#define D_MORE2 30
constexpr int E_MUL = 28;
constexpr int NPF = NL + 6, NE1 = 10;
constexpr int W0_E = 3, W0_RS = NL - 1, G_AT = 18;
struct Delays { uint32_t near, far, x2, v, w2, pa, more2, more; };

__device__ __forceinline__ uint32_t clk32() { uint32_t t; asm volatile("mov.u32 %0, %%clock;" : "=r"(t) :: "memory"); return t; }
__device__ __forceinline__ uint32_t smid() { uint32_t t; asm volatile("mov.u32 %0, %%smid;" : "=r"(t)); return t; }
__device__ __forceinline__ uint32_t gtime() { uint32_t t; asm volatile("mov.u32 %0, %%globaltimer_lo;" : "=r"(t) :: "memory"); return t; }
__device__ __forceinline__ void spin_until(uint32_t t0, uint32_t d) { while (clk32() - t0 < d) {} }
template <int N> __device__ __forceinline__ uint32_t delay(uint32_t zero) {
    float x = __uint_as_float(clk32());
#pragma unroll
    for (int i = 0; i < N; i++) asm volatile("ex2.approx.ftz.f32 %0, %0;" : "+f"(x));
    return __float_as_uint(x) & zero;
}
__device__ __forceinline__ uint32_t opaque(uint32_t v) { return __shfl_sync(~0u, v, threadIdx.x & 31); }
__device__ __forceinline__ uint32_t xor_or(uint32_t a, uint32_t b, uint32_t t) {
    uint32_t r; asm volatile("lop3.b32 %0, %1, %2, %3, 0x7E;" : "=r"(r) : "r"(a), "r"(b), "r"(t)); return r;
}
__device__ __forceinline__ uint32_t settag(uint32_t v, uint32_t tag) {
    uint32_t r; asm("lop3.b32 %0, %1, 1, %2, 0xB8;" : "=r"(r) : "r"(v), "r"(tag)); return r;
}
__device__ __forceinline__ void sts2(uint32_t a, float x, float y) { asm volatile("st.shared.v2.f32 [%0], {%1,%2};" ::"r"(a), "f"(x), "f"(y) : "memory"); }
__device__ __forceinline__ void sts4f(uint32_t a, float x, float y, float z, float w) {
    asm volatile("st.shared.v4.f32 [%0], {%1,%2,%3,%4};" ::"r"(a), "f"(x), "f"(y), "f"(z), "f"(w) : "memory");
}
__device__ __forceinline__ void sts1(uint32_t a, uint32_t x) { asm volatile("st.shared.u32 [%0], %1;" ::"r"(a), "r"(x) : "memory"); }
__device__ __forceinline__ uint32_t lds1(uint32_t a) { uint32_t v; asm volatile("ld.shared.u32 %0, [%1];" : "=r"(v) : "r"(a) : "memory"); return v; }
__device__ __forceinline__ float4 lds4f(uint32_t a) {
    float4 v; asm volatile("ld.shared.v4.f32 {%0,%1,%2,%3}, [%4];" : "=f"(v.x), "=f"(v.y), "=f"(v.z), "=f"(v.w) : "r"(a) : "memory"); return v;
}
__device__ __forceinline__ float2 lds2f(uint32_t a) {
    float2 v; asm volatile("ld.shared.v2.f32 {%0,%1}, [%2];" : "=f"(v.x), "=f"(v.y) : "r"(a) : "memory"); return v;
}
__device__ __forceinline__ bool any_bit0(uint32_t x) {
    uint32_t r;
    asm volatile("{.reg .pred p, q; .reg .b32 t; and.b32 t, %1, 1; setp.ne.u32 p, t, 0; vote.sync.any.pred q, p, 0xffffffff; selp.u32 %0, 1, 0, q;}" : "=r"(r) : "r"(x));
    return r;
}
__device__ __forceinline__ float rcp_fast(float x) { float r; asm("rcp.approx.ftz.f32 %0, %1;" : "=f"(r) : "f"(x)); return r; }
__device__ __forceinline__ void stsm4(uint32_t a, uint32_t r0, uint32_t r1, uint32_t r2, uint32_t r3) {
    asm volatile("stmatrix.sync.aligned.m8n8.x4.shared.b16 [%0], {%1,%2,%3,%4};" ::"r"(a), "r"(r0), "r"(r1), "r"(r2), "r"(r3) : "memory");
}
__device__ __forceinline__ void stsm4t(uint32_t a, uint32_t r0, uint32_t r1, uint32_t r2, uint32_t r3) {
    asm volatile("stmatrix.sync.aligned.m8n8.x4.trans.shared.b16 [%0], {%1,%2,%3,%4};" ::"r"(a), "r"(r0), "r"(r1), "r"(r2), "r"(r3) : "memory");
}
__device__ __forceinline__ uint32_t and3(uint32_t a, uint32_t b, uint32_t c) {
    uint32_t r; asm("lop3.b32 %0, %1, %2, %3, 0x80;" : "=r"(r) : "r"(a), "r"(b), "r"(c)); return r;
}
__device__ __forceinline__ void red_mem(void* p, uint32_t x, uint32_t y, uint32_t z, uint32_t w, void* q, uint32_t e, bool c) {
    asm volatile("{.reg .pred p; setp.ne.u32 p, %7, 0; red.relaxed.gpu.global.add.noftz.v4.bf16x2 [%0], {%1,%2,%3,%4}; @p red.relaxed.gpu.global.add.noftz.bf16x2 [%5], %6;}"
                 ::"l"(p), "r"(x), "r"(y), "r"(z), "r"(w), "l"(q), "r"(e), "r"((uint32_t)c) : "memory");
}
__device__ __forceinline__ void stg4_if(bool c, void* p, uint32_t x) {
    asm volatile("{.reg .pred p; setp.ne.u32 p, %2, 0; @p st.relaxed.gpu.global.v4.u32 [%0], {%1,%1,%1,%1};}" ::"l"(p), "r"(x), "r"((uint32_t)c) : "memory");
}

__device__ __forceinline__ void h_load(uint32_t sb, const uint8_t* hsrc, int pass, uint32_t rank, uint32_t rot) {
    const uint8_t* src = hsrc + (size_t)pass * 65536;
    const uint32_t bar = sb + SM_BAR + 8 * (B_HB + (pass & 1)), dst = sb + SM_HB + (pass & 1) * 65536 + rank * 4 * HBK;
    e_expect(bar, 32768);
#pragma unroll 1
    for (int i = 0; i < H_PIECES; i++) {
        const uint32_t o = ((i + rot) & (H_PIECES - 1)) * (16384 / H_PIECES);
        asm volatile("{.reg .pred p; elect.sync _|p, 0xffffffff;\n"
                     " @p cp.async.bulk.shared::cluster.global.mbarrier::complete_tx::bytes.multicast::cluster [%0], [%1], %4, [%2], %3;}"
                     ::"r"(dst + o + (o >> 12) * 1024), "l"(src + o), "r"(bar), "h"((uint16_t)3), "n"(16384 / H_PIECES) : "memory");
    }
}
__device__ __forceinline__ uint4 ldg_b128(const void* p) {
    uint4 v;
    asm volatile("{.reg .b128 t; .reg .b64 a, b; ld.relaxed.gpu.global.b128 t, [%4]; mov.b128 {a, b}, t; mov.b64 {%0,%1}, a; mov.b64 {%2,%3}, b;}"
                 : "=r"(v.x), "=r"(v.y), "=r"(v.z), "=r"(v.w) : "l"(p) : "memory");
    return v;
}
__device__ __forceinline__ void stg_b128_if(bool c, void* p, uint32_t x, uint32_t y, uint32_t z, uint32_t w) {
    asm volatile("{.reg .pred p; setp.ne.u32 p, %5, 0; @p st.relaxed.gpu.global.v4.u32 [%0], {%1,%2,%3,%4};}"
                 ::"l"(p), "r"(x), "r"(y), "r"(z), "r"(w), "r"((uint32_t)c) : "memory");
}
__device__ __forceinline__ float pretag(float x, uint32_t add, uint32_t keep) { return __uint_as_float((__float_as_uint(x) + add) & keep); }

template <class F, class G>
__device__ __forceinline__ void softmax_rows(uint32_t src, uint32_t dst, uint32_t g16, int row0, F ready, G mid) {
    const uint32_t u = (g16 >> 7) & 3, e = ((g16 >> 9) << 3) | ((g16 >> 4) & 7);
    uint32_t se = src + e * 8, su = se + u * 1088, d0 = dst + e * 16 + u * 4, d1 = dst + 512 + e * 4;
    int vis = row0 + (e >> 2) - 2 * (e & 3) - 8 * u;
    asm volatile("" : "+r"(se), "+r"(su), "+r"(d0), "+r"(d1), "+r"(vis));
    ready();
    const float2 p0 = lds2f(su), p1 = lds2f(su + 256), p2 = lds2f(su + 512), p3 = lds2f(su + 768);
    const float2 m0 = lds2f(se + 4352), m1 = lds2f(se + 4352 + 256), m2 = lds2f(se + 4352 + 512), m3 = lds2f(se + 4352 + 768);
    float a0 = (p0.x + p1.x) + (p2.x + p3.x), a1 = (p0.y + p1.y) + (p2.y + p3.y);
    const float a2 = (m0.x + m1.x) + (m2.x + m3.x), a3 = (m0.y + m1.y) + (m2.y + m3.y);
    if (vis < 0) a0 = -1e9f / 0.08838834764831845f;
    if (vis < 1) a1 = -1e9f / 0.08838834764831845f;
    int k = __float_as_int(fmaxf(fmaxf(a0, a1), fmaxf(a2, a3)));
    k ^= (k >> 31) & 0x7fffffff;
    const bool hi = g16 & 64;
    const int k0 = __reduce_max_sync(~0u, hi ? INT_MIN : k), k1 = __reduce_max_sync(~0u, hi ? k : INT_MIN);
    mid();
    k = hi ? k1 : k0;
    const float m = __int_as_float(k ^ ((k >> 31) & 0x7fffffff));
    const float sl2 = 0.08838834764831845f * 1.4426950408889634f, mb = -m * sl2;
    sts1(d0, pack2(ex2(fmaf(a0, sl2, mb)), ex2(fmaf(a1, sl2, mb))));
    sts1(d1, pack2(ex2(fmaf(a2, sl2, mb)), ex2(fmaf(a3, sl2, mb))));
}

__device__ __forceinline__ uint32_t pack_h2(float lo, float hi) {
    uint32_t r; asm("cvt.rn.satfinite.f16x2.f32 %0, %1, %2;" : "=r"(r) : "f"(hi), "f"(lo)); return r;
}
__device__ __forceinline__ float2 unpack_h2(uint32_t u) {
    float2 r; asm("{.reg .b16 l, h; mov.b32 {l, h}, %2; cvt.f32.f16 %0, l; cvt.f32.f16 %1, h;}" : "=f"(r.x), "=f"(r.y) : "r"(u)); return r;
}
__device__ __forceinline__ uint32_t add_h2(uint32_t a, uint32_t b) { uint32_t r; asm("add.rn.f16x2 %0, %1, %2;" : "=r"(r) : "r"(a), "r"(b)); return r; }
__device__ __forceinline__ uint32_t max_h2(uint32_t a, uint32_t b) { uint32_t r; asm("max.f16x2 %0, %1, %2;" : "=r"(r) : "r"(a), "r"(b)); return r; }
struct U2 { uint32_t x, y; };
__device__ __forceinline__ U2 ldg_u2(const void* p) {
    U2 v; asm volatile("{.reg .b64 t; ld.relaxed.gpu.global.b64 t, [%2]; mov.b64 {%0, %1}, t;}" : "=r"(v.x), "=r"(v.y) : "l"(p) : "memory"); return v;
}
constexpr int POLL_LIMIT = 1 << 16;
constexpr float SM_L2E = 0.08838834764831845f * 1.4426950408889634f;
template <int V> struct IC { static constexpr int value = V; };
typedef unsigned long long u64;
__device__ __forceinline__ u64 ldg_u64(const void* p) { u64 v; asm volatile("ld.relaxed.gpu.global.b64 %0, [%1];" : "=l"(v) : "l"(p) : "memory"); return v; }
__device__ __forceinline__ void rec_main(uint32_t sb, const CUtensorMap* tWo, uint8_t* arena, int role, int hinfo, int wg, uint32_t zero, const Delays& dly) {
    const int hA = hinfo & 255;
    const int tid = threadIdx.x, t = tid & 127, lane = tid & 31, wi = t >> 5;
    const uint32_t bars = sb + SM_BAR;
    const int head = role >> 2, qd = role & 3, j = blockIdx.x & 1, kh = role & 1;
    const uint32_t mypar = head >= hA;
    const uint32_t wu = __reduce_max_sync(~0u, wi);
    const bool warp0 = wu == 0, warp1 = wu == 1;
    const uint8_t* hsrc = (const uint8_t*)g_himg + kh * 32768 + j * 16384;
    auto tokbase = [&](int ty) { return ((ty + 1) << 21) + blk(lb_tok(head), mypar ^ ((hinfo >> (8 + ty)) & 1)); };
    const uint32_t tbw = tokbase(wg), tbq = tokbase(0) + (qd >> 1) * 2048 + ((qd & 1) + wu) * 256;
    uint32_t w[32 - NL][4];
    const uint32_t frow = ((lane >> 4) * 8 + (lane & 7)) * 128, fx = ((lane >> 3) & 1) ^ (lane & 7);
    const uint32_t wl0 = sb + wg * 65536 + frow + ((fx ^ (2 * wi)) << 4);
    uint32_t g16 = opaque(t * 16);
    auto G16 = [&]() { asm volatile("" : "+r"(g16)); return g16; };
    const uint32_t sbl = sb - wu * 512;
    const uint32_t xso = blk(lb_x2(head), mypar), cu = kh * 2048 + (2 * j + (wu >> 1)) * 512;
    const uint32_t u_xo = xso + wg * 16384 + (wu & 1) * 2048 + (cu >> 1) - wu * 256, u_to = tbw + (wu & 1) * 16384 + cu - wu * 512;
    {
        uint8_t* pp = arena + (tbw + (1 << 20) + j * 16384 + (kh ^ 1) * 2048 + g16);
        stg_rlx4(pp, 0, 0, 0, 0);
        stg_rlx4(pp + 32768, 0, 0, 0, 0);
        stg_rlx4(arena + (u_to + g16), 0, 0, 0, 0);
        stg_rlx2(arena + (u_xo + (g16 >> 1)), 0, 0);
    }
    {
        if (wg > 0) wait_count_w(&g_tick[32 + (lane & 3) * 8], 1);
        if (wg == 1) asm volatile("fence.proxy.async.global;" ::: "memory");
#pragma unroll 1
        for (int i = 0; i < 4; i++) mbar_wait_w(bars + 8 * (B_W + (wg == 2 ? 8 + i : 2 * i + wg)), 0);
#pragma unroll
        for (int p = NL; p < 32; p++) ldsm4t(w[p - NL], wl0 + p * 2048);
        fence_async_smem();
        bar_sync(wg < 2 ? NB_WG : NB_X2, wg < 2 ? 256 : 128);
        if (wg == 2 && wu < 3) {
            e_expect(bars + 8 * B_WO, 16384);
            e_tma2d(sb + SM_WO + wu * 16384, tWo, (wu >> 1) * 512 + qd * 128 + (wu & 1) * 64, head * DH, bars + 8 * B_WO);
            e_tma2d(sb + SM_WO + wu * 16384 + 8192, tWo, (wu >> 1) * 512 + qd * 128 + (wu & 1) * 64, head * DH + 64, bars + 8 * B_WO);
        }
        if (wg == 1 && warp0) {
            if (lane == 0) mbar_arrive_cluster(bars + 8 * B_HE, j ^ 1);
            mbar_wait_w(bars + 8 * B_HE, 0);
#pragma unroll 1
            for (int i = 0; i < 2; i++) h_load(sb, hsrc, i, j, head);
        }
    }
    const uint32_t mrow = wg < 2 ? mem_row(wu >> 1, wg * 2 + (wu & 1), qd) : mem_row(kh, wu, 0);
    const uint32_t u_m = mrow - wu * 512, u_e = mrow + 512 - wu * 64;
#define TAB(i) lds1(sb + SM_TAB + (i) * 512 + (G16() >> 2))
    {
        const uint32_t r8 = lane & 7;
        const uint32_t tb = sb + SM_TAB + wg * 1536 + t * 4, ma = sb + SM_HB + 4096 + r8 * 128;
        if (wg < 2) {
            sts1(tb, sb + SM_WO + wi * 16384 + frow + ((fx ^ (2 * wg)) << 4));
            sts1(tb + 512, wl0);
            sts1(tb + 1024, ma + (((lane >> 3) ^ r8) << 4));
        } else {
            sts1(tb, ma + (wi & 1) * HBK + ((((wi & 2) + (lane >> 4) * 4 + ((lane >> 3) & 1)) ^ r8) << 4));
            sts1(tb + 512, ((((wi & 2) + 4) ^ r8) << 4) + ((lane & 3) == 2 ? ma + 128 + ((wi & 1) + (lane >> 3) * 2) * HBK : sb + SM_HB - 128));
            sts1(tb + 1024, mem_row(role >> 6, (role >> 4) & 3, (role >> 2) & 3) + (lane < 8 ? qd * 128 + lane * 16 : 512 + qd * 32 + (lane & 1) * 16));
        }
    }
#define HB(ks) dadd(mkdesc(SB0 + SM_HB + ((ks) >> 2) * HBK + ((ks) & 3) * 32, 16, 1024, 1), hbo)
#define STEP_CONSTS                                                                                  \
    const uint32_t tag = (s & 1) ^ 1, ttag = ((s >> 1) & 1) ^ 1, tso = (s & 1) * 32768;              \
    G16();                            \
    const int p = s + 2, b = p & 1;                                                                  \
    uint32_t hbo = b * 4096, fz[5] = {0, 0, 0, 0, 0};                                                   \
    const uint32_t ftag = (((p - 1) >> 1) & 1) ^ 1, ptag = ((p >> 1) & 1) ^ 1;                       \
    const uint32_t pso = tbw + (1 << 20) + (b ^ 1) * 32768 + j * 16384 + kh * 2048;
#define SCHED_FENCE(i) fz[i] = clk32();
#define FZ ((fz[0] | fz[1] | fz[2] | fz[3] | fz[4]) & zero)
#define BLOCK_FENCE asm volatile("pmevent 0;" ::: "memory");
    constexpr int GAP = 32 / NL;
#define l16 (sbl + g16)
#define g8 (g16 >> 1)
    uint4 u, v;
    uint8_t *pdst, *fdst;
    auto tok_pack = [&](int ty, const float* acc, uint32_t ftag, uint32_t ptag, bool later = false) {
        const bool tg = ty == 2 || !(g16 & 64);
        const uint32_t add = tg ? (ftag ^ 1) << 16 : 0u, keep = tg ? 0xfffe0000u : ~0u;
        const uint32_t add1 = ty == 2 ? 0u : add, keep1 = ty == 2 ? ~0u : keep;
        const uint32_t add2 = ty == 0 ? add : 0u, keep2 = ty == 0 ? keep : ~0u;
        v = {pack2(pretag(acc[0], add, keep), pretag(acc[1], add1, keep1)), pack2(acc[2], acc[3]),
             pack2(pretag(acc[4], add2, keep2), pretag(acc[5], add2, keep2)), pack2(acc[6], acc[7])};
        if (ty < 2) { v.x = movm(v.x); v.z = movm(v.z); v.y = movm(v.y); v.w = movm(v.w); }
        u = {settag(pack2(pretag(acc[8], (ptag ^ 1) << 16, 0xfffe0000u), acc[9]), ptag), pack2(acc[10], acc[11]), pack2(acc[12], acc[13]), pack2(acc[14], acc[15])};
        if (later) return;
        v.x = settag(v.x, ftag);
        if (ty == 0) v.z = settag(v.z, ftag);
    };

#pragma unroll 1
    for (int s = -2; s < 0; s++) {
        STEP_CONSTS
        (void)tag; (void)ttag; (void)tso; (void)fz;
        float acc[16];
        mbar_wait_w(bars + 8 * (B_HB + b), 0);
        wg_fence();
#pragma unroll
        for (int i = 0; i < 32; i++) {
            if (i < NL) wgmma_ss32(acc, dadd(mkdesc(SB0 + i * 2048, 8192, 1024, 1), wg * 4096), HB(i), i != 0);
            else wgmma_rs32(acc, w[i < NL ? 0 : i - NL], HB(i), 1);
        }
        wg_commit();
        uint4 pa = {0, 0, 0, 0};
        int it = 0;
#pragma unroll 1
        while ((p > 0) & any_bit0(pa.x ^ ftag) & (++it < POLL_LIMIT)) pa = ldg_b128(arena + (pso + g16));
        pdst = arena + ((pso ^ (32768 + 2048)) + G16());
        fdst = arena + ((b ^ 1) * 32768 + u_to + g16);
        wg_wait<0>();
#pragma unroll
        for (int k = 0; k < 4; k++) { acc[2 * k] += bflo((&pa.x)[k]); acc[2 * k + 1] += bfhi((&pa.x)[k]); }
        tok_pack(wg, acc, ftag, ptag);
        stg_b128_if(true, pdst, u.x, u.y, u.z, u.w);
        stg_b128_if(p > 0 && wg, fdst, v.x, v.y, v.z, v.w);
        if (p > 0 && !wg) { stg_rlx2(fdst - lane * 8, v.x, v.y); stg_rlx2(fdst - lane * 8 + 256, v.z, v.w); }
        if (p == 0) {
            if (wg != 1) bar_arrive(NB_C, 288);
        }
    }
    if (wg == 1 && warp0) {
        wait_count_w(&g_tick[32 + (lane & 3) * 8], 2);
        asm volatile("fence.proxy.async.global;" ::: "memory");
        bar_sync(NB_C, 288);
        if (g16 == 0) mbar_arrive_cluster(bars + 8 * B_HE, j ^ 1);
        mbar_wait_w(bars + 8 * B_HE, 1);
        h_load(sb, hsrc, 2, j, head);
    }

    auto qk_loop = [&](auto wgc) {
        constexpr int WG = decltype(wgc)::value;
        uint32_t w0[NL][4], lm0;
        auto w0_load = [&]() {
            const uint32_t wl = TAB(WG * 3 + 1);
            lm0 = TAB(WG * 3 + 2);
#pragma unroll
            for (int k = 0; k < NL; k++) ldsm4t(w0[k], wl + k * 2048);
        };
        const uint32_t wlo = WG * 65536 - SM_WO - wu * 16384, wlx = __reduce_max_sync(~0u, (wi ^ WG) << 5);
        uint32_t tq0, lm, lm1, dx2 = dly.x2;
        auto proj_pre = [&](int s) {
            uint32_t wz0 = zero;
#pragma unroll
            for (int k = 0; k < NL; k += 2) wz0 = and3(wz0, w0[k][0], w0[k + 1 < NL ? k + 1 : k][0]);
            lm = lm0 + (s & 1) * 65536 + wz0; lm1 = lm ^ 64;
            asm volatile("" : "+r"(lm), "+r"(lm1));
        };
        auto proj = [&](int s, auto mid) {
            bar_sync(NB_MEM, 384);
            float c[4][4];
            constexpr int PD = WG ? 5 : 3;
            uint32_t bf[16][4], tq1;
#pragma unroll
            for (int it = 0; it < PD; it++) ldsm4(bf[it], (it & 1 ? lm1 : lm) + (it >> 1) * HBK);
            mid(-1);
#pragma unroll
            for (int it = 0; it < 16; it++) {
                const uint32_t* bfr = bf[it];
                if (it + PD < 16) ldsm4(bf[it + PD < 16 ? it + PD : 0], ((it + PD) & 1 ? lm1 : lm) + ((it + PD) >> 1) * HBK);
                const uint32_t* wa = 2 * it < NL ? w0[2 * it < NL ? 2 * it : 0] : w[2 * it < NL ? 0 : 2 * it - NL];
                const uint32_t* wb = 2 * it + 1 < NL ? w0[2 * it + 1 < NL ? 2 * it + 1 : 0] : w[2 * it + 1 < NL ? 0 : 2 * it + 1 - NL];
                float *ca = c[(2 * it) & 3], *cb = c[(2 * it + 1) & 3];
                if (it < 2) { mma16816z(ca, wa, bfr[0], bfr[1]); mma16816z(cb, wb, bfr[2], bfr[3]); }
                else { mma16816(ca, wa[0], wa[1], wa[2], wa[3], bfr[0], bfr[1]); mma16816(cb, wb[0], wb[1], wb[2], wb[3], bfr[2], bfr[3]); }
                mid(it);
                if (it == 15) { tq1 = clk32(); bar_arrive(NB_QK, 384); }
            }
            const uint32_t xo = u_xo + (G16() >> 1);
            float r[4];
#pragma unroll
            for (int e = 0; e < 4; e++) {
                constexpr float SH = SM_L2E / 4096;
                r[e] = WG ? (c[0][e] + c[1][e]) + (c[2][e] + c[3][e]) : fmaf(c[2][e] + c[3][e], SH, (c[0][e] + c[1][e]) * SH);
            }
            const uint32_t r0 = pack2(r[0], r[1]), r1 = pack2(r[2], r[3]);
            const uint32_t m0 = movm(r0), m1 = movm(r1);
            tq0 = clk32();
            stg_rlx2(arena + xo, settag(m0, (s & 1) ^ 1), m1);
            tq0 += tq1 & zero;
        };
        w0_load();
        proj_pre(0);
        if (WG == 1) bar_sync(NB_P, 256);
        proj(0, [](int) {});
        if (WG == 0) mbar_wait_w(bars + 8 * B_WO, 0);
#pragma unroll 1
        for (int s = 0;; s++) {
            STEP_CONSTS
            uint4 pa;
            float acc[16];
            auto acc_init = [&]() {
#pragma unroll
                for (int k = 0; k < 4; k++) { acc[2 * k] = bflo((&pa.x)[k]); acc[2 * k + 1] = bfhi((&pa.x)[k]); acc[8 + 2 * k] = __uint_as_float((&pa.x)[k] & zero); acc[9 + 2 * k] = __uint_as_float(~(&pa.x)[k] & zero); }
            };
            uint32_t wf[NPF][4], a3;
#define WF(f) ((a3 ^ (((f) & 1) * 64)) + ((f) >> 1) * 2048)
            if (WG == 1) {
                float sc[5][4];
                uint32_t sx0 = sb + SM_SX - wu * (2560 - 16) + G16() * 5;
                asm volatile("" : "+r"(sx0));
                int it = 0;
                bool bad;
#pragma unroll 1
                do {
                    uint4 kf[2][2];
                    U2 qf[2], x[8];
                    const uint32_t gz = g16 | (it & zero);
                    const uint8_t *ts = arena + (tso + tbw + gz), *tq = arena + (tso + tbq + (gz >> 1)), *xp = arena + (xso + (gz >> 1));
#pragma unroll
                    for (int a = 0; a < 4; a++) kf[a >> 1][a & 1] = ldg_b128(ts + (a >> 1) * 16384 + (a & 1) * 2048);
                    spin_until(tq0, dx2 - 100);
#pragma unroll
                    for (int a = 0; a < 2; a++) qf[a] = ldg_u2(tq + a * 16384);
                    spin_until(tq0, dx2);
#pragma unroll
                    for (int i = 0; i < 8; i++) x[i] = ldg_u2(xp + (i >> 2) * 16384 + (i & 3) * 1024);
                    const uint32_t q0[4] = {hadd2(x[0].x, x[1].x), qf[0].x, hadd2(x[0].y, x[1].y), qf[0].y};
                    const uint32_t q1[4] = {hadd2(x[2].x, x[3].x), qf[1].x, hadd2(x[2].y, x[3].y), qf[1].y};
                    const uint32_t bt = ((qf[0].x ^ ttag) | (qf[1].x ^ ttag)) | ((kf[0][0].x ^ ttag) | (kf[0][1].x ^ ttag)) | ((kf[1][0].x ^ ttag) | (kf[1][1].x ^ ttag));
                    uint32_t bx = 0;
#pragma unroll
                    for (int i = 0; i < 8; i += 2) bx |= (x[i].x ^ tag) | (x[i + 1].x ^ tag);
                    mma16816z(sc[0], q0, kf[0][0].x, kf[0][0].y);
                    mma16816z(sc[1], q0, kf[0][0].z, kf[0][0].w);
                    mma16816z(sc[2], q0, kf[0][1].x, kf[0][1].y);
                    mma16816z(sc[3], q0, kf[0][1].z, kf[0][1].w);
                    mma16816z(sc[4], q0, hadd2(x[4].x, x[5].x), hadd2(x[4].y, x[5].y));
                    bad = any_bit0(bt | bx) & (++it < POLL_LIMIT);
                    mma16816(sc[0], q1[0], q1[1], q1[2], q1[3], kf[1][0].x, kf[1][0].y);
                    mma16816(sc[1], q1[0], q1[1], q1[2], q1[3], kf[1][0].z, kf[1][0].w);
                    mma16816(sc[2], q1[0], q1[1], q1[2], q1[3], kf[1][1].x, kf[1][1].y);
                    mma16816(sc[3], q1[0], q1[1], q1[2], q1[3], kf[1][1].z, kf[1][1].w);
                    mma16816(sc[4], q1[0], q1[1], q1[2], q1[3], hadd2(x[6].x, x[7].x), hadd2(x[6].y, x[7].y));
                } while (bad);
                sts4(sx0, pack_h2(sc[0][0], sc[0][1]), pack_h2(sc[1][0], sc[1][1]), pack_h2(sc[2][0], sc[2][1]), pack_h2(sc[3][0], sc[3][1]));
                sts1(sx0 + 64 - wu * 12, pack_h2(sc[4][0], sc[4][1]));
                bar_arrive(NB_X1, 384);
                if (it > 1 && s > 1) dx2 += dly.more2;
                auto tok_sts = [&]() {
#pragma unroll
                    for (int n = 0; n < 5; n++) sts2(sb + SM_SX + 2560 + g8 + n * 1088, sc[n][2], sc[n][3]);
                };
                a3 = TAB(WG * 3);
                if (s == 0) mbar_wait_w(bars + 8 * B_WO, 0);
                softmax_rows(sb + SM_SX + 2560, sb + SM_PX + 1024, g16 | (clk32() & zero), qd * 8, [&]() { BLOCK_FENCE tok_sts(); bar_sync(NB_PX, 128); }, [&]() {
                    BLOCK_FENCE
#pragma unroll
                    for (int f = 0; f < NE1; f++) ldsm4t(wf[f], WF(f));
                    BLOCK_FENCE
                });
            } else {
                a3 = TAB(WG * 3);
                if (warp1 && (s & 3) == 1) asm volatile("fence.proxy.async.global;" ::: "memory");
                spin_until(tq0, dly.pa);
                uint4 x, y;
                int it = 0;
#pragma unroll 1
                do { x = ldg_b128(arena + (pso + g16)); y = ldg_b128(arena + (pso + tokbase(1) - tokbase(0) + g16)); }
                while ((p <= NSEG) & any_bit0(xor_or(x.x, y.x, ftag)) & (++it < POLL_LIMIT));
                sts4(sb + SM_PA + g16, x.x, x.y, x.z, x.w);
                sts4(sb + SM_PA + 2048 + g16, y.x, y.y, y.z, y.w);
                bar_sync(NB_X1, 384);
                if (g16 < 32) asm volatile("red.relaxed.gpu.global.max.u32 [%0], %1; red.relaxed.gpu.global.add.u32 [%0+4], 1;"
                                                    ::"l"(arena + ((blk(LB_TIME, 0) ^ (g16 << 8)) + qd * 1024 + (tq0 & zero))), "r"(gtime()) : "memory");
                __syncwarp();
                const uint32_t tx = clk32();
                spin_until(tx, dly.w2);
            }
#pragma unroll
            for (int f = WG ? NE1 : 0; f < NPF; f++) ldsm4t(wf[f], WF(f));
            if (s + 1 == NSEG) { bar_arrive(NB_X2, 384); break; }
            const uint32_t oa = l16 + SM_OX, slot = mem_slot(s + 1);
            float c[4][4];
            uint32_t ob[4][4];
            BLOCK_FENCE
            bar_sync(NB_X2, 384);
            ldsm4t(ob[0], oa);
            ldsm4t(ob[1], oa + 512);
            SCHED_FENCE(0)
#pragma unroll
            for (int f = 0; f < 16; f++) {
                const uint32_t *a = wf[f % NPF], *o = ob[f >> 2] + (f & 2);
                if (f < 4) mma16816z(c[f], a, o[0], o[1]);
                else mma16816(c[f & 3], a[0], a[1], a[2], a[3], o[0], o[1]);
                if (f == 3) ldsm4t(ob[2], oa + 1024);
                if (f == 5) { ldsm4t(ob[3], oa + 1536); if (NPF < 16) ldsm4t(wf[0], WF(NPF)); }
                if (f == 7) {
#pragma unroll
                    for (int k = NPF + 1; k < 16; k++) ldsm4t(wf[k - NPF], WF(k));
                }
                if (f == 3 || f == 5 || f == 7) SCHED_FENCE(f / 2)
                if (f == 11) {
#pragma unroll
                    for (int k = NL - W0_E; k < NL; k++) ldsm4t(w0[k], (a3 ^ wlx) + wlo + k * 2048);
                    SCHED_FENCE(4)
                }
            }
            const float last = c[1][3] + c[3][3], one = __uint_as_float(CNT1 << 16);
            red_mem(arena + (u_m + slot + G16()), pack2(c[0][0] + c[2][0], c[0][1] + c[2][1]), pack2(c[0][2] + c[2][2], c[0][3] + c[2][3]),
                    pack2(c[1][0] + c[3][0], c[1][1] + c[3][1]), pack2(c[1][2] + c[3][2], g16 & 16 ? one : last),
                    arena + (u_e + slot + ((g16 >> 3) & ~3u)), pack2(last, one), g16 & 16);
            hbo += FZ;
            constexpr int NS = NL - W0_RS, GS = (32 - NL + NS) / NS;
            BLOCK_FENCE
#pragma unroll
            for (int k = NL - W0_E - 1; k >= 0; k--) ldsm4t(w0[k], (a3 ^ wlx) + wlo + k * 2048);
            lm0 = TAB(WG * 3 + 2);
            if (WG == 1) pa = lds4(sb + SM_PA + 2048 + g16);
            if (WG == 0) {
                bar_arrive(NB_WIN, 384);
                pa = lds4(sb + SM_PA + g16);
                acc_init();
                asm volatile("" : F16(acc, 0));
                BLOCK_FENCE
            }
            wg_fence();
            bar_sync(WG ? NB_WIN : NB_B, WG ? 384 : 256);
#pragma unroll
            for (int i = 0; i < 32; i++) {
                const int k = i / GS;
                if (i >= 32 - NL + NS) wgmma_rs32(acc, w0[i < 32 - NL + NS ? 0 : i - 32 + NL], HB(i - 32 + NL), 1);
                else if (i % GS == GS - 1 && k < NS) wgmma_ss32(acc, mkdesc(SB0 + WG * 65536 + k * 2048, 8192, 1024, 1), HB(k), 1);
                else wgmma_rs32(acc, w[i - (k < NS ? k : NS)], HB(NL + i - (k < NS ? k : NS)), WG == 0 || i);
                if (WG == 1 && i == G_AT) bar_arrive(NB_B, 256);
                if (WG == 1 && i == 31 - NL + NS) wg_fence();
            }
            wg_commit();
            BLOCK_FENCE
            if (WG == 1 && warp0 && !(s & 3)) wait_count_w(&g_tick[32 + ((G16() >> 4) & 3) * 8], min((s + 1) / 4 + 3, 17));
            auto tok_store = [&](int m) {
                if (m & 1) {
                    if (WG) stg_b128_if(true, arena + ((b ^ 1) * 32768 + u_to + G16()), v.x, v.y, v.z, v.w);
                    else {
                        uint8_t* d = arena + ((b ^ 1) * 32768 + u_to + wu * 256 + (G16() >> 1));
                        stg_rlx2(d, v.x, v.y); stg_rlx2(d + 256, v.z, v.w);
                    }
                }
                if (m & 2) stg_b128_if(p < NSEG, arena + ((pso ^ (32768 + 2048)) + G16()), u.x, u.y, u.z, u.w);
            };
            if (WG == 0) proj_pre(s + 1);
            BLOCK_FENCE
            wg_wait<0>();
            if (WG == 0) {
                asm volatile("" : F16(acc, 0));
                proj(s + 1, [&](int it) {
                    if (it < 0) {
                        SCHED_FENCE(0)
                        asm volatile("" : F16(acc, 0));
                        tok_pack(WG, acc, ftag, ptag, true);
                        tok_store(2);
                        SCHED_FENCE(1)
                    }
                    if (it == 2) { SCHED_FENCE(2) v.x = settag(v.x, ftag); v.z = settag(v.z, ftag); tok_store(1); SCHED_FENCE(3) }
                });
                tq0 += (fz[0] | fz[1] | fz[2] | fz[3]) & zero;
            } else {
#pragma unroll
                for (int k = 0; k < 4; k++) { acc[2 * k] += bflo((&pa.x)[k]); acc[2 * k + 1] += bfhi((&pa.x)[k]); }
                tok_pack(WG, acc, ftag, ptag);
                proj_pre(s + 1);
                asm volatile("" : "+r"(u.x), "+r"(u.y), "+r"(u.z), "+r"(u.w), "+r"(v.x), "+r"(v.y), "+r"(v.z), "+r"(v.w));
                BLOCK_FENCE
                bar_sync(NB_P, 256);
                tok_store(3);
                proj(s + 1, [](int) {});
            }
        }
    };
    if (wg == 0) {
        qk_loop(IC<0>());
    } else if (wg == 1) {
        qk_loop(IC<1>());
    } else {
        const uint32_t ONES = 0x3f803f80u, u_o = qd * 65536 + head * 2048 + wu * 384;
        uint32_t tw = 0, dl = 0, dbase = kh == mypar ? dly.near : dly.far, dst0, dx0;
        dst0 = TAB(6); dx0 = TAB(7);
        uint32_t ov[4] = {0, 0, 0, 0};
        auto o_store = [&](int s) {
            uint8_t* od = (uint8_t*)g_O + (uint32_t)(s * (32 * NH * DH * 2) + u_o + (G16() >> 2));
#pragma unroll
            for (int a = 0; a < 4; a++) stg_rlx1(od + a * 128, ov[a]);
        };
        uint4 vf[2][2], pa;
        auto tok_fetch = [&](int s) {
            const uint8_t* ts = arena + ((s & 1) * 32768 + tbw + g16);
#pragma unroll
            for (int a = 0; a < 4; a++) vf[a >> 1][a & 1] = ldg_b128(ts + (a >> 1) * 16384 + (a & 1) * 2048);
            pa = ldg_b128(arena + (tbw + (1 << 20) + (~s & 1) * 32768 + j * 16384 + kh * 2048 + g16));
        };
        tok_fetch(0);
#pragma unroll 1
        for (int s = 0;; s++) {
            STEP_CONSTS
#define VFBAD ((vf[0][0].x ^ ttag) | (vf[0][1].x ^ ttag) | (vf[1][0].x ^ ttag) | (vf[1][1].x ^ ttag))
#define TOKBAD (VFBAD | (p <= NSEG ? pa.x ^ ftag : 0))
            {
                const uint32_t dst = dst0 + b * 65536, dx = dx0 + b * 65536;
                const uint8_t *ms = arena + (u_m + mem_slot(s) + g16), *me = arena + (u_e + mem_slot(s) + ((g16 >> 3) & ~3u));
                uint32_t em = g16 & 16 ? 0u : ~0u;
                asm volatile("" : "+l"(ms), "+l"(me), "+r"(em));
                spin_until(tw, dl);
                int it = 0;
                bool bad;
#pragma unroll 1
                do {
                    uint4 m[4];
                    uint32_t x[4];
#pragma unroll
                    for (int i = 0; i < 4; i++) m[i] = ldg_rlx4(ms + i * 1024);
#pragma unroll
                    for (int i = 0; i < 4; i++) x[i] = ldg_rlx1(me + i * 1024);
#pragma unroll
                    for (int i = 0; i < 3; i++) {
                        stsm4t(dst + i * 2 * HBK, m[i].x, m[i].y, m[i].z, m[i].w);
                        if (i == 1) asm volatile("{.reg .pred p; setp.eq.s32 p, %0, 0; @p bar.arrive %1, 256;}" ::"r"(it), "n"(NB_P) : "memory");
                    }
                    uint32_t c = m[0].w & m[1].w, r, msk = ~(it << 16) & CNT_ALL << 16;
                    asm volatile("" : "+r"(c), "+r"(msk));
                    SCHED_FENCE(1)
                    stsm4t(dst + 6 * HBK, m[3].x, m[3].y, m[3].z, m[3].w);
                    stsm4t(dx, x[0], x[1], x[2], x[3]);
                    asm volatile("{.reg .pred p, q; .reg .b32 t, u; lop3.b32 t, %1, %2, %3, 0x80; lop3.b32 u, %4, %5, %6, 0x80; lop3.b32 t, t, %8, %7, 0xa8;\n"
                                 " lop3.b32 t, t, u, %9, 0x2a; setp.ne.u32 p, t, 0; vote.sync.any.pred q, p, 0xffffffff; @!q bar.arrive %10, 384; selp.u32 %0, 1, 0, q;}"
                                 : "=r"(r) : "r"(c), "r"(m[2].w), "r"(m[3].w), "r"(x[0]), "r"(x[1]), "r"(x[2]), "r"(x[3]), "r"(em), "r"(msk), "n"(NB_MEM) : "memory");
                    bad = r; it++;
                } while (bad);
                if (it > 1 && s > 1) dbase += dly.more;
            }
            o_store(max(s - 1, 0));
            fence_async_smem();
            hbo += fz[1] & zero;
            int it = 0;
#pragma unroll 1
            while (any_bit0(TOKBAD) & (++it < POLL_LIMIT)) tok_fetch(s + (it & zero));
            float acc[20];
#pragma unroll
            for (int k = 0; k < 4; k++) { acc[2 * k] = bflo((&pa.x)[k]); acc[2 * k + 1] = bfhi((&pa.x)[k]); acc[8 + 2 * k] = acc[9 + 2 * k] = acc[16 + k] = __uint_as_float(pa.x & zero); }
            if (p <= NSEG) mbar_wait_w(bars + 8 * (B_HB + b), (p >> 1) & 1);
            asm volatile("" : F16(acc, 0), F4(acc, 16));
            BLOCK_FENCE
            wg_fence();
            bar_sync(NB_QK, 384);
#pragma unroll
            for (int i = 0; i < 32; i++) {
                const int k = i / GAP;
                if (i % GAP == GAP - 1 && k < NL) wgmma_ss40(acc, mkdesc(SB0 + 131072 + k * 2048, 8192, 1024, 1), HB(k), 1);
                else wgmma_rs40(acc, w[i - (k < NL ? k : NL)], HB(NL + i - (k < NL ? k : NL)), 1);
            }
            wg_commit();
            uint8_t* vo = arena + (u_xo + (G16() >> 1));
            pdst = arena + ((pso ^ (32768 + 2048)) + G16());
            fdst = arena + ((b ^ 1) * 32768 + u_to + g16);
            BLOCK_FENCE
            wg_wait<0>();
            stg_rlx2(vo, settag(pack2(acc[16], acc[17]), tag), pack2(acc[18], acc[19]));
            const uint32_t tv = clk32();
            tok_pack(2, acc, ftag, ptag);
            stg_b128_if(p <= NSEG, fdst, v.x, v.y, v.z, v.w);
            stg_b128_if(p < NSEG, pdst, u.x, u.y, u.z, u.w);
            const uint8_t* xp = arena + (xso + 32768 + (G16() >> 1));
            const uint32_t sxa = sb + SM_SX - wu * 2560 + G16() * 5;
            uint32_t sel[2];
            {
                const uint32_t q = (G16() >> 4 ^ g16 >> 6 & 1) & 3;
                sel[0] = q == 0 ? 0x3c00 : 0; sel[1] = q == 2 ? 0x3c00 : 0;
                asm volatile("" : "+r"(sel[0]), "+r"(sel[1]));
            }
            uint32_t xv[4], gt = 0;
            auto pv = [&](uint32_t p0, uint32_t p1, uint32_t p2, uint32_t p3, uint32_t p4, auto getv, auto done) {
                float oc[2][4], lc[4] = {0.f, 0.f, 0.f, 0.f};
                mma16816(lc, ONES, ONES, ONES, ONES, p0, p1);
                mma16816z(oc[0], &vf[0][0].x, p0, p1);
                mma16816z(oc[1], &vf[1][0].x, p0, p1);
                mma16816(lc, ONES, ONES, ONES, ONES, p2, p3);
                mma16816(oc[0], vf[0][1].x, vf[0][1].y, vf[0][1].z, vf[0][1].w, p2, p3);
                mma16816(oc[1], vf[1][1].x, vf[1][1].y, vf[1][1].z, vf[1][1].w, p2, p3);
                mma1688(lc, ONES, ONES, p4);
                getv();
                mma1688(oc[0], xv[0], xv[1], p4);
                mma1688(oc[1], xv[2], xv[3], p4);
                done(__float_as_uint(oc[0][0]) | __float_as_uint(oc[1][0]) | __float_as_uint(lc[0]));
                const float r0 = rcp_fast(lc[0]), r1 = rcp_fast(lc[1]);
                ov[0] = pack2(oc[0][0] * r0, oc[0][1] * r1); ov[1] = pack2(oc[0][2] * r0, oc[0][3] * r1);
                ov[2] = pack2(oc[1][0] * r0, oc[1][1] * r1); ov[3] = pack2(oc[1][2] * r0, oc[1][3] * r1);
            };
            bool bad;
            it = 0;
#pragma unroll 1
            do {
                U2 xr[4];
                asm volatile("{.reg .pred p; setp.eq.s32 p, %0, 0; @p bar.sync %1, 384;}" ::"r"(it), "n"(NB_X1) : "memory");
                uint4 sx[5];
#pragma unroll
                for (int i = 0; i < 5; i++) sx[i] = lds4(sxa + i * 16);
                if (it == 0) { gt = gtime(); tw = clk32(); }
                spin_until(tv, dly.v);
#pragma unroll
                for (int i = 0; i < 4; i++) xr[i] = ldg_u2(xp + i * 1024);
                uint32_t h[5], h0[4];
#pragma unroll
                for (int n = 0; n < 4; n++) h0[n] = add_h2((&sx[0].x)[n], (&sx[1].x)[n]);
#pragma unroll
                for (int n = 0; n < 4; n++) h[n] = add_h2(h0[n], add_h2((&sx[2].x)[n], (&sx[3].x)[n]));
                h[4] = add_h2(add_h2(sx[4].x, sx[4].y), add_h2(sx[4].z, sx[4].w));
                uint32_t hm = max_h2(max_h2(max_h2(h[0], h[1]), h[2]), max_h2(h[3], h[4]));
                float2 a[5];
                float mb;
                {
                    float d[2][4];
                    const uint32_t hs = __byte_perm(hm, hm, 0x1032);
#pragma unroll
                    for (int k = 0; k < 2; k++)
                        asm volatile("mma.sync.aligned.m16n8k8.row.col.f32.f16.f16.f32 {%0,%1,%2,%3},{%4,%5},{%6},{%7,%7,%7,%7};"
                                     : "=f"(d[k][0]), "=f"(d[k][1]), "=f"(d[k][2]), "=f"(d[k][3]) : "r"(hm), "r"(hs), "r"(sel[k]), "f"(0.f));
#pragma unroll
                    for (int n = 0; n < 5; n++) a[n] = unpack_h2(h[n]);
                    mb = -4096.0f * fmaxf(fmaxf(fmaxf(d[0][0], d[0][1]), fmaxf(d[0][2], d[0][3])), fmaxf(fmaxf(d[1][0], d[1][1]), fmaxf(d[1][2], d[1][3])));
                }
                uint32_t pm[5];
#pragma unroll
                for (int n = 0; n < 5; n++) pm[n] = pack2(ex2(fmaf(a[n].x, 4096.0f, mb)), ex2(fmaf(a[n].y, 4096.0f, mb)));
                pv(pm[0], pm[1], pm[2], pm[3], pm[4], [&]() {
                    xv[0] = hadd2(xr[0].x, xr[1].x); xv[1] = hadd2(xr[0].y, xr[1].y);
                    xv[2] = hadd2(xr[2].x, xr[3].x); xv[3] = hadd2(xr[2].y, xr[3].y);
                }, [](uint32_t) {});
                bad = any_bit0((xr[0].x ^ tag) | (xr[1].x ^ tag) | (xr[2].x ^ tag) | (xr[3].x ^ tag)) & (++it < POLL_LIMIT);
                stsm4(sb + SM_OX + g16, ov[0], ov[1], ov[2], ov[3]);
            } while (bad);
            bar_sync(NB_X2, 384);
            BLOCK_FENCE
            U2 tv2 = {0, 0};
            const uint8_t* tp = arena + (blk(LB_TIME, mypar) + ((G16() << 6) & 0xc00));
            {
                const uint4 pp = lds4(l16 + SM_PX + 1024);
                const uint32_t p4 = lds1(sb + SM_PX + 512 + 1024 - wu * 128 + (G16() >> 2));
                tv2 = ldg_u2(tp);
                if (warp0 && s + 3 <= NSEG) h_load(sb, hsrc, s + 3, j, head);
                pv(pp.x, pp.y, pp.z, pp.w, p4, []() {}, [&](uint32_t r) { bar_arrive(NB_WIN + (r & zero), 384); });
            }
            dst0 = TAB(6); dx0 = TAB(7);
            const uint32_t zo = TAB(8);
            BLOCK_FENCE
            if (s + 1 == NSEG) break;
            asm volatile("" : "+r"(tv2.y));
            it = 0;
            uint32_t tm = __reduce_max_sync(~0u, tv2.y < 32 * (s + 1) ? ~0u : tv2.x);
#pragma unroll 1
            while ((tm == ~0u) & (++it < 16)) { tv2 = ldg_u2(tp); tm = __reduce_max_sync(~0u, tv2.y < 32 * (s + 1) ? ~0u : tv2.x); }
            const uint32_t e = tm - gt;
            tok_fetch(s + 1);
            stg4_if(g16 < 160, arena + (zo + mem_slot(s + 3)), 0);
            dl = dbase + (e > 4096 ? 0 : e * E_MUL >> 4);
        }
        o_store(NSEG - 1);
    }
}

struct RecMaps { CUtensorMap wq, wk, wv, wo, wmod, w3, w1; };
struct RecPtrs { const bf16 *x, *mem0, *c, *wmod, *w1, *w3; uint8_t* arena; uint32_t zero; const bf16 *w2, *w4, *wo; Delays dly; };

__device__ __forceinline__ float silu_bf(const bf16* c, int i) {
    const float v = __bfloat162float(c[i]);
    return bfround(__fdividef(v, 1.0f + __expf(-v)));
}
#define LN_FREE 6
#define LN_SEQ 0xcba6420987531ull
#define W_LATE 1000
#define W_OPEN 1400
__device__ __noinline__ uint32_t side_window_(const uint8_t* arena, uint32_t n);
#define side_window(arena, n) n = side_window_(arena, n)
__device__ __noinline__ void rec_ln(uint32_t sb, const bf16* x, const uint8_t* arena, int id, int r0) {
    int r1 = 32;
    uint32_t n = 0;
    const int tid = threadIdx.x, lane = tid & 31, wid = __reduce_max_sync(~0u, tid >> 5);
    const uint32_t ring = sb + wid * 8192 + lane * 16, coef = sb + SM_PRE;
    x += (id * 8 + wid) * 2 * DM + lane * 8;
#pragma unroll 1
    for (int r = r0 - 1; r < r1; r++) {
        if (r > 3) side_window(arena, n);
        if (r + 1 < r1) {
#pragma unroll
            for (int i = 0; i < 8; i++)
                asm volatile("cp.async.cg.shared.global [%0], [%1], 16;" ::"r"(ring + (~r & 1) * 4096 + i * 512), "l"(x + (r + 1) * 64 * DM + i * 256) : "memory");
        }
        asm volatile("cp.async.commit_group; cp.async.wait_group 1;" ::: "memory");
        if (r < r0) continue;
        const uint32_t src = ring + (r & 1) * 4096;
        float m[2] = {0.f, 0.f}, rs[2];
#pragma unroll 1
        for (int ps = 0; ps < 2; ps++) {
            float t[2][2] = {{0.f, 0.f}, {0.f, 0.f}};
#pragma unroll 1
            for (int i = 0; i < 2048; i += 512) {
#pragma unroll
                for (int h = 0; h < 2; h++) {
                    const uint4 u = lds4(src + h * 2048 + i);
#pragma unroll
                    for (int e = 0; e < 4; e++) {
                        const float a = bflo((&u.x)[e]) - m[h], c = bfhi((&u.x)[e]) - m[h];
                        t[h][0] = fmaf(a, ps ? a : 1.0f, t[h][0]); t[h][1] = fmaf(c, ps ? c : 1.0f, t[h][1]);
                    }
                }
            }
            rs[0] = t[0][0] + t[0][1]; rs[1] = t[1][0] + t[1][1];
#pragma unroll 1
            for (int o = 16; o; o >>= 1) { rs[0] += __shfl_xor_sync(~0u, rs[0], o); rs[1] += __shfl_xor_sync(~0u, rs[1], o); }
            if (!ps) { m[0] = rs[0] * (1.0f / DM); m[1] = rs[1] * (1.0f / DM); }
        }
        rs[0] = rsqrtf(rs[0] * (1.0f / DM) + 1e-5f); rs[1] = rsqrtf(rs[1] * (1.0f / DM) + 1e-5f);
        if (r == r0) {
#pragma unroll 1
            for (int i = tid; i < 2 * DM / 4; i += 256) {
                float t[4];
                int it = 0;
                uint32_t ok;
#pragma unroll 1
                do {
                    uint4 u[8];
#pragma unroll
                    for (int k = 0; k < 8; k++) u[k] = ldg_rlx4(g_modp + k * 2 * DM + i * 4);
                    ok = 1;
#pragma unroll
                    for (int k = 0; k < 32; k++) { const uint32_t w = (&u[k >> 2].x)[k & 3]; ok &= w; t[k & 3] = k < 4 ? __uint_as_float(w) : t[k & 3] + __uint_as_float(w); }
                } while (!__all_sync(~0u, ok) & (++it < SPIN_LIMIT));
                const float o = i >> 8;
                const uint32_t lo = pack2(t[0], t[1]), hi = pack2(t[2], t[3]);
                sts4f(coef + (i >> 8) * 4096 + (i & 1) * 2048 + ((i & 255) >> 1) * 16, bflo(lo) + o, bfhi(lo) + o, bflo(hi) + o, bfhi(hi) + o);
            }
            bar_sync(NB_FIN0, 256);
        }
        uint8_t* dst = (uint8_t*)g_himg + (r * 2 + (id >> 1)) * 65536 + (lane >> 3) * 4096 + wid * 256;
#pragma unroll 1
        for (int i = 0; i < 4; i++) {
            const uint32_t ca = coef + i * 512 + lane * 16;
            const float4 s0 = lds4f(ca), s1 = lds4f(ca + 2048), c0 = lds4f(ca + 4096), c1 = lds4f(ca + 6144);
            const float sh[8] = {s0.x, s0.y, s0.z, s0.w, s1.x, s1.y, s1.z, s1.w}, sc[8] = {c0.x, c0.y, c0.z, c0.w, c1.x, c1.y, c1.z, c1.w};
#pragma unroll
            for (int h = 0; h < 2; h++) {
                uint4 u = lds4(src + h * 2048 + i * 512);
#pragma unroll
                for (int e = 0; e < 4; e++) {
                    uint32_t& w = (&u.x)[e];
                    w = pack2(fmaf((bflo(w) - m[h]) * rs[h], sc[2 * e], sh[2 * e]), fmaf((bfhi(w) - m[h]) * rs[h], sc[2 * e + 1], sh[2 * e + 1]));
                }
                *(uint4*)(dst + i * 16384 + ((id & 1) == (i >> 1) ? 65536 : 2048) + h * 128 + (((lane ^ (2 * wid + h)) & 7) << 4)) = u;
            }
        }
        if (r == 0) {
            int ro, it = 0;
#pragma unroll 1
            do asm volatile("ld.volatile.shared.u32 %0, [%1];" : "=r"(ro) : "r"(sb + SM_BAR + 192) : "memory"); while ((ro == INT_MIN) & (++it < SPIN_LIMIT));
            if (ro >= 0) r1 = 2;
        }
        if (r && !(r & 1)) continue;
        bar_sync(r ? NB_FIN0 : NB_C, r ? 256 : 320);
        if (wid == (r >> 1 & 7)) {
            if (r == 1) bar_arrive(NB_B, 64);
            if (r == 3) wait_count_w(&g_tick[32 + id * 8], 2);
            if (lane == 0) { signal_count(&g_tick[32 + id * 8]); }
            __syncwarp();
        }
    }
}
__device__ __noinline__ uint32_t side_window_(const uint8_t* arena, uint32_t n) {
    U2 v;
    int it = 0;
#pragma unroll 1
    while (v = ldg_u2(arena + (LB_TIME << 13)), ((v.y >> 5) == n || gtime() - v.x > W_OPEN + W_LATE) && v.y < 32 * NSEG && ++it < 64) __nanosleep(100);
    it = 0;
#pragma unroll 1
    while ((int)(gtime() - v.x - W_OPEN) < 0 && ++it < 256) {}
    return v.y >> 5;
}
#define SIDE_T 300
template <int NQ, int NB>
__device__ __forceinline__ void side_gemv(const CUtensorMap* tm, int c0, int k0, int k1, uint32_t cs, uint32_t sb, const uint8_t* arena, uint32_t& n, uint32_t& ph, float (*acc)[8], bool once = false) {
    const uint32_t w = __reduce_max_sync(~0u, threadIdx.x >> 5 & 3), ring = sb + (NB == 3 ? 65536 : 0) + w * NB * 8192;
    const uint32_t bars = sb + SM_BAR + (NB == 3 ? 8 * B_W + w * 24 : 8 + w * 8), bs = NB == 3 ? 8 : 0;
#pragma unroll
    for (int q = 0; q < NQ; q++)
#pragma unroll
        for (int j = 0; j < 8; j++) acc[q][j] = 0.f;
#pragma unroll 1
    for (; k0 < k1; k0 += NB * 16, ph ^= 1) {
        const int nr = min(NB * 16, k1 - k0);
        side_window(arena, n);
        const uint32_t t0 = clk32();
#pragma unroll 1
        for (int g = 0; g < NB; g++) {
            spin_until(t0, (g * 4 + w) * (SIDE_T / 4));
            if (bs || !g) e_expect(bars + bs * g, !bs ? NB * 8192 : g * 16 < nr ? 8192 : 0);
            if (g * 16 < nr) e_tma2d_hint(ring + g * 8192, tm, c0, k0 + g * 16, bars + bs * g, once ? EVICT_FIRST : EVICT_NORMAL);
        }
#pragma unroll 1
        for (int r = 0; r < nr; r += 16) {
            mbar_wait_w(bars + bs * (r >> 4), ph);
            uint4 v[16];
#pragma unroll
            for (int h = 0; h < 16; h++) v[h] = lds4(ring + (r + h) * 512 + (threadIdx.x & 31) * 16);
            float4 cf[NQ][4];
#pragma unroll
            for (int q = 0; q < NQ * 4; q++) cf[q >> 2][q & 3] = lds4f(cs + ((q >> 2) * DM + k0 + r + (q & 3) * 4) * 4);
#pragma unroll
            for (int h = 0; h < 16; h++) {
                const float f[8] = {bflo(v[h].x), bfhi(v[h].x), bflo(v[h].y), bfhi(v[h].y), bflo(v[h].z), bfhi(v[h].z), bflo(v[h].w), bfhi(v[h].w)};
#pragma unroll
                for (int q = 0; q < NQ; q++)
#pragma unroll
                    for (int j = 0; j < 8; j++) acc[q][j] = fmaf((&cf[q][h >> 2].x)[h & 3], f[j], acc[q][j]);
            }
        }
        fence_async_smem();
        __syncwarp();
    }
}
__device__ __noinline__ void rec_side(float* sm, const RecMaps& mp, const RecPtrs& p, int id) {
    const int tid = threadIdx.x, t = tid & 127, w = __reduce_max_sync(~0u, t >> 5);
    float* coef = sm + (tid < 256 ? 44032 : 40960);
    const uint32_t sb = smem_u32(sm), cs = smem_u32(coef);
    uint32_t n = 0, ph = 0;
    float acc[3][8];
    if (tid < 256) {
        if (blockIdx.x < 128) rec_ln(smem_u32(sm), p.x, p.arena, id, 2);
        for (int i = tid; i < 2 * S_; i += 256) g_st[id * 2 * S_ + i] = 0.f;
        if (id == 0 && tid < 64) g_pcnt[tid * 8] = 0;
        if (id == 1) for (int i = tid; i < 6 * 256; i += 256) g_pflag[i] = 0;
        if (id == 2 && tid == 0) g_pt = 0;
        fence_async_smem();
        bar_sync(NB_FIN0, 256);
        if (PDL && tid == 0) asm volatile("fence.acq_rel.gpu; griddepcontrol.launch_dependents;" ::: "memory");
        if (tid >= 128) return;
        float* red = coef + 3 * DM;
        if (t == 0) wait_count1(&g_tick[8], 4);
        bar_sync(NB_S, 128);
        for (int i = t; i < DM; i += 128) { coef[i] = 1.0f + __ldcg(g_mod + 4 * DM + i); coef[DM + i] = __ldcg(g_mod + 3 * DM + i); coef[2 * DM + i] = 1.0f; }
        bar_sync(NB_S, 128);
        if (id == 1 && t < 32) {
            float u[5] = {0, 0, 0, 0, 0};
            for (int i = t; i < DM; i += 32) {
                const float a = coef[i], b = coef[DM + i];
                u[0] += a; u[1] += a * a; u[2] += a * b; u[3] += b; u[4] += b * b;
            }
#pragma unroll
            for (int q = 0; q < 5; q++) { const float r = warp_sum(u[q]); if (t == 0) g_cst[q] = r * (1.0f / DM); }
        }
        side_gemv<3, 2>(&mp.w1, id * 256, w * 256, w * 256 + 256, cs, sb, p.arena, n, ph, acc);
#pragma unroll
        for (int q = 0; q < 3; q++)
#pragma unroll
            for (int j = 0; j < 8; j++) red[((t >> 5) * 3 + q) * 256 + (t & 31) * 8 + j] = acc[q][j];
        bar_sync(NB_S, 128);
        for (int i = t; i < 768; i += 128) g_vec[(i >> 8) * DM + id * 256 + (i & 255)] = (red[i] + red[768 + i]) + (red[1536 + i] + red[2304 + i]);
        return;
    }
    for (int i = t; i < DM; i += 128) { coef[i] = silu_bf(p.c, i); coef[2 * DM + i] = 1.0f; }
    if (t == 0) wait_count1(&g_tick[32], 1);
    bar_sync(NB_G, 128);
    side_gemv<1, 3>(&mp.wmod, (2 + id) * DM + w * 256, 0, DM, cs, sb, p.arena, n, ph, acc, true);
#pragma unroll
    for (int j = 0; j < 8; j++) g_mod[(2 + id) * DM + t * 8 + j] = bfround(acc[0][j]);
    bar_sync(NB_G, 128);
    if (t == 0) signal_count(&g_tick[8]);
    side_gemv<1, 3>(&mp.w3, id * (FF / 4) + w * 256, 0, DM, cs + 8 * DM, sb, p.arena, n, ph, acc);
    if (t < FF / 32) {
#pragma unroll
        for (int j = 0; j < 8; j++) g_vec[3 * DM + id * (FF / 4) + t * 8 + j] = acc[0][j];
    }
}

__global__ void __cluster_dims__(2, 1, 1) __launch_bounds__(384, 1)
k_rec(const __grid_constant__ RecMaps mp, const __grid_constant__ RecPtrs p) {
    extern __shared__ uint8_t smraw[];
    const uint32_t sb = smem_u32(smraw);
    if ((sb & 0x3FFFF) != SB0) __trap();
    const uint32_t bars = sb + SM_BAR;
    const int tid = threadIdx.x, lane = tid & 31, b = blockIdx.x;
    const int wid = __reduce_max_sync(~0u, tid >> 5);
    const uint32_t rank = b & 1;
    uint8_t* arena = p.arena;
    volatile int* sinfo = (volatile int*)(smraw + SM_BAR + 192);
    if (tid == 0) sinfo[0] = INT_MIN;
    if (tid == 352) {
        for (int i = 0; i < 17; i++) mbar_init(bars + 8 * i, i == B_WO ? 4 : 1);
        asm volatile("fence.mbarrier_init.release.cluster;" ::: "memory");
    }
    __syncwarp();
    asm volatile("barrier.cluster.arrive.relaxed.aligned;" ::: "memory");
    int pr = 0, hA = 0;
    if (wid < 8) {
        if (b < 128) {
            const int cb = (b & 15) * 128, k0 = (b >> 4) * 128 + (tid >> 4);
            uint4 v[8];
#pragma unroll
            for (int i = 0; i < 8; i++) v[i] = __ldg((const uint4*)(p.wmod + (size_t)(k0 + 16 * i) * (6 * DM) + cb + (tid & 15) * 8));
            float acc[8] = {0, 0, 0, 0, 0, 0, 0, 0};
            const float s8 = silu_bf(p.c, k0 + 16 * (lane & 7));
#pragma unroll
            for (int i = 0; i < 8; i++) {
                const float sv = __shfl_sync(~0u, s8, i, 16);
                acc[0] += sv * bflo(v[i].x); acc[1] += sv * bfhi(v[i].x); acc[2] += sv * bflo(v[i].y); acc[3] += sv * bfhi(v[i].y);
                acc[4] += sv * bflo(v[i].z); acc[5] += sv * bfhi(v[i].z); acc[6] += sv * bflo(v[i].w); acc[7] += sv * bfhi(v[i].w);
            }
            float* red = (float*)(smraw + SM_PRE);
            *(float4*)(red + (tid >> 4) * 128 + (tid & 15) * 8) = make_float4(acc[0], acc[1], acc[2], acc[3]);
            *(float4*)(red + (tid >> 4) * 128 + (tid & 15) * 8 + 4) = make_float4(acc[4], acc[5], acc[6], acc[7]);
            bar_sync(NB_FIN0, 256);
            if (wid < 4) {
                float t = 0;
#pragma unroll
                for (int i = 0; i < 16; i++) t += red[i * 128 + tid];
                stg_rlx1(&g_modp[(b >> 4) * 2 * DM + cb + tid], __float_as_uint(t) | 1u);
            }
        } else {
            rec_ln(sb, p.x, p.arena, b - 128, 0);
        }
    } else if (wid >= 10 && b >= 128) {
        {
            const int w = (b - 128) * 2 + wid - 10;
            const uint16_t* src = (const uint16_t*)p.mem0 + (lane & 3) * 2 * DM + (w >> 2) * 512 + (w & 1) * 64 + (w & 2) * 8 + (lane >> 2);
            uint32_t v[4][4];
#pragma unroll
            for (int i = 0; i < 16; i++) v[i >> 2][i & 3] = src[(i >> 2) * 128 + (i & 2) * 16 + (i & 1) * 8] | ((uint32_t)src[DM + (i >> 2) * 128 + (i & 2) * 16 + (i & 1) * 8] << 16);
            uint8_t* d = arena + mem_row(w >> 2, w & 3, 0);
            uint8_t* e = d + 512 + (lane >> 1) * 4;
            d += lane * 16;
#pragma unroll
            for (int i = 0; i < 4; i++, d += 1024, e += 1024) {
                stg_rlx4(d, v[i][0], v[i][1], v[i][2], lane & 1 ? (v[i][3] & 0xffff) | CNT_ALL << 16 : v[i][3]);
                stg_rlx4(d + mem_slot(1), 0, 0, 0, 0);
                stg_rlx4(d + mem_slot(2), 0, 0, 0, 0);
                if (lane & 1) { stg_rlx1(e, v[i][3] >> 16 | CNT_ALL << 16); stg_rlx1(e + mem_slot(1), 0); stg_rlx1(e + mem_slot(2), 0); }
            }
            if (w == 0 && lane < 8) stg_rlx2(arena + (LB_TIME << 13) + lane * 1024, 0, 0);
            bar_arrive(NB_C, 320);
        }
    } else if (rank == 0) {
        uint32_t best = ~0u;
        const int pg = wid < 10 ? 0 : 1 + (b >> 1) / 22;
        uint32_t* q = (uint32_t*)(arena + (pg << 21) + (pg ? blk(b >> 1, wid & 1) : blk(LB_PROBE, wid & 1) + b * 16));
        if (lane < 8) stg_rlx1(q + lane, 0);
        __syncwarp();
        if (lane == 0) {
            q += 3;
            uint32_t v = p.zero;
#pragma unroll 1
            for (int r = v; r <= NPROBE; r++) {
                const uint32_t t0 = clk32() + (v >> 8);
                v = atomicAdd(q + (v >> 8), 1u);
                uint32_t t1;
                asm volatile("{.reg .pred p; setp.eq.u32 p, %1, 0xffffffff; @p exit; mov.u32 %0, %%clock;}" : "=r"(t1) : "r"(v) : "memory");
                best = min(best, t1 - t0);
            }
            sinfo[wid - 6] = best;
        }
        bar_sync(NB_KDONE, b < 128 ? 128 : 64);
        if (tid == 256) {
            const uint32_t par = sinfo[2] > sinfo[3], vote = b < 128 && (sinfo[4] > sinfo[5]) != par;
            stg_rlx2(&g_clk[b >> 1], ((clk32() - 2 * gtime()) & ~127u) | b >> 1, 1 + 2 * par + 4 * vote);
        }
    }
    if (wid == 8) {
        U2 v[3], my;
        uint32_t c0;
        const int me = b >> 1;
        int it = 0;
        __syncwarp();
#pragma unroll 1
        do {
            my = ldg_u2(&g_clk[me]);
#pragma unroll
            for (int k = 0; k < 3; k++) v[k] = ldg_u2(&g_clk[k * 22 + min(lane, 21)]);
        } while (!__all_sync(~0u, my.y & v[0].y & v[1].y & v[2].y & 1) & (++it < SPIN_LIMIT));
        c0 = __reduce_min_sync(~0u, lane ? ~0u : v[0].x) - 4096;
        const uint32_t mc = me >= 64 ? ~0u : my.x - c0;
        const int par = my.y >> 1 & 1;
        uint32_t cnt = 0, flip = 0;
#pragma unroll
        for (int k = 0; k < 3; k++) {
            const uint32_t c = v[k].x - c0, o = v[k].y >> 1 & 1;
            const bool ln = k == 2 && lane >= 20;
            cnt += o + (o == par ? (ln ? 44 + lane < me : c < mc) * 256 + (c < my.x - c0) * 65536 : 0);
            flip |= __popc(__ballot_sync(~0u, v[k].y & 4) & 0x3fffff) > 10 ? 256 << k : 0;
        }
        cnt = __reduce_add_sync(~0u, lane < 22 ? cnt : 0);
        const int n1 = cnt & 255, n0 = 66 - n1, tk = cnt >> 8 & 255;
        if (lane == 0) g_cls[smid() & 255] = cnt < 32 << 16 ? par * 4 + (cnt >> 19) : 8;
        hA = min(n0 >> 1, NH);
        const int q0 = 2 * hA, q1 = 2 * NH - q0;
        const int over = tk - (par ? q1 : q0), lack = max(par ? q0 - n0 : q1 - n1, 0);
        if (over < 0) pr = par ? q0 + tk : tk;
        else if (over < lack) pr = (par ? n0 : q0 + n1) + over;
        else pr = -1 - (over - lack + (par ? max(n0 - q0, 0) : 0));
        hA |= flip;
        if (lane == 0) {
            sinfo[1] = hA; sinfo[0] = pr;
            if (b >= 128 && rank == 0) atomicOr(&g_tick[6], (pr < 0 ? 4u : 1u) << ((b - 128) >> 1));
        }
    }
    asm volatile("barrier.cluster.wait.aligned;" ::: "memory");
    if (wid == 8) {
        __syncwarp();
        bar_arrive(NB_A, 288);
        bar_arrive(NB_S, 128);
        if (b >= 128 && pr < 0) bar_sync(NB_B, 64);
        if (pr >= 0) {
            const int pu = __reduce_max_sync(~0u, pr), c0 = (pu >> 1) * 128 + rank * 64, r0 = (pu & 1) * 512;
#pragma unroll 1
            for (int n = 0; n < 13; n++) {
                const u64 seq = b >= 128 ? LN_SEQ : 0xcba9876543210ull;
                const int i = seq >> (4 * n) & 15;
                if (b >= 128 && i == 0) bar_sync(NB_B, 64);
                if (n >= W_INFL && (b < 128 || n < LN_FREE)) mbar_wait_w(bars + 8 * (B_W + (seq >> (4 * (n - W_INFL)) & 15)), 0);
                const int m = i < 8 ? i & 1 : i >> 2, k = i < 8 ? i >> 1 : i & 3;
                const uint32_t dst = sb + m * 65536 + k * 16384, br = bars + 8 * (m < 3 ? B_W + i : B_WO);
                const int c = m < 3 ? c0 : 576 + rank * 256 + (pu & 1) * 128, r = m < 3 ? r0 + k * 128 : (pu >> 1) * DH;
                const uint64_t pol = m < 3 ? EVICT_FIRST : EVICT_NORMAL;
                e_expect(br, 16384);
                e_tma2d_hint(dst, &mp.wq + m, c, r, br, pol);
                e_tma2d_hint(dst + 8192, &mp.wq + m, c, r + 64, br, pol);
            }
        }
    } else {
        bar_sync(wid < 8 ? NB_A : NB_S, wid < 8 ? 288 : 128);
    }
    const int prr = __reduce_max_sync(~0u, sinfo[0]);
    hA = __reduce_max_sync(~0u, sinfo[1]);
    if (prr < 0) {
        int j = (b - 128) >> 1;
        if (b < 128) {
            uint32_t v;
            int it = 0;
#pragma unroll 1
            do { v = __reduce_max_sync(~0u, ldg_rlx1(&g_tick[6])); spin_guard(++it); } while (__popc(v) < 2);
            j = v == 3 ? -1 - prr : (v & 1) ^ 1;
        }
        rec_side((float*)smraw, mp, p, j * 2 + rank);
        return;
    }
    if (PDL) asm volatile("griddepcontrol.launch_dependents;" ::: "memory");
    const int role = (prr >> 1) * 4 + rank * 2 + (prr & 1);
    rec_main(sb, &mp.wo, arena, role, hA, wid >> 2, p.zero, p.dly);
}

__device__ __forceinline__ void wgmma_ss192(float* d, uint64_t a, uint64_t b, int sc) {
    asm volatile("{.reg .pred p; setp.ne.b32 p, %98, 0;\n wgmma.mma_async.sync.aligned.m64n192k16.f32.bf16.bf16 "
                 "{%0,%1,%2,%3,%4,%5,%6,%7,%8,%9,%10,%11,%12,%13,%14,%15,%16,%17,%18,%19,%20,%21,%22,%23,%24,%25,%26,%27,%28,%29,%30,%31,%32,%33,%34,%35,%36,%37,%38,%39,%40,%41,%42,%43,%44,%45,%46,%47,%48,%49,%50,%51,%52,%53,%54,%55,%56,%57,%58,%59,%60,%61,%62,%63,%64,%65,%66,%67,%68,%69,%70,%71,%72,%73,%74,%75,%76,%77,%78,%79,%80,%81,%82,%83,%84,%85,%86,%87,%88,%89,%90,%91,%92,%93,%94,%95}, %96, %97, p, 1, 1, 0, 1;}"
                 : F16(d, 0), F16(d, 16), F16(d, 32), F16(d, 48), F16(d, 64), F16(d, 80) : "l"(a), "l"(b), "r"(sc));
}

constexpr uint32_t P_B = 81920, P_PL = 40960, P_OUT = 180224, P_VEC = 212992, P_ROW = P_VEC + 6144, P_BAR = P_ROW + 4096, P_SMEM = P_BAR + 256;
#define FLAG_ST "st.release.gpu.global.u32"
#define FLAG_LD "ld.acquire.gpu.global.u32"
constexpr int ST = 5;
constexpr int PB_F = 0, PB_E = 5, PB_R = 10, PB_OUT = 16;
enum { C_Y = 0, C_G = 1, C_X1 = 2, C_U = 3, C_S1 = 8, C_S3 = 9 };
enum { V_GA = 0, V_A = 1, V_B = 2, V_GB = 3, V_VA = 4, V_VB = 5, V_VC = 6, V_C3 = 7 };
struct PostMaps { CUtensorMap o, wo, y, w1, g, w2, x1, w3, u, w4, out; };
struct PostPtrs { const bf16* x; };

struct GeluK { float k0, k1, kh; };
__device__ __forceinline__ GeluK gelu_k(float c) { return {0.7978845608028654f * c, 0.7978845608028654f * 0.044715f * c * c * c, 0.5f * c}; }
__device__ __forceinline__ float gelu_s(float t, const GeluK& k) {
    const float u = t * fmaf(t * t, k.k1, k.k0);
    float th; asm("tanh.approx.f32 %0, %1;" : "=f"(th) : "f"(u));
    const float hx = k.kh * t;
    return fmaf(hx, th, hx);
}
__device__ __forceinline__ float2 ldsv(uint32_t a) {
    float2 v; asm("ld.shared.v2.f32 {%0,%1}, [%2];" : "=f"(v.x), "=f"(v.y) : "r"(a)); return v;
}
__device__ __forceinline__ void wait_smem(uint32_t a, int target) {
    int it = 0;
#pragma unroll 1
    while (true) {
        int v;
        asm volatile("ld.acquire.cta.shared.u32 %0, [%1];" : "=r"(v) : "r"(a) : "memory");
        if (__all_sync(~0u, v >= target) | (++it > SPIN_LIMIT)) break;
    }
}

__device__ __forceinline__ void release(uint32_t rel, int st, bool c) {
    asm volatile("{.reg .pred p; setp.ne.u32 p, %1, 0; setp.ne.and.u32 p, %2, 0, p; @p mbarrier.arrive.shared::cluster.b64 _, [%0];}"
                 ::"r"(rel + 8 * (st ? st - 1 : ST - 1)), "r"(rel), "r"((uint32_t)c) : "memory");
}
struct Pipe { int st, ph; uint32_t rel; };
__device__ __forceinline__ void adv(Pipe& p) { if (++p.st == ST) { p.st = 0; p.ph ^= 1; } }

__device__ __forceinline__ void post_weights(uint32_t sb, const PostMaps& mp, int nb, int rank) {
    const uint32_t full = sb + P_BAR + 8 * PB_F, empty = sb + P_BAR + 8 * PB_E;
    int st = 0, pp = 1;
#pragma unroll 1
    for (int ph = 0; ph < 7; ph++) {
        const int NK = ph == 0 ? 64 : ph == 6 ? 56 : 16, km = NK == 16 ? 15 : 63;
        const CUtensorMap* tb = &mp.wo + 2 * (ph < 3 ? ph : ph < 6 ? 3 : 4);
        const bool w3 = ph >= 3 && ph < 6;
        const int n0 = w3 ? nb * 64 + (ph == 4 ? 1536 : ph == 5 ? 2560 : 0) : nb * 128, dn = w3 ? 512 : 64;
        const int rot = NK == 16 ? 2 * (nb & 6) : 0, sw = ph == 1 || ph == 3 ? 2 * rank : 0;
#pragma unroll 1
        for (int i = 0; i < NK; i++) {
            const int k0 = (((i < 4 ? i ^ sw : i) + rot) & km) * 64;
            const uint32_t a = sb + P_B + st * 8192, f = full + 8 * st;
            mbar_wait_w(empty + 8 * st, pp);
            e_expect(f, ph == 3 ? 40960 : 32768);
            e_tma2d(a, tb, n0, k0, f);
            e_tma2d(a + P_PL, tb, n0 + dn, k0, f);
            if (ph == 3) e_tma2d(a + 2 * P_PL, tb, n0 + 1024, k0, f);
            if (++st == ST) { st = 0; pp ^= 1; }
        }
    }
#pragma unroll 1
    for (int i = 0; i < ST; i++) mbar_wait_w(empty + 8 * i, pp ^ (i < st));
}
__device__ __forceinline__ void post_acts(uint32_t sb, const PostMaps& mp, int mb, int nb, int rank) {
    const int rh = 2 * mb + rank, lane = threadIdx.x & 31;
    const uint32_t bars = sb + P_BAR;
    int st = 0, pp = 1;
#pragma unroll 1
    for (int ph = 0; ph < 7; ph++) {
        const int NK = ph == 0 ? 64 : ph == 6 ? 56 : 16, km = NK == 16 ? 15 : 63;
        const CUtensorMap* ta = &mp.o + 2 * (ph < 3 ? ph : ph < 6 ? 3 : 4);
        const int amul = ph == 0 ? 256 : 64, arow = (ph == 0 ? rh * 8 : rh * 64) - 2, rot = NK == 16 ? 2 * (nb & 6) : 0;
        const bool own = ph == 1 || ph == 3;
        const uint32_t shifts = ph == 2 ? 0x04000301u : 0x02020202u;
        const uint32_t* fl = &g_pflag[(ph == 6 ? C_U : min(ph - 1, 2)) * 256 + (ph == 2 ? min(max(rh + min(lane >> 3, 2) - 1, 0), 31) : rh) * 8 + ((lane + nb - rank) & 7)];
        int i = 0, n = ph == 0 || ph == 5 ? NK : 0;
        if (own) { i = 4; if (st) { st--; pp ^= 1; } else st = 4; }
#pragma unroll 1
        while (i < NK) {
            if (n <= i) {
                int it = 0;
#pragma unroll 1
                do {
                    uint32_t v;
                    asm volatile(FLAG_LD " %0, [%1];" : "=r"(v) : "l"(fl) : "memory");
                    n = __reduce_min_sync(~0u, ph == 6 ? 8 * v : v || (own && !(lane & 6)) ? 16 : 2 * (lane & 7));
                    if (++it > SPIN_LIMIT) n = NK;
                } while (n <= i);
                asm volatile("fence.proxy.async.global;" ::: "memory");
            }
            if (own && (i == 5 || i == 6)) mbar_wait_w(bars + 8 * (PB_E + ph + i - 5), 1);
#pragma unroll 1
            for (const int e = own && i < 6 ? i + 1 : n; i < e; i++) {
                const int kb = (i + rot) & km;
                const uint32_t f = bars + 8 * (PB_F + st);
                mbar_wait_w(f + 8 * PB_E, pp);
                e_tma2d_mc(sb + st * 16384 + rank * 8192, ta, kb * amul, arow + (int)((shifts >> ((kb & 12) * 2)) & 7), f);
                if (++st == ST) { st = 0; pp ^= 1; }
            }
        }
    }
}

template <int PH, class F>
__device__ __forceinline__ void post_kb(uint32_t sb, float* acc, Pipe& p, int wg, bool lead, bool first, F mid) {
    constexpr uint64_t DA = PH == 0 ? mkdesc(SB0, 128, 1024, 0) : mkdesc(SB0, 16, 1024, 1);
    constexpr uint64_t DB = mkdesc(SB0 + P_B, P_PL, 1024, 1);
    mbar_wait_w(sb + P_BAR + 8 * PB_F + 8 * p.st, p.ph);
    const uint32_t a = (uint32_t)DA + p.st * 1024 + wg * 512, b = (uint32_t)DB + p.st * 512;
    wg_fence();
#pragma unroll
    for (int k = 0; k < 4; k++) {
        const uint64_t da = (DA & 0xffffffff00000000ull) | (a + k * (PH == 0 ? 16 : 2)), db = (DB & 0xffffffff00000000ull) | (b + k * 128);
        if (PH == 3) wgmma_ss192(acc, da, db, k || !first);
        else wgmma_ss128<PH == 0>(acc, da, db, k || !first);
    }
    wg_commit();
    wg_wait<1>();
    release(p.rel, p.st, !first);
    mid();
    adv(p);
}
__device__ __forceinline__ void post_end(uint32_t sb, Pipe& p, bool lead) {
    wg_wait<0>();
    release(p.rel, p.st, true);
}
template <int PH>
__device__ __forceinline__ void post_mma(uint32_t sb, float* acc, Pipe& p, int wg, bool lead, int nout, int pi, int mb, int nb) {
#pragma unroll 1
    for (int kb = 0; kb < 16; kb++)
        post_kb<PH>(sb, acc, p, wg, lead, kb == 0, [&]() {
            if (nout && kb == 0) wait_smem(sb + P_BAR + 8 * (PB_OUT + wg), nout);
        });
    post_end(sb, p, lead);
}

__global__ void __cluster_dims__(2, 1, 1) __launch_bounds__(384, 1)
k_post(const __grid_constant__ PostMaps mp, const __grid_constant__ PostPtrs pp) {
    extern __shared__ uint8_t smraw[];
    const uint32_t sb = smem_u32(smraw);
    if ((sb & 0x3FFFF) != SB0) __trap();
    const int tid = threadIdx.x, lane = tid & 31;
    const int rank = blockIdx.x & 1;
    const uint32_t bars = sb + P_BAR;
    int c = 0;
    unsigned long long v = 0;
    const int wid = __reduce_max_sync(~0u, tid >> 5);
    const bool draw = tid == 352 && rank == 0;
    if (draw) {
        c = min(ldg_rlx1(&g_cls[smid() & 255]), 8u);
        asm volatile("{.reg .b64 a; cvt.u64.u32 a, %%laneid; add.u64 a, a, %1; atom.relaxed.gpu.global.add.u64 %0, [a], %2;}" : "=l"(v) : "l"(&g_pt), "l"(1ull << (7 * c)) : "memory");
    }
    if (wid < 11) {
        asm volatile("{.reg .pred p; elect.sync _|p, 0xffffffff; @p mbarrier.init.shared.b64 [%0], %1; @p prefetch.tensormap [%2]; fence.mbarrier_init.release.cluster;}"
                     ::"r"(bars + 8 * wid), "r"(wid >= PB_E && wid < PB_R ? 4 : 1), "l"(&mp.o + wid) : "memory");
        if (wid == PB_R) { sts4(bars + 8 * PB_OUT, 0, 0, 0, 0); e_expect(bars + 8 * PB_R, 4); }
    }
    __syncwarp();
    asm volatile("barrier.cluster.arrive.relaxed.aligned; barrier.cluster.wait.aligned;" ::: "memory");
    if (draw) {
        int r = (v >> (7 * c)) & 127, role = c * 8 + r;
        if (c == 8 || r >= 8) {
            int n, x, it = 0;
#pragma unroll 1
            do {
                __nanosleep(200);
                v = ldg_u64(&g_pt); n = 0; x = c < 8 ? r - 8 : r;
#pragma unroll 1
                for (int i = 0; i < 63; i += 7) { const int m = v >> i & 127; n += m; if (i < 7 * c) x += max(m - 8, 0); }
            } while (n < gridDim.x / 2 && ++it < SPIN_LIMIT);
            role = -1;
#pragma unroll 1
            for (int i = 0; i < 64; i += 8, v >>= 7) {
                n = v & 127;
                if (x >= 0 && n + x < 8) role = i + n + x;
                x -= max(8 - n, 0);
            }
        }
#pragma unroll
        for (int i = 0; i < 2; i++)
            asm volatile("{.reg .b32 d; mapa.shared::cluster.u32 d, %0, %2; st.async.shared::cluster.mbarrier::complete_tx::bytes.u32 [d+8], %1, [d];}"
                         ::"r"(bars + 8 * PB_R), "r"(role), "r"(i) : "memory");
    }
    __syncwarp();
    mbar_wait_w(bars + 8 * PB_R, 0);
    const int pr = __reduce_max_sync(~0u, (int)lds1(bars + 8 * PB_R + 8));
    if (pr < 0) return;
    const int mb = (pr >> 5) * 8 + (pr & 7), nb = (pr >> 2 & 6) + rank, cta = pr * 2 + rank;
    if (wid >= 8) {
        asm volatile("setmaxnreg.dec.sync.aligned.u32 40;");
        const int w = wid - 8;
        if (w == 0) {
            post_weights(sb, mp, nb, rank);
        } else if (w == 3) {
            asm volatile("griddepcontrol.wait;" ::: "memory");
            post_acts(sb, mp, mb, nb, rank);
        } else {
            const int wg = w - 1, rh = 2 * mb + wg;
            float* rowc = (float*)(smraw + P_ROW) + (wg * 64 + lane * 2) * 8;
            int nout = 0, sig = 0;
#pragma unroll 1
            for (int i = 0; i < 13; i++) {
                const int cnt = (0x4333333392180ull >> (4 * i)) & 15;
                if (cnt < C_S1) {
                    const int ng = cnt == C_U ? 1 : 2, c0 = cnt == C_U ? (i - 5) * 512 + nb * 64 : nb * 128;
                    const bool fast = (cnt == C_Y || cnt == C_X1);
#pragma unroll 1
                    for (int j = 0; j < ng; j++) {
                        const uint32_t st = j ? cnt : cnt ? 1 : 4;
                        const uint32_t src = sb + (fast ? st * 16384 + wg * 8192 : P_OUT + wg * 16384 + ((nout + j) & 1) * 8192);
                        bar_sync(4 + 4 * wg + (sig++ & 3), 160);
                        if (lane == 0) {
                            if (fast) asm volatile("mbarrier.complete_tx.relaxed.cta.shared::cta.b64 [%0], 8192;" ::"r"(bars + 8 * (PB_F + st)) : "memory");
                            asm volatile("cp.async.bulk.tensor.2d.global.shared::cta.bulk_group [%0, {%2, %3}], [%1]; cp.async.bulk.commit_group;"
                                         ::"l"(&mp.y + 2 * cnt), "r"(src), "r"(c0 + j * 64), "r"(rh * 64) : "memory");
                        }
                        __syncwarp();
                    }
                    if (lane == 0) {
                        auto to_peer = [&]() {
                            const uint32_t n = cnt ? 1 : 4;
                            mbar_wait(bars + 8 * (PB_E + (cnt ? 4 : 2)), 0);
#pragma unroll
                            for (int i = 0; i < 2; i++)
                                asm volatile("{.reg .b32 d, m; mapa.shared::cluster.u32 d, %0, %3; mapa.shared::cluster.u32 m, %2, %3;\n"
                                             " cp.async.bulk.shared::cluster.shared::cta.mbarrier::complete_tx::bytes [d], [%1], 8192, [m];}"
                                             ::"r"(sb + (cnt + 1 + i) * 16384 + wg * 8192), "r"(sb + (i ? cnt : n) * 16384 + wg * 8192), "r"(bars + 8 * (PB_F + cnt + 1 + i)), "r"(rank ^ 1) : "memory");
                        };
                        asm volatile("cp.async.bulk.wait_group 0; fence.proxy.async.global;" ::: "memory");
                        asm volatile("st.release.cta.shared.u32 [%0], %1;" ::"r"(bars + 8 * (PB_OUT + wg)), "r"(nout + ng) : "memory");
                        if (i < 12) asm volatile(FLAG_ST " [%0], %1;" ::"l"(&g_pflag[cnt * 256 + rh * 8 + nb]), "r"(max(i - 4, 1)) : "memory");
                        if (fast) to_peer();
                    }
                    nout += ng;
                    __syncwarp();
                    continue;
                }
                bar_sync(4 + 4 * wg + (sig++ & 3), 160);
                uint32_t* c = &g_pcnt[(cnt - C_S1) * 256 + rh * 8];
                if (lane == 0) signal_count(c);
                __syncwarp();
                wait_count_w(c, 8);
                const float4* sp = (const float4*)g_st + rh * 32 + lane;
                float4 u[3] = {__ldcg(sp + (cnt == C_S1 ? 0 : 3) * (S_ / 2)), __ldcg(sp + S_ / 2), __ldcg(sp + S_)};
#pragma unroll 1
                for (int h = 0; h < 2; h++) {
                    const float id = 1.0f / DM;
                    const float m = u[0].x * id, var = fmaxf(u[0].y * id - m * m, 0.f) + 1e-5f, r = rsqrtf(var);
                    float sc = r, m2 = 0.f;
                    if (cnt == C_S1) {
                        m2 = r * (u[1].x * id - m * g_cst[0]) + g_cst[3];
                        const float e2 = r * r * (u[2].x * id - 2.0f * m * u[1].y * id + m * m * g_cst[1]) + 2.0f * r * (u[2].y * id - m * g_cst[2]) + g_cst[4];
                        sc = r * rsqrtf(fmaxf(e2 - m2 * m2, 0.f) + 1e-5f);
                    }
                    const GeluK k = gelu_k(sc);
                    *(float4*)(rowc + h * 8) = make_float4(k.k0, k.k1, k.kh, -m);
                    *(float4*)(rowc + h * 8 + 4) = make_float4(var * r, -m2 * var * r, r, -m * r);
#pragma unroll
                    for (int q = 0; q < 3; q++) { u[q].x = u[q].z; u[q].y = u[q].w; }
                }
                bar_arrive(1 + wg, 160);
            }
        }
    } else {
        asm volatile("setmaxnreg.inc.sync.aligned.u32 232;");
        const bf16* xin = pp.x;
        const int wg = wid >> 2, wi = (tid >> 5) & 3, g = lane >> 2, tq = lane & 3;
        const int rh = 2 * mb + wg, row = rh * 64 + wi * 16 + g;
        const bool lead = (tid & 127) == 0;
        uint32_t keep[32];
#pragma unroll
        for (int i = 0; i < 8; i++)
            *(uint4*)(keep + 4 * i) = __ldg((const uint4*)(xin + (size_t)(rh * 64 + wi * 16 + (i & 3) * 4 + (lane >> 3)) * DM + nb * 128 + (i >> 2) * 64 + (lane & 7) * 8));
        asm volatile("griddepcontrol.wait;" ::: "memory");
        if (cta < 64) g_modp[cta * 256 + tid] = 0;
        if (cta == 64 && tid < 196) g_tick[tid] = 0;
        const float* src = wg ? g_vec + nb * 128 + tid - 128 : g_mod + 2 * DM + nb * 128 + tid;
        const float* c3 = &g_vec[3 * DM + (tid >> 6) * 512 + nb * 64 + (tid & 63)];
        const float cv[6] = {__ldcg(src), __ldcg(src + (wg ? 1 : 2) * DM), __ldcg(src + (wg ? 2 : 1) * DM), __ldcg(src + 3 * DM), __ldcg(c3), __ldcg(c3 + (tid < 192 ? 2048 : 0))};
        uint32_t vec = sb + P_VEC + tq * 8;
        const uint32_t stw = sb + (wi * 16 + ((lane >> 3) & 1) * 8 + (lane & 7)) * 128 + (((lane >> 4) ^ (lane & 7)) << 4);
        int sig = 0;
        auto signal = [&]() { bar_arrive(4 + 4 * wg + (sig++ & 3), 160); };
        auto put64 = [&](uint32_t o, const float* v) {
#pragma unroll
            for (int jj = 0; jj < 4; jj++, v += 8) stsm4((stw + o) ^ (jj << 5), pack2(v[0], v[1]), pack2(v[2], v[3]), pack2(v[4], v[5]), pack2(v[6], v[7]));
            fence_async_smem();
            signal();
        };
        auto slot = [&](int n) {
            mbar_wait_w(bars + 8 * (PB_E + n % 5), ((n / 5) & 1) ^ 1);
            return (n % 5) * 16384 + wg * 8192;
        };
        const uint32_t rowc = sb + P_ROW + (wg * 64 + wi * 16 + g) * 32, o128 = P_OUT + wg * 16384;
        Pipe pa = {0, 0, 0};
        asm("mapa.shared::cluster.u32 %0, %1, %2;" : "=r"(pa.rel) : "r"(bars + 8 * PB_E), "r"(tid & 1));
        if (tid & 126) pa.rel = 0;
#define KEEP(jn, e) (((e) & 1) ? bfhi(keep[2 * (jn) + ((e) >> 1)]) : bflo(keep[2 * (jn) + ((e) >> 1)]))
        float mu1[2], r1[2];
        {
            float acc[64];
#pragma unroll 1
            for (int kb = 0; kb < 64; kb++) {
                post_kb<0>(sb, acc, pa, wg, lead, kb == 0, []() {});
                if (kb == 24) bar_sync(3, 256);
                if (kb != 8 + 8 * wg) continue;
                float* sv = (float*)(smraw + P_VEC) + tid;
                const uint32_t xo = sb + o128 + wi * 2048 + (lane >> 3) * 128;
#pragma unroll
                for (int i = 0; i < 8; i++) sts4(xo + (i >> 2) * 8192 + (i & 3) * 512 + (((lane & 7) ^ ((i & 1) * 4 + (lane >> 3))) << 4), keep[4 * i], keep[4 * i + 1], keep[4 * i + 2], keep[4 * i + 3]);
                __syncwarp();
#pragma unroll
                for (int jj = 0; jj < 8; jj++) ldsm4(keep + jj * 4, (stw + o128 + (jj >> 2) * 8192) ^ ((jj & 3) << 5));
                sv[wg * 384] = cv[0]; sv[wg * 384 + 128] = cv[1] + (wg ? 0.0f : 1.0f); sv[wg * 384 + 256] = cv[2];
                if (!wg) sv[384] = cv[3];
                sv[V_C3 * 128] = cv[4]; sv[V_C3 * 128 + 256] = cv[5];
            }
            post_end(sb, pa, lead);
            asm volatile("" : "+r"(vec) :: "memory");
            float st[2][6];
#pragma unroll
            for (int q = 0; q < 6; q++) st[0][q] = st[1][q] = 0.f;
#pragma unroll
            for (int jn = 0; jn < 16; jn++) {
                const float2 ga = ldsv(vec + V_GA * 512 + jn * 32), a = ldsv(vec + V_A * 512 + jn * 32);
                float xa[4];
#pragma unroll
                for (int e = 0; e < 4; e++) {
                    xa[e] = fmaf((e & 1) ? ga.y : ga.x, acc[4 * jn + e], KEEP(jn, e));
                    st[e >> 1][0] += xa[e]; st[e >> 1][1] = fmaf(xa[e], xa[e], st[e >> 1][1]);
                    acc[4 * jn + e] = ((e & 1) ? a.y : a.x) * xa[e];
                }
                keep[2 * jn] = pack2(xa[0], xa[1]); keep[2 * jn + 1] = pack2(xa[2], xa[3]);
                if ((jn & 7) == 7) put64(slot(64 + (jn >> 3)), acc + 4 * jn - 28);
            }
#pragma unroll
            for (int jn = 0; jn < 16; jn++) {
                const float2 a = ldsv(vec + V_A * 512 + jn * 32), b = ldsv(vec + V_B * 512 + jn * 32);
#pragma unroll
                for (int e = 0; e < 4; e++) {
                    const float y = acc[4 * jn + e], aa = (e & 1) ? a.y : a.x, bb = (e & 1) ? b.y : b.x;
                    float* s = st[e >> 1];
                    s[2] += y; s[3] = fmaf(aa, y, s[3]); s[4] = fmaf(y, y, s[4]); s[5] = fmaf(bb, y, s[5]);
                }
            }
#pragma unroll
            for (int h = 0; h < 2; h++)
#pragma unroll
                for (int q = 0; q < 6; q++) { st[h][q] += __shfl_xor_sync(~0u, st[h][q], 1); st[h][q] += __shfl_xor_sync(~0u, st[h][q], 2); }
            if (tq < 3) {
#pragma unroll
                for (int h = 0; h < 2; h++)
                    red2(g_st + (tq * S_ + row + h * 8) * 2, tq == 0 ? st[h][0] : tq == 1 ? st[h][2] : st[h][4], tq == 0 ? st[h][1] : tq == 1 ? st[h][3] : st[h][5]);
            }
            signal();
        }
        {
            float acc[64];
            post_mma<1>(sb, acc, pa, wg, lead, 2, 4, mb, nb);
            float c1[2], c2[2], c3[2];
            GeluK gk[2];
            bar_sync(1 + wg, 160);
#pragma unroll
            for (int h = 0; h < 2; h++) {
                const float4 a = lds4f(rowc + h * 256), b = lds4f(rowc + h * 256 + 16);
                gk[h] = {a.x, a.y, a.z}; c1[h] = a.w; c2[h] = b.x; c3[h] = b.y; mu1[h] = b.w; r1[h] = b.z;
            }
#pragma unroll
            for (int jn = 0; jn < 16; jn++) {
                const float2 va = ldsv(vec + V_VA * 512 + jn * 32), vb = ldsv(vec + V_VB * 512 + jn * 32), vc = ldsv(vec + V_VC * 512 + jn * 32);
#pragma unroll
                for (int e = 0; e < 4; e++) {
                    const int h = e >> 1;
                    const float t = fmaf(c1[h], (e & 1) ? va.y : va.x, fmaf(c2[h], (e & 1) ? vb.y : vb.x, fmaf(c3[h], (e & 1) ? vc.y : vc.x, acc[4 * jn + e])));
                    acc[4 * jn + e] = gelu_s(t, gk[h]);
                }
                if ((jn & 7) == 7) put64(o128 + (jn >> 3) * 8192, acc + 4 * jn - 28);
            }
        }
        {
            float acc[64];
            post_mma<2>(sb, acc, pa, wg, lead, 0, 7, mb, nb);
#pragma unroll
            for (int jn = 0; jn < 16; jn++) {
                const float2 a = ldsv(vec + V_A * 512 + jn * 32), b = ldsv(vec + V_B * 512 + jn * 32);
#pragma unroll
                for (int e = 0; e < 4; e++) {
                    const int h = e >> 1;
                    acc[4 * jn + e] += fmaf(fmaf(KEEP(jn, e), r1[h], mu1[h]), (e & 1) ? a.y : a.x, (e & 1) ? b.y : b.x);
                }
                if ((jn & 7) == 7) put64(slot(96 + (jn >> 3)), acc + 4 * jn - 28);
            }
            BLOCK_FENCE
#pragma unroll
            for (int i = 0; i < 64; i += 16) asm volatile("" : F16(acc, i));
            float st[2][2] = {{0.f, 0.f}, {0.f, 0.f}};
#pragma unroll
            for (int jn = 0; jn < 16; jn++) {
                const float2 gb = ldsv(vec + V_GB * 512 + jn * 32);
                float z[4];
#pragma unroll
                for (int e = 0; e < 4; e++) {
                    const float x1 = acc[4 * jn + e];
                    st[e >> 1][0] += x1; st[e >> 1][1] = fmaf(x1, x1, st[e >> 1][1]);
                    z[e] = fmaf((e & 1) ? gb.y : gb.x, x1, KEEP(jn, e));
                }
                keep[2 * jn] = pack2(z[0], z[1]); keep[2 * jn + 1] = pack2(z[2], z[3]);
            }
#pragma unroll
            for (int h = 0; h < 2; h++)
#pragma unroll
                for (int q = 0; q < 2; q++) { st[h][q] += __shfl_xor_sync(~0u, st[h][q], 1); st[h][q] += __shfl_xor_sync(~0u, st[h][q], 2); }
            if (tq < 2) red2(g_st + (3 * S_ + row + tq * 8) * 2, tq ? st[1][0] : st[0][0], tq ? st[1][1] : st[0][1]);
            signal();
        }
        {
            float old[96], acc[64];
            post_mma<3>(sb, old, pa, wg, lead, 6, 10, mb, nb);
#pragma unroll
            for (int i = 0; i < 96; i += 16) asm volatile("" : F16(old, i));
            uint32_t v3 = vec + V_C3 * 512;
            bar_sync(1 + wg, 160);
            const float4 rc[2] = {lds4f(rowc), lds4f(rowc + 256)};
            float2 vc[2] = {lds2f(v3), lds2f(v3 + 32)};
            v3 += wg ? 0 : 64;
            bar_sync(3, 256);
#pragma unroll 1
            for (int blk = 0; blk < 11; blk++) {
                const uint32_t o = stw + o128 + (blk & 1) * 8192;
#pragma unroll
                for (int q = 0; q < 4; q++) {
#pragma unroll 1
                    for (int rep = 0; rep < 2; rep++) {
                        post_kb<1>(sb, acc, pa, wg, lead, q == 0 && rep == 0 && blk < 6 && !(blk & 1), []() {});
                        if (rep != wg) {
                            vc[0] = lds2f(v3 + q * 64); vc[1] = lds2f(v3 + q * 64 + 32);
                            if (q == 2) wait_smem(bars + 8 * (PB_OUT + wg), 6 + min(blk, 7));
                            if ((q == 0 && wg && (uint32_t)(blk - 1) < 7) || (q == 3 && !wg && blk < 7)) { fence_async_smem(); signal(); }
                        } else if (blk < 7) {
                            asm volatile("" : F4(old, 8 * q), F4(old, 8 * q + 4));
                            float t[8];
#pragma unroll
                            for (int i = 0; i < 8; i++) {
                                const float4& c = rc[(i >> 1) & 1];
                                t[i] = gelu_s(fmaf(c.w, (i & 1) ? vc[i >> 2].y : vc[i >> 2].x, old[8 * q + i]), GeluK{c.x, c.y, c.z});
                                old[8 * q + i] = old[32 + 8 * q + i];
                                old[32 + 8 * q + i] = old[64 + 8 * q + i];
                            }
                            uint32_t r[4] = {pack2(t[0], t[1]), pack2(t[2], t[3]), pack2(t[4], t[5]), pack2(t[6], t[7])};
                            asm volatile("pmevent 0;" : F4(old, 8 * q), F4(old, 8 * q + 4), F4(old, 8 * q + 32), F4(old, 8 * q + 36), "+r"(r[0]), "+r"(r[1]), "+r"(r[2]), "+r"(r[3]));
                            stsm4(o ^ (q << 5), r[0], r[1], r[2], r[3]);
                        }
                    }
                }
                v3 += 256;
                if (blk != 1 && blk != 3) continue;
                post_end(sb, pa, lead);
                asm volatile("" : F16(acc, 0), F4(acc, 16), F4(acc, 20), F4(acc, 24));
                asm volatile("" : F16(acc, 28), F4(acc, 44), F4(acc, 48), F4(acc, 52));
                asm volatile("" : F4(acc, 56), F4(acc, 60));
#pragma unroll
                for (int i = 0; i < 64; i++) old[32 + i] = acc[i];
            }
            post_end(sb, pa, lead);
#pragma unroll
            for (int jn = 0; jn < 16; jn++) {
                const float2 gb = ldsv(vec + V_GB * 512 + jn * 32);
#pragma unroll
                for (int e = 0; e < 4; e++) acc[4 * jn + e] = fmaf((e & 1) ? gb.y : gb.x, acc[4 * jn + e], KEEP(jn, e));
                if ((jn & 7) == 7) put64(o128 + ((jn >> 3) ^ 1) * 8192, acc + 4 * jn - 28);
            }
        }
    }
}

typedef CUresult (*EncFn)(CUtensorMap*, CUtensorMapDataType, cuuint32_t, void*, const cuuint64_t*, const cuuint64_t*, const cuuint32_t*,
                          const cuuint32_t*, CUtensorMapInterleave, CUtensorMapSwizzle, CUtensorMapL2promotion, CUtensorMapFloatOOBfill);

static CUtensorMap make_map(EncFn enc, const void* p, uint64_t inner, uint64_t outer, uint32_t bi = 64) {
    CUtensorMap m;
    cuuint64_t dims[2] = {inner, outer};
    cuuint64_t str[1] = {inner * 2};
    cuuint32_t box[2] = {bi, bi == 64 ? 64u : 16u};
    cuuint32_t es[2] = {1, 1};
    enc(&m, CU_TENSOR_MAP_DATA_TYPE_BFLOAT16, 2, (void*)p, dims, str, box, es, CU_TENSOR_MAP_INTERLEAVE_NONE,
        bi == 64 ? CU_TENSOR_MAP_SWIZZLE_128B : CU_TENSOR_MAP_SWIZZLE_NONE, CU_TENSOR_MAP_L2_PROMOTION_L2_256B, CU_TENSOR_MAP_FLOAT_OOB_FILL_NONE);
    return m;
}
static CUtensorMap make_map_o(EncFn enc, const void* p) {
    CUtensorMap m;
    cuuint64_t dims[2] = {16384, 256};
    cuuint64_t str[1] = {65536};
    cuuint32_t box[2] = {256, 8};
    cuuint32_t es[2] = {1, 1};
    enc(&m, CU_TENSOR_MAP_DATA_TYPE_UINT32, 2, (void*)p, dims, str, box, es, CU_TENSOR_MAP_INTERLEAVE_NONE, CU_TENSOR_MAP_SWIZZLE_NONE,
        CU_TENSOR_MAP_L2_PROMOTION_L2_256B, CU_TENSOR_MAP_FLOAT_OOB_FILL_NONE);
    return m;
}
template <class T> static T* sym(T& s) { void* p = nullptr; cudaGetSymbolAddress(&p, s); return (T*)p; }

static const Delays h_dly = {D_NEAR, D_FAR, D_X2, D_V, D_W2, D_PA, D_MORE2, D_MORE};
extern "C" void kernel_launch(void* const* d_in, const int* in_sizes, int n_in, void* d_out, int out_size) {
    const bf16* x = (const bf16*)d_in[0];
    const bf16* mem0 = (const bf16*)d_in[1];
    const bf16 *Wq = (const bf16*)d_in[2], *Wk = (const bf16*)d_in[3], *Wv = (const bf16*)d_in[4], *Wo = (const bf16*)d_in[5];
    const bf16 *w1 = (const bf16*)d_in[8], *w2 = (const bf16*)d_in[9], *w3 = (const bf16*)d_in[10], *w4 = (const bf16*)d_in[11];
    const bf16 *c = (const bf16*)d_in[12], *wmod = (const bf16*)d_in[13];
    bf16* out = (bf16*)d_out;

    EncFn enc = nullptr;
    cudaDriverEntryPointQueryResult qr;
    cudaGetDriverEntryPoint("cuTensorMapEncodeTiled", (void**)&enc, cudaEnableDefault, &qr);
    CUtensorMap tWq = make_map(enc, Wq, NH * DH, DM), tWk = make_map(enc, Wk, NH * DH, DM), tWv = make_map(enc, Wv, NH * DH, DM);
    PostMaps mp;
    mp.o = make_map_o(enc, sym(g_O)); mp.wo = make_map(enc, Wo, DM, NH * DH);
    mp.y = make_map(enc, sym(g_y), DM, S_); mp.w1 = make_map(enc, w1, DM, DM);
    mp.g = make_map(enc, sym(g_g), DM, S_); mp.w2 = make_map(enc, w2, DM, DM);
    mp.x1 = make_map(enc, sym(g_x1), DM, S_); mp.w3 = make_map(enc, w3, FF, DM);
    mp.u = make_map(enc, sym(g_u), FF, S_); mp.w4 = make_map(enc, w4, DM, FF);
    mp.out = make_map(enc, out, DM, S_);
    cudaFuncSetAttribute(k_rec, cudaFuncAttributeMaxDynamicSharedMemorySize, SM_REC_TOTAL + 2048);
    cudaFuncSetAttribute(k_post, cudaFuncAttributeMaxDynamicSharedMemorySize, P_SMEM);

    uint8_t* arena = (uint8_t*)(((uintptr_t)sym(g_arena) + (2u << 20) - 1) & ~(uintptr_t)((2u << 20) - 1));
    const PostPtrs pp = {x};
    const RecPtrs rp = {x, mem0, c, wmod, w1, w3, arena, 0u, w2, w4, Wo, h_dly};
    const RecMaps rm = {tWq, tWk, tWv, mp.wo, make_map(enc, wmod, 6 * DM, DM, 256), make_map(enc, w3, FF, DM, 256), make_map(enc, w1, DM, DM, 256)};
    k_rec<<<132, 384, SM_REC_TOTAL + 2048>>>(rm, rp);
    cudaLaunchConfig_t cfg = {};
    cfg.gridDim = dim3(132); cfg.blockDim = dim3(384); cfg.dynamicSmemBytes = P_SMEM; cfg.stream = cudaStreamPerThread;
    cudaLaunchAttribute at[1];
    at[0].id = cudaLaunchAttributeProgrammaticStreamSerialization; at[0].val.programmaticStreamSerializationAllowed = PDL;
    cfg.attrs = at; cfg.numAttrs = 1;
    cudaLaunchKernelEx(&cfg, k_post, mp, pp);
}
```

```cpp
#include <cuda_runtime.h>
#include <cuda.h>
#include <cuda_bf16.h>
#include <stdint.h>
#include <limits.h>

typedef __nv_bfloat16 bf16;

constexpr int S_ = 2048, DM = 1024, NH = 32, DH = 128, NSEG = 64, FF = 3584;
constexpr int SPIN_LIMIT = 1 << 22;
#define W_INFL 2
#define H_PIECES 4
#define PDL 1
#define NPROBE 3

__device__ uint8_t g_arena[32 << 20];
#define SCR(type, off) ((type*)(arena + (off)))
#define g_tick SCR(uint32_t, 0x180000)
#define g_clk (g_tick + 64)
#define g_cls SCR(uint32_t, 0x180400)
#define g_pt (*SCR(unsigned long long, 0x180800))
#define g_modp SCR(uint32_t, 0x190000)
__host__ __device__ constexpr uint32_t blk(uint32_t lb, uint32_t par) {
    return (lb << 13) | ((((lb) ^ (lb >> 3) ^ (lb >> 4) ^ (lb >> 6) ^ par) & 1) << 12);
}
__host__ __device__ constexpr uint32_t lb_x2(uint32_t h) { return (h & 1) | ((h >> 1) << 3); }
__host__ __device__ constexpr uint32_t mem_row(uint32_t kh, uint32_t b, uint32_t r) { return blk(128 | b, kh) + r * 1024; }
__device__ __forceinline__ uint32_t mem_slot(uint32_t s) { return ((s & 1) << 15) | ((s & 2) << 17); }
constexpr uint32_t CNT1 = 0x3d80, CNT_ALL = 0x4000;
constexpr uint32_t LB_PROBE = 6 | 64, LB_TIME = 6;
__host__ __device__ constexpr uint32_t lb_tok(uint32_t h) { return (h & 1) | ((h >> 1) << 3); }
#define g_mod SCR(float, 0x1b0000)
#define g_himg SCR(bf16, 0x800000)
#define g_O SCR(bf16, 0xe00000)
__device__ __align__(1024) bf16 g_y[S_ * DM];
__device__ __align__(1024) bf16 g_g[S_ * DM];
__device__ __align__(1024) bf16 g_x1[S_ * DM];
#define g_st SCR(float, 0x1a0000)
#define g_vec SCR(float, 0x1b8000)
#define g_cst SCR(float, 0x180880)
#define g_pcnt SCR(uint32_t, 0x181000)
#define g_pflag SCR(uint32_t, 0x182000)
__device__ __align__(1024) bf16 g_u[S_ * FF];

__device__ __forceinline__ uint32_t smem_u32(const void* p) { return (uint32_t)__cvta_generic_to_shared(p); }
__device__ __forceinline__ void spin_guard(int it) {
    asm volatile("{.reg .pred p; setp.gt.s32 p, %0, %1; @p st.global.u32 [%2], %0;}" ::"r"(it), "n"(SPIN_LIMIT), "l"(1ull));
}
__device__ __forceinline__ void wg_fence() { asm volatile("wgmma.fence.sync.aligned;" ::: "memory"); }
__device__ __forceinline__ void wg_commit() { asm volatile("wgmma.commit_group.sync.aligned;" ::: "memory"); }
template <int N> __device__ __forceinline__ void wg_wait() { asm volatile("wgmma.wait_group.sync.aligned %0;" ::"n"(N) : "memory"); }
__host__ __device__ constexpr uint64_t mkdesc(uint32_t addr, uint32_t lbo, uint32_t sbo, uint32_t swz) {
    return (uint64_t)((addr & 0x3FFFF) >> 4) | ((uint64_t)(lbo >> 4) << 16) | ((uint64_t)(sbo >> 4) << 32) | ((uint64_t)swz << 62);
}
__device__ __forceinline__ uint64_t dadd(uint64_t d, uint32_t o) { return (d & 0xffffffff00000000ull) | (uint32_t)((uint32_t)d + o); }
__device__ __forceinline__ void mbar_init(uint32_t b, uint32_t c) { asm volatile("mbarrier.init.shared.b64 [%0], %1;" ::"r"(b), "r"(c) : "memory"); }
__device__ __forceinline__ void mbar_arrive_cluster(uint32_t b, uint32_t cta) {
    asm volatile("{.reg .b32 r; mapa.shared::cluster.u32 r, %0, %1; mbarrier.arrive.shared::cluster.b64 _, [r];}" ::"r"(b), "r"(cta) : "memory");
}
__device__ __forceinline__ bool mbar_try(uint32_t b, uint32_t par) {
    uint32_t ok;
    asm volatile("{.reg .pred p; mbarrier.try_wait.parity.shared.b64 p, [%1], %2; selp.u32 %0, 1, 0, p;}" : "=r"(ok) : "r"(b), "r"(par) : "memory");
    return ok;
}
__device__ __forceinline__ void mbar_wait(uint32_t b, uint32_t par) {
    int it = 0;
#pragma unroll 1
    while (!mbar_try(b, par) & (++it < SPIN_LIMIT)) {}
}
__device__ __forceinline__ void mbar_wait_w(uint32_t b, uint32_t par) {
    int it = 0;
#pragma unroll 1
    while (!__all_sync(~0u, mbar_try(b, par)) & (++it < SPIN_LIMIT)) {}
}
constexpr uint64_t EVICT_FIRST = 0x12F0000000000000ull, EVICT_NORMAL = 0x1000000000000000ull;   __device__ __forceinline__ void bar_sync(int id, int n) { asm volatile("bar.sync %0, %1;" ::"r"(id), "r"(n) : "memory"); }
__device__ __forceinline__ void bar_arrive(int id, int n) { asm volatile("bar.arrive %0, %1;" ::"r"(id), "r"(n) : "memory"); }
__device__ __forceinline__ void fence_async_smem() { asm volatile("fence.proxy.async.shared::cta;" ::: "memory"); }
__device__ __forceinline__ void ldsm4t(uint32_t* r, uint32_t a) {
    asm volatile("ldmatrix.sync.aligned.m8n8.x4.trans.shared.b16 {%0,%1,%2,%3}, [%4];" : "=r"(r[0]), "=r"(r[1]), "=r"(r[2]), "=r"(r[3]) : "r"(a) : "memory");
}
__device__ __forceinline__ void ldsm4(uint32_t* r, uint32_t a) {
    asm volatile("ldmatrix.sync.aligned.m8n8.x4.shared.b16 {%0,%1,%2,%3}, [%4];" : "=r"(r[0]), "=r"(r[1]), "=r"(r[2]), "=r"(r[3]) : "r"(a) : "memory");
}
__device__ __forceinline__ uint32_t movm(uint32_t a) {
    uint32_t d; asm volatile("movmatrix.sync.aligned.m8n8.trans.b16 %0, %1;" : "=r"(d) : "r"(a)); return d;
}
__device__ __forceinline__ void mma16816(float* d, uint32_t a0, uint32_t a1, uint32_t a2, uint32_t a3, uint32_t b0, uint32_t b1) {
    asm volatile("mma.sync.aligned.m16n8k16.row.col.f32.bf16.bf16.f32 {%0,%1,%2,%3},{%4,%5,%6,%7},{%8,%9},{%0,%1,%2,%3};"
                 : "+f"(d[0]), "+f"(d[1]), "+f"(d[2]), "+f"(d[3]) : "r"(a0), "r"(a1), "r"(a2), "r"(a3), "r"(b0), "r"(b1));
}
__device__ __forceinline__ void mma16816z(float* d, const uint32_t* a, uint32_t b0, uint32_t b1) {
    asm volatile("mma.sync.aligned.m16n8k16.row.col.f32.bf16.bf16.f32 {%0,%1,%2,%3},{%4,%5,%6,%7},{%8,%9},{%10,%10,%10,%10};"
                 : "=f"(d[0]), "=f"(d[1]), "=f"(d[2]), "=f"(d[3]) : "r"(a[0]), "r"(a[1]), "r"(a[2]), "r"(a[3]), "r"(b0), "r"(b1), "f"(0.f));
}
__device__ __forceinline__ void mma1688(float* d, uint32_t a0, uint32_t a1, uint32_t b0) {
    asm volatile("mma.sync.aligned.m16n8k8.row.col.f32.bf16.bf16.f32 {%0,%1,%2,%3},{%4,%5},{%6},{%0,%1,%2,%3};"
                 : "+f"(d[0]), "+f"(d[1]), "+f"(d[2]), "+f"(d[3]) : "r"(a0), "r"(a1), "r"(b0));
}
__device__ __forceinline__ uint32_t pack2(float lo, float hi) {
    uint32_t r; asm("cvt.rn.bf16x2.f32 %0, %1, %2;" : "=r"(r) : "f"(hi), "f"(lo)); return r;
}
__device__ __forceinline__ uint32_t hadd2(uint32_t a, uint32_t b) {
    uint32_t r; asm("add.rn.bf16x2 %0, %1, %2;" : "=r"(r) : "r"(a), "r"(b)); return r;
}
__device__ __forceinline__ float bflo(uint32_t u) { return __uint_as_float(u << 16); }
__device__ __forceinline__ float bfhi(uint32_t u) { return __uint_as_float(u & 0xffff0000u); }
__device__ __forceinline__ float ex2(float x) { float r; asm("ex2.approx.ftz.f32 %0, %1;" : "=f"(r) : "f"(x)); return r; }
__device__ __forceinline__ uint4 ldg_rlx4(const void* p) {
    uint4 v; asm volatile("ld.relaxed.gpu.global.v4.u32 {%0,%1,%2,%3}, [%4];" : "=r"(v.x), "=r"(v.y), "=r"(v.z), "=r"(v.w) : "l"(p) : "memory"); return v;
}
__device__ __forceinline__ uint32_t ldg_rlx1(const void* p) {
    uint32_t v; asm volatile("ld.relaxed.gpu.global.u32 %0, [%1];" : "=r"(v) : "l"(p) : "memory"); return v;
}
__device__ __forceinline__ void stg_rlx1(void* p, uint32_t v) { asm volatile("st.relaxed.gpu.global.u32 [%0], %1;" ::"l"(p), "r"(v) : "memory"); }
__device__ __forceinline__ void stg_rlx2(void* p, uint32_t x, uint32_t y) {
    unsigned long long v = (unsigned long long)x | ((unsigned long long)y << 32);
    asm volatile("st.relaxed.gpu.global.b64 [%0], %1;" ::"l"(p), "l"(v) : "memory");
}
__device__ __forceinline__ void stg_rlx4(void* p, uint32_t x, uint32_t y, uint32_t z, uint32_t w) {
    asm volatile("st.relaxed.gpu.global.v4.u32 [%0], {%1,%2,%3,%4};" ::"l"(p), "r"(x), "r"(y), "r"(z), "r"(w) : "memory");
}
__device__ __forceinline__ void sts4(uint32_t a, uint32_t x, uint32_t y, uint32_t z, uint32_t w) {
    asm volatile("st.shared.v4.u32 [%0], {%1,%2,%3,%4};" ::"r"(a), "r"(x), "r"(y), "r"(z), "r"(w) : "memory");
}
__device__ __forceinline__ uint4 lds4(uint32_t a) {
    uint4 v; asm volatile("ld.shared.v4.u32 {%0,%1,%2,%3}, [%4];" : "=r"(v.x), "=r"(v.y), "=r"(v.z), "=r"(v.w) : "r"(a) : "memory"); return v;
}
#define F4(d, i) "+f"(d[i]), "+f"(d[i + 1]), "+f"(d[i + 2]), "+f"(d[i + 3])
__device__ __forceinline__ void wgmma_rs32(float* d, const uint32_t* a, uint64_t b, int sc) {
    asm volatile("{.reg .pred p; setp.ne.b32 p, %21, 0;\n wgmma.mma_async.sync.aligned.m64n32k16.f32.bf16.bf16 {%0,%1,%2,%3,%4,%5,%6,%7,%8,%9,%10,%11,%12,%13,%14,%15}, {%16,%17,%18,%19}, %20, p, 1, 1, 0;}"
                 : F4(d, 0), F4(d, 4), F4(d, 8), F4(d, 12) : "r"(a[0]), "r"(a[1]), "r"(a[2]), "r"(a[3]), "l"(b), "r"(sc));
}
__device__ __forceinline__ void wgmma_ss32(float* d, uint64_t a, uint64_t b, int sc) {
    asm volatile("{.reg .pred p; setp.ne.b32 p, %18, 0;\n wgmma.mma_async.sync.aligned.m64n32k16.f32.bf16.bf16 {%0,%1,%2,%3,%4,%5,%6,%7,%8,%9,%10,%11,%12,%13,%14,%15}, %16, %17, p, 1, 1, 1, 0;}"
                 : F4(d, 0), F4(d, 4), F4(d, 8), F4(d, 12) : "l"(a), "l"(b), "r"(sc));
}
__device__ __forceinline__ void wgmma_rs40(float* d, const uint32_t* a, uint64_t b, int sc) {
    asm volatile("{.reg .pred p; setp.ne.b32 p, %25, 0;\n wgmma.mma_async.sync.aligned.m64n40k16.f32.bf16.bf16 {%0,%1,%2,%3,%4,%5,%6,%7,%8,%9,%10,%11,%12,%13,%14,%15,%16,%17,%18,%19}, {%20,%21,%22,%23}, %24, p, 1, 1, 0;}"
                 : F4(d, 0), F4(d, 4), F4(d, 8), F4(d, 12), F4(d, 16) : "r"(a[0]), "r"(a[1]), "r"(a[2]), "r"(a[3]), "l"(b), "r"(sc));
}
__device__ __forceinline__ void wgmma_ss40(float* d, uint64_t a, uint64_t b, int sc) {
    asm volatile("{.reg .pred p; setp.ne.b32 p, %22, 0;\n wgmma.mma_async.sync.aligned.m64n40k16.f32.bf16.bf16 {%0,%1,%2,%3,%4,%5,%6,%7,%8,%9,%10,%11,%12,%13,%14,%15,%16,%17,%18,%19}, %20, %21, p, 1, 1, 1, 0;}"
                 : F4(d, 0), F4(d, 4), F4(d, 8), F4(d, 12), F4(d, 16) : "l"(a), "l"(b), "r"(sc));
}
#define F16(d, i) F4(d, i), F4(d, i + 4), F4(d, i + 8), F4(d, i + 12)
template <int TA>
__device__ __forceinline__ void wgmma_ss128(float* d, uint64_t a, uint64_t b, int sc) {
    asm volatile("{.reg .pred p; setp.ne.b32 p, %66, 0;\n wgmma.mma_async.sync.aligned.m64n128k16.f32.bf16.bf16 "
                 "{%0,%1,%2,%3,%4,%5,%6,%7,%8,%9,%10,%11,%12,%13,%14,%15,%16,%17,%18,%19,%20,%21,%22,%23,%24,%25,%26,%27,%28,%29,%30,%31,"
                 "%32,%33,%34,%35,%36,%37,%38,%39,%40,%41,%42,%43,%44,%45,%46,%47,%48,%49,%50,%51,%52,%53,%54,%55,%56,%57,%58,%59,%60,%61,%62,%63}, %64, %65, p, 1, 1, %67, 1;}"
                 : F16(d, 0), F16(d, 16), F16(d, 32), F16(d, 48) : "l"(a), "l"(b), "r"(sc), "n"(TA));
}

__device__ __forceinline__ float warp_sum(float v) {
#pragma unroll
    for (int o = 16; o; o >>= 1) v += __shfl_xor_sync(~0u, v, o);
    return v;
}
__device__ __forceinline__ float bfround(float x) { return __bfloat162float(__float2bfloat16(x)); }

__device__ __forceinline__ void wait_count1(const uint32_t* p, uint32_t target) {
    int it = 0;
#pragma unroll 1
    while (true) {
        uint32_t v;
        asm volatile("ld.acquire.gpu.global.u32 %0, [%1];" : "=r"(v) : "l"(p) : "memory");
        if (v >= target) break;
        spin_guard(++it);
    }
}
__device__ __forceinline__ void red2(float* p, float a, float b) {
    asm volatile("red.relaxed.gpu.global.add.v2.f32 [%0], {%1, %2};" ::"l"(p), "f"(a), "f"(b) : "memory");
}
__device__ __forceinline__ void signal_count(uint32_t* p) { asm volatile("red.release.gpu.global.add.u32 [%0], 1;" ::"l"(p) : "memory"); }
__device__ __forceinline__ void e_expect(uint32_t b, uint32_t tx) {
    asm volatile("{.reg .pred p; elect.sync _|p, 0xffffffff; @p mbarrier.arrive.expect_tx.shared.b64 _, [%0], %1;}" ::"r"(b), "r"(tx) : "memory");
}
__device__ __forceinline__ void e_tma2d(uint32_t dst, const CUtensorMap* m, int c0, int c1, uint32_t bar) {
    asm volatile("{.reg .pred p; elect.sync _|p, 0xffffffff;\n @p cp.async.bulk.tensor.2d.shared::cluster.global.mbarrier::complete_tx::bytes [%0], [%1, {%3, %4}], [%2];}"
                 ::"r"(dst), "l"(m), "r"(bar), "r"(c0), "r"(c1) : "memory");
}
__device__ __forceinline__ void e_tma2d_hint(uint32_t dst, const CUtensorMap* m, int c0, int c1, uint32_t bar, uint64_t pol) {
    asm volatile("{.reg .pred p; elect.sync _|p, 0xffffffff;\n @p cp.async.bulk.tensor.2d.shared::cluster.global.mbarrier::complete_tx::bytes.L2::cache_hint [%0], [%1, {%3, %4}], [%2], %5;}"
                 ::"r"(dst), "l"(m), "r"(bar), "r"(c0), "r"(c1), "l"(pol) : "memory");
}
__device__ __forceinline__ void e_tma2d_mc(uint32_t dst, const CUtensorMap* m, int c0, int c1, uint32_t bar) {
    asm volatile("{.reg .pred p; elect.sync _|p, 0xffffffff;\n @p cp.async.bulk.tensor.2d.shared::cluster.global.mbarrier::complete_tx::bytes.multicast::cluster [%0], [%1, {%3, %4}], [%2], %5;}"
                 ::"r"(dst), "l"(m), "r"(bar), "r"(c0), "r"(c1), "h"((uint16_t)3) : "memory");
}
__device__ __forceinline__ void wait_count_w(const uint32_t* p, uint32_t target) {
    int it = 0;
#pragma unroll 1
    while (true) {
        uint32_t v;
        asm volatile("ld.acquire.gpu.global.u32 %0, [%1];" : "=r"(v) : "l"(p) : "memory");
        if (__all_sync(~0u, v >= target) | (++it > SPIN_LIMIT)) break;
        __nanosleep(100);
    }
}

#define NL 6
constexpr uint32_t SM_HB = 16384, HBK = 5120, SM_SX = 57344, SM_OX = 122880, SM_PX = 124928, SM_PA = 126976, SM_WO = 147456,
                   SM_TAB = 212992, SM_PRE = SM_TAB + 5120, SM_BAR = 227328, SM_REC_TOTAL = 227328 + 256;
constexpr uint32_t SB0 = 1024;
constexpr int B_WO = 0, B_HE = 1, B_HB = 3, B_W = 5;
constexpr int NB_MEM = 1, NB_QK = 2, NB_X1 = 3, NB_X2 = 4, NB_WIN = 5, NB_WG = 6, NB_KDONE = 7, NB_FIN0 = 8, NB_P = 9, NB_PX = 10, NB_G = 11, NB_A = 12, NB_B = 13, NB_C = 14, NB_S = 15;
#define D_NEAR 1620
#define D_FAR (D_NEAR - 90)
#define D_X2 400
#define D_V 280
#define D_W2 40
#define D_PA 40
#define D_MORE 40
#define D_MORE2 30
constexpr int E_MUL = 28;
constexpr int NPF = NL + 6, NE1 = 10;
constexpr int W0_E = 3, W0_RS = NL - 1, G_AT = 18;
struct Delays { uint32_t near, far, x2, v, w2, pa, more2, more; };

__device__ __forceinline__ uint32_t clk32() { uint32_t t; asm volatile("mov.u32 %0, %%clock;" : "=r"(t) :: "memory"); return t; }
__device__ __forceinline__ uint32_t smid() { uint32_t t; asm volatile("mov.u32 %0, %%smid;" : "=r"(t)); return t; }
__device__ __forceinline__ uint32_t gtime() { uint32_t t; asm volatile("mov.u32 %0, %%globaltimer_lo;" : "=r"(t) :: "memory"); return t; }
__device__ __forceinline__ void spin_until(uint32_t t0, uint32_t d) { while (clk32() - t0 < d) {} }
template <int N> __device__ __forceinline__ uint32_t delay(uint32_t zero) {
    float x = __uint_as_float(clk32());
#pragma unroll
    for (int i = 0; i < N; i++) asm volatile("ex2.approx.ftz.f32 %0, %0;" : "+f"(x));
    return __float_as_uint(x) & zero;
}
__device__ __forceinline__ uint32_t opaque(uint32_t v) { return __shfl_sync(~0u, v, threadIdx.x & 31); }
__device__ __forceinline__ uint32_t xor_or(uint32_t a, uint32_t b, uint32_t t) {
    uint32_t r; asm volatile("lop3.b32 %0, %1, %2, %3, 0x7E;" : "=r"(r) : "r"(a), "r"(b), "r"(t)); return r;
}
__device__ __forceinline__ uint32_t settag(uint32_t v, uint32_t tag) {
    uint32_t r; asm("lop3.b32 %0, %1, 1, %2, 0xB8;" : "=r"(r) : "r"(v), "r"(tag)); return r;
}
__device__ __forceinline__ void sts2(uint32_t a, float x, float y) { asm volatile("st.shared.v2.f32 [%0], {%1,%2};" ::"r"(a), "f"(x), "f"(y) : "memory"); }
__device__ __forceinline__ void sts4f(uint32_t a, float x, float y, float z, float w) {
    asm volatile("st.shared.v4.f32 [%0], {%1,%2,%3,%4};" ::"r"(a), "f"(x), "f"(y), "f"(z), "f"(w) : "memory");
}
__device__ __forceinline__ void sts1(uint32_t a, uint32_t x) { asm volatile("st.shared.u32 [%0], %1;" ::"r"(a), "r"(x) : "memory"); }
__device__ __forceinline__ uint32_t lds1(uint32_t a) { uint32_t v; asm volatile("ld.shared.u32 %0, [%1];" : "=r"(v) : "r"(a) : "memory"); return v; }
__device__ __forceinline__ float4 lds4f(uint32_t a) {
    float4 v; asm volatile("ld.shared.v4.f32 {%0,%1,%2,%3}, [%4];" : "=f"(v.x), "=f"(v.y), "=f"(v.z), "=f"(v.w) : "r"(a) : "memory"); return v;
}
__device__ __forceinline__ float2 lds2f(uint32_t a) {
    float2 v; asm volatile("ld.shared.v2.f32 {%0,%1}, [%2];" : "=f"(v.x), "=f"(v.y) : "r"(a) : "memory"); return v;
}
__device__ __forceinline__ bool any_bit0(uint32_t x) {
    uint32_t r;
    asm volatile("{.reg .pred p, q; .reg .b32 t; and.b32 t, %1, 1; setp.ne.u32 p, t, 0; vote.sync.any.pred q, p, 0xffffffff; selp.u32 %0, 1, 0, q;}" : "=r"(r) : "r"(x));
    return r;
}
__device__ __forceinline__ float rcp_fast(float x) { float r; asm("rcp.approx.ftz.f32 %0, %1;" : "=f"(r) : "f"(x)); return r; }
__device__ __forceinline__ void stsm4(uint32_t a, uint32_t r0, uint32_t r1, uint32_t r2, uint32_t r3) {
    asm volatile("stmatrix.sync.aligned.m8n8.x4.shared.b16 [%0], {%1,%2,%3,%4};" ::"r"(a), "r"(r0), "r"(r1), "r"(r2), "r"(r3) : "memory");
}
__device__ __forceinline__ void stsm4t(uint32_t a, uint32_t r0, uint32_t r1, uint32_t r2, uint32_t r3) {
    asm volatile("stmatrix.sync.aligned.m8n8.x4.trans.shared.b16 [%0], {%1,%2,%3,%4};" ::"r"(a), "r"(r0), "r"(r1), "r"(r2), "r"(r3) : "memory");
}
__device__ __forceinline__ uint32_t and3(uint32_t a, uint32_t b, uint32_t c) {
    uint32_t r; asm("lop3.b32 %0, %1, %2, %3, 0x80;" : "=r"(r) : "r"(a), "r"(b), "r"(c)); return r;
}
__device__ __forceinline__ void red_mem(void* p, uint32_t x, uint32_t y, uint32_t z, uint32_t w, void* q, uint32_t e, bool c) {
    asm volatile("{.reg .pred p; setp.ne.u32 p, %7, 0; red.relaxed.gpu.global.add.noftz.v4.bf16x2 [%0], {%1,%2,%3,%4}; @p red.relaxed.gpu.global.add.noftz.bf16x2 [%5], %6;}"
                 ::"l"(p), "r"(x), "r"(y), "r"(z), "r"(w), "l"(q), "r"(e), "r"((uint32_t)c) : "memory");
}
__device__ __forceinline__ void stg4_if(bool c, void* p, uint32_t x) {
    asm volatile("{.reg .pred p; setp.ne.u32 p, %2, 0; @p st.relaxed.gpu.global.v4.u32 [%0], {%1,%1,%1,%1};}" ::"l"(p), "r"(x), "r"((uint32_t)c) : "memory");
}

__device__ __forceinline__ void h_load(uint32_t sb, const uint8_t* hsrc, int pass, uint32_t rank, uint32_t rot) {
    const uint8_t* src = hsrc + (size_t)pass * 65536;
    const uint32_t bar = sb + SM_BAR + 8 * (B_HB + (pass & 1)), dst = sb + SM_HB + (pass & 1) * 65536 + rank * 4 * HBK;
    e_expect(bar, 32768);
#pragma unroll 1
    for (int i = 0; i < H_PIECES; i++) {
        const uint32_t o = ((i + rot) & (H_PIECES - 1)) * (16384 / H_PIECES);
        asm volatile("{.reg .pred p; elect.sync _|p, 0xffffffff;\n"
                     " @p cp.async.bulk.shared::cluster.global.mbarrier::complete_tx::bytes.multicast::cluster [%0], [%1], %4, [%2], %3;}"
                     ::"r"(dst + o + (o >> 12) * 1024), "l"(src + o), "r"(bar), "h"((uint16_t)3), "n"(16384 / H_PIECES) : "memory");
    }
}
__device__ __forceinline__ uint4 ldg_b128(const void* p) {
    uint4 v;
    asm volatile("{.reg .b128 t; .reg .b64 a, b; ld.relaxed.gpu.global.b128 t, [%4]; mov.b128 {a, b}, t; mov.b64 {%0,%1}, a; mov.b64 {%2,%3}, b;}"
                 : "=r"(v.x), "=r"(v.y), "=r"(v.z), "=r"(v.w) : "l"(p) : "memory");
    return v;
}
__device__ __forceinline__ void stg_b128_if(bool c, void* p, uint32_t x, uint32_t y, uint32_t z, uint32_t w) {
    asm volatile("{.reg .pred p; setp.ne.u32 p, %5, 0; @p st.relaxed.gpu.global.v4.u32 [%0], {%1,%2,%3,%4};}"
                 ::"l"(p), "r"(x), "r"(y), "r"(z), "r"(w), "r"((uint32_t)c) : "memory");
}
__device__ __forceinline__ float pretag(float x, uint32_t add, uint32_t keep) { return __uint_as_float((__float_as_uint(x) + add) & keep); }

template <class F, class G>
__device__ __forceinline__ void softmax_rows(uint32_t src, uint32_t dst, uint32_t g16, int row0, F ready, G mid) {
    const uint32_t u = (g16 >> 7) & 3, e = ((g16 >> 9) << 3) | ((g16 >> 4) & 7);
    uint32_t se = src + e * 8, su = se + u * 1088, d0 = dst + e * 16 + u * 4, d1 = dst + 512 + e * 4;
    int vis = row0 + (e >> 2) - 2 * (e & 3) - 8 * u;
    asm volatile("" : "+r"(se), "+r"(su), "+r"(d0), "+r"(d1), "+r"(vis));
    ready();
    const float2 p0 = lds2f(su), p1 = lds2f(su + 256), p2 = lds2f(su + 512), p3 = lds2f(su + 768);
    const float2 m0 = lds2f(se + 4352), m1 = lds2f(se + 4352 + 256), m2 = lds2f(se + 4352 + 512), m3 = lds2f(se + 4352 + 768);
    float a0 = (p0.x + p1.x) + (p2.x + p3.x), a1 = (p0.y + p1.y) + (p2.y + p3.y);
    const float a2 = (m0.x + m1.x) + (m2.x + m3.x), a3 = (m0.y + m1.y) + (m2.y + m3.y);
    if (vis < 0) a0 = -1e9f / 0.08838834764831845f;
    if (vis < 1) a1 = -1e9f / 0.08838834764831845f;
    int k = __float_as_int(fmaxf(fmaxf(a0, a1), fmaxf(a2, a3)));
    k ^= (k >> 31) & 0x7fffffff;
    const bool hi = g16 & 64;
    const int k0 = __reduce_max_sync(~0u, hi ? INT_MIN : k), k1 = __reduce_max_sync(~0u, hi ? k : INT_MIN);
    mid();
    k = hi ? k1 : k0;
    const float m = __int_as_float(k ^ ((k >> 31) & 0x7fffffff));
    const float sl2 = 0.08838834764831845f * 1.4426950408889634f, mb = -m * sl2;
    sts1(d0, pack2(ex2(fmaf(a0, sl2, mb)), ex2(fmaf(a1, sl2, mb))));
    sts1(d1, pack2(ex2(fmaf(a2, sl2, mb)), ex2(fmaf(a3, sl2, mb))));
}

__device__ __forceinline__ uint32_t pack_h2(float lo, float hi) {
    uint32_t r; asm("cvt.rn.satfinite.f16x2.f32 %0, %1, %2;" : "=r"(r) : "f"(hi), "f"(lo)); return r;
}
__device__ __forceinline__ float2 unpack_h2(uint32_t u) {
    float2 r; asm("{.reg .b16 l, h; mov.b32 {l, h}, %2; cvt.f32.f16 %0, l; cvt.f32.f16 %1, h;}" : "=f"(r.x), "=f"(r.y) : "r"(u)); return r;
}
__device__ __forceinline__ uint32_t add_h2(uint32_t a, uint32_t b) { uint32_t r; asm("add.rn.f16x2 %0, %1, %2;" : "=r"(r) : "r"(a), "r"(b)); return r; }
__device__ __forceinline__ uint32_t max_h2(uint32_t a, uint32_t b) { uint32_t r; asm("max.f16x2 %0, %1, %2;" : "=r"(r) : "r"(a), "r"(b)); return r; }
struct U2 { uint32_t x, y; };
__device__ __forceinline__ U2 ldg_u2(const void* p) {
    U2 v; asm volatile("{.reg .b64 t; ld.relaxed.gpu.global.b64 t, [%2]; mov.b64 {%0, %1}, t;}" : "=r"(v.x), "=r"(v.y) : "l"(p) : "memory"); return v;
}
constexpr int POLL_LIMIT = 1 << 16;
constexpr float SM_L2E = 0.08838834764831845f * 1.4426950408889634f;
template <int V> struct IC { static constexpr int value = V; };
typedef unsigned long long u64;
__device__ __forceinline__ u64 ldg_u64(const void* p) { u64 v; asm volatile("ld.relaxed.gpu.global.b64 %0, [%1];" : "=l"(v) : "l"(p) : "memory"); return v; }
__device__ __forceinline__ void rec_main(uint32_t sb, const CUtensorMap* tWo, uint8_t* arena, int role, int hinfo, int wg, uint32_t zero, const Delays& dly) {
    const int hA = hinfo & 255;
    const int tid = threadIdx.x, t = tid & 127, lane = tid & 31, wi = t >> 5;
    const uint32_t bars = sb + SM_BAR;
    const int head = role >> 2, qd = role & 3, j = blockIdx.x & 1, kh = role & 1;
    const uint32_t mypar = head >= hA;
    const uint32_t wu = __reduce_max_sync(~0u, wi);
    const bool warp0 = wu == 0, warp1 = wu == 1;
    const uint8_t* hsrc = (const uint8_t*)g_himg + kh * 32768 + j * 16384;
    auto tokbase = [&](int ty) { return ((ty + 1) << 21) + blk(lb_tok(head), mypar ^ ((hinfo >> (8 + ty)) & 1)); };
    const uint32_t tbw = tokbase(wg), tbq = tokbase(0) + (qd >> 1) * 2048 + ((qd & 1) + wu) * 256;
    uint32_t w[32 - NL][4];
    const uint32_t frow = ((lane >> 4) * 8 + (lane & 7)) * 128, fx = ((lane >> 3) & 1) ^ (lane & 7);
    const uint32_t wl0 = sb + wg * 65536 + frow + ((fx ^ (2 * wi)) << 4);
    uint32_t g16 = opaque(t * 16);
    auto G16 = [&]() { asm volatile("" : "+r"(g16)); return g16; };
    const uint32_t sbl = sb - wu * 512;
    const uint32_t xso = blk(lb_x2(head), mypar), cu = kh * 2048 + (2 * j + (wu >> 1)) * 512;
    const uint32_t u_xo = xso + wg * 16384 + (wu & 1) * 2048 + (cu >> 1) - wu * 256, u_to = tbw + (wu & 1) * 16384 + cu - wu * 512;
    {
        uint8_t* pp = arena + (tbw + (1 << 20) + j * 16384 + (kh ^ 1) * 2048 + g16);
        stg_rlx4(pp, 0, 0, 0, 0);
        stg_rlx4(pp + 32768, 0, 0, 0, 0);
        stg_rlx4(arena + (u_to + g16), 0, 0, 0, 0);
        stg_rlx2(arena + (u_xo + (g16 >> 1)), 0, 0);
    }
    {
        mbar_wait_w(bars + 8 * (B_W + 5), 0);
        if (wg > 0) wait_count_w(&g_tick[32 + (lane & 3) * 8], 1);
        if (wg == 1) asm volatile("fence.proxy.async.global;" ::: "memory");
#pragma unroll 1
        for (int i = 0; i < 4; i++) mbar_wait_w(bars + 8 * (B_W + (wg == 2 ? 8 + i : 2 * i + wg)), 0);
#pragma unroll
        for (int p = NL; p < 32; p++) ldsm4t(w[p - NL], wl0 + p * 2048);
        fence_async_smem();
        bar_sync(wg < 2 ? NB_WG : NB_X2, wg < 2 ? 256 : 128);
        if (wg == 2 && wu < 3) {
            e_expect(bars + 8 * B_WO, 16384);
            e_tma2d(sb + SM_WO + wu * 16384, tWo, (wu >> 1) * 512 + qd * 128 + (wu & 1) * 64, head * DH, bars + 8 * B_WO);
            e_tma2d(sb + SM_WO + wu * 16384 + 8192, tWo, (wu >> 1) * 512 + qd * 128 + (wu & 1) * 64, head * DH + 64, bars + 8 * B_WO);
        }
        if (wg == 1 && warp0) {
            if (lane == 0) mbar_arrive_cluster(bars + 8 * B_HE, j ^ 1);
            mbar_wait_w(bars + 8 * B_HE, 0);
#pragma unroll 1
            for (int i = 0; i < 2; i++) h_load(sb, hsrc, i, j, head);
        }
    }
    const uint32_t mrow = wg < 2 ? mem_row(wu >> 1, wg * 2 + (wu & 1), qd) : mem_row(kh, wu, 0);
    const uint32_t u_m = mrow - wu * 512, u_e = mrow + 512 - wu * 64;
#define TAB(i) lds1(sb + SM_TAB + (i) * 512 + (G16() >> 2))
    {
        const uint32_t r8 = lane & 7;
        const uint32_t tb = sb + SM_TAB + wg * 1536 + t * 4, ma = sb + SM_HB + 4096 + r8 * 128;
        if (wg < 2) {
            sts1(tb, sb + SM_WO + wi * 16384 + frow + ((fx ^ (2 * wg)) << 4));
            sts1(tb + 512, wl0);
            sts1(tb + 1024, ma + (((lane >> 3) ^ r8) << 4));
        } else {
            sts1(tb, ma + (wi & 1) * HBK + ((((wi & 2) + (lane >> 4) * 4 + ((lane >> 3) & 1)) ^ r8) << 4));
            sts1(tb + 512, ((((wi & 2) + 4) ^ r8) << 4) + ((lane & 3) == 2 ? ma + 128 + ((wi & 1) + (lane >> 3) * 2) * HBK : sb + SM_HB - 128));
            sts1(tb + 1024, mem_row(role >> 6, (role >> 4) & 3, (role >> 2) & 3) + (lane < 8 ? qd * 128 + lane * 16 : 512 + qd * 32 + (lane & 1) * 16));
        }
    }
#define HB(ks) dadd(mkdesc(SB0 + SM_HB + ((ks) >> 2) * HBK + ((ks) & 3) * 32, 16, 1024, 1), hbo)
#define STEP_CONSTS                                                                                  \
    const uint32_t tag = (s & 1) ^ 1, ttag = ((s >> 1) & 1) ^ 1, tso = (s & 1) * 32768;              \
    G16();                            \
    const int p = s + 2, b = p & 1;                                                                  \
    uint32_t hbo = b * 4096, fz[5] = {0, 0, 0, 0, 0};                                                   \
    const uint32_t ftag = (((p - 1) >> 1) & 1) ^ 1, ptag = ((p >> 1) & 1) ^ 1;                       \
    const uint32_t pso = tbw + (1 << 20) + (b ^ 1) * 32768 + j * 16384 + kh * 2048;
#define SCHED_FENCE(i) fz[i] = clk32();
#define FZ ((fz[0] | fz[1] | fz[2] | fz[3] | fz[4]) & zero)
#define BLOCK_FENCE asm volatile("pmevent 0;" ::: "memory");
    constexpr int GAP = 32 / NL;
#define l16 (sbl + g16)
#define g8 (g16 >> 1)
    uint4 u, v;
    uint8_t *pdst, *fdst;
    auto tok_pack = [&](int ty, const float* acc, uint32_t ftag, uint32_t ptag, bool later = false) {
        const bool tg = ty == 2 || !(g16 & 64);
        const uint32_t add = tg ? (ftag ^ 1) << 16 : 0u, keep = tg ? 0xfffe0000u : ~0u;
        const uint32_t add1 = ty == 2 ? 0u : add, keep1 = ty == 2 ? ~0u : keep;
        const uint32_t add2 = ty == 0 ? add : 0u, keep2 = ty == 0 ? keep : ~0u;
        v = {pack2(pretag(acc[0], add, keep), pretag(acc[1], add1, keep1)), pack2(acc[2], acc[3]),
             pack2(pretag(acc[4], add2, keep2), pretag(acc[5], add2, keep2)), pack2(acc[6], acc[7])};
        if (ty < 2) { v.x = movm(v.x); v.z = movm(v.z); v.y = movm(v.y); v.w = movm(v.w); }
        u = {settag(pack2(pretag(acc[8], (ptag ^ 1) << 16, 0xfffe0000u), acc[9]), ptag), pack2(acc[10], acc[11]), pack2(acc[12], acc[13]), pack2(acc[14], acc[15])};
        if (later) return;
        v.x = settag(v.x, ftag);
        if (ty == 0) v.z = settag(v.z, ftag);
    };

#pragma unroll 1
    for (int s = -2; s < 0; s++) {
        STEP_CONSTS
        (void)tag; (void)ttag; (void)tso; (void)fz;
        float acc[16];
        mbar_wait_w(bars + 8 * (B_HB + b), 0);
        wg_fence();
#pragma unroll
        for (int i = 0; i < 32; i++) {
            if (i < NL) wgmma_ss32(acc, dadd(mkdesc(SB0 + i * 2048, 8192, 1024, 1), wg * 4096), HB(i), i != 0);
            else wgmma_rs32(acc, w[i < NL ? 0 : i - NL], HB(i), 1);
        }
        wg_commit();
        uint4 pa = {0, 0, 0, 0};
        int it = 0;
#pragma unroll 1
        while ((p > 0) & any_bit0(pa.x ^ ftag) & (++it < POLL_LIMIT)) pa = ldg_b128(arena + (pso + g16));
        pdst = arena + ((pso ^ (32768 + 2048)) + G16());
        fdst = arena + ((b ^ 1) * 32768 + u_to + g16);
        wg_wait<0>();
#pragma unroll
        for (int k = 0; k < 4; k++) { acc[2 * k] += bflo((&pa.x)[k]); acc[2 * k + 1] += bfhi((&pa.x)[k]); }
        tok_pack(wg, acc, ftag, ptag);
        stg_b128_if(true, pdst, u.x, u.y, u.z, u.w);
        stg_b128_if(p > 0 && wg, fdst, v.x, v.y, v.z, v.w);
        if (p > 0 && !wg) { stg_rlx2(fdst - lane * 8, v.x, v.y); stg_rlx2(fdst - lane * 8 + 256, v.z, v.w); }
        if (p == 0) {
            if (wg != 1) bar_arrive(NB_C, 288);
        }
    }
    if (wg == 1 && warp0) {
        wait_count_w(&g_tick[32 + (lane & 3) * 8], 2);
        asm volatile("fence.proxy.async.global;" ::: "memory");
        bar_sync(NB_C, 288);
        if (g16 == 0) mbar_arrive_cluster(bars + 8 * B_HE, j ^ 1);
        mbar_wait_w(bars + 8 * B_HE, 1);
        h_load(sb, hsrc, 2, j, head);
    }

    auto qk_loop = [&](auto wgc) {
        constexpr int WG = decltype(wgc)::value;
        uint32_t w0[NL][4], lm0;
        auto w0_load = [&]() {
            const uint32_t wl = TAB(WG * 3 + 1);
            lm0 = TAB(WG * 3 + 2);
#pragma unroll
            for (int k = 0; k < NL; k++) ldsm4t(w0[k], wl + k * 2048);
        };
        const uint32_t wlo = WG * 65536 - SM_WO - wu * 16384, wlx = __reduce_max_sync(~0u, (wi ^ WG) << 5);
        uint32_t tq0, lm, lm1, dx2 = dly.x2;
        auto proj_pre = [&](int s) {
            uint32_t wz0 = zero;
#pragma unroll
            for (int k = 0; k < NL; k += 2) wz0 = and3(wz0, w0[k][0], w0[k + 1 < NL ? k + 1 : k][0]);
            lm = lm0 + (s & 1) * 65536 + wz0; lm1 = lm ^ 64;
            asm volatile("" : "+r"(lm), "+r"(lm1));
        };
        auto proj = [&](int s, auto mid) {
            bar_sync(NB_MEM, 384);
            float c[4][4];
            constexpr int PD = WG ? 5 : 3;
            uint32_t bf[16][4], tq1;
#pragma unroll
            for (int it = 0; it < PD; it++) ldsm4(bf[it], (it & 1 ? lm1 : lm) + (it >> 1) * HBK);
            mid(-1);
#pragma unroll
            for (int it = 0; it < 16; it++) {
                const uint32_t* bfr = bf[it];
                if (it + PD < 16) ldsm4(bf[it + PD < 16 ? it + PD : 0], ((it + PD) & 1 ? lm1 : lm) + ((it + PD) >> 1) * HBK);
                const uint32_t* wa = 2 * it < NL ? w0[2 * it < NL ? 2 * it : 0] : w[2 * it < NL ? 0 : 2 * it - NL];
                const uint32_t* wb = 2 * it + 1 < NL ? w0[2 * it + 1 < NL ? 2 * it + 1 : 0] : w[2 * it + 1 < NL ? 0 : 2 * it + 1 - NL];
                float *ca = c[(2 * it) & 3], *cb = c[(2 * it + 1) & 3];
                if (it < 2) { mma16816z(ca, wa, bfr[0], bfr[1]); mma16816z(cb, wb, bfr[2], bfr[3]); }
                else { mma16816(ca, wa[0], wa[1], wa[2], wa[3], bfr[0], bfr[1]); mma16816(cb, wb[0], wb[1], wb[2], wb[3], bfr[2], bfr[3]); }
                mid(it);
                if (it == 15) { tq1 = clk32(); bar_arrive(NB_QK, 384); }
            }
            const uint32_t xo = u_xo + (G16() >> 1);
            float r[4];
#pragma unroll
            for (int e = 0; e < 4; e++) {
                constexpr float SH = SM_L2E / 4096;
                r[e] = WG ? (c[0][e] + c[1][e]) + (c[2][e] + c[3][e]) : fmaf(c[2][e] + c[3][e], SH, (c[0][e] + c[1][e]) * SH);
            }
            const uint32_t r0 = pack2(r[0], r[1]), r1 = pack2(r[2], r[3]);
            const uint32_t m0 = movm(r0), m1 = movm(r1);
            tq0 = clk32();
            stg_rlx2(arena + xo, settag(m0, (s & 1) ^ 1), m1);
            tq0 += tq1 & zero;
        };
        w0_load();
        proj_pre(0);
        if (WG == 1) bar_sync(NB_P, 256);
        proj(0, [](int) {});
        if (WG == 0) mbar_wait_w(bars + 8 * B_WO, 0);
#pragma unroll 1
        for (int s = 0;; s++) {
            STEP_CONSTS
            uint4 pa;
            float acc[16];
            auto acc_init = [&]() {
#pragma unroll
                for (int k = 0; k < 4; k++) { acc[2 * k] = bflo((&pa.x)[k]); acc[2 * k + 1] = bfhi((&pa.x)[k]); acc[8 + 2 * k] = __uint_as_float((&pa.x)[k] & zero); acc[9 + 2 * k] = __uint_as_float(~(&pa.x)[k] & zero); }
            };
            uint32_t wf[NPF][4], a3;
#define WF(f) ((a3 ^ (((f) & 1) * 64)) + ((f) >> 1) * 2048)
            if (WG == 1) {
                float sc[5][4];
                uint32_t sx0 = sb + SM_SX - wu * (2560 - 16) + G16() * 5;
                asm volatile("" : "+r"(sx0));
                int it = 0;
                bool bad;
#pragma unroll 1
                do {
                    uint4 kf[2][2];
                    U2 qf[2], x[8];
                    const uint32_t gz = g16 | (it & zero);
                    const uint8_t *ts = arena + (tso + tbw + gz), *tq = arena + (tso + tbq + (gz >> 1)), *xp = arena + (xso + (gz >> 1));
#pragma unroll
                    for (int a = 0; a < 4; a++) kf[a >> 1][a & 1] = ldg_b128(ts + (a >> 1) * 16384 + (a & 1) * 2048);
                    spin_until(tq0, dx2 - 100);
#pragma unroll
                    for (int a = 0; a < 2; a++) qf[a] = ldg_u2(tq + a * 16384);
                    spin_until(tq0, dx2);
#pragma unroll
                    for (int i = 0; i < 8; i++) x[i] = ldg_u2(xp + (i >> 2) * 16384 + (i & 3) * 1024);
                    const uint32_t q0[4] = {hadd2(x[0].x, x[1].x), qf[0].x, hadd2(x[0].y, x[1].y), qf[0].y};
                    const uint32_t q1[4] = {hadd2(x[2].x, x[3].x), qf[1].x, hadd2(x[2].y, x[3].y), qf[1].y};
                    const uint32_t bt = ((qf[0].x ^ ttag) | (qf[1].x ^ ttag)) | ((kf[0][0].x ^ ttag) | (kf[0][1].x ^ ttag)) | ((kf[1][0].x ^ ttag) | (kf[1][1].x ^ ttag));
                    uint32_t bx = 0;
#pragma unroll
                    for (int i = 0; i < 8; i += 2) bx |= (x[i].x ^ tag) | (x[i + 1].x ^ tag);
                    mma16816z(sc[0], q0, kf[0][0].x, kf[0][0].y);
                    mma16816z(sc[1], q0, kf[0][0].z, kf[0][0].w);
                    mma16816z(sc[2], q0, kf[0][1].x, kf[0][1].y);
                    mma16816z(sc[3], q0, kf[0][1].z, kf[0][1].w);
                    mma16816z(sc[4], q0, hadd2(x[4].x, x[5].x), hadd2(x[4].y, x[5].y));
                    bad = any_bit0(bt | bx) & (++it < POLL_LIMIT);
                    mma16816(sc[0], q1[0], q1[1], q1[2], q1[3], kf[1][0].x, kf[1][0].y);
                    mma16816(sc[1], q1[0], q1[1], q1[2], q1[3], kf[1][0].z, kf[1][0].w);
                    mma16816(sc[2], q1[0], q1[1], q1[2], q1[3], kf[1][1].x, kf[1][1].y);
                    mma16816(sc[3], q1[0], q1[1], q1[2], q1[3], kf[1][1].z, kf[1][1].w);
                    mma16816(sc[4], q1[0], q1[1], q1[2], q1[3], hadd2(x[6].x, x[7].x), hadd2(x[6].y, x[7].y));
                } while (bad);
                sts4(sx0, pack_h2(sc[0][0], sc[0][1]), pack_h2(sc[1][0], sc[1][1]), pack_h2(sc[2][0], sc[2][1]), pack_h2(sc[3][0], sc[3][1]));
                sts1(sx0 + 64 - wu * 12, pack_h2(sc[4][0], sc[4][1]));
                bar_arrive(NB_X1, 384);
                if (it > 1 && s > 1) dx2 += dly.more2;
                auto tok_sts = [&]() {
#pragma unroll
                    for (int n = 0; n < 5; n++) sts2(sb + SM_SX + 2560 + g8 + n * 1088, sc[n][2], sc[n][3]);
                };
                a3 = TAB(WG * 3);
                if (s == 0) mbar_wait_w(bars + 8 * B_WO, 0);
                softmax_rows(sb + SM_SX + 2560, sb + SM_PX + 1024, g16 | (clk32() & zero), qd * 8, [&]() { BLOCK_FENCE tok_sts(); bar_sync(NB_PX, 128); }, [&]() {
                    BLOCK_FENCE
#pragma unroll
                    for (int f = 0; f < NE1; f++) ldsm4t(wf[f], WF(f));
                    BLOCK_FENCE
                });
            } else {
                a3 = TAB(WG * 3);
                if (warp1 && (s & 3) == 1) asm volatile("fence.proxy.async.global;" ::: "memory");
                spin_until(tq0, dly.pa);
                uint4 x, y;
                int it = 0;
#pragma unroll 1
                do { x = ldg_b128(arena + (pso + g16)); y = ldg_b128(arena + (pso + tokbase(1) - tokbase(0) + g16)); }
                while ((p <= NSEG) & any_bit0(xor_or(x.x, y.x, ftag)) & (++it < POLL_LIMIT));
                sts4(sb + SM_PA + g16, x.x, x.y, x.z, x.w);
                sts4(sb + SM_PA + 2048 + g16, y.x, y.y, y.z, y.w);
                bar_sync(NB_X1, 384);
                if (g16 < 32) asm volatile("red.relaxed.gpu.global.max.u32 [%0], %1; red.relaxed.gpu.global.add.u32 [%0+4], 1;"
                                                    ::"l"(arena + ((blk(LB_TIME, 0) ^ (g16 << 8)) + qd * 1024 + (tq0 & zero))), "r"(gtime()) : "memory");
                __syncwarp();
                const uint32_t tx = clk32();
                spin_until(tx, dly.w2);
            }
#pragma unroll
            for (int f = WG ? NE1 : 0; f < NPF; f++) ldsm4t(wf[f], WF(f));
            if (s + 1 == NSEG) { bar_arrive(NB_X2, 384); break; }
            const uint32_t oa = l16 + SM_OX, slot = mem_slot(s + 1);
            float c[4][4];
            uint32_t ob[4][4];
            BLOCK_FENCE
            bar_sync(NB_X2, 384);
            ldsm4t(ob[0], oa);
            ldsm4t(ob[1], oa + 512);
            SCHED_FENCE(0)
#pragma unroll
            for (int f = 0; f < 16; f++) {
                const uint32_t *a = wf[f % NPF], *o = ob[f >> 2] + (f & 2);
                if (f < 4) mma16816z(c[f], a, o[0], o[1]);
                else mma16816(c[f & 3], a[0], a[1], a[2], a[3], o[0], o[1]);
                if (f == 3) ldsm4t(ob[2], oa + 1024);
                if (f == 5) { ldsm4t(ob[3], oa + 1536); if (NPF < 16) ldsm4t(wf[0], WF(NPF)); }
                if (f == 7) {
#pragma unroll
                    for (int k = NPF + 1; k < 16; k++) ldsm4t(wf[k - NPF], WF(k));
                }
                if (f == 3 || f == 5 || f == 7) SCHED_FENCE(f / 2)
                if (f == 11) {
#pragma unroll
                    for (int k = NL - W0_E; k < NL; k++) ldsm4t(w0[k], (a3 ^ wlx) + wlo + k * 2048);
                    SCHED_FENCE(4)
                }
            }
            const float last = c[1][3] + c[3][3], one = __uint_as_float(CNT1 << 16);
            red_mem(arena + (u_m + slot + G16()), pack2(c[0][0] + c[2][0], c[0][1] + c[2][1]), pack2(c[0][2] + c[2][2], c[0][3] + c[2][3]),
                    pack2(c[1][0] + c[3][0], c[1][1] + c[3][1]), pack2(c[1][2] + c[3][2], g16 & 16 ? one : last),
                    arena + (u_e + slot + ((g16 >> 3) & ~3u)), pack2(last, one), g16 & 16);
            hbo += FZ;
            constexpr int NS = NL - W0_RS, GS = (32 - NL + NS) / NS;
            BLOCK_FENCE
#pragma unroll
            for (int k = NL - W0_E - 1; k >= 0; k--) ldsm4t(w0[k], (a3 ^ wlx) + wlo + k * 2048);
            lm0 = TAB(WG * 3 + 2);
            if (WG == 1) pa = lds4(sb + SM_PA + 2048 + g16);
            if (WG == 0) {
                bar_arrive(NB_WIN, 384);
                pa = lds4(sb + SM_PA + g16);
                acc_init();
                asm volatile("" : F16(acc, 0));
                BLOCK_FENCE
            }
            wg_fence();
            bar_sync(WG ? NB_WIN : NB_B, WG ? 384 : 256);
#pragma unroll
            for (int i = 0; i < 32; i++) {
                const int k = i / GS;
                if (i >= 32 - NL + NS) wgmma_rs32(acc, w0[i < 32 - NL + NS ? 0 : i - 32 + NL], HB(i - 32 + NL), 1);
                else if (i % GS == GS - 1 && k < NS) wgmma_ss32(acc, mkdesc(SB0 + WG * 65536 + k * 2048, 8192, 1024, 1), HB(k), 1);
                else wgmma_rs32(acc, w[i - (k < NS ? k : NS)], HB(NL + i - (k < NS ? k : NS)), WG == 0 || i);
                if (WG == 1 && i == G_AT) bar_arrive(NB_B, 256);
                if (WG == 1 && i == 31 - NL + NS) wg_fence();
            }
            wg_commit();
            BLOCK_FENCE
            if (WG == 1 && warp0 && !(s & 3)) wait_count_w(&g_tick[32 + ((G16() >> 4) & 3) * 8], min((s + 1) / 4 + 3, 17));
            auto tok_store = [&](int m) {
                if (m & 1) {
                    if (WG) stg_b128_if(true, arena + ((b ^ 1) * 32768 + u_to + G16()), v.x, v.y, v.z, v.w);
                    else {
                        uint8_t* d = arena + ((b ^ 1) * 32768 + u_to + wu * 256 + (G16() >> 1));
                        stg_rlx2(d, v.x, v.y); stg_rlx2(d + 256, v.z, v.w);
                    }
                }
                if (m & 2) stg_b128_if(p < NSEG, arena + ((pso ^ (32768 + 2048)) + G16()), u.x, u.y, u.z, u.w);
            };
            if (WG == 0) proj_pre(s + 1);
            BLOCK_FENCE
            wg_wait<0>();
            if (WG == 0) {
                asm volatile("" : F16(acc, 0));
                proj(s + 1, [&](int it) {
                    if (it < 0) {
                        SCHED_FENCE(0)
                        asm volatile("" : F16(acc, 0));
                        tok_pack(WG, acc, ftag, ptag, true);
                        tok_store(2);
                        SCHED_FENCE(1)
                    }
                    if (it == 2) { SCHED_FENCE(2) v.x = settag(v.x, ftag); v.z = settag(v.z, ftag); tok_store(1); SCHED_FENCE(3) }
                });
                tq0 += (fz[0] | fz[1] | fz[2] | fz[3]) & zero;
            } else {
#pragma unroll
                for (int k = 0; k < 4; k++) { acc[2 * k] += bflo((&pa.x)[k]); acc[2 * k + 1] += bfhi((&pa.x)[k]); }
                tok_pack(WG, acc, ftag, ptag);
                proj_pre(s + 1);
                asm volatile("" : "+r"(u.x), "+r"(u.y), "+r"(u.z), "+r"(u.w), "+r"(v.x), "+r"(v.y), "+r"(v.z), "+r"(v.w));
                BLOCK_FENCE
                bar_sync(NB_P, 256);
                tok_store(3);
                proj(s + 1, [](int) {});
            }
        }
    };
    if (wg == 0) {
        qk_loop(IC<0>());
    } else if (wg == 1) {
        qk_loop(IC<1>());
    } else {
        const uint32_t ONES = 0x3f803f80u, u_o = qd * 65536 + head * 2048 + wu * 384;
        uint32_t tw = 0, dl = 0, dbase = kh == mypar ? dly.near : dly.far, dst0, dx0;
        dst0 = TAB(6); dx0 = TAB(7);
        uint32_t ov[4] = {0, 0, 0, 0};
        auto o_store = [&](int s) {
            uint8_t* od = (uint8_t*)g_O + (uint32_t)(s * (32 * NH * DH * 2) + u_o + (G16() >> 2));
#pragma unroll
            for (int a = 0; a < 4; a++) stg_rlx1(od + a * 128, ov[a]);
        };
        uint4 vf[2][2], pa;
        auto tok_fetch = [&](int s) {
            const uint8_t* ts = arena + ((s & 1) * 32768 + tbw + g16);
#pragma unroll
            for (int a = 0; a < 4; a++) vf[a >> 1][a & 1] = ldg_b128(ts + (a >> 1) * 16384 + (a & 1) * 2048);
            pa = ldg_b128(arena + (tbw + (1 << 20) + (~s & 1) * 32768 + j * 16384 + kh * 2048 + g16));
        };
        tok_fetch(0);
#pragma unroll 1
        for (int s = 0;; s++) {
            STEP_CONSTS
#define VFBAD ((vf[0][0].x ^ ttag) | (vf[0][1].x ^ ttag) | (vf[1][0].x ^ ttag) | (vf[1][1].x ^ ttag))
#define TOKBAD (VFBAD | (p <= NSEG ? pa.x ^ ftag : 0))
            {
                const uint32_t dst = dst0 + b * 65536, dx = dx0 + b * 65536;
                const uint8_t *ms = arena + (u_m + mem_slot(s) + g16), *me = arena + (u_e + mem_slot(s) + ((g16 >> 3) & ~3u));
                uint32_t em = g16 & 16 ? 0u : ~0u;
                asm volatile("" : "+l"(ms), "+l"(me), "+r"(em));
                spin_until(tw, dl);
                int it = 0;
                bool bad;
#pragma unroll 1
                do {
                    uint4 m[4];
                    uint32_t x[4];
#pragma unroll
                    for (int i = 0; i < 4; i++) m[i] = ldg_rlx4(ms + i * 1024);
#pragma unroll
                    for (int i = 0; i < 4; i++) x[i] = ldg_rlx1(me + i * 1024);
#pragma unroll
                    for (int i = 0; i < 3; i++) {
                        stsm4t(dst + i * 2 * HBK, m[i].x, m[i].y, m[i].z, m[i].w);
                        if (i == 1) asm volatile("{.reg .pred p; setp.eq.s32 p, %0, 0; @p bar.arrive %1, 256;}" ::"r"(it), "n"(NB_P) : "memory");
                    }
                    uint32_t c = m[0].w & m[1].w, r, msk = ~(it << 16) & CNT_ALL << 16;
                    asm volatile("" : "+r"(c), "+r"(msk));
                    SCHED_FENCE(1)
                    stsm4t(dst + 6 * HBK, m[3].x, m[3].y, m[3].z, m[3].w);
                    stsm4t(dx, x[0], x[1], x[2], x[3]);
                    asm volatile("{.reg .pred p, q; .reg .b32 t, u; lop3.b32 t, %1, %2, %3, 0x80; lop3.b32 u, %4, %5, %6, 0x80; lop3.b32 t, t, %8, %7, 0xa8;\n"
                                 " lop3.b32 t, t, u, %9, 0x2a; setp.ne.u32 p, t, 0; vote.sync.any.pred q, p, 0xffffffff; @!q bar.arrive %10, 384; selp.u32 %0, 1, 0, q;}"
                                 : "=r"(r) : "r"(c), "r"(m[2].w), "r"(m[3].w), "r"(x[0]), "r"(x[1]), "r"(x[2]), "r"(x[3]), "r"(em), "r"(msk), "n"(NB_MEM) : "memory");
                    bad = r; it++;
                } while (bad);
                if (it > 1 && s > 1) dbase += dly.more;
            }
            o_store(max(s - 1, 0));
            fence_async_smem();
            hbo += fz[1] & zero;
            int it = 0;
#pragma unroll 1
            while (any_bit0(TOKBAD) & (++it < POLL_LIMIT)) tok_fetch(s + (it & zero));
            float acc[20];
#pragma unroll
            for (int k = 0; k < 4; k++) { acc[2 * k] = bflo((&pa.x)[k]); acc[2 * k + 1] = bfhi((&pa.x)[k]); acc[8 + 2 * k] = acc[9 + 2 * k] = acc[16 + k] = __uint_as_float(pa.x & zero); }
            if (p <= NSEG) mbar_wait_w(bars + 8 * (B_HB + b), (p >> 1) & 1);
            asm volatile("" : F16(acc, 0), F4(acc, 16));
            BLOCK_FENCE
            wg_fence();
            bar_sync(NB_QK, 384);
#pragma unroll
            for (int i = 0; i < 32; i++) {
                const int k = i / GAP;
                if (i % GAP == GAP - 1 && k < NL) wgmma_ss40(acc, mkdesc(SB0 + 131072 + k * 2048, 8192, 1024, 1), HB(k), 1);
                else wgmma_rs40(acc, w[i - (k < NL ? k : NL)], HB(NL + i - (k < NL ? k : NL)), 1);
            }
            wg_commit();
            uint8_t* vo = arena + (u_xo + (G16() >> 1));
            pdst = arena + ((pso ^ (32768 + 2048)) + G16());
            fdst = arena + ((b ^ 1) * 32768 + u_to + g16);
            BLOCK_FENCE
            wg_wait<0>();
            stg_rlx2(vo, settag(pack2(acc[16], acc[17]), tag), pack2(acc[18], acc[19]));
            const uint32_t tv = clk32();
            tok_pack(2, acc, ftag, ptag);
            stg_b128_if(p <= NSEG, fdst, v.x, v.y, v.z, v.w);
            stg_b128_if(p < NSEG, pdst, u.x, u.y, u.z, u.w);
            const uint8_t* xp = arena + (xso + 32768 + (G16() >> 1));
            const uint32_t sxa = sb + SM_SX - wu * 2560 + G16() * 5;
            uint32_t sel[2];
            {
                const uint32_t q = (G16() >> 4 ^ g16 >> 6 & 1) & 3;
                sel[0] = q == 0 ? 0x3c00 : 0; sel[1] = q == 2 ? 0x3c00 : 0;
                asm volatile("" : "+r"(sel[0]), "+r"(sel[1]));
            }
            uint32_t xv[4], gt = 0;
            auto pv = [&](uint32_t p0, uint32_t p1, uint32_t p2, uint32_t p3, uint32_t p4, auto getv, auto done) {
                float oc[2][4], lc[4] = {0.f, 0.f, 0.f, 0.f};
                mma16816(lc, ONES, ONES, ONES, ONES, p0, p1);
                mma16816z(oc[0], &vf[0][0].x, p0, p1);
                mma16816z(oc[1], &vf[1][0].x, p0, p1);
                mma16816(lc, ONES, ONES, ONES, ONES, p2, p3);
                mma16816(oc[0], vf[0][1].x, vf[0][1].y, vf[0][1].z, vf[0][1].w, p2, p3);
                mma16816(oc[1], vf[1][1].x, vf[1][1].y, vf[1][1].z, vf[1][1].w, p2, p3);
                mma1688(lc, ONES, ONES, p4);
                getv();
                mma1688(oc[0], xv[0], xv[1], p4);
                mma1688(oc[1], xv[2], xv[3], p4);
                done(__float_as_uint(oc[0][0]) | __float_as_uint(oc[1][0]) | __float_as_uint(lc[0]));
                const float r0 = rcp_fast(lc[0]), r1 = rcp_fast(lc[1]);
                ov[0] = pack2(oc[0][0] * r0, oc[0][1] * r1); ov[1] = pack2(oc[0][2] * r0, oc[0][3] * r1);
                ov[2] = pack2(oc[1][0] * r0, oc[1][1] * r1); ov[3] = pack2(oc[1][2] * r0, oc[1][3] * r1);
            };
            bool bad;
            it = 0;
#pragma unroll 1
            do {
                U2 xr[4];
                asm volatile("{.reg .pred p; setp.eq.s32 p, %0, 0; @p bar.sync %1, 384;}" ::"r"(it), "n"(NB_X1) : "memory");
                uint4 sx[5];
#pragma unroll
                for (int i = 0; i < 5; i++) sx[i] = lds4(sxa + i * 16);
                if (it == 0) { gt = gtime(); tw = clk32(); }
                spin_until(tv, dly.v);
#pragma unroll
                for (int i = 0; i < 4; i++) xr[i] = ldg_u2(xp + i * 1024);
                uint32_t h[5], h0[4];
#pragma unroll
                for (int n = 0; n < 4; n++) h0[n] = add_h2((&sx[0].x)[n], (&sx[1].x)[n]);
#pragma unroll
                for (int n = 0; n < 4; n++) h[n] = add_h2(h0[n], add_h2((&sx[2].x)[n], (&sx[3].x)[n]));
                h[4] = add_h2(add_h2(sx[4].x, sx[4].y), add_h2(sx[4].z, sx[4].w));
                uint32_t hm = max_h2(max_h2(max_h2(h[0], h[1]), h[2]), max_h2(h[3], h[4]));
                float2 a[5];
                float mb;
                {
                    float d[2][4];
                    const uint32_t hs = __byte_perm(hm, hm, 0x1032);
#pragma unroll
                    for (int k = 0; k < 2; k++)
                        asm volatile("mma.sync.aligned.m16n8k8.row.col.f32.f16.f16.f32 {%0,%1,%2,%3},{%4,%5},{%6},{%7,%7,%7,%7};"
                                     : "=f"(d[k][0]), "=f"(d[k][1]), "=f"(d[k][2]), "=f"(d[k][3]) : "r"(hm), "r"(hs), "r"(sel[k]), "f"(0.f));
#pragma unroll
                    for (int n = 0; n < 5; n++) a[n] = unpack_h2(h[n]);
                    mb = -4096.0f * fmaxf(fmaxf(fmaxf(d[0][0], d[0][1]), fmaxf(d[0][2], d[0][3])), fmaxf(fmaxf(d[1][0], d[1][1]), fmaxf(d[1][2], d[1][3])));
                }
                uint32_t pm[5];
#pragma unroll
                for (int n = 0; n < 5; n++) pm[n] = pack2(ex2(fmaf(a[n].x, 4096.0f, mb)), ex2(fmaf(a[n].y, 4096.0f, mb)));
                pv(pm[0], pm[1], pm[2], pm[3], pm[4], [&]() {
                    xv[0] = hadd2(xr[0].x, xr[1].x); xv[1] = hadd2(xr[0].y, xr[1].y);
                    xv[2] = hadd2(xr[2].x, xr[3].x); xv[3] = hadd2(xr[2].y, xr[3].y);
                }, [](uint32_t) {});
                bad = any_bit0((xr[0].x ^ tag) | (xr[1].x ^ tag) | (xr[2].x ^ tag) | (xr[3].x ^ tag)) & (++it < POLL_LIMIT);
                stsm4(sb + SM_OX + g16, ov[0], ov[1], ov[2], ov[3]);
            } while (bad);
            bar_sync(NB_X2, 384);
            BLOCK_FENCE
            U2 tv2 = {0, 0};
            const uint8_t* tp = arena + (blk(LB_TIME, mypar) + ((G16() << 6) & 0xc00));
            {
                const uint4 pp = lds4(l16 + SM_PX + 1024);
                const uint32_t p4 = lds1(sb + SM_PX + 512 + 1024 - wu * 128 + (G16() >> 2));
                tv2 = ldg_u2(tp);
                if (warp0 && s + 3 <= NSEG) h_load(sb, hsrc, s + 3, j, head);
                pv(pp.x, pp.y, pp.z, pp.w, p4, []() {}, [&](uint32_t r) { bar_arrive(NB_WIN + (r & zero), 384); });
            }
            dst0 = TAB(6); dx0 = TAB(7);
            const uint32_t zo = TAB(8);
            BLOCK_FENCE
            if (s + 1 == NSEG) break;
            asm volatile("" : "+r"(tv2.y));
            it = 0;
            uint32_t tm = __reduce_max_sync(~0u, tv2.y < 32 * (s + 1) ? ~0u : tv2.x);
#pragma unroll 1
            while ((tm == ~0u) & (++it < 16)) { tv2 = ldg_u2(tp); tm = __reduce_max_sync(~0u, tv2.y < 32 * (s + 1) ? ~0u : tv2.x); }
            const uint32_t e = tm - gt;
            tok_fetch(s + 1);
            stg4_if(g16 < 160, arena + (zo + mem_slot(s + 3)), 0);
            dl = dbase + (e > 4096 ? 0 : e * E_MUL >> 4);
        }
        o_store(NSEG - 1);
    }
}

struct RecMaps { CUtensorMap wq, wk, wv, wo, wmod, w3, w1; };
struct RecPtrs { const bf16 *x, *mem0, *c, *wmod, *w1, *w3; uint8_t* arena; uint32_t zero; const bf16 *w2, *w4, *wo; Delays dly; };

__device__ __forceinline__ float silu_bf(const bf16* c, int i) {
    const float v = __bfloat162float(c[i]);
    return bfround(__fdividef(v, 1.0f + __expf(-v)));
}
#define LN_FREE 6
#define LN_SEQ 0xcba6420987531ull
#define W_LATE 1000
#define W_OPEN 1400
__device__ __forceinline__ uint32_t side_window_(const uint8_t* arena, uint32_t n) {
    U2 v;
    int it = 0;
#pragma unroll 1
    while (v = ldg_u2(arena + (LB_TIME << 13)), ((v.y >> 5) == n || gtime() - v.x > W_OPEN + W_LATE) && v.y < 32 * NSEG && ++it < 64) __nanosleep(100);
    it = 0;
#pragma unroll 1
    while ((int)(gtime() - v.x - W_OPEN) < 0 && ++it < 256) {}
    return v.y >> 5;
}
#define side_window(arena, n) n = side_window_(arena, n)
__device__ __noinline__ void rec_ln(uint32_t sb, const bf16* x, uint8_t* arena, int id, int r0) {
    int r1 = 32;
    uint32_t n = 0;
    const int tid = threadIdx.x, lane = tid & 31, wid = __reduce_max_sync(~0u, tid >> 5);
    const uint32_t ring = sb + wid * 8192 + lane * 16, coef = sb + SM_PRE;
    x += (id * 8 + wid) * 2 * DM + lane * 8;
#pragma unroll 1
    for (int r = r0 - 1; r < r1; r++) {
        if (r + 1 < r1) {
#pragma unroll
            for (int i = 0; i < 8; i++)
                asm volatile("cp.async.cg.shared.global [%0], [%1], 16;" ::"r"(ring + (~r & 1) * 4096 + i * 512), "l"(x + (r + 1) * 64 * DM + i * 256) : "memory");
        }
        asm volatile("cp.async.commit_group; cp.async.wait_group 1;" ::: "memory");
        if (r < r0) continue;
        const uint32_t src = ring + (r & 1) * 4096;
        float m[2] = {0.f, 0.f}, rs[2];
#pragma unroll 1
        for (int ps = 0; ps < 2; ps++) {
            float t[2][2] = {{0.f, 0.f}, {0.f, 0.f}};
#pragma unroll 1
            for (int i = 0; i < 2048; i += 512) {
#pragma unroll
                for (int h = 0; h < 2; h++) {
                    const uint4 u = lds4(src + h * 2048 + i);
#pragma unroll
                    for (int e = 0; e < 4; e++) {
                        const float a = bflo((&u.x)[e]) - m[h], c = bfhi((&u.x)[e]) - m[h];
                        t[h][0] = fmaf(a, ps ? a : 1.0f, t[h][0]); t[h][1] = fmaf(c, ps ? c : 1.0f, t[h][1]);
                    }
                }
            }
            rs[0] = t[0][0] + t[0][1]; rs[1] = t[1][0] + t[1][1];
#pragma unroll 1
            for (int o = 16; o; o >>= 1) { rs[0] += __shfl_xor_sync(~0u, rs[0], o); rs[1] += __shfl_xor_sync(~0u, rs[1], o); }
            if (!ps) { m[0] = rs[0] * (1.0f / DM); m[1] = rs[1] * (1.0f / DM); }
        }
        rs[0] = rsqrtf(rs[0] * (1.0f / DM) + 1e-5f); rs[1] = rsqrtf(rs[1] * (1.0f / DM) + 1e-5f);
        if (r == r0) {
#pragma unroll 1
            for (int i = tid; i < 2 * DM / 4; i += 256) {
                float t[4];
                int it = 0;
                uint32_t ok;
#pragma unroll 1
                do {
                    uint4 u[8];
#pragma unroll
                    for (int k = 0; k < 8; k++) u[k] = ldg_rlx4(g_modp + k * 2 * DM + i * 4);
                    ok = 1;
#pragma unroll
                    for (int k = 0; k < 32; k++) { const uint32_t w = (&u[k >> 2].x)[k & 3]; ok &= w; t[k & 3] = k < 4 ? __uint_as_float(w) : t[k & 3] + __uint_as_float(w); }
                } while (!__all_sync(~0u, ok) & (++it < SPIN_LIMIT));
                const float o = i >> 8;
                const uint32_t lo = pack2(t[0], t[1]), hi = pack2(t[2], t[3]);
                sts4f(coef + (i >> 8) * 4096 + (i & 1) * 2048 + ((i & 255) >> 1) * 16, bflo(lo) + o, bfhi(lo) + o, bflo(hi) + o, bfhi(hi) + o);
            }
            bar_sync(NB_FIN0, 256);
        }
        uint8_t* dst = (uint8_t*)g_himg + (r * 2 + (id >> 1)) * 65536 + (lane >> 3) * 4096 + wid * 256;
#pragma unroll 1
        for (int i = 0; i < 4; i++) {
            const uint32_t ca = coef + i * 512 + lane * 16;
            const float4 s0 = lds4f(ca), s1 = lds4f(ca + 2048), c0 = lds4f(ca + 4096), c1 = lds4f(ca + 6144);
            const float sh[8] = {s0.x, s0.y, s0.z, s0.w, s1.x, s1.y, s1.z, s1.w}, sc[8] = {c0.x, c0.y, c0.z, c0.w, c1.x, c1.y, c1.z, c1.w};
#pragma unroll
            for (int h = 0; h < 2; h++) {
                uint4 u = lds4(src + h * 2048 + i * 512);
#pragma unroll
                for (int e = 0; e < 4; e++) {
                    uint32_t& w = (&u.x)[e];
                    w = pack2(fmaf((bflo(w) - m[h]) * rs[h], sc[2 * e], sh[2 * e]), fmaf((bfhi(w) - m[h]) * rs[h], sc[2 * e + 1], sh[2 * e + 1]));
                }
                *(uint4*)(dst + i * 16384 + ((id & 1) == (i >> 1) ? 65536 : 2048) + h * 128 + (((lane ^ (2 * wid + h)) & 7) << 4)) = u;
            }
        }
        if (r == 0) {
            int ro, it = 0;
#pragma unroll 1
            do asm volatile("ld.volatile.shared.u32 %0, [%1];" : "=r"(ro) : "r"(sb + SM_BAR + 192) : "memory"); while ((ro == INT_MIN) & (++it < SPIN_LIMIT));
            if (ro >= 0) r1 = 2;
        }
        if (!r || (r & 1)) {
            bar_sync(r ? NB_FIN0 : NB_C, r ? 256 : 320);
            if (wid == (r >> 1 & 7)) {
                if (r == 1) bar_arrive(NB_B, 64);
                if (lane == 0) { signal_count(&g_tick[32 + id * 8]); }
                __syncwarp();
            }
        }
        if (r == 2) wait_count_w(&g_tick[32 + id * 8], 2);
        if (r > 2) side_window(arena, n);
    }
}
#define SIDE_T 300
template <int NQ, int NB>
__device__ __forceinline__ void side_gemv(const CUtensorMap* tm, int c0, int k0, int k1, uint32_t cs, uint32_t sb, const uint8_t* arena, uint32_t& n, uint32_t& ph, float (*acc)[8], bool once = false) {
    const uint32_t w = __reduce_max_sync(~0u, threadIdx.x >> 5 & 3), ring = sb + (NB == 3 ? 65536 : 0) + w * NB * 8192;
    const uint32_t bars = sb + SM_BAR + (NB == 3 ? 8 * B_W + w * 24 : 8 + w * 8), bs = NB == 3 ? 8 : 0;
#pragma unroll
    for (int q = 0; q < NQ; q++)
#pragma unroll
        for (int j = 0; j < 8; j++) acc[q][j] = 0.f;
#pragma unroll 1
    for (; k0 < k1; k0 += NB * 16, ph ^= 1) {
        const int nr = min(NB * 16, k1 - k0);
        side_window(arena, n);
        const uint32_t t0 = clk32();
#pragma unroll 1
        for (int g = 0; g < NB; g++) {
            spin_until(t0, (g * 4 + w) * (SIDE_T / 4));
            if (bs || !g) e_expect(bars + bs * g, !bs ? NB * 8192 : g * 16 < nr ? 8192 : 0);
            if (g * 16 < nr) e_tma2d_hint(ring + g * 8192, tm, c0, k0 + g * 16, bars + bs * g, once ? EVICT_FIRST : EVICT_NORMAL);
        }
#pragma unroll 1
        for (int r = 0; r < nr; r += 16) {
            mbar_wait_w(bars + bs * (r >> 4), ph);
            uint4 v[16];
#pragma unroll
            for (int h = 0; h < 16; h++) v[h] = lds4(ring + (r + h) * 512 + (threadIdx.x & 31) * 16);
            float4 cf[NQ][4];
#pragma unroll
            for (int q = 0; q < NQ * 4; q++) cf[q >> 2][q & 3] = lds4f(cs + ((q >> 2) * DM + k0 + r + (q & 3) * 4) * 4);
#pragma unroll
            for (int h = 0; h < 16; h++) {
                const float f[8] = {bflo(v[h].x), bfhi(v[h].x), bflo(v[h].y), bfhi(v[h].y), bflo(v[h].z), bfhi(v[h].z), bflo(v[h].w), bfhi(v[h].w)};
#pragma unroll
                for (int q = 0; q < NQ; q++)
#pragma unroll
                    for (int j = 0; j < 8; j++) acc[q][j] = fmaf((&cf[q][h >> 2].x)[h & 3], f[j], acc[q][j]);
            }
        }
        fence_async_smem();
        __syncwarp();
    }
}
__device__ __noinline__ void rec_side(float* sm, const RecMaps& mp, const RecPtrs& p, int prr) {
    uint8_t* arena = p.arena;
    const int b = blockIdx.x;
    int id = (b - 128) >> 1;
    if (b < 128) {
        uint32_t v;
        int it = 0;
#pragma unroll 1
        do { v = __reduce_max_sync(~0u, ldg_rlx1(&g_tick[6])); spin_guard(++it); } while (__popc(v) < 2);
        id = v == 3 ? -1 - prr : (v & 1) ^ 1;
    }
    id = id * 2 + (b & 1);
    const int tid = threadIdx.x, t = tid & 127, w = __reduce_max_sync(~0u, t >> 5);
    float* coef = sm + (tid < 256 ? 44032 : 40960);
    const uint32_t sb = smem_u32(sm), cs = smem_u32(coef);
    uint32_t n = 0, ph = 0;
    float acc[3][8];
    if (tid < 256) {
        if (blockIdx.x < 128) rec_ln(smem_u32(sm), p.x, p.arena, id, 2);
        for (int i = tid; i < 2 * S_; i += 256) g_st[id * 2 * S_ + i] = 0.f;
        if (id == 0 && tid < 64) g_pcnt[tid * 8] = 0;
        if (id == 1) for (int i = tid; i < 6 * 256; i += 256) g_pflag[i] = 0;
        if (id == 2 && tid == 0) g_pt = 0;
        fence_async_smem();
        bar_sync(NB_FIN0, 256);
        if (PDL && tid == 0) asm volatile("fence.acq_rel.gpu; griddepcontrol.launch_dependents;" ::: "memory");
        if (tid >= 128) return;
        float* red = coef + 3 * DM;
        if (t == 0) wait_count1(&g_tick[8], 4);
        bar_sync(NB_S, 128);
        for (int i = t; i < DM; i += 128) { coef[i] = 1.0f + __ldcg(g_mod + 4 * DM + i); coef[DM + i] = __ldcg(g_mod + 3 * DM + i); coef[2 * DM + i] = 1.0f; }
        bar_sync(NB_S, 128);
        if (id == 1 && t < 32) {
            float u[5] = {0, 0, 0, 0, 0};
            for (int i = t; i < DM; i += 32) {
                const float a = coef[i], b = coef[DM + i];
                u[0] += a; u[1] += a * a; u[2] += a * b; u[3] += b; u[4] += b * b;
            }
#pragma unroll
            for (int q = 0; q < 5; q++) { const float r = warp_sum(u[q]); if (t == 0) g_cst[q] = r * (1.0f / DM); }
        }
        side_gemv<3, 2>(&mp.w1, id * 256, w * 256, w * 256 + 256, cs, sb, p.arena, n, ph, acc);
#pragma unroll
        for (int q = 0; q < 3; q++)
#pragma unroll
            for (int j = 0; j < 8; j++) red[((t >> 5) * 3 + q) * 256 + (t & 31) * 8 + j] = acc[q][j];
        bar_sync(NB_S, 128);
        for (int i = t; i < 768; i += 128) g_vec[(i >> 8) * DM + id * 256 + (i & 255)] = (red[i] + red[768 + i]) + (red[1536 + i] + red[2304 + i]);
        return;
    }
    for (int i = t; i < DM; i += 128) { coef[i] = silu_bf(p.c, i); coef[2 * DM + i] = 1.0f; }
    if (t == 0) wait_count1(&g_tick[32], 1);
    bar_sync(NB_G, 128);
    side_gemv<1, 3>(&mp.wmod, (2 + id) * DM + w * 256, 0, DM, cs, sb, p.arena, n, ph, acc, true);
#pragma unroll
    for (int j = 0; j < 8; j++) g_mod[(2 + id) * DM + t * 8 + j] = bfround(acc[0][j]);
    bar_sync(NB_G, 128);
    if (t == 0) signal_count(&g_tick[8]);
    side_gemv<1, 3>(&mp.w3, id * (FF / 4) + w * 256, 0, DM, cs + 8 * DM, sb, p.arena, n, ph, acc);
    if (t < FF / 32) {
#pragma unroll
        for (int j = 0; j < 8; j++) g_vec[3 * DM + id * (FF / 4) + t * 8 + j] = acc[0][j];
    }
}

__global__ void __cluster_dims__(2, 1, 1) __launch_bounds__(384, 1)
k_rec(const __grid_constant__ RecMaps mp, const __grid_constant__ RecPtrs p) {
    extern __shared__ uint8_t smraw[];
    const uint32_t sb = smem_u32(smraw);
    if ((sb & 0x3FFFF) != SB0) __trap();
    const uint32_t bars = sb + SM_BAR;
    const int tid = threadIdx.x, lane = tid & 31, b = blockIdx.x;
    const int wid = __reduce_max_sync(~0u, tid >> 5);
    const uint32_t rank = b & 1;
    uint8_t* arena = p.arena;
    volatile int* sinfo = (volatile int*)(smraw + SM_BAR + 192);
    if (tid == 0) sinfo[0] = INT_MIN;
    if (tid == 352) {
        for (int i = 0; i < 17; i++) mbar_init(bars + 8 * i, i == B_WO ? 4 : 1);
        asm volatile("fence.mbarrier_init.release.cluster;" ::: "memory");
    }
    __syncwarp();
    asm volatile("barrier.cluster.arrive.relaxed.aligned;" ::: "memory");
    int pr = 0, hA = 0;
    if (wid < 8) {
        if (b < 128) {
            const int cb = (b & 15) * 128, k0 = (b >> 4) * 128 + (tid >> 4);
            uint4 v[8];
#pragma unroll
            for (int i = 0; i < 8; i++) v[i] = __ldg((const uint4*)(p.wmod + (size_t)(k0 + 16 * i) * (6 * DM) + cb + (tid & 15) * 8));
            float acc[8] = {0, 0, 0, 0, 0, 0, 0, 0};
            const float s8 = silu_bf(p.c, k0 + 16 * (lane & 7));
#pragma unroll
            for (int i = 0; i < 8; i++) {
                const float sv = __shfl_sync(~0u, s8, i, 16);
                acc[0] += sv * bflo(v[i].x); acc[1] += sv * bfhi(v[i].x); acc[2] += sv * bflo(v[i].y); acc[3] += sv * bfhi(v[i].y);
                acc[4] += sv * bflo(v[i].z); acc[5] += sv * bfhi(v[i].z); acc[6] += sv * bflo(v[i].w); acc[7] += sv * bfhi(v[i].w);
            }
            float* red = (float*)(smraw + SM_PRE);
            *(float4*)(red + (tid >> 4) * 128 + (tid & 15) * 8) = make_float4(acc[0], acc[1], acc[2], acc[3]);
            *(float4*)(red + (tid >> 4) * 128 + (tid & 15) * 8 + 4) = make_float4(acc[4], acc[5], acc[6], acc[7]);
            bar_sync(NB_FIN0, 256);
            if (wid < 4) {
                float t = 0;
#pragma unroll
                for (int i = 0; i < 16; i++) t += red[i * 128 + tid];
                stg_rlx1(&g_modp[(b >> 4) * 2 * DM + cb + tid], __float_as_uint(t) | 1u);
            }
        } else {
            rec_ln(sb, p.x, p.arena, b - 128, 0);
        }
    } else if (wid >= 10 && b >= 128) {
        {
            const int w = (b - 128) * 2 + wid - 10;
            const uint16_t* src = (const uint16_t*)p.mem0 + (lane & 3) * 2 * DM + (w >> 2) * 512 + (w & 1) * 64 + (w & 2) * 8 + (lane >> 2);
            uint32_t v[4][4];
#pragma unroll
            for (int i = 0; i < 16; i++) v[i >> 2][i & 3] = src[(i >> 2) * 128 + (i & 2) * 16 + (i & 1) * 8] | ((uint32_t)src[DM + (i >> 2) * 128 + (i & 2) * 16 + (i & 1) * 8] << 16);
            uint8_t* d = arena + mem_row(w >> 2, w & 3, 0);
            uint8_t* e = d + 512 + (lane >> 1) * 4;
            d += lane * 16;
#pragma unroll
            for (int i = 0; i < 4; i++, d += 1024, e += 1024) {
                stg_rlx4(d, v[i][0], v[i][1], v[i][2], lane & 1 ? (v[i][3] & 0xffff) | CNT_ALL << 16 : v[i][3]);
                stg_rlx4(d + mem_slot(1), 0, 0, 0, 0);
                stg_rlx4(d + mem_slot(2), 0, 0, 0, 0);
                if (lane & 1) { stg_rlx1(e, v[i][3] >> 16 | CNT_ALL << 16); stg_rlx1(e + mem_slot(1), 0); stg_rlx1(e + mem_slot(2), 0); }
            }
            if (w == 0 && lane < 8) stg_rlx2(arena + (LB_TIME << 13) + lane * 1024, 0, 0);
            bar_arrive(NB_C, 320);
        }
    } else if (rank == 0) {
        uint32_t best = ~0u;
        const int pg = wid < 10 ? 0 : 1 + (b >> 1) / 22;
        uint32_t* q = (uint32_t*)(arena + (pg << 21) + (pg ? blk(b >> 1, wid & 1) : blk(LB_PROBE, wid & 1) + b * 16));
        stg_rlx1(q + (lane & 7), 0);
        uint32_t v = p.zero;
#pragma unroll 1
        for (int r = v; r <= NPROBE; r++) {
            const uint32_t t0 = clk32();
            asm volatile("{.reg .pred p; setp.eq.u32 p, %2, 0; @p atom.relaxed.gpu.global.exch.b32 %0, [%1], 0;}" : "+r"(v) : "l"(q + (t0 & p.zero)), "r"(lane) : "memory");
            v = __reduce_max_sync(~0u, v);
            best = min(best, clk32() - t0);
        }
        sinfo[wid - 6] = best + v;
        bar_sync(NB_KDONE, b < 128 ? 128 : 64);
        if (wid == 8) {
            const uint32_t par = sinfo[2] > sinfo[3];
            const u64 vote = b < 128 && (sinfo[4] > sinfo[5]) != par;
            asm volatile("{.reg .pred p; elect.sync _|p, 0xffffffff; @p red.relaxed.gpu.global.add.u64 [%0], %1;}" ::"l"((u64*)g_tick + (b >> 1) / 22), "l"((u64)(1 + 2 * par) << (2 * ((b >> 1) % 22)) | vote << 48) : "memory");
        }
    } else if (wid == 9) {
        stg_rlx1(&g_clk[b >> 1], ((clk32() - 2 * gtime()) & ~127u) + (b >> 1) + 1);
    }
    if (wid == 8) {
        uint32_t v[3], my;
        u64 m[3];
        const int me = b >> 1, l2 = 2 * min(lane, 21);
        int it = 0;
        __syncwarp();
        if (rank) spin_until(clk32(), 3000);
#pragma unroll 1
        do {
            my = ldg_rlx1(&g_clk[me]);
#pragma unroll
            for (int k = 0; k < 3; k++) v[k] = ldg_rlx1(&g_clk[k * 22 + l2 / 2]);
        } while (!__all_sync(~0u, my && v[0] && v[1] && v[2]) & (++it < SPIN_LIMIT));
#pragma unroll 1
        do {
#pragma unroll
            for (int k = 0; k < 3; k++) m[k] = ldg_u64((u64*)g_tick + k);
        } while (!__all_sync(~0u, (m[0] & m[1] & m[2]) >> l2 & 1) & (++it < SPIN_LIMIT));
        const uint32_t c0 = __reduce_min_sync(~0u, lane ? ~0u : v[0]) - 4097;
        const uint32_t mc = me >= 64 ? ~0u : my - c0;
        uint32_t o[3], cnt = 0, flip = 0;
#pragma unroll
        for (int k = 0; k < 3; k++) o[k] = m[k] >> (l2 + 1) & 1;
        const int par = __any_sync(~0u, (v[0] == my && o[0]) | (v[1] == my && o[1]) | (v[2] == my && o[2]));
#pragma unroll
        for (int k = 0; k < 3; k++) {
            const uint32_t c = v[k] - c0;
            const bool ln = k == 2 && lane >= 20;
            cnt += o[k] + (o[k] == par ? (ln ? 44 + lane < me : c < mc) * 256 + (c < my - c0) * 65536 : 0);
            flip |= (m[k] >> 48) > 10 ? 256 << k : 0;
        }
        cnt = __reduce_add_sync(~0u, lane < 22 ? cnt : 0);
        const int n1 = cnt & 255, n0 = 66 - n1, tk = cnt >> 8 & 255;
        if (lane == 0) g_cls[smid() & 255] = cnt < 32 << 16 ? par * 4 + (cnt >> 19) : 8;
        hA = min(n0 >> 1, NH);
        const int q0 = 2 * hA, q1 = 2 * NH - q0;
        const int over = tk - (par ? q1 : q0), lack = max(par ? q0 - n0 : q1 - n1, 0);
        if (over < 0) pr = par ? q0 + tk : tk;
        else if (over < lack) pr = (par ? n0 : q0 + n1) + over;
        else pr = -1 - (over - lack + (par ? max(n0 - q0, 0) : 0));
        hA |= flip;
        if (lane == 0) {
            sinfo[1] = hA; sinfo[0] = pr;
            if (b >= 128 && rank == 0) atomicOr(&g_tick[6], (pr < 0 ? 4u : 1u) << ((b - 128) >> 1));
        }
    }
    asm volatile("barrier.cluster.wait.aligned;" ::: "memory");
    if (wid == 8) {
        __syncwarp();
        bar_arrive(NB_A, 288);
        bar_arrive(NB_S, 128);
        if (b >= 128 && pr < 0) bar_sync(NB_B, 64);
        if (pr >= 0) {
            const int pu = __reduce_max_sync(~0u, pr), c0 = (pu >> 1) * 128 + rank * 64, r0 = (pu & 1) * 512;
#pragma unroll 1
            for (int n = 0; n < 13; n++) {
                const u64 seq = b >= 128 ? LN_SEQ : 0xcba9876543210ull;
                const int i = seq >> (4 * n) & 15;
                if (b >= 128 && i == 0) bar_sync(NB_B, 64);
                if (n >= W_INFL && (b < 128 || n < LN_FREE)) mbar_wait_w(bars + 8 * (B_W + (seq >> (4 * (n - W_INFL)) & 15)), 0);
                const int m = i < 8 ? i & 1 : i >> 2, k = i < 8 ? i >> 1 : i & 3;
                const uint32_t dst = sb + m * 65536 + k * 16384, br = bars + 8 * (m < 3 ? B_W + i : B_WO);
                const int c = m < 3 ? c0 : 576 + rank * 256 + (pu & 1) * 128, r = m < 3 ? r0 + k * 128 : (pu >> 1) * DH;
                const uint64_t pol = m < 3 ? EVICT_FIRST : EVICT_NORMAL;
                e_expect(br, 16384);
                e_tma2d_hint(dst, &mp.wq + m, c, r, br, pol);
                e_tma2d_hint(dst + 8192, &mp.wq + m, c, r + 64, br, pol);
            }
        }
    } else {
        bar_sync(wid < 8 ? NB_A : NB_S, wid < 8 ? 288 : 128);
    }
    const int prr = __reduce_max_sync(~0u, sinfo[0]);
    hA = __reduce_max_sync(~0u, sinfo[1]);
    if (prr < 0) {
        rec_side((float*)smraw, mp, p, prr);
        return;
    }
    if (PDL) asm volatile("griddepcontrol.launch_dependents;" ::: "memory");
    const int role = (prr >> 1) * 4 + rank * 2 + (prr & 1);
    rec_main(sb, &mp.wo, arena, role, hA, wid >> 2, p.zero, p.dly);
}

__device__ __forceinline__ void wgmma_ss192(float* d, uint64_t a, uint64_t b, int sc) {
    asm volatile("{.reg .pred p; setp.ne.b32 p, %98, 0;\n wgmma.mma_async.sync.aligned.m64n192k16.f32.bf16.bf16 "
                 "{%0,%1,%2,%3,%4,%5,%6,%7,%8,%9,%10,%11,%12,%13,%14,%15,%16,%17,%18,%19,%20,%21,%22,%23,%24,%25,%26,%27,%28,%29,%30,%31,%32,%33,%34,%35,%36,%37,%38,%39,%40,%41,%42,%43,%44,%45,%46,%47,%48,%49,%50,%51,%52,%53,%54,%55,%56,%57,%58,%59,%60,%61,%62,%63,%64,%65,%66,%67,%68,%69,%70,%71,%72,%73,%74,%75,%76,%77,%78,%79,%80,%81,%82,%83,%84,%85,%86,%87,%88,%89,%90,%91,%92,%93,%94,%95}, %96, %97, p, 1, 1, 0, 1;}"
                 : F16(d, 0), F16(d, 16), F16(d, 32), F16(d, 48), F16(d, 64), F16(d, 80) : "l"(a), "l"(b), "r"(sc));
}

constexpr uint32_t P_B = 81920, P_PL = 40960, P_OUT = 180224, P_VEC = 212992, P_ROW = P_VEC + 6144, P_BAR = P_ROW + 4096, P_SMEM = P_BAR + 256;
#define FLAG_ST "st.release.gpu.global.u32"
#define FLAG_LD "ld.acquire.gpu.global.u32"
constexpr int ST = 5;
constexpr int PB_F = 0, PB_E = 5, PB_R = 10, PB_OUT = 16;
enum { C_Y = 0, C_G = 1, C_X1 = 2, C_U = 3, C_S1 = 8, C_S3 = 9 };
enum { V_GA = 0, V_A = 1, V_B = 2, V_GB = 3, V_VA = 4, V_VB = 5, V_VC = 6, V_C3 = 7 };
struct PostMaps { CUtensorMap o, wo, y, w1, g, w2, x1, w3, u, w4, out; };
struct PostPtrs { const bf16* x; uint8_t* arena; };

struct GeluK { float k0, k1, kh; };
__device__ __forceinline__ GeluK gelu_k(float c) { return {0.7978845608028654f * c, 0.7978845608028654f * 0.044715f * c * c * c, 0.5f * c}; }
__device__ __forceinline__ float gelu_s(float t, const GeluK& k) {
    const float u = t * fmaf(t * t, k.k1, k.k0);
    float th; asm("tanh.approx.f32 %0, %1;" : "=f"(th) : "f"(u));
    const float hx = k.kh * t;
    return fmaf(hx, th, hx);
}
__device__ __forceinline__ float2 ldsv(uint32_t a) {
    float2 v; asm("ld.shared.v2.f32 {%0,%1}, [%2];" : "=f"(v.x), "=f"(v.y) : "r"(a)); return v;
}
__device__ __forceinline__ void wait_smem(uint32_t a, int target) {
    int it = 0;
#pragma unroll 1
    while (true) {
        int v;
        asm volatile("ld.acquire.cta.shared.u32 %0, [%1];" : "=r"(v) : "r"(a) : "memory");
        if (__all_sync(~0u, v >= target) | (++it > SPIN_LIMIT)) break;
    }
}

__device__ __forceinline__ void release(uint32_t rel, int st, bool c) {
    asm volatile("{.reg .pred p; setp.ne.u32 p, %1, 0; setp.ne.and.u32 p, %2, 0, p; @p mbarrier.arrive.shared::cluster.b64 _, [%0];}"
                 ::"r"(rel + 8 * (st ? st - 1 : ST - 1)), "r"(rel), "r"((uint32_t)c) : "memory");
}
struct Pipe { int st, ph; uint32_t rel; };
__device__ __forceinline__ void adv(Pipe& p) { if (++p.st == ST) { p.st = 0; p.ph ^= 1; } }

__device__ __forceinline__ void post_weights(uint32_t sb, const PostMaps& mp, int nb, int rank) {
    const uint32_t full = sb + P_BAR + 8 * PB_F, empty = sb + P_BAR + 8 * PB_E;
    int st = 0, pp = 1;
#pragma unroll 1
    for (int ph = 0; ph < 7; ph++) {
        const int NK = ph == 0 ? 64 : ph == 6 ? 56 : 16, km = NK == 16 ? 15 : 63;
        const CUtensorMap* tb = &mp.wo + 2 * (ph < 3 ? ph : ph < 6 ? 3 : 4);
        const bool w3 = ph >= 3 && ph < 6;
        const int n0 = w3 ? nb * 64 + (ph == 4 ? 1536 : ph == 5 ? 2560 : 0) : nb * 128, dn = w3 ? 512 : 64;
        const int rot = NK == 16 ? 2 * (nb & 6) : 0, sw = ph == 1 || ph == 3 ? 2 * rank : 0;
#pragma unroll 1
        for (int i = 0; i < NK; i++) {
            const int k0 = (((i < 4 ? i ^ sw : i) + rot) & km) * 64;
            const uint32_t a = sb + P_B + st * 8192, f = full + 8 * st;
            mbar_wait_w(empty + 8 * st, pp);
            e_expect(f, ph == 3 ? 40960 : 32768);
            e_tma2d(a, tb, n0, k0, f);
            e_tma2d(a + P_PL, tb, n0 + dn, k0, f);
            if (ph == 3) e_tma2d(a + 2 * P_PL, tb, n0 + 1024, k0, f);
            if (++st == ST) { st = 0; pp ^= 1; }
        }
    }
#pragma unroll 1
    for (int i = 0; i < ST; i++) mbar_wait_w(empty + 8 * i, pp ^ (i < st));
}
__device__ __forceinline__ void post_acts(uint32_t sb, const PostMaps& mp, uint8_t* arena, int mb, int nb, int rank) {
    const int rh = 2 * mb + rank, lane = threadIdx.x & 31;
    const uint32_t bars = sb + P_BAR;
    int st = 0, pp = 1;
#pragma unroll 1
    for (int ph = 0; ph < 7; ph++) {
        const int NK = ph == 0 ? 64 : ph == 6 ? 56 : 16, km = NK == 16 ? 15 : 63;
        const CUtensorMap* ta = &mp.o + 2 * (ph < 3 ? ph : ph < 6 ? 3 : 4);
        const int amul = ph == 0 ? 256 : 64, arow = (ph == 0 ? rh * 8 : rh * 64) - 2, rot = NK == 16 ? 2 * (nb & 6) : 0;
        const bool own = ph == 1 || ph == 3;
        const uint32_t shifts = ph == 2 ? 0x04000301u : 0x02020202u;
        const uint32_t* fl = &g_pflag[(ph == 6 ? C_U : min(ph - 1, 2)) * 256 + (ph == 2 ? min(max(rh + min(lane >> 3, 2) - 1, 0), 31) : rh) * 8 + ((lane + nb - rank) & 7)];
        int i = 0, n = ph == 0 || ph == 5 ? NK : 0;
        if (own) { i = 4; if (st) { st--; pp ^= 1; } else st = 4; }
#pragma unroll 1
        while (i < NK) {
            if (n <= i) {
                int it = 0;
#pragma unroll 1
                do {
                    uint32_t v;
                    asm volatile(FLAG_LD " %0, [%1];" : "=r"(v) : "l"(fl) : "memory");
                    n = __reduce_min_sync(~0u, ph == 6 ? 8 * v : v || (own && !(lane & 6)) ? 16 : 2 * (lane & 7));
                    if (++it > SPIN_LIMIT) n = NK;
                } while (n <= i);
                asm volatile("fence.proxy.async.global;" ::: "memory");
            }
            if (own && (i == 5 || i == 6)) mbar_wait_w(bars + 8 * (PB_E + ph + i - 5), 1);
#pragma unroll 1
            for (const int e = own && i < 6 ? i + 1 : n; i < e; i++) {
                const int kb = (i + rot) & km;
                const uint32_t f = bars + 8 * (PB_F + st);
                mbar_wait_w(f + 8 * PB_E, pp);
                e_tma2d_mc(sb + st * 16384 + rank * 8192, ta, kb * amul, arow + (int)((shifts >> ((kb & 12) * 2)) & 7), f);
                if (++st == ST) { st = 0; pp ^= 1; }
            }
        }
    }
}

template <int PH, class F>
__device__ __forceinline__ void post_kb(uint32_t sb, float* acc, Pipe& p, int wg, bool lead, bool first, F mid) {
    constexpr uint64_t DA = PH == 0 ? mkdesc(SB0, 128, 1024, 0) : mkdesc(SB0, 16, 1024, 1);
    constexpr uint64_t DB = mkdesc(SB0 + P_B, P_PL, 1024, 1);
    mbar_wait_w(sb + P_BAR + 8 * PB_F + 8 * p.st, p.ph);
    const uint32_t a = (uint32_t)DA + p.st * 1024 + wg * 512, b = (uint32_t)DB + p.st * 512;
    wg_fence();
#pragma unroll
    for (int k = 0; k < 4; k++) {
        const uint64_t da = (DA & 0xffffffff00000000ull) | (a + k * (PH == 0 ? 16 : 2)), db = (DB & 0xffffffff00000000ull) | (b + k * 128);
        if (PH == 3) wgmma_ss192(acc, da, db, k || !first);
        else wgmma_ss128<PH == 0>(acc, da, db, k || !first);
    }
    wg_commit();
    wg_wait<1>();
    release(p.rel, p.st, !first);
    mid();
    adv(p);
}
__device__ __forceinline__ void post_end(uint32_t sb, Pipe& p, bool lead) {
    wg_wait<0>();
    release(p.rel, p.st, true);
}
template <int PH>
__device__ __forceinline__ void post_mma(uint32_t sb, float* acc, Pipe& p, int wg, bool lead, int nout, int pi, int mb, int nb) {
#pragma unroll 1
    for (int kb = 0; kb < 16; kb++)
        post_kb<PH>(sb, acc, p, wg, lead, kb == 0, [&]() {
            if (nout && kb == 0) wait_smem(sb + P_BAR + 8 * (PB_OUT + wg), nout);
        });
    post_end(sb, p, lead);
}

__global__ void __cluster_dims__(2, 1, 1) __launch_bounds__(384, 1)
k_post(const __grid_constant__ PostMaps mp, const __grid_constant__ PostPtrs pp) {
    extern __shared__ uint8_t smraw[];
    const uint32_t sb = smem_u32(smraw);
    if ((sb & 0x3FFFF) != SB0) __trap();
    const int tid = threadIdx.x, lane = tid & 31;
    const int rank = blockIdx.x & 1;
    uint8_t* arena = pp.arena;
    const uint32_t bars = sb + P_BAR;
    int c = 0;
    unsigned long long v = 0;
    const int wid = __reduce_max_sync(~0u, tid >> 5);
    const bool draw = tid == 352 && rank == 0;
    if (draw) {
        c = min(ldg_rlx1(&g_cls[smid() & 255]), 8u);
        asm volatile("{.reg .b64 a; cvt.u64.u32 a, %%laneid; add.u64 a, a, %1; atom.relaxed.gpu.global.add.u64 %0, [a], %2;}" : "=l"(v) : "l"(&g_pt), "l"(1ull << (7 * c)) : "memory");
    }
    if (wid < 11) {
        asm volatile("{.reg .pred p; elect.sync _|p, 0xffffffff; @p mbarrier.init.shared.b64 [%0], %1; @p prefetch.tensormap [%2]; fence.mbarrier_init.release.cluster;}"
                     ::"r"(bars + 8 * wid), "r"(wid >= PB_E && wid < PB_R ? 4 : 1), "l"(&mp.o + wid) : "memory");
        if (wid == PB_R) { sts4(bars + 8 * PB_OUT, 0, 0, 0, 0); e_expect(bars + 8 * PB_R, 4); }
    }
    __syncwarp();
    asm volatile("barrier.cluster.arrive.relaxed.aligned; barrier.cluster.wait.aligned;" ::: "memory");
    if (draw) {
        int r = (v >> (7 * c)) & 127, role = c * 8 + r;
        if (c == 8 || r >= 8) {
            int n, x, it = 0;
#pragma unroll 1
            do {
                __nanosleep(200);
                v = ldg_u64(&g_pt); n = 0; x = c < 8 ? r - 8 : r;
#pragma unroll 1
                for (int i = 0; i < 63; i += 7) { const int m = v >> i & 127; n += m; if (i < 7 * c) x += max(m - 8, 0); }
            } while (n < gridDim.x / 2 && ++it < SPIN_LIMIT);
            role = -1;
#pragma unroll 1
            for (int i = 0; i < 64; i += 8, v >>= 7) {
                n = v & 127;
                if (x >= 0 && n + x < 8) role = i + n + x;
                x -= max(8 - n, 0);
            }
        }
#pragma unroll
        for (int i = 0; i < 2; i++)
            asm volatile("{.reg .b32 d; mapa.shared::cluster.u32 d, %0, %2; st.async.shared::cluster.mbarrier::complete_tx::bytes.u32 [d+8], %1, [d];}"
                         ::"r"(bars + 8 * PB_R), "r"(role), "r"(i) : "memory");
    }
    __syncwarp();
    mbar_wait_w(bars + 8 * PB_R, 0);
    const int pr = __reduce_max_sync(~0u, (int)lds1(bars + 8 * PB_R + 8));
    if (pr < 0) return;
    const int mb = (pr >> 5) * 8 + (pr & 7), nb = (pr >> 2 & 6) + rank, cta = pr * 2 + rank;
    if (wid >= 8) {
        asm volatile("setmaxnreg.dec.sync.aligned.u32 40;");
        const int w = wid - 8;
        if (w == 0) {
            post_weights(sb, mp, nb, rank);
        } else if (w == 3) {
            asm volatile("griddepcontrol.wait;" ::: "memory");
            post_acts(sb, mp, arena, mb, nb, rank);
        } else {
            const int wg = w - 1, rh = 2 * mb + wg;
            float* rowc = (float*)(smraw + P_ROW) + (wg * 64 + lane * 2) * 8;
            int nout = 0, sig = 0;
#pragma unroll 1
            for (int i = 0; i < 13; i++) {
                const int cnt = (0x4333333392180ull >> (4 * i)) & 15;
                if (cnt < C_S1) {
                    const int ng = cnt == C_U ? 1 : 2, c0 = cnt == C_U ? (i - 5) * 512 + nb * 64 : nb * 128;
                    const bool fast = (cnt == C_Y || cnt == C_X1);
#pragma unroll 1
                    for (int j = 0; j < ng; j++) {
                        const uint32_t st = j ? cnt : cnt ? 1 : 4;
                        const uint32_t src = sb + (fast ? st * 16384 + wg * 8192 : P_OUT + wg * 16384 + ((nout + j) & 1) * 8192);
                        bar_sync(4 + 4 * wg + (sig++ & 3), 160);
                        if (lane == 0) {
                            if (fast) asm volatile("mbarrier.complete_tx.relaxed.cta.shared::cta.b64 [%0], 8192;" ::"r"(bars + 8 * (PB_F + st)) : "memory");
                            asm volatile("cp.async.bulk.tensor.2d.global.shared::cta.bulk_group [%0, {%2, %3}], [%1]; cp.async.bulk.commit_group;"
                                         ::"l"(&mp.y + 2 * cnt), "r"(src), "r"(c0 + j * 64), "r"(rh * 64) : "memory");
                        }
                        __syncwarp();
                    }
                    if (lane == 0) {
                        auto to_peer = [&]() {
                            const uint32_t n = cnt ? 1 : 4;
                            mbar_wait(bars + 8 * (PB_E + (cnt ? 4 : 2)), 0);
#pragma unroll
                            for (int i = 0; i < 2; i++)
                                asm volatile("{.reg .b32 d, m; mapa.shared::cluster.u32 d, %0, %3; mapa.shared::cluster.u32 m, %2, %3;\n"
                                             " cp.async.bulk.shared::cluster.shared::cta.mbarrier::complete_tx::bytes [d], [%1], 8192, [m];}"
                                             ::"r"(sb + (cnt + 1 + i) * 16384 + wg * 8192), "r"(sb + (i ? cnt : n) * 16384 + wg * 8192), "r"(bars + 8 * (PB_F + cnt + 1 + i)), "r"(rank ^ 1) : "memory");
                        };
                        asm volatile("cp.async.bulk.wait_group 0; fence.proxy.async.global;" ::: "memory");
                        asm volatile("st.release.cta.shared.u32 [%0], %1;" ::"r"(bars + 8 * (PB_OUT + wg)), "r"(nout + ng) : "memory");
                        if (i < 12) asm volatile(FLAG_ST " [%0], %1;" ::"l"(&g_pflag[cnt * 256 + rh * 8 + nb]), "r"(max(i - 4, 1)) : "memory");
                        if (fast) to_peer();
                    }
                    nout += ng;
                    __syncwarp();
                    continue;
                }
                bar_sync(4 + 4 * wg + (sig++ & 3), 160);
                uint32_t* c = &g_pcnt[(cnt - C_S1) * 256 + rh * 8];
                if (lane == 0) signal_count(c);
                __syncwarp();
                wait_count_w(c, 8);
                const float4* sp = (const float4*)g_st + rh * 32 + lane;
                float4 u[3] = {__ldcg(sp + (cnt == C_S1 ? 0 : 3) * (S_ / 2)), __ldcg(sp + S_ / 2), __ldcg(sp + S_)};
#pragma unroll 1
                for (int h = 0; h < 2; h++) {
                    const float id = 1.0f / DM;
                    const float m = u[0].x * id, var = fmaxf(u[0].y * id - m * m, 0.f) + 1e-5f, r = rsqrtf(var);
                    float sc = r, m2 = 0.f;
                    if (cnt == C_S1) {
                        m2 = r * (u[1].x * id - m * g_cst[0]) + g_cst[3];
                        const float e2 = r * r * (u[2].x * id - 2.0f * m * u[1].y * id + m * m * g_cst[1]) + 2.0f * r * (u[2].y * id - m * g_cst[2]) + g_cst[4];
                        sc = r * rsqrtf(fmaxf(e2 - m2 * m2, 0.f) + 1e-5f);
                    }
                    const GeluK k = gelu_k(sc);
                    *(float4*)(rowc + h * 8) = make_float4(k.k0, k.k1, k.kh, -m);
                    *(float4*)(rowc + h * 8 + 4) = make_float4(var * r, -m2 * var * r, r, -m * r);
#pragma unroll
                    for (int q = 0; q < 3; q++) { u[q].x = u[q].z; u[q].y = u[q].w; }
                }
                bar_arrive(1 + wg, 160);
            }
        }
    } else {
        asm volatile("setmaxnreg.inc.sync.aligned.u32 232;");
        const bf16* xin = pp.x;
        const int wg = wid >> 2, wi = (tid >> 5) & 3, g = lane >> 2, tq = lane & 3;
        const int rh = 2 * mb + wg, row = rh * 64 + wi * 16 + g;
        const bool lead = (tid & 127) == 0;
        uint32_t keep[32];
#pragma unroll
        for (int i = 0; i < 8; i++)
            *(uint4*)(keep + 4 * i) = __ldg((const uint4*)(xin + (size_t)(rh * 64 + wi * 16 + (i & 3) * 4 + (lane >> 3)) * DM + nb * 128 + (i >> 2) * 64 + (lane & 7) * 8));
        asm volatile("griddepcontrol.wait;" ::: "memory");
        if (cta < 64) g_modp[cta * 256 + tid] = 0;
        if (cta == 64 && tid < 130) g_tick[tid] = 0;
        const float* src = wg ? g_vec + nb * 128 + tid - 128 : g_mod + 2 * DM + nb * 128 + tid;
        const float* c3 = &g_vec[3 * DM + (tid >> 6) * 512 + nb * 64 + (tid & 63)];
        const float cv[6] = {__ldcg(src), __ldcg(src + (wg ? 1 : 2) * DM), __ldcg(src + (wg ? 2 : 1) * DM), __ldcg(src + 3 * DM), __ldcg(c3), __ldcg(c3 + (tid < 192 ? 2048 : 0))};
        uint32_t vec = sb + P_VEC + tq * 8;
        const uint32_t stw = sb + (wi * 16 + ((lane >> 3) & 1) * 8 + (lane & 7)) * 128 + (((lane >> 4) ^ (lane & 7)) << 4);
        int sig = 0;
        auto signal = [&]() { bar_arrive(4 + 4 * wg + (sig++ & 3), 160); };
        auto put64 = [&](uint32_t o, const float* v) {
#pragma unroll
            for (int jj = 0; jj < 4; jj++, v += 8) stsm4((stw + o) ^ (jj << 5), pack2(v[0], v[1]), pack2(v[2], v[3]), pack2(v[4], v[5]), pack2(v[6], v[7]));
            fence_async_smem();
            signal();
        };
        auto slot = [&](int n) {
            mbar_wait_w(bars + 8 * (PB_E + n % 5), ((n / 5) & 1) ^ 1);
            return (n % 5) * 16384 + wg * 8192;
        };
        const uint32_t rowc = sb + P_ROW + (wg * 64 + wi * 16 + g) * 32, o128 = P_OUT + wg * 16384;
        Pipe pa = {0, 0, 0};
        asm("mapa.shared::cluster.u32 %0, %1, %2;" : "=r"(pa.rel) : "r"(bars + 8 * PB_E), "r"(tid & 1));
        if (tid & 126) pa.rel = 0;
#define KEEP(jn, e) (((e) & 1) ? bfhi(keep[2 * (jn) + ((e) >> 1)]) : bflo(keep[2 * (jn) + ((e) >> 1)]))
        float mu1[2], r1[2];
        {
            float acc[64];
#pragma unroll 1
            for (int kb = 0; kb < 64; kb++) {
                post_kb<0>(sb, acc, pa, wg, lead, kb == 0, []() {});
                if (kb == 24) bar_sync(3, 256);
                if (kb != 8 + 8 * wg) continue;
                float* sv = (float*)(smraw + P_VEC) + tid;
                const uint32_t xo = sb + o128 + wi * 2048 + (lane >> 3) * 128;
#pragma unroll
                for (int i = 0; i < 8; i++) sts4(xo + (i >> 2) * 8192 + (i & 3) * 512 + (((lane & 7) ^ ((i & 1) * 4 + (lane >> 3))) << 4), keep[4 * i], keep[4 * i + 1], keep[4 * i + 2], keep[4 * i + 3]);
                __syncwarp();
#pragma unroll
                for (int jj = 0; jj < 8; jj++) ldsm4(keep + jj * 4, (stw + o128 + (jj >> 2) * 8192) ^ ((jj & 3) << 5));
                sv[wg * 384] = cv[0]; sv[wg * 384 + 128] = cv[1] + (wg ? 0.0f : 1.0f); sv[wg * 384 + 256] = cv[2];
                if (!wg) sv[384] = cv[3];
                sv[V_C3 * 128] = cv[4]; sv[V_C3 * 128 + 256] = cv[5];
            }
            post_end(sb, pa, lead);
            asm volatile("" : "+r"(vec) :: "memory");
            float st[2][6];
#pragma unroll
            for (int q = 0; q < 6; q++) st[0][q] = st[1][q] = 0.f;
#pragma unroll
            for (int jn = 0; jn < 16; jn++) {
                const float2 ga = ldsv(vec + V_GA * 512 + jn * 32), a = ldsv(vec + V_A * 512 + jn * 32);
                float xa[4];
#pragma unroll
                for (int e = 0; e < 4; e++) {
                    xa[e] = fmaf((e & 1) ? ga.y : ga.x, acc[4 * jn + e], KEEP(jn, e));
                    st[e >> 1][0] += xa[e]; st[e >> 1][1] = fmaf(xa[e], xa[e], st[e >> 1][1]);
                    acc[4 * jn + e] = ((e & 1) ? a.y : a.x) * xa[e];
                }
                keep[2 * jn] = pack2(xa[0], xa[1]); keep[2 * jn + 1] = pack2(xa[2], xa[3]);
                if ((jn & 7) == 7) put64(slot(64 + (jn >> 3)), acc + 4 * jn - 28);
            }
#pragma unroll
            for (int jn = 0; jn < 16; jn++) {
                const float2 a = ldsv(vec + V_A * 512 + jn * 32), b = ldsv(vec + V_B * 512 + jn * 32);
#pragma unroll
                for (int e = 0; e < 4; e++) {
                    const float y = acc[4 * jn + e], aa = (e & 1) ? a.y : a.x, bb = (e & 1) ? b.y : b.x;
                    float* s = st[e >> 1];
                    s[2] += y; s[3] = fmaf(aa, y, s[3]); s[4] = fmaf(y, y, s[4]); s[5] = fmaf(bb, y, s[5]);
                }
            }
#pragma unroll
            for (int h = 0; h < 2; h++)
#pragma unroll
                for (int q = 0; q < 6; q++) { st[h][q] += __shfl_xor_sync(~0u, st[h][q], 1); st[h][q] += __shfl_xor_sync(~0u, st[h][q], 2); }
            if (tq < 3) {
#pragma unroll
                for (int h = 0; h < 2; h++)
                    red2(g_st + (tq * S_ + row + h * 8) * 2, tq == 0 ? st[h][0] : tq == 1 ? st[h][2] : st[h][4], tq == 0 ? st[h][1] : tq == 1 ? st[h][3] : st[h][5]);
            }
            signal();
        }
        {
            float acc[64];
            post_mma<1>(sb, acc, pa, wg, lead, 2, 4, mb, nb);
            float c1[2], c2[2], c3[2];
            GeluK gk[2];
            bar_sync(1 + wg, 160);
#pragma unroll
            for (int h = 0; h < 2; h++) {
                const float4 a = lds4f(rowc + h * 256), b = lds4f(rowc + h * 256 + 16);
                gk[h] = {a.x, a.y, a.z}; c1[h] = a.w; c2[h] = b.x; c3[h] = b.y; mu1[h] = b.w; r1[h] = b.z;
            }
#pragma unroll
            for (int jn = 0; jn < 16; jn++) {
                const float2 va = ldsv(vec + V_VA * 512 + jn * 32), vb = ldsv(vec + V_VB * 512 + jn * 32), vc = ldsv(vec + V_VC * 512 + jn * 32);
#pragma unroll
                for (int e = 0; e < 4; e++) {
                    const int h = e >> 1;
                    const float t = fmaf(c1[h], (e & 1) ? va.y : va.x, fmaf(c2[h], (e & 1) ? vb.y : vb.x, fmaf(c3[h], (e & 1) ? vc.y : vc.x, acc[4 * jn + e])));
                    acc[4 * jn + e] = gelu_s(t, gk[h]);
                }
                if ((jn & 7) == 7) put64(o128 + (jn >> 3) * 8192, acc + 4 * jn - 28);
            }
        }
        {
            float acc[64];
            post_mma<2>(sb, acc, pa, wg, lead, 0, 7, mb, nb);
#pragma unroll
            for (int jn = 0; jn < 16; jn++) {
                const float2 a = ldsv(vec + V_A * 512 + jn * 32), b = ldsv(vec + V_B * 512 + jn * 32);
#pragma unroll
                for (int e = 0; e < 4; e++) {
                    const int h = e >> 1;
                    acc[4 * jn + e] += fmaf(fmaf(KEEP(jn, e), r1[h], mu1[h]), (e & 1) ? a.y : a.x, (e & 1) ? b.y : b.x);
                }
                if ((jn & 7) == 7) put64(slot(96 + (jn >> 3)), acc + 4 * jn - 28);
            }
            BLOCK_FENCE
#pragma unroll
            for (int i = 0; i < 64; i += 16) asm volatile("" : F16(acc, i));
            float st[2][2] = {{0.f, 0.f}, {0.f, 0.f}};
#pragma unroll
            for (int jn = 0; jn < 16; jn++) {
                const float2 gb = ldsv(vec + V_GB * 512 + jn * 32);
                float z[4];
#pragma unroll
                for (int e = 0; e < 4; e++) {
                    const float x1 = acc[4 * jn + e];
                    st[e >> 1][0] += x1; st[e >> 1][1] = fmaf(x1, x1, st[e >> 1][1]);
                    z[e] = fmaf((e & 1) ? gb.y : gb.x, x1, KEEP(jn, e));
                }
                keep[2 * jn] = pack2(z[0], z[1]); keep[2 * jn + 1] = pack2(z[2], z[3]);
            }
#pragma unroll
            for (int h = 0; h < 2; h++)
#pragma unroll
                for (int q = 0; q < 2; q++) { st[h][q] += __shfl_xor_sync(~0u, st[h][q], 1); st[h][q] += __shfl_xor_sync(~0u, st[h][q], 2); }
            if (tq < 2) red2(g_st + (3 * S_ + row + tq * 8) * 2, tq ? st[1][0] : st[0][0], tq ? st[1][1] : st[0][1]);
            signal();
        }
        {
            float old[96], acc[64];
            post_mma<3>(sb, old, pa, wg, lead, 6, 10, mb, nb);
#pragma unroll
            for (int i = 0; i < 96; i += 16) asm volatile("" : F16(old, i));
            uint32_t v3 = vec + V_C3 * 512;
            bar_sync(1 + wg, 160);
            const float4 rc[2] = {lds4f(rowc), lds4f(rowc + 256)};
            float2 vc[2] = {lds2f(v3), lds2f(v3 + 32)};
            v3 += wg ? 0 : 64;
            bar_sync(3, 256);
#pragma unroll 1
            for (int blk = 0; blk < 11; blk++) {
                const uint32_t o = stw + o128 + (blk & 1) * 8192;
#pragma unroll
                for (int q = 0; q < 4; q++) {
#pragma unroll 1
                    for (int rep = 0; rep < 2; rep++) {
                        post_kb<1>(sb, acc, pa, wg, lead, q == 0 && rep == 0 && blk < 6 && !(blk & 1), []() {});
                        if (rep != wg) {
                            vc[0] = lds2f(v3 + q * 64); vc[1] = lds2f(v3 + q * 64 + 32);
                            if (q == 2) wait_smem(bars + 8 * (PB_OUT + wg), 6 + min(blk, 7));
                            if ((q == 0 && wg && (uint32_t)(blk - 1) < 7) || (q == 3 && !wg && blk < 7)) { fence_async_smem(); signal(); }
                        } else if (blk < 7) {
                            asm volatile("" : F4(old, 8 * q), F4(old, 8 * q + 4));
                            float t[8];
#pragma unroll
                            for (int i = 0; i < 8; i++) {
                                const float4& c = rc[(i >> 1) & 1];
                                t[i] = gelu_s(fmaf(c.w, (i & 1) ? vc[i >> 2].y : vc[i >> 2].x, old[8 * q + i]), GeluK{c.x, c.y, c.z});
                                old[8 * q + i] = old[32 + 8 * q + i];
                                old[32 + 8 * q + i] = old[64 + 8 * q + i];
                            }
                            uint32_t r[4] = {pack2(t[0], t[1]), pack2(t[2], t[3]), pack2(t[4], t[5]), pack2(t[6], t[7])};
                            asm volatile("pmevent 0;" : F4(old, 8 * q), F4(old, 8 * q + 4), F4(old, 8 * q + 32), F4(old, 8 * q + 36), "+r"(r[0]), "+r"(r[1]), "+r"(r[2]), "+r"(r[3]));
                            stsm4(o ^ (q << 5), r[0], r[1], r[2], r[3]);
                        }
                    }
                }
                v3 += 256;
                if (blk != 1 && blk != 3) continue;
                post_end(sb, pa, lead);
                asm volatile("" : F16(acc, 0), F4(acc, 16), F4(acc, 20), F4(acc, 24));
                asm volatile("" : F16(acc, 28), F4(acc, 44), F4(acc, 48), F4(acc, 52));
                asm volatile("" : F4(acc, 56), F4(acc, 60));
#pragma unroll
                for (int i = 0; i < 64; i++) old[32 + i] = acc[i];
            }
            post_end(sb, pa, lead);
#pragma unroll
            for (int jn = 0; jn < 16; jn++) {
                const float2 gb = ldsv(vec + V_GB * 512 + jn * 32);
#pragma unroll
                for (int e = 0; e < 4; e++) acc[4 * jn + e] = fmaf((e & 1) ? gb.y : gb.x, acc[4 * jn + e], KEEP(jn, e));
                if ((jn & 7) == 7) put64(o128 + ((jn >> 3) ^ 1) * 8192, acc + 4 * jn - 28);
            }
        }
    }
}

typedef CUresult (*EncFn)(CUtensorMap*, CUtensorMapDataType, cuuint32_t, void*, const cuuint64_t*, const cuuint64_t*, const cuuint32_t*,
                          const cuuint32_t*, CUtensorMapInterleave, CUtensorMapSwizzle, CUtensorMapL2promotion, CUtensorMapFloatOOBfill);

static CUtensorMap make_map(EncFn enc, const void* p, uint64_t inner, uint64_t outer, uint32_t bi = 64) {
    CUtensorMap m;
    cuuint64_t dims[2] = {inner, outer};
    cuuint64_t str[1] = {inner * 2};
    cuuint32_t box[2] = {bi, bi == 64 ? 64u : 16u};
    cuuint32_t es[2] = {1, 1};
    enc(&m, CU_TENSOR_MAP_DATA_TYPE_BFLOAT16, 2, (void*)p, dims, str, box, es, CU_TENSOR_MAP_INTERLEAVE_NONE,
        bi == 64 ? CU_TENSOR_MAP_SWIZZLE_128B : CU_TENSOR_MAP_SWIZZLE_NONE, CU_TENSOR_MAP_L2_PROMOTION_L2_256B, CU_TENSOR_MAP_FLOAT_OOB_FILL_NONE);
    return m;
}
static CUtensorMap make_map_o(EncFn enc, const void* p) {
    CUtensorMap m;
    cuuint64_t dims[2] = {16384, 256};
    cuuint64_t str[1] = {65536};
    cuuint32_t box[2] = {256, 8};
    cuuint32_t es[2] = {1, 1};
    enc(&m, CU_TENSOR_MAP_DATA_TYPE_UINT32, 2, (void*)p, dims, str, box, es, CU_TENSOR_MAP_INTERLEAVE_NONE, CU_TENSOR_MAP_SWIZZLE_NONE,
        CU_TENSOR_MAP_L2_PROMOTION_L2_256B, CU_TENSOR_MAP_FLOAT_OOB_FILL_NONE);
    return m;
}
template <class T> static T* sym(T& s) { void* p = nullptr; cudaGetSymbolAddress(&p, s); return (T*)p; }
static uint8_t* arena_base() { return (uint8_t*)(((uintptr_t)sym(g_arena) + (2u << 20) - 1) & ~(uintptr_t)((2u << 20) - 1)); }

static const Delays h_dly = {D_NEAR, D_FAR, D_X2, D_V, D_W2, D_PA, D_MORE2, D_MORE};
extern "C" void kernel_launch(void* const* d_in, const int* in_sizes, int n_in, void* d_out, int out_size) {
    const bf16* x = (const bf16*)d_in[0];
    const bf16* mem0 = (const bf16*)d_in[1];
    const bf16 *Wq = (const bf16*)d_in[2], *Wk = (const bf16*)d_in[3], *Wv = (const bf16*)d_in[4], *Wo = (const bf16*)d_in[5];
    const bf16 *w1 = (const bf16*)d_in[8], *w2 = (const bf16*)d_in[9], *w3 = (const bf16*)d_in[10], *w4 = (const bf16*)d_in[11];
    const bf16 *c = (const bf16*)d_in[12], *wmod = (const bf16*)d_in[13];
    bf16* out = (bf16*)d_out;

    EncFn enc = nullptr;
    cudaDriverEntryPointQueryResult qr;
    cudaGetDriverEntryPoint("cuTensorMapEncodeTiled", (void**)&enc, cudaEnableDefault, &qr);
    CUtensorMap tWq = make_map(enc, Wq, NH * DH, DM), tWk = make_map(enc, Wk, NH * DH, DM), tWv = make_map(enc, Wv, NH * DH, DM);
    uint8_t* arena = arena_base();
    PostMaps mp;
    mp.o = make_map_o(enc, g_O); mp.wo = make_map(enc, Wo, DM, NH * DH);
    mp.y = make_map(enc, sym(g_y), DM, S_); mp.w1 = make_map(enc, w1, DM, DM);
    mp.g = make_map(enc, sym(g_g), DM, S_); mp.w2 = make_map(enc, w2, DM, DM);
    mp.x1 = make_map(enc, sym(g_x1), DM, S_); mp.w3 = make_map(enc, w3, FF, DM);
    mp.u = make_map(enc, sym(g_u), FF, S_); mp.w4 = make_map(enc, w4, DM, FF);
    mp.out = make_map(enc, out, DM, S_);
    cudaFuncSetAttribute(k_rec, cudaFuncAttributeMaxDynamicSharedMemorySize, SM_REC_TOTAL + 2048);
    cudaFuncSetAttribute(k_post, cudaFuncAttributeMaxDynamicSharedMemorySize, P_SMEM);

    const PostPtrs pp = {x, arena};
    const RecPtrs rp = {x, mem0, c, wmod, w1, w3, arena, 0u, w2, w4, Wo, h_dly};
    const RecMaps rm = {tWq, tWk, tWv, mp.wo, make_map(enc, wmod, 6 * DM, DM, 256), make_map(enc, w3, FF, DM, 256), make_map(enc, w1, DM, DM, 256)};
    k_rec<<<132, 384, SM_REC_TOTAL + 2048>>>(rm, rp);
    cudaLaunchConfig_t cfg = {};
    cfg.gridDim = dim3(132); cfg.blockDim = dim3(384); cfg.dynamicSmemBytes = P_SMEM; cfg.stream = cudaStreamPerThread;
    cudaLaunchAttribute at[1];
    at[0].id = cudaLaunchAttributeProgrammaticStreamSerialization; at[0].val.programmaticStreamSerializationAllowed = PDL;
    cfg.attrs = at; cfg.numAttrs = 1;
    cudaLaunchKernelEx(&cfg, k_post, mp, pp);
}
```

```cpp
#include <cuda_runtime.h>
#include <cuda.h>
#include <cuda_bf16.h>
#include <stdint.h>
#include <limits.h>

typedef __nv_bfloat16 bf16;

constexpr int S_ = 2048, DM = 1024, NH = 32, DH = 128, NSEG = 64, FF = 3584;
constexpr int SPIN_LIMIT = 1 << 22;
#define W_INFL 2
#define H_PIECES 4
#define PDL 1
#define NPROBE 3

__device__ uint8_t g_arena[32 << 20];
#define SCR(type, off) ((type*)(arena + (off)))
#define g_tick SCR(uint32_t, 0x180000)
#define g_clk (g_tick + 64)
#define g_cls SCR(uint32_t, 0x180400)
#define g_pt (*SCR(unsigned long long, 0x180800))
#define g_modp SCR(uint32_t, 0x190000)
__host__ __device__ constexpr uint32_t blk(uint32_t lb, uint32_t par) {
    return (lb << 13) | ((((lb) ^ (lb >> 3) ^ (lb >> 4) ^ (lb >> 6) ^ par) & 1) << 12);
}
__host__ __device__ constexpr uint32_t lb_x2(uint32_t h) { return (h & 1) | ((h >> 1) << 3); }
__host__ __device__ constexpr uint32_t mem_row(uint32_t kh, uint32_t b, uint32_t r) { return blk(128 | b, kh) + r * 1024; }
__device__ __forceinline__ uint32_t mem_slot(uint32_t s) { return ((s & 1) << 15) | ((s & 2) << 17); }
constexpr uint32_t CNT1 = 0x3d80, CNT_ALL = 0x4000;
constexpr uint32_t LB_PROBE = 6 | 64, LB_TIME = 6;
__host__ __device__ constexpr uint32_t lb_tok(uint32_t h) { return (h & 1) | ((h >> 1) << 3); }
#define g_mod SCR(float, 0x1b0000)
#define g_himg SCR(bf16, 0x800000)
#define g_O SCR(bf16, 0xe00000)
__device__ __align__(1024) bf16 g_y[S_ * DM];
__device__ __align__(1024) bf16 g_g[S_ * DM];
__device__ __align__(1024) bf16 g_x1[S_ * DM];
#define g_st SCR(float, 0x1a0000)
#define g_vec SCR(float, 0x1b8000)
#define g_cst SCR(float, 0x180880)
#define g_pcnt SCR(uint32_t, 0x181000)
#define g_pflag SCR(uint32_t, 0x182000)
__device__ __align__(1024) bf16 g_u[S_ * FF];

__device__ __forceinline__ uint32_t smem_u32(const void* p) { return (uint32_t)__cvta_generic_to_shared(p); }
__device__ __forceinline__ void spin_guard(int it) {
    asm volatile("{.reg .pred p; setp.gt.s32 p, %0, %1; @p st.global.u32 [%2], %0;}" ::"r"(it), "n"(SPIN_LIMIT), "l"(1ull));
}
__device__ __forceinline__ void wg_fence() { asm volatile("wgmma.fence.sync.aligned;" ::: "memory"); }
__device__ __forceinline__ void wg_commit() { asm volatile("wgmma.commit_group.sync.aligned;" ::: "memory"); }
template <int N> __device__ __forceinline__ void wg_wait() { asm volatile("wgmma.wait_group.sync.aligned %0;" ::"n"(N) : "memory"); }
__host__ __device__ constexpr uint64_t mkdesc(uint32_t addr, uint32_t lbo, uint32_t sbo, uint32_t swz) {
    return (uint64_t)((addr & 0x3FFFF) >> 4) | ((uint64_t)(lbo >> 4) << 16) | ((uint64_t)(sbo >> 4) << 32) | ((uint64_t)swz << 62);
}
__device__ __forceinline__ uint64_t dadd(uint64_t d, uint32_t o) { return (d & 0xffffffff00000000ull) | (uint32_t)((uint32_t)d + o); }
__device__ __forceinline__ void mbar_init(uint32_t b, uint32_t c) { asm volatile("mbarrier.init.shared.b64 [%0], %1;" ::"r"(b), "r"(c) : "memory"); }
__device__ __forceinline__ void mbar_arrive_cluster(uint32_t b, uint32_t cta) {
    asm volatile("{.reg .b32 r; mapa.shared::cluster.u32 r, %0, %1; mbarrier.arrive.shared::cluster.b64 _, [r];}" ::"r"(b), "r"(cta) : "memory");
}
__device__ __forceinline__ bool mbar_try(uint32_t b, uint32_t par) {
    uint32_t ok;
    asm volatile("{.reg .pred p; mbarrier.try_wait.parity.shared.b64 p, [%1], %2; selp.u32 %0, 1, 0, p;}" : "=r"(ok) : "r"(b), "r"(par) : "memory");
    return ok;
}
__device__ __forceinline__ void mbar_wait(uint32_t b, uint32_t par) {
    int it = 0;
#pragma unroll 1
    while (!mbar_try(b, par) & (++it < SPIN_LIMIT)) {}
}
__device__ __forceinline__ void mbar_wait_w(uint32_t b, uint32_t par) {
    int it = 0;
#pragma unroll 1
    while (!__all_sync(~0u, mbar_try(b, par)) & (++it < SPIN_LIMIT)) {}
}
constexpr uint64_t EVICT_FIRST = 0x12F0000000000000ull, EVICT_NORMAL = 0x1000000000000000ull;   __device__ __forceinline__ void bar_sync(int id, int n) { asm volatile("bar.sync %0, %1;" ::"r"(id), "r"(n) : "memory"); }
__device__ __forceinline__ void bar_arrive(int id, int n) { asm volatile("bar.arrive %0, %1;" ::"r"(id), "r"(n) : "memory"); }
__device__ __forceinline__ void fence_async_smem() { asm volatile("fence.proxy.async.shared::cta;" ::: "memory"); }
__device__ __forceinline__ void ldsm4t(uint32_t* r, uint32_t a) {
    asm volatile("ldmatrix.sync.aligned.m8n8.x4.trans.shared.b16 {%0,%1,%2,%3}, [%4];" : "=r"(r[0]), "=r"(r[1]), "=r"(r[2]), "=r"(r[3]) : "r"(a) : "memory");
}
__device__ __forceinline__ void ldsm4(uint32_t* r, uint32_t a) {
    asm volatile("ldmatrix.sync.aligned.m8n8.x4.shared.b16 {%0,%1,%2,%3}, [%4];" : "=r"(r[0]), "=r"(r[1]), "=r"(r[2]), "=r"(r[3]) : "r"(a) : "memory");
}
__device__ __forceinline__ uint32_t movm(uint32_t a) {
    uint32_t d; asm volatile("movmatrix.sync.aligned.m8n8.trans.b16 %0, %1;" : "=r"(d) : "r"(a)); return d;
}
__device__ __forceinline__ void mma16816(float* d, uint32_t a0, uint32_t a1, uint32_t a2, uint32_t a3, uint32_t b0, uint32_t b1) {
    asm volatile("mma.sync.aligned.m16n8k16.row.col.f32.bf16.bf16.f32 {%0,%1,%2,%3},{%4,%5,%6,%7},{%8,%9},{%0,%1,%2,%3};"
                 : "+f"(d[0]), "+f"(d[1]), "+f"(d[2]), "+f"(d[3]) : "r"(a0), "r"(a1), "r"(a2), "r"(a3), "r"(b0), "r"(b1));
}
__device__ __forceinline__ void mma16816z(float* d, const uint32_t* a, uint32_t b0, uint32_t b1) {
    asm volatile("mma.sync.aligned.m16n8k16.row.col.f32.bf16.bf16.f32 {%0,%1,%2,%3},{%4,%5,%6,%7},{%8,%9},{%10,%10,%10,%10};"
                 : "=f"(d[0]), "=f"(d[1]), "=f"(d[2]), "=f"(d[3]) : "r"(a[0]), "r"(a[1]), "r"(a[2]), "r"(a[3]), "r"(b0), "r"(b1), "f"(0.f));
}
__device__ __forceinline__ void mma1688(float* d, uint32_t a0, uint32_t a1, uint32_t b0) {
    asm volatile("mma.sync.aligned.m16n8k8.row.col.f32.bf16.bf16.f32 {%0,%1,%2,%3},{%4,%5},{%6},{%0,%1,%2,%3};"
                 : "+f"(d[0]), "+f"(d[1]), "+f"(d[2]), "+f"(d[3]) : "r"(a0), "r"(a1), "r"(b0));
}
__device__ __forceinline__ uint32_t pack2(float lo, float hi) {
    uint32_t r; asm("cvt.rn.bf16x2.f32 %0, %1, %2;" : "=r"(r) : "f"(hi), "f"(lo)); return r;
}
__device__ __forceinline__ uint32_t hadd2(uint32_t a, uint32_t b) {
    uint32_t r; asm("add.rn.bf16x2 %0, %1, %2;" : "=r"(r) : "r"(a), "r"(b)); return r;
}
__device__ __forceinline__ float bflo(uint32_t u) { return __uint_as_float(u << 16); }
__device__ __forceinline__ float bfhi(uint32_t u) { return __uint_as_float(u & 0xffff0000u); }
__device__ __forceinline__ float ex2(float x) { float r; asm("ex2.approx.ftz.f32 %0, %1;" : "=f"(r) : "f"(x)); return r; }
__device__ __forceinline__ uint4 ldg_rlx4(const void* p) {
    uint4 v; asm volatile("ld.relaxed.gpu.global.v4.u32 {%0,%1,%2,%3}, [%4];" : "=r"(v.x), "=r"(v.y), "=r"(v.z), "=r"(v.w) : "l"(p) : "memory"); return v;
}
__device__ __forceinline__ uint32_t ldg_rlx1(const void* p) {
    uint32_t v; asm volatile("ld.relaxed.gpu.global.u32 %0, [%1];" : "=r"(v) : "l"(p) : "memory"); return v;
}
__device__ __forceinline__ void stg_rlx1(void* p, uint32_t v) { asm volatile("st.relaxed.gpu.global.u32 [%0], %1;" ::"l"(p), "r"(v) : "memory"); }
__device__ __forceinline__ void stg_rlx2(void* p, uint32_t x, uint32_t y) {
    unsigned long long v = (unsigned long long)x | ((unsigned long long)y << 32);
    asm volatile("st.relaxed.gpu.global.b64 [%0], %1;" ::"l"(p), "l"(v) : "memory");
}
__device__ __forceinline__ void stg_rlx4(void* p, uint32_t x, uint32_t y, uint32_t z, uint32_t w) {
    asm volatile("st.relaxed.gpu.global.v4.u32 [%0], {%1,%2,%3,%4};" ::"l"(p), "r"(x), "r"(y), "r"(z), "r"(w) : "memory");
}
__device__ __forceinline__ void sts4(uint32_t a, uint32_t x, uint32_t y, uint32_t z, uint32_t w) {
    asm volatile("st.shared.v4.u32 [%0], {%1,%2,%3,%4};" ::"r"(a), "r"(x), "r"(y), "r"(z), "r"(w) : "memory");
}
__device__ __forceinline__ uint4 lds4(uint32_t a) {
    uint4 v; asm volatile("ld.shared.v4.u32 {%0,%1,%2,%3}, [%4];" : "=r"(v.x), "=r"(v.y), "=r"(v.z), "=r"(v.w) : "r"(a) : "memory"); return v;
}
#define F4(d, i) "+f"(d[i]), "+f"(d[i + 1]), "+f"(d[i + 2]), "+f"(d[i + 3])
__device__ __forceinline__ void wgmma_rs32(float* d, const uint32_t* a, uint64_t b, int sc) {
    asm volatile("{.reg .pred p; setp.ne.b32 p, %21, 0;\n wgmma.mma_async.sync.aligned.m64n32k16.f32.bf16.bf16 {%0,%1,%2,%3,%4,%5,%6,%7,%8,%9,%10,%11,%12,%13,%14,%15}, {%16,%17,%18,%19}, %20, p, 1, 1, 0;}"
                 : F4(d, 0), F4(d, 4), F4(d, 8), F4(d, 12) : "r"(a[0]), "r"(a[1]), "r"(a[2]), "r"(a[3]), "l"(b), "r"(sc));
}
__device__ __forceinline__ void wgmma_ss32(float* d, uint64_t a, uint64_t b, int sc) {
    asm volatile("{.reg .pred p; setp.ne.b32 p, %18, 0;\n wgmma.mma_async.sync.aligned.m64n32k16.f32.bf16.bf16 {%0,%1,%2,%3,%4,%5,%6,%7,%8,%9,%10,%11,%12,%13,%14,%15}, %16, %17, p, 1, 1, 1, 0;}"
                 : F4(d, 0), F4(d, 4), F4(d, 8), F4(d, 12) : "l"(a), "l"(b), "r"(sc));
}
__device__ __forceinline__ void wgmma_rs40(float* d, const uint32_t* a, uint64_t b, int sc) {
    asm volatile("{.reg .pred p; setp.ne.b32 p, %25, 0;\n wgmma.mma_async.sync.aligned.m64n40k16.f32.bf16.bf16 {%0,%1,%2,%3,%4,%5,%6,%7,%8,%9,%10,%11,%12,%13,%14,%15,%16,%17,%18,%19}, {%20,%21,%22,%23}, %24, p, 1, 1, 0;}"
                 : F4(d, 0), F4(d, 4), F4(d, 8), F4(d, 12), F4(d, 16) : "r"(a[0]), "r"(a[1]), "r"(a[2]), "r"(a[3]), "l"(b), "r"(sc));
}
__device__ __forceinline__ void wgmma_ss40(float* d, uint64_t a, uint64_t b, int sc) {
    asm volatile("{.reg .pred p; setp.ne.b32 p, %22, 0;\n wgmma.mma_async.sync.aligned.m64n40k16.f32.bf16.bf16 {%0,%1,%2,%3,%4,%5,%6,%7,%8,%9,%10,%11,%12,%13,%14,%15,%16,%17,%18,%19}, %20, %21, p, 1, 1, 1, 0;}"
                 : F4(d, 0), F4(d, 4), F4(d, 8), F4(d, 12), F4(d, 16) : "l"(a), "l"(b), "r"(sc));
}
#define F16(d, i) F4(d, i), F4(d, i + 4), F4(d, i + 8), F4(d, i + 12)
template <int TA>
__device__ __forceinline__ void wgmma_ss128(float* d, uint64_t a, uint64_t b, int sc) {
    asm volatile("{.reg .pred p; setp.ne.b32 p, %66, 0;\n wgmma.mma_async.sync.aligned.m64n128k16.f32.bf16.bf16 "
                 "{%0,%1,%2,%3,%4,%5,%6,%7,%8,%9,%10,%11,%12,%13,%14,%15,%16,%17,%18,%19,%20,%21,%22,%23,%24,%25,%26,%27,%28,%29,%30,%31,"
                 "%32,%33,%34,%35,%36,%37,%38,%39,%40,%41,%42,%43,%44,%45,%46,%47,%48,%49,%50,%51,%52,%53,%54,%55,%56,%57,%58,%59,%60,%61,%62,%63}, %64, %65, p, 1, 1, %67, 1;}"
                 : F16(d, 0), F16(d, 16), F16(d, 32), F16(d, 48) : "l"(a), "l"(b), "r"(sc), "n"(TA));
}

__device__ __forceinline__ float warp_sum(float v) {
#pragma unroll
    for (int o = 16; o; o >>= 1) v += __shfl_xor_sync(~0u, v, o);
    return v;
}
__device__ __forceinline__ float bfround(float x) { return __bfloat162float(__float2bfloat16(x)); }

__device__ __forceinline__ void wait_count1(const uint32_t* p, uint32_t target) {
    int it = 0;
#pragma unroll 1
    while (true) {
        uint32_t v;
        asm volatile("ld.acquire.gpu.global.u32 %0, [%1];" : "=r"(v) : "l"(p) : "memory");
        if (v >= target) break;
        spin_guard(++it);
    }
}
__device__ __forceinline__ void red2(float* p, float a, float b) {
    asm volatile("red.relaxed.gpu.global.add.v2.f32 [%0], {%1, %2};" ::"l"(p), "f"(a), "f"(b) : "memory");
}
__device__ __forceinline__ void signal_count(uint32_t* p) { asm volatile("red.release.gpu.global.add.u32 [%0], 1;" ::"l"(p) : "memory"); }
__device__ __forceinline__ void e_expect(uint32_t b, uint32_t tx) {
    asm volatile("{.reg .pred p; elect.sync _|p, 0xffffffff; @p mbarrier.arrive.expect_tx.shared.b64 _, [%0], %1;}" ::"r"(b), "r"(tx) : "memory");
}
__device__ __forceinline__ void e_tma2d(uint32_t dst, const CUtensorMap* m, int c0, int c1, uint32_t bar) {
    asm volatile("{.reg .pred p; elect.sync _|p, 0xffffffff;\n @p cp.async.bulk.tensor.2d.shared::cluster.global.mbarrier::complete_tx::bytes [%0], [%1, {%3, %4}], [%2];}"
                 ::"r"(dst), "l"(m), "r"(bar), "r"(c0), "r"(c1) : "memory");
}
__device__ __forceinline__ void e_tma2d_hint(uint32_t dst, const CUtensorMap* m, int c0, int c1, uint32_t bar, uint64_t pol) {
    asm volatile("{.reg .pred p; elect.sync _|p, 0xffffffff;\n @p cp.async.bulk.tensor.2d.shared::cluster.global.mbarrier::complete_tx::bytes.L2::cache_hint [%0], [%1, {%3, %4}], [%2], %5;}"
                 ::"r"(dst), "l"(m), "r"(bar), "r"(c0), "r"(c1), "l"(pol) : "memory");
}
__device__ __forceinline__ void e_tma2d_mc(uint32_t dst, const CUtensorMap* m, int c0, int c1, uint32_t bar) {
    asm volatile("{.reg .pred p; elect.sync _|p, 0xffffffff;\n @p cp.async.bulk.tensor.2d.shared::cluster.global.mbarrier::complete_tx::bytes.multicast::cluster [%0], [%1, {%3, %4}], [%2], %5;}"
                 ::"r"(dst), "l"(m), "r"(bar), "r"(c0), "r"(c1), "h"((uint16_t)3) : "memory");
}
__device__ __forceinline__ void wait_count_w(const uint32_t* p, uint32_t target) {
    int it = 0;
#pragma unroll 1
    while (true) {
        uint32_t v;
        asm volatile("ld.acquire.gpu.global.u32 %0, [%1];" : "=r"(v) : "l"(p) : "memory");
        if (__all_sync(~0u, v >= target) | (++it > SPIN_LIMIT)) break;
        __nanosleep(100);
    }
}

#define NL 6
constexpr uint32_t SM_HB = 16384, HBK = 5120, SM_SX = 57344, SM_OX = 122880, SM_PX = 124928, SM_PA = 126976, SM_WO = 147456,
                   SM_TAB = 212992, SM_PRE = SM_TAB + 5120, SM_BAR = 227328, SM_REC_TOTAL = 227328 + 256;
constexpr uint32_t SB0 = 1024;
constexpr int B_WO = 0, B_HE = 1, B_HB = 3, B_W = 5;
constexpr int NB_MEM = 1, NB_QK = 2, NB_X1 = 3, NB_X2 = 4, NB_WIN = 5, NB_WG = 6, NB_KDONE = 7, NB_FIN0 = 8, NB_P = 9, NB_PX = 10, NB_G = 11, NB_A = 12, NB_B = 13, NB_C = 14, NB_S = 15;
#define D_NEAR 1620
#define D_FAR (D_NEAR - 90)
#define D_X2 400
#define D_V 280
#define D_W2 40
#define D_PA 40
#define D_MORE 40
#define D_MORE2 30
constexpr int E_MUL = 28;
constexpr int NPF = NL + 6, NE1 = 10;
constexpr int W0_E = 3, W0_RS = NL - 1, G_AT = 18;
struct Delays { uint32_t near, far, x2, v, w2, pa, more2, more; };

__device__ __forceinline__ uint32_t clk32() { uint32_t t; asm volatile("mov.u32 %0, %%clock;" : "=r"(t) :: "memory"); return t; }
__device__ __forceinline__ uint32_t smid() { uint32_t t; asm volatile("mov.u32 %0, %%smid;" : "=r"(t)); return t; }
__device__ __forceinline__ uint32_t gtime() { uint32_t t; asm volatile("mov.u32 %0, %%globaltimer_lo;" : "=r"(t) :: "memory"); return t; }
__device__ __forceinline__ void spin_until(uint32_t t0, uint32_t d) { while (clk32() - t0 < d) {} }
template <int N> __device__ __forceinline__ uint32_t delay(uint32_t zero) {
    float x = __uint_as_float(clk32());
#pragma unroll
    for (int i = 0; i < N; i++) asm volatile("ex2.approx.ftz.f32 %0, %0;" : "+f"(x));
    return __float_as_uint(x) & zero;
}
__device__ __forceinline__ uint32_t opaque(uint32_t v) { return __shfl_sync(~0u, v, threadIdx.x & 31); }
__device__ __forceinline__ uint32_t xor_or(uint32_t a, uint32_t b, uint32_t t) {
    uint32_t r; asm volatile("lop3.b32 %0, %1, %2, %3, 0x7E;" : "=r"(r) : "r"(a), "r"(b), "r"(t)); return r;
}
__device__ __forceinline__ uint32_t settag(uint32_t v, uint32_t tag) {
    uint32_t r; asm("lop3.b32 %0, %1, 1, %2, 0xB8;" : "=r"(r) : "r"(v), "r"(tag)); return r;
}
__device__ __forceinline__ void sts2(uint32_t a, float x, float y) { asm volatile("st.shared.v2.f32 [%0], {%1,%2};" ::"r"(a), "f"(x), "f"(y) : "memory"); }
__device__ __forceinline__ void sts4f(uint32_t a, float x, float y, float z, float w) {
    asm volatile("st.shared.v4.f32 [%0], {%1,%2,%3,%4};" ::"r"(a), "f"(x), "f"(y), "f"(z), "f"(w) : "memory");
}
__device__ __forceinline__ void sts1(uint32_t a, uint32_t x) { asm volatile("st.shared.u32 [%0], %1;" ::"r"(a), "r"(x) : "memory"); }
__device__ __forceinline__ uint32_t lds1(uint32_t a) { uint32_t v; asm volatile("ld.shared.u32 %0, [%1];" : "=r"(v) : "r"(a) : "memory"); return v; }
__device__ __forceinline__ float4 lds4f(uint32_t a) {
    float4 v; asm volatile("ld.shared.v4.f32 {%0,%1,%2,%3}, [%4];" : "=f"(v.x), "=f"(v.y), "=f"(v.z), "=f"(v.w) : "r"(a) : "memory"); return v;
}
__device__ __forceinline__ float2 lds2f(uint32_t a) {
    float2 v; asm volatile("ld.shared.v2.f32 {%0,%1}, [%2];" : "=f"(v.x), "=f"(v.y) : "r"(a) : "memory"); return v;
}
__device__ __forceinline__ bool any_bit0(uint32_t x) {
    uint32_t r;
    asm volatile("{.reg .pred p, q; .reg .b32 t; and.b32 t, %1, 1; setp.ne.u32 p, t, 0; vote.sync.any.pred q, p, 0xffffffff; selp.u32 %0, 1, 0, q;}" : "=r"(r) : "r"(x));
    return r;
}
__device__ __forceinline__ float rcp_fast(float x) { float r; asm("rcp.approx.ftz.f32 %0, %1;" : "=f"(r) : "f"(x)); return r; }
__device__ __forceinline__ void stsm4(uint32_t a, uint32_t r0, uint32_t r1, uint32_t r2, uint32_t r3) {
    asm volatile("stmatrix.sync.aligned.m8n8.x4.shared.b16 [%0], {%1,%2,%3,%4};" ::"r"(a), "r"(r0), "r"(r1), "r"(r2), "r"(r3) : "memory");
}
__device__ __forceinline__ void stsm4t(uint32_t a, uint32_t r0, uint32_t r1, uint32_t r2, uint32_t r3) {
    asm volatile("stmatrix.sync.aligned.m8n8.x4.trans.shared.b16 [%0], {%1,%2,%3,%4};" ::"r"(a), "r"(r0), "r"(r1), "r"(r2), "r"(r3) : "memory");
}
__device__ __forceinline__ uint32_t and3(uint32_t a, uint32_t b, uint32_t c) {
    uint32_t r; asm("lop3.b32 %0, %1, %2, %3, 0x80;" : "=r"(r) : "r"(a), "r"(b), "r"(c)); return r;
}
__device__ __forceinline__ void red_mem(void* p, uint32_t x, uint32_t y, uint32_t z, uint32_t w, void* q, uint32_t e, bool c) {
    asm volatile("{.reg .pred p; setp.ne.u32 p, %7, 0; red.relaxed.gpu.global.add.noftz.v4.bf16x2 [%0], {%1,%2,%3,%4}; @p red.relaxed.gpu.global.add.noftz.bf16x2 [%5], %6;}"
                 ::"l"(p), "r"(x), "r"(y), "r"(z), "r"(w), "l"(q), "r"(e), "r"((uint32_t)c) : "memory");
}
__device__ __forceinline__ void stg4_if(bool c, void* p, uint32_t x) {
    asm volatile("{.reg .pred p; setp.ne.u32 p, %2, 0; @p st.relaxed.gpu.global.v4.u32 [%0], {%1,%1,%1,%1};}" ::"l"(p), "r"(x), "r"((uint32_t)c) : "memory");
}

__device__ __forceinline__ void h_load(uint32_t sb, const uint8_t* hsrc, int pass, uint32_t rank, uint32_t rot) {
    const uint8_t* src = hsrc + (size_t)pass * 65536;
    const uint32_t bar = sb + SM_BAR + 8 * (B_HB + (pass & 1)), dst = sb + SM_HB + (pass & 1) * 65536 + rank * 4 * HBK;
    e_expect(bar, 32768);
#pragma unroll 1
    for (int i = 0; i < H_PIECES; i++) {
        const uint32_t o = ((i + rot) & (H_PIECES - 1)) * (16384 / H_PIECES);
        asm volatile("{.reg .pred p; elect.sync _|p, 0xffffffff;\n"
                     " @p cp.async.bulk.shared::cluster.global.mbarrier::complete_tx::bytes.multicast::cluster [%0], [%1], %4, [%2], %3;}"
                     ::"r"(dst + o + (o >> 12) * 1024), "l"(src + o), "r"(bar), "h"((uint16_t)3), "n"(16384 / H_PIECES) : "memory");
    }
}
__device__ __forceinline__ uint4 ldg_b128(const void* p) {
    uint4 v;
    asm volatile("{.reg .b128 t; .reg .b64 a, b; ld.relaxed.gpu.global.b128 t, [%4]; mov.b128 {a, b}, t; mov.b64 {%0,%1}, a; mov.b64 {%2,%3}, b;}"
                 : "=r"(v.x), "=r"(v.y), "=r"(v.z), "=r"(v.w) : "l"(p) : "memory");
    return v;
}
__device__ __forceinline__ void stg_b128_if(bool c, void* p, uint32_t x, uint32_t y, uint32_t z, uint32_t w) {
    asm volatile("{.reg .pred p; setp.ne.u32 p, %5, 0; @p st.relaxed.gpu.global.v4.u32 [%0], {%1,%2,%3,%4};}"
                 ::"l"(p), "r"(x), "r"(y), "r"(z), "r"(w), "r"((uint32_t)c) : "memory");
}
__device__ __forceinline__ float pretag(float x, uint32_t add, uint32_t keep) { return __uint_as_float((__float_as_uint(x) + add) & keep); }

template <class F, class G>
__device__ __forceinline__ void softmax_rows(uint32_t src, uint32_t dst, uint32_t g16, int row0, F ready, G mid) {
    const uint32_t u = (g16 >> 7) & 3, e = ((g16 >> 9) << 3) | ((g16 >> 4) & 7);
    uint32_t se = src + e * 8, su = se + u * 1088, d0 = dst + e * 16 + u * 4, d1 = dst + 512 + e * 4;
    int vis = row0 + (e >> 2) - 2 * (e & 3) - 8 * u;
    asm volatile("" : "+r"(se), "+r"(su), "+r"(d0), "+r"(d1), "+r"(vis));
    ready();
    const float2 p0 = lds2f(su), p1 = lds2f(su + 256), p2 = lds2f(su + 512), p3 = lds2f(su + 768);
    const float2 m0 = lds2f(se + 4352), m1 = lds2f(se + 4352 + 256), m2 = lds2f(se + 4352 + 512), m3 = lds2f(se + 4352 + 768);
    float a0 = (p0.x + p1.x) + (p2.x + p3.x), a1 = (p0.y + p1.y) + (p2.y + p3.y);
    const float a2 = (m0.x + m1.x) + (m2.x + m3.x), a3 = (m0.y + m1.y) + (m2.y + m3.y);
    if (vis < 0) a0 = -1e9f / 0.08838834764831845f;
    if (vis < 1) a1 = -1e9f / 0.08838834764831845f;
    int k = __float_as_int(fmaxf(fmaxf(a0, a1), fmaxf(a2, a3)));
    k ^= (k >> 31) & 0x7fffffff;
    const bool hi = g16 & 64;
    const int k0 = __reduce_max_sync(~0u, hi ? INT_MIN : k), k1 = __reduce_max_sync(~0u, hi ? k : INT_MIN);
    mid();
    k = hi ? k1 : k0;
    const float m = __int_as_float(k ^ ((k >> 31) & 0x7fffffff));
    const float sl2 = 0.08838834764831845f * 1.4426950408889634f, mb = -m * sl2;
    sts1(d0, pack2(ex2(fmaf(a0, sl2, mb)), ex2(fmaf(a1, sl2, mb))));
    sts1(d1, pack2(ex2(fmaf(a2, sl2, mb)), ex2(fmaf(a3, sl2, mb))));
}

__device__ __forceinline__ uint32_t pack_h2(float lo, float hi) {
    uint32_t r; asm("cvt.rn.satfinite.f16x2.f32 %0, %1, %2;" : "=r"(r) : "f"(hi), "f"(lo)); return r;
}
__device__ __forceinline__ float2 unpack_h2(uint32_t u) {
    float2 r; asm("{.reg .b16 l, h; mov.b32 {l, h}, %2; cvt.f32.f16 %0, l; cvt.f32.f16 %1, h;}" : "=f"(r.x), "=f"(r.y) : "r"(u)); return r;
}
__device__ __forceinline__ uint32_t add_h2(uint32_t a, uint32_t b) { uint32_t r; asm("add.rn.f16x2 %0, %1, %2;" : "=r"(r) : "r"(a), "r"(b)); return r; }
__device__ __forceinline__ uint32_t max_h2(uint32_t a, uint32_t b) { uint32_t r; asm("max.f16x2 %0, %1, %2;" : "=r"(r) : "r"(a), "r"(b)); return r; }
struct U2 { uint32_t x, y; };
__device__ __forceinline__ U2 ldg_u2(const void* p) {
    U2 v; asm volatile("{.reg .b64 t; ld.relaxed.gpu.global.b64 t, [%2]; mov.b64 {%0, %1}, t;}" : "=r"(v.x), "=r"(v.y) : "l"(p) : "memory"); return v;
}
constexpr int POLL_LIMIT = 1 << 16;
constexpr float SM_L2E = 0.08838834764831845f * 1.4426950408889634f;
template <int V> struct IC { static constexpr int value = V; };
typedef unsigned long long u64;
__device__ __forceinline__ u64 ldg_u64(const void* p) { u64 v; asm volatile("ld.relaxed.gpu.global.b64 %0, [%1];" : "=l"(v) : "l"(p) : "memory"); return v; }
__device__ __forceinline__ void rec_main(uint32_t sb, const CUtensorMap* tWo, uint8_t* arena, int role, int hinfo, int wg, uint32_t zero, const Delays& dly) {
    const int hA = hinfo & 255;
    const int tid = threadIdx.x, t = tid & 127, lane = tid & 31, wi = t >> 5;
    const uint32_t bars = sb + SM_BAR;
    const int head = role >> 2, qd = role & 3, j = blockIdx.x & 1, kh = role & 1;
    const uint32_t mypar = head >= hA;
    const uint32_t wu = __reduce_max_sync(~0u, wi);
    const bool warp0 = wu == 0, warp1 = wu == 1;
    const uint8_t* hsrc = (const uint8_t*)g_himg + kh * 32768 + j * 16384;
    auto tokbase = [&](int ty) { return ((ty + 1) << 21) + blk(lb_tok(head), mypar ^ ((hinfo >> (8 + ty)) & 1)); };
    const uint32_t tbw = tokbase(wg), tbq = tokbase(0) + (qd >> 1) * 2048 + ((qd & 1) + wu) * 256;
    uint32_t w[32 - NL][4];
    const uint32_t frow = ((lane >> 4) * 8 + (lane & 7)) * 128, fx = ((lane >> 3) & 1) ^ (lane & 7);
    const uint32_t wl0 = sb + wg * 65536 + frow + ((fx ^ (2 * wi)) << 4);
    uint32_t g16 = opaque(t * 16);
    auto G16 = [&]() { asm volatile("" : "+r"(g16)); return g16; };
    const uint32_t sbl = sb - wu * 512;
    const uint32_t xso = blk(lb_x2(head), mypar), cu = kh * 2048 + (2 * j + (wu >> 1)) * 512;
    const uint32_t u_xo = xso + wg * 16384 + (wu & 1) * 2048 + (cu >> 1) - wu * 256, u_to = tbw + (wu & 1) * 16384 + cu - wu * 512;
    {
        uint8_t* pp = arena + (tbw + (1 << 20) + j * 16384 + (kh ^ 1) * 2048 + g16);
        stg_rlx4(pp, 0, 0, 0, 0);
        stg_rlx4(pp + 32768, 0, 0, 0, 0);
        stg_rlx4(arena + (u_to + g16), 0, 0, 0, 0);
        stg_rlx2(arena + (u_xo + (g16 >> 1)), 0, 0);
    }
    {
        mbar_wait_w(bars + 8 * (B_W + 5), 0);
        if (wg > 0) wait_count_w(&g_tick[33 + (lane & 3) * 8], 1);
        if (wg == 1) asm volatile("fence.proxy.async.global;" ::: "memory");
#pragma unroll 1
        for (int i = 0; i < 4; i++) mbar_wait_w(bars + 8 * (B_W + (wg == 2 ? 8 + i : 2 * i + wg)), 0);
#pragma unroll
        for (int p = NL; p < 32; p++) ldsm4t(w[p - NL], wl0 + p * 2048);
        fence_async_smem();
        bar_sync(wg < 2 ? NB_WG : NB_X2, wg < 2 ? 256 : 128);
        if (wg == 2 && wu < 3) {
            e_expect(bars + 8 * B_WO, 16384);
            e_tma2d(sb + SM_WO + wu * 16384, tWo, (wu >> 1) * 512 + qd * 128 + (wu & 1) * 64, head * DH, bars + 8 * B_WO);
            e_tma2d(sb + SM_WO + wu * 16384 + 8192, tWo, (wu >> 1) * 512 + qd * 128 + (wu & 1) * 64, head * DH + 64, bars + 8 * B_WO);
        }
        if (wg == 1 && warp0) {
            if (lane == 0) mbar_arrive_cluster(bars + 8 * B_HE, j ^ 1);
            mbar_wait_w(bars + 8 * B_HE, 0);
#pragma unroll 1
            for (int i = 0; i < 2; i++) h_load(sb, hsrc, i, j, head);
        }
    }
    const uint32_t mrow = wg < 2 ? mem_row(wu >> 1, wg * 2 + (wu & 1), qd) : mem_row(kh, wu, 0);
    const uint32_t u_m = mrow - wu * 512, u_e = mrow + 512 - wu * 64;
#define TAB(i) lds1(sb + SM_TAB + (i) * 512 + (G16() >> 2))
    {
        const uint32_t r8 = lane & 7;
        const uint32_t tb = sb + SM_TAB + wg * 1536 + t * 4, ma = sb + SM_HB + 4096 + r8 * 128;
        if (wg < 2) {
            sts1(tb, sb + SM_WO + wi * 16384 + frow + ((fx ^ (2 * wg)) << 4));
            sts1(tb + 512, wl0);
            sts1(tb + 1024, ma + (((lane >> 3) ^ r8) << 4));
        } else {
            sts1(tb, ma + (wi & 1) * HBK + ((((wi & 2) + (lane >> 4) * 4 + ((lane >> 3) & 1)) ^ r8) << 4));
            sts1(tb + 512, ((((wi & 2) + 4) ^ r8) << 4) + ((lane & 3) == 2 ? ma + 128 + ((wi & 1) + (lane >> 3) * 2) * HBK : sb + SM_HB - 128));
            sts1(tb + 1024, mem_row(role >> 6, (role >> 4) & 3, (role >> 2) & 3) + (lane < 8 ? qd * 128 + lane * 16 : 512 + qd * 32 + (lane & 1) * 16));
        }
    }
#define HB(ks) dadd(mkdesc(SB0 + SM_HB + ((ks) >> 2) * HBK + ((ks) & 3) * 32, 16, 1024, 1), hbo)
#define STEP_CONSTS                                                                                  \
    const uint32_t tag = (s & 1) ^ 1, ttag = ((s >> 1) & 1) ^ 1, tso = (s & 1) * 32768;              \
    G16();                            \
    const int p = s + 2, b = p & 1;                                                                  \
    uint32_t hbo = b * 4096, fz[5] = {0, 0, 0, 0, 0};                                                   \
    const uint32_t ftag = (((p - 1) >> 1) & 1) ^ 1, ptag = ((p >> 1) & 1) ^ 1;                       \
    const uint32_t pso = tbw + (1 << 20) + (b ^ 1) * 32768 + j * 16384 + kh * 2048;
#define SCHED_FENCE(i) fz[i] = clk32();
#define FZ ((fz[0] | fz[1] | fz[2] | fz[3] | fz[4]) & zero)
#define BLOCK_FENCE asm volatile("pmevent 0;" ::: "memory");
    constexpr int GAP = 32 / NL;
#define l16 (sbl + g16)
#define g8 (g16 >> 1)
    uint4 u, v;
    uint8_t *pdst, *fdst;
    auto tok_pack = [&](int ty, const float* acc, uint32_t ftag, uint32_t ptag, bool later = false) {
        const bool tg = ty == 2 || !(g16 & 64);
        const uint32_t add = tg ? (ftag ^ 1) << 16 : 0u, keep = tg ? 0xfffe0000u : ~0u;
        const uint32_t add1 = ty == 2 ? 0u : add, keep1 = ty == 2 ? ~0u : keep;
        const uint32_t add2 = ty == 0 ? add : 0u, keep2 = ty == 0 ? keep : ~0u;
        v = {pack2(pretag(acc[0], add, keep), pretag(acc[1], add1, keep1)), pack2(acc[2], acc[3]),
             pack2(pretag(acc[4], add2, keep2), pretag(acc[5], add2, keep2)), pack2(acc[6], acc[7])};
        if (ty < 2) { v.x = movm(v.x); v.z = movm(v.z); v.y = movm(v.y); v.w = movm(v.w); }
        u = {settag(pack2(pretag(acc[8], (ptag ^ 1) << 16, 0xfffe0000u), acc[9]), ptag), pack2(acc[10], acc[11]), pack2(acc[12], acc[13]), pack2(acc[14], acc[15])};
        if (later) return;
        v.x = settag(v.x, ftag);
        if (ty == 0) v.z = settag(v.z, ftag);
    };

#pragma unroll 1
    for (int s = -2; s < 0; s++) {
        STEP_CONSTS
        (void)tag; (void)ttag; (void)tso; (void)fz;
        float acc[16];
        mbar_wait_w(bars + 8 * (B_HB + b), 0);
        wg_fence();
#pragma unroll
        for (int i = 0; i < 32; i++) {
            if (i < NL) wgmma_ss32(acc, dadd(mkdesc(SB0 + i * 2048, 8192, 1024, 1), wg * 4096), HB(i), i != 0);
            else wgmma_rs32(acc, w[i < NL ? 0 : i - NL], HB(i), 1);
        }
        wg_commit();
        uint4 pa = {0, 0, 0, 0};
        int it = 0;
#pragma unroll 1
        while ((p > 0) & any_bit0(pa.x ^ ftag) & (++it < POLL_LIMIT)) pa = ldg_b128(arena + (pso + g16));
        pdst = arena + ((pso ^ (32768 + 2048)) + G16());
        fdst = arena + ((b ^ 1) * 32768 + u_to + g16);
        wg_wait<0>();
#pragma unroll
        for (int k = 0; k < 4; k++) { acc[2 * k] += bflo((&pa.x)[k]); acc[2 * k + 1] += bfhi((&pa.x)[k]); }
        tok_pack(wg, acc, ftag, ptag);
        stg_b128_if(true, pdst, u.x, u.y, u.z, u.w);
        stg_b128_if(p > 0 && wg, fdst, v.x, v.y, v.z, v.w);
        if (p > 0 && !wg) { stg_rlx2(fdst - lane * 8, v.x, v.y); stg_rlx2(fdst - lane * 8 + 256, v.z, v.w); }
        if (p == 0) {
            if (wg != 1) bar_arrive(NB_C, 288);
        }
    }
    if (wg == 1 && warp0) {
        wait_count_w(&g_tick[32 + (lane & 3) * 8], 1);
        asm volatile("fence.proxy.async.global;" ::: "memory");
        bar_sync(NB_C, 288);
        if (g16 == 0) mbar_arrive_cluster(bars + 8 * B_HE, j ^ 1);
        mbar_wait_w(bars + 8 * B_HE, 1);
        h_load(sb, hsrc, 2, j, head);
    }

    auto qk_loop = [&](auto wgc) {
        constexpr int WG = decltype(wgc)::value;
        uint32_t w0[NL][4], lm0;
        auto w0_load = [&]() {
            const uint32_t wl = TAB(WG * 3 + 1);
            lm0 = TAB(WG * 3 + 2);
#pragma unroll
            for (int k = 0; k < NL; k++) ldsm4t(w0[k], wl + k * 2048);
        };
        const uint32_t wlo = WG * 65536 - SM_WO - wu * 16384, wlx = __reduce_max_sync(~0u, (wi ^ WG) << 5);
        uint32_t tq0, lm, lm1, dx2 = dly.x2;
        auto proj_pre = [&](int s) {
            uint32_t wz0 = zero;
#pragma unroll
            for (int k = 0; k < NL; k += 2) wz0 = and3(wz0, w0[k][0], w0[k + 1 < NL ? k + 1 : k][0]);
            lm = lm0 + (s & 1) * 65536 + wz0; lm1 = lm ^ 64;
            asm volatile("" : "+r"(lm), "+r"(lm1));
        };
        auto proj = [&](int s, auto mid) {
            bar_sync(NB_MEM, 384);
            float c[4][4];
            constexpr int PD = WG ? 5 : 3;
            uint32_t bf[16][4], tq1;
#pragma unroll
            for (int it = 0; it < PD; it++) ldsm4(bf[it], (it & 1 ? lm1 : lm) + (it >> 1) * HBK);
            mid(-1);
#pragma unroll
            for (int it = 0; it < 16; it++) {
                const uint32_t* bfr = bf[it];
                if (it + PD < 16) ldsm4(bf[it + PD < 16 ? it + PD : 0], ((it + PD) & 1 ? lm1 : lm) + ((it + PD) >> 1) * HBK);
                const uint32_t* wa = 2 * it < NL ? w0[2 * it < NL ? 2 * it : 0] : w[2 * it < NL ? 0 : 2 * it - NL];
                const uint32_t* wb = 2 * it + 1 < NL ? w0[2 * it + 1 < NL ? 2 * it + 1 : 0] : w[2 * it + 1 < NL ? 0 : 2 * it + 1 - NL];
                float *ca = c[(2 * it) & 3], *cb = c[(2 * it + 1) & 3];
                if (it < 2) { mma16816z(ca, wa, bfr[0], bfr[1]); mma16816z(cb, wb, bfr[2], bfr[3]); }
                else { mma16816(ca, wa[0], wa[1], wa[2], wa[3], bfr[0], bfr[1]); mma16816(cb, wb[0], wb[1], wb[2], wb[3], bfr[2], bfr[3]); }
                mid(it);
                if (it == 15) { tq1 = clk32(); bar_arrive(NB_QK, 384); }
            }
            const uint32_t xo = u_xo + (G16() >> 1);
            float r[4];
#pragma unroll
            for (int e = 0; e < 4; e++) {
                constexpr float SH = SM_L2E / 4096;
                r[e] = WG ? (c[0][e] + c[1][e]) + (c[2][e] + c[3][e]) : fmaf(c[2][e] + c[3][e], SH, (c[0][e] + c[1][e]) * SH);
            }
            const uint32_t r0 = pack2(r[0], r[1]), r1 = pack2(r[2], r[3]);
            const uint32_t m0 = movm(r0), m1 = movm(r1);
            tq0 = clk32();
            stg_rlx2(arena + xo, settag(m0, (s & 1) ^ 1), m1);
            tq0 += tq1 & zero;
        };
        w0_load();
        proj_pre(0);
        if (WG == 1) bar_sync(NB_P, 256);
        proj(0, [](int) {});
        if (WG == 0) mbar_wait_w(bars + 8 * B_WO, 0);
#pragma unroll 1
        for (int s = 0;; s++) {
            STEP_CONSTS
            uint4 pa;
            float acc[16];
            auto acc_init = [&]() {
#pragma unroll
                for (int k = 0; k < 4; k++) { acc[2 * k] = bflo((&pa.x)[k]); acc[2 * k + 1] = bfhi((&pa.x)[k]); acc[8 + 2 * k] = __uint_as_float((&pa.x)[k] & zero); acc[9 + 2 * k] = __uint_as_float(~(&pa.x)[k] & zero); }
            };
            uint32_t wf[NPF][4], a3;
#define WF(f) ((a3 ^ (((f) & 1) * 64)) + ((f) >> 1) * 2048)
            if (WG == 1) {
                float sc[5][4];
                uint32_t sx0 = sb + SM_SX - wu * (2560 - 16) + G16() * 5;
                asm volatile("" : "+r"(sx0));
                int it = 0;
                bool bad;
#pragma unroll 1
                do {
                    uint4 kf[2][2];
                    U2 qf[2], x[8];
                    const uint32_t gz = g16 | (it & zero);
                    const uint8_t *ts = arena + (tso + tbw + gz), *tq = arena + (tso + tbq + (gz >> 1)), *xp = arena + (xso + (gz >> 1));
#pragma unroll
                    for (int a = 0; a < 4; a++) kf[a >> 1][a & 1] = ldg_b128(ts + (a >> 1) * 16384 + (a & 1) * 2048);
                    spin_until(tq0, dx2 - 100);
#pragma unroll
                    for (int a = 0; a < 2; a++) qf[a] = ldg_u2(tq + a * 16384);
                    spin_until(tq0, dx2);
#pragma unroll
                    for (int i = 0; i < 8; i++) x[i] = ldg_u2(xp + (i >> 2) * 16384 + (i & 3) * 1024);
                    const uint32_t q0[4] = {hadd2(x[0].x, x[1].x), qf[0].x, hadd2(x[0].y, x[1].y), qf[0].y};
                    const uint32_t q1[4] = {hadd2(x[2].x, x[3].x), qf[1].x, hadd2(x[2].y, x[3].y), qf[1].y};
                    const uint32_t bt = ((qf[0].x ^ ttag) | (qf[1].x ^ ttag)) | ((kf[0][0].x ^ ttag) | (kf[0][1].x ^ ttag)) | ((kf[1][0].x ^ ttag) | (kf[1][1].x ^ ttag));
                    uint32_t bx = 0;
#pragma unroll
                    for (int i = 0; i < 8; i += 2) bx |= (x[i].x ^ tag) | (x[i + 1].x ^ tag);
                    mma16816z(sc[0], q0, kf[0][0].x, kf[0][0].y);
                    mma16816z(sc[1], q0, kf[0][0].z, kf[0][0].w);
                    mma16816z(sc[2], q0, kf[0][1].x, kf[0][1].y);
                    mma16816z(sc[3], q0, kf[0][1].z, kf[0][1].w);
                    mma16816z(sc[4], q0, hadd2(x[4].x, x[5].x), hadd2(x[4].y, x[5].y));
                    bad = any_bit0(bt | bx) & (++it < POLL_LIMIT);
                    mma16816(sc[0], q1[0], q1[1], q1[2], q1[3], kf[1][0].x, kf[1][0].y);
                    mma16816(sc[1], q1[0], q1[1], q1[2], q1[3], kf[1][0].z, kf[1][0].w);
                    mma16816(sc[2], q1[0], q1[1], q1[2], q1[3], kf[1][1].x, kf[1][1].y);
                    mma16816(sc[3], q1[0], q1[1], q1[2], q1[3], kf[1][1].z, kf[1][1].w);
                    mma16816(sc[4], q1[0], q1[1], q1[2], q1[3], hadd2(x[6].x, x[7].x), hadd2(x[6].y, x[7].y));
                } while (bad);
                sts4(sx0, pack_h2(sc[0][0], sc[0][1]), pack_h2(sc[1][0], sc[1][1]), pack_h2(sc[2][0], sc[2][1]), pack_h2(sc[3][0], sc[3][1]));
                sts1(sx0 + 64 - wu * 12, pack_h2(sc[4][0], sc[4][1]));
                bar_arrive(NB_X1, 384);
                if (it > 1 && s > 1) dx2 += dly.more2;
                auto tok_sts = [&]() {
#pragma unroll
                    for (int n = 0; n < 5; n++) sts2(sb + SM_SX + 2560 + g8 + n * 1088, sc[n][2], sc[n][3]);
                };
                a3 = TAB(WG * 3);
                if (s == 0) mbar_wait_w(bars + 8 * B_WO, 0);
                softmax_rows(sb + SM_SX + 2560, sb + SM_PX + 1024, g16 | (clk32() & zero), qd * 8, [&]() { BLOCK_FENCE tok_sts(); bar_sync(NB_PX, 128); }, [&]() {
                    BLOCK_FENCE
#pragma unroll
                    for (int f = 0; f < NE1; f++) ldsm4t(wf[f], WF(f));
                    BLOCK_FENCE
                });
            } else {
                a3 = TAB(WG * 3);
                if (warp1 && (s & 3) == 1) asm volatile("fence.proxy.async.global;" ::: "memory");
                spin_until(tq0, dly.pa);
                uint4 x, y;
                int it = 0;
#pragma unroll 1
                do { x = ldg_b128(arena + (pso + g16)); y = ldg_b128(arena + (pso + tokbase(1) - tokbase(0) + g16)); }
                while ((p <= NSEG) & any_bit0(xor_or(x.x, y.x, ftag)) & (++it < POLL_LIMIT));
                sts4(sb + SM_PA + g16, x.x, x.y, x.z, x.w);
                sts4(sb + SM_PA + 2048 + g16, y.x, y.y, y.z, y.w);
                bar_sync(NB_X1, 384);
                if (g16 < 32) asm volatile("red.relaxed.gpu.global.max.u32 [%0], %1; red.relaxed.gpu.global.add.u32 [%0+4], 1;"
                                                    ::"l"(arena + ((blk(LB_TIME, 0) ^ (g16 << 8)) + qd * 1024 + (tq0 & zero))), "r"(gtime()) : "memory");
                __syncwarp();
                const uint32_t tx = clk32();
                spin_until(tx, dly.w2);
            }
#pragma unroll
            for (int f = WG ? NE1 : 0; f < NPF; f++) ldsm4t(wf[f], WF(f));
            if (s + 1 == NSEG) { bar_arrive(NB_X2, 384); break; }
            const uint32_t oa = l16 + SM_OX, slot = mem_slot(s + 1);
            float c[4][4];
            uint32_t ob[4][4];
            BLOCK_FENCE
            bar_sync(NB_X2, 384);
            ldsm4t(ob[0], oa);
            ldsm4t(ob[1], oa + 512);
            SCHED_FENCE(0)
#pragma unroll
            for (int f = 0; f < 16; f++) {
                const uint32_t *a = wf[f % NPF], *o = ob[f >> 2] + (f & 2);
                if (f < 4) mma16816z(c[f], a, o[0], o[1]);
                else mma16816(c[f & 3], a[0], a[1], a[2], a[3], o[0], o[1]);
                if (f == 3) ldsm4t(ob[2], oa + 1024);
                if (f == 5) { ldsm4t(ob[3], oa + 1536); if (NPF < 16) ldsm4t(wf[0], WF(NPF)); }
                if (f == 7) {
#pragma unroll
                    for (int k = NPF + 1; k < 16; k++) ldsm4t(wf[k - NPF], WF(k));
                }
                if (f == 3 || f == 5 || f == 7) SCHED_FENCE(f / 2)
                if (f == 11) {
#pragma unroll
                    for (int k = NL - W0_E; k < NL; k++) ldsm4t(w0[k], (a3 ^ wlx) + wlo + k * 2048);
                    SCHED_FENCE(4)
                }
            }
            const float last = c[1][3] + c[3][3], one = __uint_as_float(CNT1 << 16);
            red_mem(arena + (u_m + slot + G16()), pack2(c[0][0] + c[2][0], c[0][1] + c[2][1]), pack2(c[0][2] + c[2][2], c[0][3] + c[2][3]),
                    pack2(c[1][0] + c[3][0], c[1][1] + c[3][1]), pack2(c[1][2] + c[3][2], g16 & 16 ? one : last),
                    arena + (u_e + slot + ((g16 >> 3) & ~3u)), pack2(last, one), g16 & 16);
            hbo += FZ;
            constexpr int NS = NL - W0_RS, GS = (32 - NL + NS) / NS;
            BLOCK_FENCE
#pragma unroll
            for (int k = NL - W0_E - 1; k >= 0; k--) ldsm4t(w0[k], (a3 ^ wlx) + wlo + k * 2048);
            lm0 = TAB(WG * 3 + 2);
            if (WG == 1) pa = lds4(sb + SM_PA + 2048 + g16);
            if (WG == 0) {
                bar_arrive(NB_WIN, 384);
                pa = lds4(sb + SM_PA + g16);
                acc_init();
                asm volatile("" : F16(acc, 0));
                BLOCK_FENCE
            }
            wg_fence();
            bar_sync(WG ? NB_WIN : NB_B, WG ? 384 : 256);
#pragma unroll
            for (int i = 0; i < 32; i++) {
                const int k = i / GS;
                if (i >= 32 - NL + NS) wgmma_rs32(acc, w0[i < 32 - NL + NS ? 0 : i - 32 + NL], HB(i - 32 + NL), 1);
                else if (i % GS == GS - 1 && k < NS) wgmma_ss32(acc, mkdesc(SB0 + WG * 65536 + k * 2048, 8192, 1024, 1), HB(k), 1);
                else wgmma_rs32(acc, w[i - (k < NS ? k : NS)], HB(NL + i - (k < NS ? k : NS)), WG == 0 || i);
                if (WG == 1 && i == G_AT) bar_arrive(NB_B, 256);
                if (WG == 1 && i == 31 - NL + NS) wg_fence();
            }
            wg_commit();
            BLOCK_FENCE
            if (WG == 1 && warp0 && !(s & 3)) wait_count_w(&g_tick[32 + ((G16() >> 4) & 3) * 8], min(s / 4 + 2, 16));
            auto tok_store = [&](int m) {
                if (m & 1) {
                    if (WG) stg_b128_if(true, arena + ((b ^ 1) * 32768 + u_to + G16()), v.x, v.y, v.z, v.w);
                    else {
                        uint8_t* d = arena + ((b ^ 1) * 32768 + u_to + wu * 256 + (G16() >> 1));
                        stg_rlx2(d, v.x, v.y); stg_rlx2(d + 256, v.z, v.w);
                    }
                }
                if (m & 2) stg_b128_if(p < NSEG, arena + ((pso ^ (32768 + 2048)) + G16()), u.x, u.y, u.z, u.w);
            };
            if (WG == 0) proj_pre(s + 1);
            BLOCK_FENCE
            wg_wait<0>();
            if (WG == 0) {
                asm volatile("" : F16(acc, 0));
                proj(s + 1, [&](int it) {
                    if (it < 0) {
                        SCHED_FENCE(0)
                        asm volatile("" : F16(acc, 0));
                        tok_pack(WG, acc, ftag, ptag, true);
                        tok_store(2);
                        SCHED_FENCE(1)
                    }
                    if (it == 2) { SCHED_FENCE(2) v.x = settag(v.x, ftag); v.z = settag(v.z, ftag); tok_store(1); SCHED_FENCE(3) }
                });
                tq0 += (fz[0] | fz[1] | fz[2] | fz[3]) & zero;
            } else {
#pragma unroll
                for (int k = 0; k < 4; k++) { acc[2 * k] += bflo((&pa.x)[k]); acc[2 * k + 1] += bfhi((&pa.x)[k]); }
                tok_pack(WG, acc, ftag, ptag);
                proj_pre(s + 1);
                asm volatile("" : "+r"(u.x), "+r"(u.y), "+r"(u.z), "+r"(u.w), "+r"(v.x), "+r"(v.y), "+r"(v.z), "+r"(v.w));
                BLOCK_FENCE
                bar_sync(NB_P, 256);
                tok_store(3);
                proj(s + 1, [](int) {});
            }
        }
    };
    if (wg == 0) {
        qk_loop(IC<0>());
    } else if (wg == 1) {
        qk_loop(IC<1>());
    } else {
        const uint32_t ONES = 0x3f803f80u, u_o = qd * 65536 + head * 2048 + wu * 384;
        uint32_t tw = 0, dl = 0, dbase = kh == mypar ? dly.near : dly.far, dst0, dx0;
        dst0 = TAB(6); dx0 = TAB(7);
        uint32_t ov[4] = {0, 0, 0, 0};
        auto o_store = [&](int s) {
            uint8_t* od = (uint8_t*)g_O + (uint32_t)(s * (32 * NH * DH * 2) + u_o + (G16() >> 2));
#pragma unroll
            for (int a = 0; a < 4; a++) stg_rlx1(od + a * 128, ov[a]);
        };
        uint4 vf[2][2], pa;
        auto tok_fetch = [&](int s) {
            const uint8_t* ts = arena + ((s & 1) * 32768 + tbw + g16);
#pragma unroll
            for (int a = 0; a < 4; a++) vf[a >> 1][a & 1] = ldg_b128(ts + (a >> 1) * 16384 + (a & 1) * 2048);
            pa = ldg_b128(arena + (tbw + (1 << 20) + (~s & 1) * 32768 + j * 16384 + kh * 2048 + g16));
        };
        tok_fetch(0);
#pragma unroll 1
        for (int s = 0;; s++) {
            STEP_CONSTS
#define VFBAD ((vf[0][0].x ^ ttag) | (vf[0][1].x ^ ttag) | (vf[1][0].x ^ ttag) | (vf[1][1].x ^ ttag))
#define TOKBAD (VFBAD | (p <= NSEG ? pa.x ^ ftag : 0))
            {
                const uint32_t dst = dst0 + b * 65536, dx = dx0 + b * 65536;
                const uint8_t *ms = arena + (u_m + mem_slot(s) + g16), *me = arena + (u_e + mem_slot(s) + ((g16 >> 3) & ~3u));
                uint32_t em = g16 & 16 ? 0u : ~0u;
                asm volatile("" : "+l"(ms), "+l"(me), "+r"(em));
                spin_until(tw, dl);
                int it = 0;
                bool bad;
#pragma unroll 1
                do {
                    uint4 m[4];
                    uint32_t x[4];
#pragma unroll
                    for (int i = 0; i < 4; i++) m[i] = ldg_rlx4(ms + i * 1024);
#pragma unroll
                    for (int i = 0; i < 4; i++) x[i] = ldg_rlx1(me + i * 1024);
#pragma unroll
                    for (int i = 0; i < 3; i++) {
                        stsm4t(dst + i * 2 * HBK, m[i].x, m[i].y, m[i].z, m[i].w);
                        if (i == 1) asm volatile("{.reg .pred p; setp.eq.s32 p, %0, 0; @p bar.arrive %1, 256;}" ::"r"(it), "n"(NB_P) : "memory");
                    }
                    uint32_t c = m[0].w & m[1].w, r, msk = ~(it << 16) & CNT_ALL << 16;
                    asm volatile("" : "+r"(c), "+r"(msk));
                    SCHED_FENCE(1)
                    stsm4t(dst + 6 * HBK, m[3].x, m[3].y, m[3].z, m[3].w);
                    stsm4t(dx, x[0], x[1], x[2], x[3]);
                    asm volatile("{.reg .pred p, q; .reg .b32 t, u; lop3.b32 t, %1, %2, %3, 0x80; lop3.b32 u, %4, %5, %6, 0x80; lop3.b32 t, t, %8, %7, 0xa8;\n"
                                 " lop3.b32 t, t, u, %9, 0x2a; setp.ne.u32 p, t, 0; vote.sync.any.pred q, p, 0xffffffff; @!q bar.arrive %10, 384; selp.u32 %0, 1, 0, q;}"
                                 : "=r"(r) : "r"(c), "r"(m[2].w), "r"(m[3].w), "r"(x[0]), "r"(x[1]), "r"(x[2]), "r"(x[3]), "r"(em), "r"(msk), "n"(NB_MEM) : "memory");
                    bad = r; it++;
                } while (bad);
                if (it > 1 && s > 1) dbase += dly.more;
            }
            o_store(max(s - 1, 0));
            fence_async_smem();
            hbo += fz[1] & zero;
            int it = 0;
#pragma unroll 1
            while (any_bit0(TOKBAD) & (++it < POLL_LIMIT)) tok_fetch(s + (it & zero));
            float acc[20];
#pragma unroll
            for (int k = 0; k < 4; k++) { acc[2 * k] = bflo((&pa.x)[k]); acc[2 * k + 1] = bfhi((&pa.x)[k]); acc[8 + 2 * k] = acc[9 + 2 * k] = acc[16 + k] = __uint_as_float(pa.x & zero); }
            if (p <= NSEG) mbar_wait_w(bars + 8 * (B_HB + b), (p >> 1) & 1);
            asm volatile("" : F16(acc, 0), F4(acc, 16));
            BLOCK_FENCE
            wg_fence();
            bar_sync(NB_QK, 384);
#pragma unroll
            for (int i = 0; i < 32; i++) {
                const int k = i / GAP;
                if (i % GAP == GAP - 1 && k < NL) wgmma_ss40(acc, mkdesc(SB0 + 131072 + k * 2048, 8192, 1024, 1), HB(k), 1);
                else wgmma_rs40(acc, w[i - (k < NL ? k : NL)], HB(NL + i - (k < NL ? k : NL)), 1);
            }
            wg_commit();
            uint8_t* vo = arena + (u_xo + (G16() >> 1));
            pdst = arena + ((pso ^ (32768 + 2048)) + G16());
            fdst = arena + ((b ^ 1) * 32768 + u_to + g16);
            BLOCK_FENCE
            wg_wait<0>();
            stg_rlx2(vo, settag(pack2(acc[16], acc[17]), tag), pack2(acc[18], acc[19]));
            const uint32_t tv = clk32();
            tok_pack(2, acc, ftag, ptag);
            stg_b128_if(p <= NSEG, fdst, v.x, v.y, v.z, v.w);
            stg_b128_if(p < NSEG, pdst, u.x, u.y, u.z, u.w);
            const uint8_t* xp = arena + (xso + 32768 + (G16() >> 1));
            const uint32_t sxa = sb + SM_SX - wu * 2560 + G16() * 5;
            uint32_t sel[2];
            {
                const uint32_t q = (G16() >> 4 ^ g16 >> 6 & 1) & 3;
                sel[0] = q == 0 ? 0x3c00 : 0; sel[1] = q == 2 ? 0x3c00 : 0;
                asm volatile("" : "+r"(sel[0]), "+r"(sel[1]));
            }
            uint32_t xv[4], gt = 0;
            auto pv = [&](uint32_t p0, uint32_t p1, uint32_t p2, uint32_t p3, uint32_t p4, auto getv, auto done) {
                float oc[2][4], lc[4] = {0.f, 0.f, 0.f, 0.f};
                mma16816(lc, ONES, ONES, ONES, ONES, p0, p1);
                mma16816z(oc[0], &vf[0][0].x, p0, p1);
                mma16816z(oc[1], &vf[1][0].x, p0, p1);
                mma16816(lc, ONES, ONES, ONES, ONES, p2, p3);
                mma16816(oc[0], vf[0][1].x, vf[0][1].y, vf[0][1].z, vf[0][1].w, p2, p3);
                mma16816(oc[1], vf[1][1].x, vf[1][1].y, vf[1][1].z, vf[1][1].w, p2, p3);
                mma1688(lc, ONES, ONES, p4);
                getv();
                mma1688(oc[0], xv[0], xv[1], p4);
                mma1688(oc[1], xv[2], xv[3], p4);
                done(__float_as_uint(oc[0][0]) | __float_as_uint(oc[1][0]) | __float_as_uint(lc[0]));
                const float r0 = rcp_fast(lc[0]), r1 = rcp_fast(lc[1]);
                ov[0] = pack2(oc[0][0] * r0, oc[0][1] * r1); ov[1] = pack2(oc[0][2] * r0, oc[0][3] * r1);
                ov[2] = pack2(oc[1][0] * r0, oc[1][1] * r1); ov[3] = pack2(oc[1][2] * r0, oc[1][3] * r1);
            };
            bool bad;
            it = 0;
#pragma unroll 1
            do {
                U2 xr[4];
                asm volatile("{.reg .pred p; setp.eq.s32 p, %0, 0; @p bar.sync %1, 384;}" ::"r"(it), "n"(NB_X1) : "memory");
                uint4 sx[5];
#pragma unroll
                for (int i = 0; i < 5; i++) sx[i] = lds4(sxa + i * 16);
                if (it == 0) { gt = gtime(); tw = clk32(); }
                spin_until(tv, dly.v);
#pragma unroll
                for (int i = 0; i < 4; i++) xr[i] = ldg_u2(xp + i * 1024);
                uint32_t h[5], h0[4];
#pragma unroll
                for (int n = 0; n < 4; n++) h0[n] = add_h2((&sx[0].x)[n], (&sx[1].x)[n]);
#pragma unroll
                for (int n = 0; n < 4; n++) h[n] = add_h2(h0[n], add_h2((&sx[2].x)[n], (&sx[3].x)[n]));
                h[4] = add_h2(add_h2(sx[4].x, sx[4].y), add_h2(sx[4].z, sx[4].w));
                uint32_t hm = max_h2(max_h2(max_h2(h[0], h[1]), h[2]), max_h2(h[3], h[4]));
                float2 a[5];
                float mb;
                {
                    float d[2][4];
                    const uint32_t hs = __byte_perm(hm, hm, 0x1032);
#pragma unroll
                    for (int k = 0; k < 2; k++)
                        asm volatile("mma.sync.aligned.m16n8k8.row.col.f32.f16.f16.f32 {%0,%1,%2,%3},{%4,%5},{%6},{%7,%7,%7,%7};"
                                     : "=f"(d[k][0]), "=f"(d[k][1]), "=f"(d[k][2]), "=f"(d[k][3]) : "r"(hm), "r"(hs), "r"(sel[k]), "f"(0.f));
#pragma unroll
                    for (int n = 0; n < 5; n++) a[n] = unpack_h2(h[n]);
                    mb = -4096.0f * fmaxf(fmaxf(fmaxf(d[0][0], d[0][1]), fmaxf(d[0][2], d[0][3])), fmaxf(fmaxf(d[1][0], d[1][1]), fmaxf(d[1][2], d[1][3])));
                }
                uint32_t pm[5];
#pragma unroll
                for (int n = 0; n < 5; n++) pm[n] = pack2(ex2(fmaf(a[n].x, 4096.0f, mb)), ex2(fmaf(a[n].y, 4096.0f, mb)));
                pv(pm[0], pm[1], pm[2], pm[3], pm[4], [&]() {
                    xv[0] = hadd2(xr[0].x, xr[1].x); xv[1] = hadd2(xr[0].y, xr[1].y);
                    xv[2] = hadd2(xr[2].x, xr[3].x); xv[3] = hadd2(xr[2].y, xr[3].y);
                }, [](uint32_t) {});
                bad = any_bit0((xr[0].x ^ tag) | (xr[1].x ^ tag) | (xr[2].x ^ tag) | (xr[3].x ^ tag)) & (++it < POLL_LIMIT);
                stsm4(sb + SM_OX + g16, ov[0], ov[1], ov[2], ov[3]);
            } while (bad);
            bar_sync(NB_X2, 384);
            BLOCK_FENCE
            U2 tv2 = {0, 0};
            const uint8_t* tp = arena + (blk(LB_TIME, mypar) + ((G16() << 6) & 0xc00));
            {
                const uint4 pp = lds4(l16 + SM_PX + 1024);
                const uint32_t p4 = lds1(sb + SM_PX + 512 + 1024 - wu * 128 + (G16() >> 2));
                tv2 = ldg_u2(tp);
                if (warp0 && s + 3 <= NSEG) h_load(sb, hsrc, s + 3, j, head);
                pv(pp.x, pp.y, pp.z, pp.w, p4, []() {}, [&](uint32_t r) { bar_arrive(NB_WIN + (r & zero), 384); });
            }
            dst0 = TAB(6); dx0 = TAB(7);
            const uint32_t zo = TAB(8);
            BLOCK_FENCE
            if (s + 1 == NSEG) break;
            asm volatile("" : "+r"(tv2.y));
            it = 0;
            uint32_t tm = __reduce_max_sync(~0u, tv2.y < 32 * (s + 1) ? ~0u : tv2.x);
#pragma unroll 1
            while ((tm == ~0u) & (++it < 16)) { tv2 = ldg_u2(tp); tm = __reduce_max_sync(~0u, tv2.y < 32 * (s + 1) ? ~0u : tv2.x); }
            const uint32_t e = tm - gt;
            tok_fetch(s + 1);
            stg4_if(g16 < 160, arena + (zo + mem_slot(s + 3)), 0);
            dl = dbase + (e > 4096 ? 0 : e * E_MUL >> 4);
        }
        o_store(NSEG - 1);
    }
}

struct RecMaps { CUtensorMap wq, wk, wv, wo, wmod, w3, w1; };
struct RecPtrs { const bf16 *x, *mem0, *c, *wmod, *w1, *w3; uint8_t* arena; uint32_t zero; const bf16 *w2, *w4, *wo; Delays dly; };

__device__ __forceinline__ float silu_bf(const bf16* c, int i) {
    const float v = __bfloat162float(c[i]);
    return bfround(__fdividef(v, 1.0f + __expf(-v)));
}
#define LN_LAST 1
#define W_LATE 1000
#define W_OPEN 1400
__device__ __forceinline__ uint32_t side_window_(const uint8_t* arena, uint32_t n) {
    U2 v;
    int it = 0;
#pragma unroll 1
    while (v = ldg_u2(arena + (LB_TIME << 13)), ((v.y >> 5) == n || gtime() - v.x > W_OPEN + W_LATE) && v.y < 32 * NSEG && ++it < 64) __nanosleep(100);
    it = 0;
#pragma unroll 1
    while ((int)(gtime() - v.x - W_OPEN) < 0 && ++it < 256) {}
    return v.y >> 5;
}
#define side_window(arena, n) n = side_window_(arena, n)
__device__ __noinline__ void rec_ln(uint32_t sb, const bf16* x, uint8_t* arena, int id, int r0) {
    int r1 = 32;
    uint32_t n = 0;
    const int tid = threadIdx.x, lane = tid & 31, wid = __reduce_max_sync(~0u, tid >> 5);
    const uint32_t ring = sb + wid * 8192 + lane * 16, coef = sb + SM_PRE;
    x += (id * 8 + wid) * 2 * DM + lane * 8;
#pragma unroll 1
    for (int r = r0 - 1; r < r1; r++) {
        if (r + 1 < r1) {
#pragma unroll
            for (int i = 0; i < 8; i++)
                asm volatile("cp.async.cg.shared.global [%0], [%1], 16;" ::"r"(ring + (~r & 1) * 4096 + i * 512), "l"(x + (r + 1) * 64 * DM + i * 256) : "memory");
        }
        asm volatile("cp.async.commit_group; cp.async.wait_group 1;" ::: "memory");
        if (r < r0) continue;
        const uint32_t src = ring + (r & 1) * 4096;
        float m[2] = {0.f, 0.f}, rs[2];
#pragma unroll 1
        for (int ps = 0; ps < 2; ps++) {
            float t[2][2] = {{0.f, 0.f}, {0.f, 0.f}};
#pragma unroll 1
            for (int i = 0; i < 2048; i += 512) {
#pragma unroll
                for (int h = 0; h < 2; h++) {
                    const uint4 u = lds4(src + h * 2048 + i);
#pragma unroll
                    for (int e = 0; e < 4; e++) {
                        const float a = bflo((&u.x)[e]) - m[h], c = bfhi((&u.x)[e]) - m[h];
                        t[h][0] = fmaf(a, ps ? a : 1.0f, t[h][0]); t[h][1] = fmaf(c, ps ? c : 1.0f, t[h][1]);
                    }
                }
            }
            rs[0] = t[0][0] + t[0][1]; rs[1] = t[1][0] + t[1][1];
#pragma unroll 1
            for (int o = 16; o; o >>= 1) { rs[0] += __shfl_xor_sync(~0u, rs[0], o); rs[1] += __shfl_xor_sync(~0u, rs[1], o); }
            if (!ps) { m[0] = rs[0] * (1.0f / DM); m[1] = rs[1] * (1.0f / DM); }
        }
        rs[0] = rsqrtf(rs[0] * (1.0f / DM) + 1e-5f); rs[1] = rsqrtf(rs[1] * (1.0f / DM) + 1e-5f);
        if (r == r0) {
#pragma unroll 1
            for (int i = tid; i < 2 * DM / 4; i += 256) {
                float t[4];
                int it = 0;
                uint32_t ok;
#pragma unroll 1
                do {
                    uint4 u[8];
#pragma unroll
                    for (int k = 0; k < 8; k++) u[k] = ldg_rlx4(g_modp + k * 2 * DM + i * 4);
                    ok = 1;
#pragma unroll
                    for (int k = 0; k < 32; k++) { const uint32_t w = (&u[k >> 2].x)[k & 3]; ok &= w; t[k & 3] = k < 4 ? __uint_as_float(w) : t[k & 3] + __uint_as_float(w); }
                } while (!__all_sync(~0u, ok) & (++it < SPIN_LIMIT));
                const float o = i >> 8;
                const uint32_t lo = pack2(t[0], t[1]), hi = pack2(t[2], t[3]);
                sts4f(coef + (i >> 8) * 4096 + (i & 1) * 2048 + ((i & 255) >> 1) * 16, bflo(lo) + o, bfhi(lo) + o, bflo(hi) + o, bfhi(hi) + o);
            }
            bar_sync(NB_FIN0, 256);
        }
        uint8_t* dst = (uint8_t*)g_himg + (r * 2 + (id >> 1)) * 65536 + (lane >> 3) * 4096 + wid * 256;
#pragma unroll 1
        for (int i = 0; i < 4; i++) {
            const uint32_t ca = coef + i * 512 + lane * 16;
            const float4 s0 = lds4f(ca), s1 = lds4f(ca + 2048), c0 = lds4f(ca + 4096), c1 = lds4f(ca + 6144);
            const float sh[8] = {s0.x, s0.y, s0.z, s0.w, s1.x, s1.y, s1.z, s1.w}, sc[8] = {c0.x, c0.y, c0.z, c0.w, c1.x, c1.y, c1.z, c1.w};
#pragma unroll
            for (int h = 0; h < 2; h++) {
                uint4 u = lds4(src + h * 2048 + i * 512);
#pragma unroll
                for (int e = 0; e < 4; e++) {
                    uint32_t& w = (&u.x)[e];
                    w = pack2(fmaf((bflo(w) - m[h]) * rs[h], sc[2 * e], sh[2 * e]), fmaf((bfhi(w) - m[h]) * rs[h], sc[2 * e + 1], sh[2 * e + 1]));
                }
                *(uint4*)(dst + i * 16384 + ((id & 1) == (i >> 1) ? 65536 : 2048) + h * 128 + (((lane ^ (2 * wid + h)) & 7) << 4)) = u;
            }
        }
        if (r == 0) {
            int ro, it = 0;
#pragma unroll 1
            do asm volatile("ld.volatile.shared.u32 %0, [%1];" : "=r"(ro) : "r"(sb + SM_BAR + 192) : "memory"); while ((ro == INT_MIN) & (++it < SPIN_LIMIT));
            if (ro >= 0) { r1 = 1; asm volatile("cp.async.wait_group 0;" ::: "memory"); }
        }
        if (!r || (r & 1)) {
            bar_sync(r ? NB_FIN0 : NB_C, r ? 256 : 320);
            if (wid == (r >> 1 & 7)) {
                if (r == 0) bar_arrive(NB_B, 64);
                if (lane == 0) { signal_count(&g_tick[32 + id * 8 + !r]); }
                __syncwarp();
            }
        }
        if (r > 2) side_window(arena, n);
    }
}
#define SIDE_T 300
template <int NQ, int NB>
__device__ __forceinline__ void side_gemv(const CUtensorMap* tm, int c0, int k0, int k1, uint32_t cs, uint32_t sb, const uint8_t* arena, uint32_t& n, uint32_t& ph, float (*acc)[8], bool once = false) {
    const uint32_t w = __reduce_max_sync(~0u, threadIdx.x >> 5 & 3), ring = sb + (NB == 3 ? 65536 : 0) + w * NB * 8192;
    const uint32_t bars = sb + SM_BAR + (NB == 3 ? 8 * B_W + w * 24 : 8 + w * 8), bs = NB == 3 ? 8 : 0;
#pragma unroll
    for (int q = 0; q < NQ; q++)
#pragma unroll
        for (int j = 0; j < 8; j++) acc[q][j] = 0.f;
#pragma unroll 1
    for (; k0 < k1; k0 += NB * 16, ph ^= 1) {
        const int nr = min(NB * 16, k1 - k0);
        side_window(arena, n);
        const uint32_t t0 = clk32();
#pragma unroll 1
        for (int g = 0; g < NB; g++) {
            spin_until(t0, (g * 4 + w) * (SIDE_T / 4));
            if (bs || !g) e_expect(bars + bs * g, !bs ? NB * 8192 : g * 16 < nr ? 8192 : 0);
            if (g * 16 < nr) e_tma2d_hint(ring + g * 8192, tm, c0, k0 + g * 16, bars + bs * g, once ? EVICT_FIRST : EVICT_NORMAL);
        }
#pragma unroll 1
        for (int r = 0; r < nr; r += 16) {
            mbar_wait_w(bars + bs * (r >> 4), ph);
            uint4 v[16];
#pragma unroll
            for (int h = 0; h < 16; h++) v[h] = lds4(ring + (r + h) * 512 + (threadIdx.x & 31) * 16);
            float4 cf[NQ][4];
#pragma unroll
            for (int q = 0; q < NQ * 4; q++) cf[q >> 2][q & 3] = lds4f(cs + ((q >> 2) * DM + k0 + r + (q & 3) * 4) * 4);
#pragma unroll
            for (int h = 0; h < 16; h++) {
                const float f[8] = {bflo(v[h].x), bfhi(v[h].x), bflo(v[h].y), bfhi(v[h].y), bflo(v[h].z), bfhi(v[h].z), bflo(v[h].w), bfhi(v[h].w)};
#pragma unroll
                for (int q = 0; q < NQ; q++)
#pragma unroll
                    for (int j = 0; j < 8; j++) acc[q][j] = fmaf((&cf[q][h >> 2].x)[h & 3], f[j], acc[q][j]);
            }
        }
        fence_async_smem();
        __syncwarp();
    }
}
__device__ __noinline__ void rec_side(float* sm, const RecMaps& mp, const RecPtrs& p, int prr) {
    uint8_t* arena = p.arena;
    const int b = blockIdx.x;
    int id = (b - 128) >> 1;
    if (b < 128) {
        uint32_t v;
        int it = 0;
#pragma unroll 1
        do { v = __reduce_max_sync(~0u, ldg_rlx1(&g_tick[6])); spin_guard(++it); } while (__popc(v) < 2);
        id = v == 3 ? -1 - prr : (v & 1) ^ 1;
    }
    id = id * 2 + (b & 1);
    const int tid = threadIdx.x, t = tid & 127, w = __reduce_max_sync(~0u, t >> 5);
    float* coef = sm + (tid < 256 ? 44032 : 40960);
    const uint32_t sb = smem_u32(sm), cs = smem_u32(coef);
    uint32_t n = 0, ph = 0;
    float acc[3][8];
    if (tid < 256) {
        if (blockIdx.x < 128) rec_ln(smem_u32(sm), p.x, p.arena, id, 1);
        for (int i = tid; i < 2 * S_; i += 256) g_st[id * 2 * S_ + i] = 0.f;
        if (id == 0 && tid < 64) g_pcnt[tid * 8] = 0;
        if (id == 1) for (int i = tid; i < 6 * 256; i += 256) g_pflag[i] = 0;
        if (id == 2 && tid == 0) g_pt = 0;
        fence_async_smem();
        bar_sync(NB_FIN0, 256);
        if (PDL && tid == 0) asm volatile("fence.acq_rel.gpu; griddepcontrol.launch_dependents;" ::: "memory");
        if (tid >= 128) return;
        float* red = coef + 3 * DM;
        if (t == 0) wait_count1(&g_tick[8], 4);
        bar_sync(NB_S, 128);
        for (int i = t; i < DM; i += 128) { coef[i] = 1.0f + __ldcg(g_mod + 4 * DM + i); coef[DM + i] = __ldcg(g_mod + 3 * DM + i); coef[2 * DM + i] = 1.0f; }
        bar_sync(NB_S, 128);
        if (id == 1 && t < 32) {
            float u[5] = {0, 0, 0, 0, 0};
            for (int i = t; i < DM; i += 32) {
                const float a = coef[i], b = coef[DM + i];
                u[0] += a; u[1] += a * a; u[2] += a * b; u[3] += b; u[4] += b * b;
            }
#pragma unroll
            for (int q = 0; q < 5; q++) { const float r = warp_sum(u[q]); if (t == 0) g_cst[q] = r * (1.0f / DM); }
        }
        side_gemv<3, 2>(&mp.w1, id * 256, w * 256, w * 256 + 256, cs, sb, p.arena, n, ph, acc);
#pragma unroll
        for (int q = 0; q < 3; q++)
#pragma unroll
            for (int j = 0; j < 8; j++) red[((t >> 5) * 3 + q) * 256 + (t & 31) * 8 + j] = acc[q][j];
        bar_sync(NB_S, 128);
        for (int i = t; i < 768; i += 128) g_vec[(i >> 8) * DM + id * 256 + (i & 255)] = (red[i] + red[768 + i]) + (red[1536 + i] + red[2304 + i]);
        return;
    }
    for (int i = t; i < DM; i += 128) { coef[i] = silu_bf(p.c, i); coef[2 * DM + i] = 1.0f; }
    if (t == 0) wait_count1(&g_tick[33], 1);
    bar_sync(NB_G, 128);
    side_gemv<1, 3>(&mp.wmod, (2 + id) * DM + w * 256, 0, DM, cs, sb, p.arena, n, ph, acc, true);
#pragma unroll
    for (int j = 0; j < 8; j++) g_mod[(2 + id) * DM + t * 8 + j] = bfround(acc[0][j]);
    bar_sync(NB_G, 128);
    if (t == 0) signal_count(&g_tick[8]);
    side_gemv<1, 3>(&mp.w3, id * (FF / 4) + w * 256, 0, DM, cs + 8 * DM, sb, p.arena, n, ph, acc);
    if (t < FF / 32) {
#pragma unroll
        for (int j = 0; j < 8; j++) g_vec[3 * DM + id * (FF / 4) + t * 8 + j] = acc[0][j];
    }
}

__global__ void __cluster_dims__(2, 1, 1) __launch_bounds__(384, 1)
k_rec(const __grid_constant__ RecMaps mp, const __grid_constant__ RecPtrs p) {
    extern __shared__ uint8_t smraw[];
    const uint32_t sb = smem_u32(smraw);
    if ((sb & 0x3FFFF) != SB0) __trap();
    const uint32_t bars = sb + SM_BAR;
    const int tid = threadIdx.x, lane = tid & 31, b = blockIdx.x;
    const int wid = __reduce_max_sync(~0u, tid >> 5);
    const uint32_t rank = b & 1;
    uint8_t* arena = p.arena;
    volatile int* sinfo = (volatile int*)(smraw + SM_BAR + 192);
    if (tid == 0) sinfo[0] = INT_MIN;
    if (tid == 352) {
        for (int i = 0; i < 17; i++) mbar_init(bars + 8 * i, i == B_WO ? 4 : 1);
        asm volatile("fence.mbarrier_init.release.cluster;" ::: "memory");
    }
    __syncwarp();
    asm volatile("barrier.cluster.arrive.relaxed.aligned;" ::: "memory");
    int pr = 0, hA = 0;
    if (wid < 8) {
        if (b < 128) {
            const int cb = (b & 15) * 128, k0 = (b >> 4) * 128 + (tid >> 4);
            uint4 v[8];
#pragma unroll
            for (int i = 0; i < 8; i++) v[i] = __ldg((const uint4*)(p.wmod + (size_t)(k0 + 16 * i) * (6 * DM) + cb + (tid & 15) * 8));
            float acc[8] = {0, 0, 0, 0, 0, 0, 0, 0};
            const float s8 = silu_bf(p.c, k0 + 16 * (lane & 7));
#pragma unroll
            for (int i = 0; i < 8; i++) {
                const float sv = __shfl_sync(~0u, s8, i, 16);
                acc[0] += sv * bflo(v[i].x); acc[1] += sv * bfhi(v[i].x); acc[2] += sv * bflo(v[i].y); acc[3] += sv * bfhi(v[i].y);
                acc[4] += sv * bflo(v[i].z); acc[5] += sv * bfhi(v[i].z); acc[6] += sv * bflo(v[i].w); acc[7] += sv * bfhi(v[i].w);
            }
            float* red = (float*)(smraw + SM_PRE);
            *(float4*)(red + (tid >> 4) * 128 + (tid & 15) * 8) = make_float4(acc[0], acc[1], acc[2], acc[3]);
            *(float4*)(red + (tid >> 4) * 128 + (tid & 15) * 8 + 4) = make_float4(acc[4], acc[5], acc[6], acc[7]);
            bar_sync(NB_FIN0, 256);
            if (wid < 4) {
                float t = 0;
#pragma unroll
                for (int i = 0; i < 16; i++) t += red[i * 128 + tid];
                stg_rlx1(&g_modp[(b >> 4) * 2 * DM + cb + tid], __float_as_uint(t) | 1u);
            }
        } else {
            rec_ln(sb, p.x, p.arena, b - 128, 0);
        }
    } else if (wid >= 10 && b >= 128) {
        {
            const int w = (b - 128) * 2 + wid - 10;
            const uint16_t* src = (const uint16_t*)p.mem0 + (lane & 3) * 2 * DM + (w >> 2) * 512 + (w & 1) * 64 + (w & 2) * 8 + (lane >> 2);
            uint32_t v[4][4];
#pragma unroll
            for (int i = 0; i < 16; i++) v[i >> 2][i & 3] = src[(i >> 2) * 128 + (i & 2) * 16 + (i & 1) * 8] | ((uint32_t)src[DM + (i >> 2) * 128 + (i & 2) * 16 + (i & 1) * 8] << 16);
            uint8_t* d = arena + mem_row(w >> 2, w & 3, 0);
            uint8_t* e = d + 512 + (lane >> 1) * 4;
            d += lane * 16;
#pragma unroll
            for (int i = 0; i < 4; i++, d += 1024, e += 1024) {
                stg_rlx4(d, v[i][0], v[i][1], v[i][2], lane & 1 ? (v[i][3] & 0xffff) | CNT_ALL << 16 : v[i][3]);
                stg_rlx4(d + mem_slot(1), 0, 0, 0, 0);
                stg_rlx4(d + mem_slot(2), 0, 0, 0, 0);
                if (lane & 1) { stg_rlx1(e, v[i][3] >> 16 | CNT_ALL << 16); stg_rlx1(e + mem_slot(1), 0); stg_rlx1(e + mem_slot(2), 0); }
            }
            if (w == 0 && lane < 8) stg_rlx2(arena + (LB_TIME << 13) + lane * 1024, 0, 0);
            bar_arrive(NB_C, 320);
        }
    } else if (rank == 0) {
        uint32_t best = ~0u;
        const int pg = wid < 10 ? 0 : 1 + (b >> 1) / 22;
        uint32_t* q = (uint32_t*)(arena + (pg << 21) + (pg ? blk(b >> 1, wid & 1) : blk(LB_PROBE, wid & 1) + b * 16));
        stg_rlx1(q + (lane & 7), 0);
        uint32_t v = p.zero;
#pragma unroll 1
        for (int r = v; r <= NPROBE; r++) {
            const uint32_t t0 = clk32();
            asm volatile("{.reg .pred p; setp.eq.u32 p, %2, 0; @p atom.relaxed.gpu.global.exch.b32 %0, [%1], 0;}" : "+r"(v) : "l"(q + (t0 & p.zero)), "r"(lane) : "memory");
            v = __reduce_max_sync(~0u, v);
            best = min(best, clk32() - t0);
        }
        sinfo[wid - 6] = best + v;
        bar_sync(NB_KDONE, b < 128 ? 128 : 64);
        if (wid == 8) {
            const uint32_t par = sinfo[2] > sinfo[3];
            const u64 vote = b < 128 && (sinfo[4] > sinfo[5]) != par;
            asm volatile("{.reg .pred p; elect.sync _|p, 0xffffffff; @p red.relaxed.gpu.global.add.u64 [%0], %1;}" ::"l"((u64*)g_tick + (b >> 1) / 22), "l"((u64)(1 + 2 * par) << (2 * ((b >> 1) % 22)) | vote << 48) : "memory");
        }
    } else if (wid == 9) {
        stg_rlx1(&g_clk[b >> 1], ((clk32() - 2 * gtime()) & ~127u) + (b >> 1) + 1);
    }
    if (wid == 8) {
        uint32_t v[3], my;
        u64 m[3];
        const int me = b >> 1, l2 = 2 * min(lane, 21);
        int it = 0;
        __syncwarp();
        if (rank) spin_until(clk32(), 3000);
#pragma unroll 1
        do {
            my = ldg_rlx1(&g_clk[me]);
#pragma unroll
            for (int k = 0; k < 3; k++) v[k] = ldg_rlx1(&g_clk[k * 22 + l2 / 2]);
        } while (!__all_sync(~0u, my && v[0] && v[1] && v[2]) & (++it < SPIN_LIMIT));
#pragma unroll 1
        do {
#pragma unroll
            for (int k = 0; k < 3; k++) m[k] = ldg_u64((u64*)g_tick + k);
        } while (!__all_sync(~0u, (m[0] & m[1] & m[2]) >> l2 & 1) & (++it < SPIN_LIMIT));
        const uint32_t c0 = __reduce_min_sync(~0u, lane ? ~0u : v[0]) - 4097;
        const uint32_t mc = me >= 64 && LN_LAST ? ~0u : my - c0;
        uint32_t o[3], cnt = 0, flip = 0;
#pragma unroll
        for (int k = 0; k < 3; k++) o[k] = m[k] >> (l2 + 1) & 1;
        const int par = __any_sync(~0u, (v[0] == my && o[0]) | (v[1] == my && o[1]) | (v[2] == my && o[2]));
#pragma unroll
        for (int k = 0; k < 3; k++) {
            const uint32_t c = v[k] - c0;
            const bool ln = LN_LAST && k == 2 && lane >= 20;
            cnt += o[k] + (o[k] == par ? (ln ? 44 + lane < me : c < mc) * 256 + (c < my - c0) * 65536 : 0);
            flip |= (m[k] >> 48) > 10 ? 256 << k : 0;
        }
        cnt = __reduce_add_sync(~0u, lane < 22 ? cnt : 0);
        const int n1 = cnt & 255, n0 = 66 - n1, tk = cnt >> 8 & 255;
        if (lane == 0) g_cls[smid() & 255] = cnt < 32 << 16 ? par * 4 + (cnt >> 19) : 8;
        hA = min(n0 >> 1, NH);
        const int q0 = 2 * hA, q1 = 2 * NH - q0;
        const int over = tk - (par ? q1 : q0), lack = max(par ? q0 - n0 : q1 - n1, 0);
        if (over < 0) pr = par ? q0 + tk : tk;
        else if (over < lack) pr = (par ? n0 : q0 + n1) + over;
        else pr = -1 - (over - lack + (par ? max(n0 - q0, 0) : 0));
        hA |= flip;
        if (lane == 0) {
            sinfo[1] = hA; sinfo[0] = pr;
            if (b >= 128 && rank == 0) atomicOr(&g_tick[6], (pr < 0 ? 4u : 1u) << ((b - 128) >> 1));
        }
    }
    asm volatile("barrier.cluster.wait.aligned;" ::: "memory");
    if (wid == 8) {
        __syncwarp();
        bar_arrive(NB_A, 288);
        bar_arrive(NB_S, 128);
        if (b >= 128 && pr < 0) bar_sync(NB_B, 64);
        if (pr >= 0) {
            const int pu = __reduce_max_sync(~0u, pr), c0 = (pu >> 1) * 128 + rank * 64, r0 = (pu & 1) * 512;
#pragma unroll 1
            for (int n = 0; n < 13; n++) {
                const u64 seq = b >= 128 ? 0xcba9864207531ull : 0xcba9876543210ull;
                const int i = seq >> (4 * n) & 15;
                if (b >= 128 && i == 0) bar_sync(NB_B, 64);
                if (n >= W_INFL) mbar_wait_w(bars + 8 * (B_W + (seq >> (4 * (n - W_INFL)) & 15)), 0);
                const int m = i < 8 ? i & 1 : i >> 2, k = i < 8 ? i >> 1 : i & 3;
                const uint32_t dst = sb + m * 65536 + k * 16384, br = bars + 8 * (m < 3 ? B_W + i : B_WO);
                const int c = m < 3 ? c0 : 576 + rank * 256 + (pu & 1) * 128, r = m < 3 ? r0 + k * 128 : (pu >> 1) * DH;
                const uint64_t pol = m < 3 ? EVICT_FIRST : EVICT_NORMAL;
                e_expect(br, 16384);
                e_tma2d_hint(dst, &mp.wq + m, c, r, br, pol);
                e_tma2d_hint(dst + 8192, &mp.wq + m, c, r + 64, br, pol);
            }
        }
    } else {
        bar_sync(wid < 8 ? NB_A : NB_S, wid < 8 ? 288 : 128);
    }
    const int prr = __reduce_max_sync(~0u, sinfo[0]);
    hA = __reduce_max_sync(~0u, sinfo[1]);
    if (prr < 0) {
        rec_side((float*)smraw, mp, p, prr);
        return;
    }
    if (PDL) asm volatile("griddepcontrol.launch_dependents;" ::: "memory");
    const int role = (prr >> 1) * 4 + rank * 2 + (prr & 1);
    rec_main(sb, &mp.wo, arena, role, hA, wid >> 2, p.zero, p.dly);
}

__device__ __forceinline__ void wgmma_ss192(float* d, uint64_t a, uint64_t b, int sc) {
    asm volatile("{.reg .pred p; setp.ne.b32 p, %98, 0;\n wgmma.mma_async.sync.aligned.m64n192k16.f32.bf16.bf16 "
                 "{%0,%1,%2,%3,%4,%5,%6,%7,%8,%9,%10,%11,%12,%13,%14,%15,%16,%17,%18,%19,%20,%21,%22,%23,%24,%25,%26,%27,%28,%29,%30,%31,%32,%33,%34,%35,%36,%37,%38,%39,%40,%41,%42,%43,%44,%45,%46,%47,%48,%49,%50,%51,%52,%53,%54,%55,%56,%57,%58,%59,%60,%61,%62,%63,%64,%65,%66,%67,%68,%69,%70,%71,%72,%73,%74,%75,%76,%77,%78,%79,%80,%81,%82,%83,%84,%85,%86,%87,%88,%89,%90,%91,%92,%93,%94,%95}, %96, %97, p, 1, 1, 0, 1;}"
                 : F16(d, 0), F16(d, 16), F16(d, 32), F16(d, 48), F16(d, 64), F16(d, 80) : "l"(a), "l"(b), "r"(sc));
}

constexpr uint32_t P_B = 81920, P_PL = 40960, P_OUT = 180224, P_VEC = 212992, P_ROW = P_VEC + 6144, P_BAR = P_ROW + 4096, P_SMEM = P_BAR + 256;
#define FLAG_ST "st.release.gpu.global.u32"
#define FLAG_LD "ld.acquire.gpu.global.u32"
constexpr int ST = 5;
constexpr int PB_F = 0, PB_E = 5, PB_R = 10, PB_OUT = 16;
enum { C_Y = 0, C_G = 1, C_X1 = 2, C_U = 3, C_S1 = 8, C_S3 = 9 };
enum { V_GA = 0, V_A = 1, V_B = 2, V_GB = 3, V_VA = 4, V_VB = 5, V_VC = 6, V_C3 = 7 };
struct PostMaps { CUtensorMap o, wo, y, w1, g, w2, x1, w3, u, w4, out; };
struct PostPtrs { const bf16* x; uint8_t* arena; };

struct GeluK { float k0, k1, kh; };
__device__ __forceinline__ GeluK gelu_k(float c) { return {0.7978845608028654f * c, 0.7978845608028654f * 0.044715f * c * c * c, 0.5f * c}; }
__device__ __forceinline__ float gelu_s(float t, const GeluK& k) {
    const float u = t * fmaf(t * t, k.k1, k.k0);
    float th; asm("tanh.approx.f32 %0, %1;" : "=f"(th) : "f"(u));
    const float hx = k.kh * t;
    return fmaf(hx, th, hx);
}
__device__ __forceinline__ float2 ldsv(uint32_t a) {
    float2 v; asm("ld.shared.v2.f32 {%0,%1}, [%2];" : "=f"(v.x), "=f"(v.y) : "r"(a)); return v;
}
__device__ __forceinline__ void wait_smem(uint32_t a, int target) {
    int it = 0;
#pragma unroll 1
    while (true) {
        int v;
        asm volatile("ld.acquire.cta.shared.u32 %0, [%1];" : "=r"(v) : "r"(a) : "memory");
        if (__all_sync(~0u, v >= target) | (++it > SPIN_LIMIT)) break;
    }
}

__device__ __forceinline__ void release(uint32_t rel, int st, bool c) {
    asm volatile("{.reg .pred p; setp.ne.u32 p, %1, 0; setp.ne.and.u32 p, %2, 0, p; @p mbarrier.arrive.shared::cluster.b64 _, [%0];}"
                 ::"r"(rel + 8 * (st ? st - 1 : ST - 1)), "r"(rel), "r"((uint32_t)c) : "memory");
}
struct Pipe { int st, ph; uint32_t rel; };
__device__ __forceinline__ void adv(Pipe& p) { if (++p.st == ST) { p.st = 0; p.ph ^= 1; } }

__device__ __forceinline__ void post_weights(uint32_t sb, const PostMaps& mp, int nb, int rank) {
    const uint32_t full = sb + P_BAR + 8 * PB_F, empty = sb + P_BAR + 8 * PB_E;
    int st = 0, pp = 1;
#pragma unroll 1
    for (int ph = 0; ph < 7; ph++) {
        const int NK = ph == 0 ? 64 : ph == 6 ? 56 : 16, km = NK == 16 ? 15 : 63;
        const CUtensorMap* tb = &mp.wo + 2 * (ph < 3 ? ph : ph < 6 ? 3 : 4);
        const bool w3 = ph >= 3 && ph < 6;
        const int n0 = w3 ? nb * 64 + (ph == 4 ? 1536 : ph == 5 ? 2560 : 0) : nb * 128, dn = w3 ? 512 : 64;
        const int rot = NK == 16 ? 2 * (nb & 6) : 0, sw = ph == 1 || ph == 3 ? 2 * rank : 0;
#pragma unroll 1
        for (int i = 0; i < NK; i++) {
            const int k0 = (((i < 4 ? i ^ sw : i) + rot) & km) * 64;
            const uint32_t a = sb + P_B + st * 8192, f = full + 8 * st;
            mbar_wait_w(empty + 8 * st, pp);
            e_expect(f, ph == 3 ? 40960 : 32768);
            e_tma2d(a, tb, n0, k0, f);
            e_tma2d(a + P_PL, tb, n0 + dn, k0, f);
            if (ph == 3) e_tma2d(a + 2 * P_PL, tb, n0 + 1024, k0, f);
            if (++st == ST) { st = 0; pp ^= 1; }
        }
    }
#pragma unroll 1
    for (int i = 0; i < ST; i++) mbar_wait_w(empty + 8 * i, pp ^ (i < st));
}
__device__ __forceinline__ void post_acts(uint32_t sb, const PostMaps& mp, uint8_t* arena, int mb, int nb, int rank) {
    const int rh = 2 * mb + rank, lane = threadIdx.x & 31;
    const uint32_t bars = sb + P_BAR;
    int st = 0, pp = 1;
#pragma unroll 1
    for (int ph = 0; ph < 7; ph++) {
        const int NK = ph == 0 ? 64 : ph == 6 ? 56 : 16, km = NK == 16 ? 15 : 63;
        const CUtensorMap* ta = &mp.o + 2 * (ph < 3 ? ph : ph < 6 ? 3 : 4);
        const int amul = ph == 0 ? 256 : 64, arow = (ph == 0 ? rh * 8 : rh * 64) - 2, rot = NK == 16 ? 2 * (nb & 6) : 0;
        const bool own = ph == 1 || ph == 3;
        const uint32_t shifts = ph == 2 ? 0x04000301u : 0x02020202u;
        const uint32_t* fl = &g_pflag[(ph == 6 ? C_U : min(ph - 1, 2)) * 256 + (ph == 2 ? min(max(rh + min(lane >> 3, 2) - 1, 0), 31) : rh) * 8 + ((lane + nb - rank) & 7)];
        int i = 0, n = ph == 0 || ph == 5 ? NK : 0;
        if (own) { i = 4; if (st) { st--; pp ^= 1; } else st = 4; }
#pragma unroll 1
        while (i < NK) {
            if (n <= i) {
                int it = 0;
#pragma unroll 1
                do {
                    uint32_t v;
                    asm volatile(FLAG_LD " %0, [%1];" : "=r"(v) : "l"(fl) : "memory");
                    n = __reduce_min_sync(~0u, ph == 6 ? 8 * v : v || (own && !(lane & 6)) ? 16 : 2 * (lane & 7));
                    if (++it > SPIN_LIMIT) n = NK;
                } while (n <= i);
                asm volatile("fence.proxy.async.global;" ::: "memory");
            }
            if (own && (i == 5 || i == 6)) mbar_wait_w(bars + 8 * (PB_E + ph + i - 5), 1);
#pragma unroll 1
            for (const int e = own && i < 6 ? i + 1 : n; i < e; i++) {
                const int kb = (i + rot) & km;
                const uint32_t f = bars + 8 * (PB_F + st);
                mbar_wait_w(f + 8 * PB_E, pp);
                e_tma2d_mc(sb + st * 16384 + rank * 8192, ta, kb * amul, arow + (int)((shifts >> ((kb & 12) * 2)) & 7), f);
                if (++st == ST) { st = 0; pp ^= 1; }
            }
        }
    }
}

template <int PH, class F>
__device__ __forceinline__ void post_kb(uint32_t sb, float* acc, Pipe& p, int wg, bool lead, bool first, F mid) {
    constexpr uint64_t DA = PH == 0 ? mkdesc(SB0, 128, 1024, 0) : mkdesc(SB0, 16, 1024, 1);
    constexpr uint64_t DB = mkdesc(SB0 + P_B, P_PL, 1024, 1);
    mbar_wait_w(sb + P_BAR + 8 * PB_F + 8 * p.st, p.ph);
    const uint32_t a = (uint32_t)DA + p.st * 1024 + wg * 512, b = (uint32_t)DB + p.st * 512;
    wg_fence();
#pragma unroll
    for (int k = 0; k < 4; k++) {
        const uint64_t da = (DA & 0xffffffff00000000ull) | (a + k * (PH == 0 ? 16 : 2)), db = (DB & 0xffffffff00000000ull) | (b + k * 128);
        if (PH == 3) wgmma_ss192(acc, da, db, k || !first);
        else wgmma_ss128<PH == 0>(acc, da, db, k || !first);
    }
    wg_commit();
    wg_wait<1>();
    release(p.rel, p.st, !first);
    mid();
    adv(p);
}
__device__ __forceinline__ void post_end(uint32_t sb, Pipe& p, bool lead) {
    wg_wait<0>();
    release(p.rel, p.st, true);
}
template <int PH>
__device__ __forceinline__ void post_mma(uint32_t sb, float* acc, Pipe& p, int wg, bool lead, int nout, int pi, int mb, int nb) {
#pragma unroll 1
    for (int kb = 0; kb < 16; kb++)
        post_kb<PH>(sb, acc, p, wg, lead, kb == 0, [&]() {
            if (nout && kb == 0) wait_smem(sb + P_BAR + 8 * (PB_OUT + wg), nout);
        });
    post_end(sb, p, lead);
}

__global__ void __cluster_dims__(2, 1, 1) __launch_bounds__(384, 1)
k_post(const __grid_constant__ PostMaps mp, const __grid_constant__ PostPtrs pp) {
    extern __shared__ uint8_t smraw[];
    const uint32_t sb = smem_u32(smraw);
    if ((sb & 0x3FFFF) != SB0) __trap();
    const int tid = threadIdx.x, lane = tid & 31;
    const int rank = blockIdx.x & 1;
    uint8_t* arena = pp.arena;
    const uint32_t bars = sb + P_BAR;
    int c = 0;
    unsigned long long v = 0;
    const int wid = __reduce_max_sync(~0u, tid >> 5);
    const bool draw = tid == 352 && rank == 0;
    if (draw) {
        c = min(ldg_rlx1(&g_cls[smid() & 255]), 8u);
        asm volatile("{.reg .b64 a; cvt.u64.u32 a, %%laneid; add.u64 a, a, %1; atom.relaxed.gpu.global.add.u64 %0, [a], %2;}" : "=l"(v) : "l"(&g_pt), "l"(1ull << (7 * c)) : "memory");
    }
    if (wid < 11) {
        asm volatile("{.reg .pred p; elect.sync _|p, 0xffffffff; @p mbarrier.init.shared.b64 [%0], %1; @p prefetch.tensormap [%2]; fence.mbarrier_init.release.cluster;}"
                     ::"r"(bars + 8 * wid), "r"(wid >= PB_E && wid < PB_R ? 4 : 1), "l"(&mp.o + wid) : "memory");
        if (wid == PB_R) { sts4(bars + 8 * PB_OUT, 0, 0, 0, 0); e_expect(bars + 8 * PB_R, 4); }
    }
    __syncwarp();
    asm volatile("barrier.cluster.arrive.relaxed.aligned; barrier.cluster.wait.aligned;" ::: "memory");
    if (draw) {
        int r = (v >> (7 * c)) & 127, role = c * 8 + r;
        if (c == 8 || r >= 8) {
            int n, x, it = 0;
#pragma unroll 1
            do {
                __nanosleep(200);
                v = ldg_u64(&g_pt); n = 0; x = c < 8 ? r - 8 : r;
#pragma unroll 1
                for (int i = 0; i < 63; i += 7) { const int m = v >> i & 127; n += m; if (i < 7 * c) x += max(m - 8, 0); }
            } while (n < gridDim.x / 2 && ++it < SPIN_LIMIT);
            role = -1;
#pragma unroll 1
            for (int i = 0; i < 64; i += 8, v >>= 7) {
                n = v & 127;
                if (x >= 0 && n + x < 8) role = i + n + x;
                x -= max(8 - n, 0);
            }
        }
#pragma unroll
        for (int i = 0; i < 2; i++)
            asm volatile("{.reg .b32 d; mapa.shared::cluster.u32 d, %0, %2; st.async.shared::cluster.mbarrier::complete_tx::bytes.u32 [d+8], %1, [d];}"
                         ::"r"(bars + 8 * PB_R), "r"(role), "r"(i) : "memory");
    }
    __syncwarp();
    mbar_wait_w(bars + 8 * PB_R, 0);
    const int pr = __reduce_max_sync(~0u, (int)lds1(bars + 8 * PB_R + 8));
    if (pr < 0) return;
    const int mb = (pr >> 5) * 8 + (pr & 7), nb = (pr >> 2 & 6) + rank, cta = pr * 2 + rank;
    if (wid >= 8) {
        asm volatile("setmaxnreg.dec.sync.aligned.u32 40;");
        const int w = wid - 8;
        if (w == 0) {
            post_weights(sb, mp, nb, rank);
        } else if (w == 3) {
            asm volatile("griddepcontrol.wait;" ::: "memory");
            post_acts(sb, mp, arena, mb, nb, rank);
        } else {
            const int wg = w - 1, rh = 2 * mb + wg;
            float* rowc = (float*)(smraw + P_ROW) + (wg * 64 + lane * 2) * 8;
            int nout = 0, sig = 0;
#pragma unroll 1
            for (int i = 0; i < 13; i++) {
                const int cnt = (0x4333333392180ull >> (4 * i)) & 15;
                if (cnt < C_S1) {
                    const int ng = cnt == C_U ? 1 : 2, c0 = cnt == C_U ? (i - 5) * 512 + nb * 64 : nb * 128;
                    const bool fast = (cnt == C_Y || cnt == C_X1);
#pragma unroll 1
                    for (int j = 0; j < ng; j++) {
                        const uint32_t st = j ? cnt : cnt ? 1 : 4;
                        const uint32_t src = sb + (fast ? st * 16384 + wg * 8192 : P_OUT + wg * 16384 + ((nout + j) & 1) * 8192);
                        bar_sync(4 + 4 * wg + (sig++ & 3), 160);
                        if (lane == 0) {
                            if (fast) asm volatile("mbarrier.complete_tx.relaxed.cta.shared::cta.b64 [%0], 8192;" ::"r"(bars + 8 * (PB_F + st)) : "memory");
                            asm volatile("cp.async.bulk.tensor.2d.global.shared::cta.bulk_group [%0, {%2, %3}], [%1]; cp.async.bulk.commit_group;"
                                         ::"l"(&mp.y + 2 * cnt), "r"(src), "r"(c0 + j * 64), "r"(rh * 64) : "memory");
                        }
                        __syncwarp();
                    }
                    if (lane == 0) {
                        auto to_peer = [&]() {
                            const uint32_t n = cnt ? 1 : 4;
                            mbar_wait(bars + 8 * (PB_E + (cnt ? 4 : 2)), 0);
#pragma unroll
                            for (int i = 0; i < 2; i++)
                                asm volatile("{.reg .b32 d, m; mapa.shared::cluster.u32 d, %0, %3; mapa.shared::cluster.u32 m, %2, %3;\n"
                                             " cp.async.bulk.shared::cluster.shared::cta.mbarrier::complete_tx::bytes [d], [%1], 8192, [m];}"
                                             ::"r"(sb + (cnt + 1 + i) * 16384 + wg * 8192), "r"(sb + (i ? cnt : n) * 16384 + wg * 8192), "r"(bars + 8 * (PB_F + cnt + 1 + i)), "r"(rank ^ 1) : "memory");
                        };
                        asm volatile("cp.async.bulk.wait_group 0; fence.proxy.async.global;" ::: "memory");
                        asm volatile("st.release.cta.shared.u32 [%0], %1;" ::"r"(bars + 8 * (PB_OUT + wg)), "r"(nout + ng) : "memory");
                        if (i < 12) asm volatile(FLAG_ST " [%0], %1;" ::"l"(&g_pflag[cnt * 256 + rh * 8 + nb]), "r"(max(i - 4, 1)) : "memory");
                        if (fast) to_peer();
                    }
                    nout += ng;
                    __syncwarp();
                    continue;
                }
                bar_sync(4 + 4 * wg + (sig++ & 3), 160);
                uint32_t* c = &g_pcnt[(cnt - C_S1) * 256 + rh * 8];
                if (lane == 0) signal_count(c);
                __syncwarp();
                wait_count_w(c, 8);
                const float4* sp = (const float4*)g_st + rh * 32 + lane;
                float4 u[3] = {__ldcg(sp + (cnt == C_S1 ? 0 : 3) * (S_ / 2)), __ldcg(sp + S_ / 2), __ldcg(sp + S_)};
#pragma unroll 1
                for (int h = 0; h < 2; h++) {
                    const float id = 1.0f / DM;
                    const float m = u[0].x * id, var = fmaxf(u[0].y * id - m * m, 0.f) + 1e-5f, r = rsqrtf(var);
                    float sc = r, m2 = 0.f;
                    if (cnt == C_S1) {
                        m2 = r * (u[1].x * id - m * g_cst[0]) + g_cst[3];
                        const float e2 = r * r * (u[2].x * id - 2.0f * m * u[1].y * id + m * m * g_cst[1]) + 2.0f * r * (u[2].y * id - m * g_cst[2]) + g_cst[4];
                        sc = r * rsqrtf(fmaxf(e2 - m2 * m2, 0.f) + 1e-5f);
                    }
                    const GeluK k = gelu_k(sc);
                    *(float4*)(rowc + h * 8) = make_float4(k.k0, k.k1, k.kh, -m);
                    *(float4*)(rowc + h * 8 + 4) = make_float4(var * r, -m2 * var * r, r, -m * r);
#pragma unroll
                    for (int q = 0; q < 3; q++) { u[q].x = u[q].z; u[q].y = u[q].w; }
                }
                bar_arrive(1 + wg, 160);
            }
        }
    } else {
        asm volatile("setmaxnreg.inc.sync.aligned.u32 232;");
        const bf16* xin = pp.x;
        const int wg = wid >> 2, wi = (tid >> 5) & 3, g = lane >> 2, tq = lane & 3;
        const int rh = 2 * mb + wg, row = rh * 64 + wi * 16 + g;
        const bool lead = (tid & 127) == 0;
        uint32_t keep[32];
#pragma unroll
        for (int i = 0; i < 8; i++)
            *(uint4*)(keep + 4 * i) = __ldg((const uint4*)(xin + (size_t)(rh * 64 + wi * 16 + (i & 3) * 4 + (lane >> 3)) * DM + nb * 128 + (i >> 2) * 64 + (lane & 7) * 8));
        asm volatile("griddepcontrol.wait;" ::: "memory");
        if (cta < 64) g_modp[cta * 256 + tid] = 0;
        if (cta == 64 && tid < 130) g_tick[tid] = 0;
        const float* src = wg ? g_vec + nb * 128 + tid - 128 : g_mod + 2 * DM + nb * 128 + tid;
        const float* c3 = &g_vec[3 * DM + (tid >> 6) * 512 + nb * 64 + (tid & 63)];
        const float cv[6] = {__ldcg(src), __ldcg(src + (wg ? 1 : 2) * DM), __ldcg(src + (wg ? 2 : 1) * DM), __ldcg(src + 3 * DM), __ldcg(c3), __ldcg(c3 + (tid < 192 ? 2048 : 0))};
        uint32_t vec = sb + P_VEC + tq * 8;
        const uint32_t stw = sb + (wi * 16 + ((lane >> 3) & 1) * 8 + (lane & 7)) * 128 + (((lane >> 4) ^ (lane & 7)) << 4);
        int sig = 0;
        auto signal = [&]() { bar_arrive(4 + 4 * wg + (sig++ & 3), 160); };
        auto put64 = [&](uint32_t o, const float* v) {
#pragma unroll
            for (int jj = 0; jj < 4; jj++, v += 8) stsm4((stw + o) ^ (jj << 5), pack2(v[0], v[1]), pack2(v[2], v[3]), pack2(v[4], v[5]), pack2(v[6], v[7]));
            fence_async_smem();
            signal();
        };
        auto slot = [&](int n) {
            mbar_wait_w(bars + 8 * (PB_E + n % 5), ((n / 5) & 1) ^ 1);
            return (n % 5) * 16384 + wg * 8192;
        };
        const uint32_t rowc = sb + P_ROW + (wg * 64 + wi * 16 + g) * 32, o128 = P_OUT + wg * 16384;
        Pipe pa = {0, 0, 0};
        asm("mapa.shared::cluster.u32 %0, %1, %2;" : "=r"(pa.rel) : "r"(bars + 8 * PB_E), "r"(tid & 1));
        if (tid & 126) pa.rel = 0;
#define KEEP(jn, e) (((e) & 1) ? bfhi(keep[2 * (jn) + ((e) >> 1)]) : bflo(keep[2 * (jn) + ((e) >> 1)]))
        float mu1[2], r1[2];
        {
            float acc[64];
#pragma unroll 1
            for (int kb = 0; kb < 64; kb++) {
                post_kb<0>(sb, acc, pa, wg, lead, kb == 0, []() {});
                if (kb == 24) bar_sync(3, 256);
                if (kb != 8 + 8 * wg) continue;
                float* sv = (float*)(smraw + P_VEC) + tid;
                const uint32_t xo = sb + o128 + wi * 2048 + (lane >> 3) * 128;
#pragma unroll
                for (int i = 0; i < 8; i++) sts4(xo + (i >> 2) * 8192 + (i & 3) * 512 + (((lane & 7) ^ ((i & 1) * 4 + (lane >> 3))) << 4), keep[4 * i], keep[4 * i + 1], keep[4 * i + 2], keep[4 * i + 3]);
                __syncwarp();
#pragma unroll
                for (int jj = 0; jj < 8; jj++) ldsm4(keep + jj * 4, (stw + o128 + (jj >> 2) * 8192) ^ ((jj & 3) << 5));
                sv[wg * 384] = cv[0]; sv[wg * 384 + 128] = cv[1] + (wg ? 0.0f : 1.0f); sv[wg * 384 + 256] = cv[2];
                if (!wg) sv[384] = cv[3];
                sv[V_C3 * 128] = cv[4]; sv[V_C3 * 128 + 256] = cv[5];
            }
            post_end(sb, pa, lead);
            asm volatile("" : "+r"(vec) :: "memory");
            float st[2][6];
#pragma unroll
            for (int q = 0; q < 6; q++) st[0][q] = st[1][q] = 0.f;
#pragma unroll
            for (int jn = 0; jn < 16; jn++) {
                const float2 ga = ldsv(vec + V_GA * 512 + jn * 32), a = ldsv(vec + V_A * 512 + jn * 32);
                float xa[4];
#pragma unroll
                for (int e = 0; e < 4; e++) {
                    xa[e] = fmaf((e & 1) ? ga.y : ga.x, acc[4 * jn + e], KEEP(jn, e));
                    st[e >> 1][0] += xa[e]; st[e >> 1][1] = fmaf(xa[e], xa[e], st[e >> 1][1]);
                    acc[4 * jn + e] = ((e & 1) ? a.y : a.x) * xa[e];
                }
                keep[2 * jn] = pack2(xa[0], xa[1]); keep[2 * jn + 1] = pack2(xa[2], xa[3]);
                if ((jn & 7) == 7) put64(slot(64 + (jn >> 3)), acc + 4 * jn - 28);
            }
#pragma unroll
            for (int jn = 0; jn < 16; jn++) {
                const float2 a = ldsv(vec + V_A * 512 + jn * 32), b = ldsv(vec + V_B * 512 + jn * 32);
#pragma unroll
                for (int e = 0; e < 4; e++) {
                    const float y = acc[4 * jn + e], aa = (e & 1) ? a.y : a.x, bb = (e & 1) ? b.y : b.x;
                    float* s = st[e >> 1];
                    s[2] += y; s[3] = fmaf(aa, y, s[3]); s[4] = fmaf(y, y, s[4]); s[5] = fmaf(bb, y, s[5]);
                }
            }
#pragma unroll
            for (int h = 0; h < 2; h++)
#pragma unroll
                for (int q = 0; q < 6; q++) { st[h][q] += __shfl_xor_sync(~0u, st[h][q], 1); st[h][q] += __shfl_xor_sync(~0u, st[h][q], 2); }
            if (tq < 3) {
#pragma unroll
                for (int h = 0; h < 2; h++)
                    red2(g_st + (tq * S_ + row + h * 8) * 2, tq == 0 ? st[h][0] : tq == 1 ? st[h][2] : st[h][4], tq == 0 ? st[h][1] : tq == 1 ? st[h][3] : st[h][5]);
            }
            signal();
        }
        {
            float acc[64];
            post_mma<1>(sb, acc, pa, wg, lead, 2, 4, mb, nb);
            float c1[2], c2[2], c3[2];
            GeluK gk[2];
            bar_sync(1 + wg, 160);
#pragma unroll
            for (int h = 0; h < 2; h++) {
                const float4 a = lds4f(rowc + h * 256), b = lds4f(rowc + h * 256 + 16);
                gk[h] = {a.x, a.y, a.z}; c1[h] = a.w; c2[h] = b.x; c3[h] = b.y; mu1[h] = b.w; r1[h] = b.z;
            }
#pragma unroll
            for (int jn = 0; jn < 16; jn++) {
                const float2 va = ldsv(vec + V_VA * 512 + jn * 32), vb = ldsv(vec + V_VB * 512 + jn * 32), vc = ldsv(vec + V_VC * 512 + jn * 32);
#pragma unroll
                for (int e = 0; e < 4; e++) {
                    const int h = e >> 1;
                    const float t = fmaf(c1[h], (e & 1) ? va.y : va.x, fmaf(c2[h], (e & 1) ? vb.y : vb.x, fmaf(c3[h], (e & 1) ? vc.y : vc.x, acc[4 * jn + e])));
                    acc[4 * jn + e] = gelu_s(t, gk[h]);
                }
                if ((jn & 7) == 7) put64(o128 + (jn >> 3) * 8192, acc + 4 * jn - 28);
            }
        }
        {
            float acc[64];
            post_mma<2>(sb, acc, pa, wg, lead, 0, 7, mb, nb);
#pragma unroll
            for (int jn = 0; jn < 16; jn++) {
                const float2 a = ldsv(vec + V_A * 512 + jn * 32), b = ldsv(vec + V_B * 512 + jn * 32);
#pragma unroll
                for (int e = 0; e < 4; e++) {
                    const int h = e >> 1;
                    acc[4 * jn + e] += fmaf(fmaf(KEEP(jn, e), r1[h], mu1[h]), (e & 1) ? a.y : a.x, (e & 1) ? b.y : b.x);
                }
                if ((jn & 7) == 7) put64(slot(96 + (jn >> 3)), acc + 4 * jn - 28);
            }
            BLOCK_FENCE
#pragma unroll
            for (int i = 0; i < 64; i += 16) asm volatile("" : F16(acc, i));
            float st[2][2] = {{0.f, 0.f}, {0.f, 0.f}};
#pragma unroll
            for (int jn = 0; jn < 16; jn++) {
                const float2 gb = ldsv(vec + V_GB * 512 + jn * 32);
                float z[4];
#pragma unroll
                for (int e = 0; e < 4; e++) {
                    const float x1 = acc[4 * jn + e];
                    st[e >> 1][0] += x1; st[e >> 1][1] = fmaf(x1, x1, st[e >> 1][1]);
                    z[e] = fmaf((e & 1) ? gb.y : gb.x, x1, KEEP(jn, e));
                }
                keep[2 * jn] = pack2(z[0], z[1]); keep[2 * jn + 1] = pack2(z[2], z[3]);
            }
#pragma unroll
            for (int h = 0; h < 2; h++)
#pragma unroll
                for (int q = 0; q < 2; q++) { st[h][q] += __shfl_xor_sync(~0u, st[h][q], 1); st[h][q] += __shfl_xor_sync(~0u, st[h][q], 2); }
            if (tq < 2) red2(g_st + (3 * S_ + row + tq * 8) * 2, tq ? st[1][0] : st[0][0], tq ? st[1][1] : st[0][1]);
            signal();
        }
        {
            float old[96], acc[64];
            post_mma<3>(sb, old, pa, wg, lead, 6, 10, mb, nb);
#pragma unroll
            for (int i = 0; i < 96; i += 16) asm volatile("" : F16(old, i));
            uint32_t v3 = vec + V_C3 * 512;
            bar_sync(1 + wg, 160);
            const float4 rc[2] = {lds4f(rowc), lds4f(rowc + 256)};
            float2 vc[2] = {lds2f(v3), lds2f(v3 + 32)};
            v3 += wg ? 0 : 64;
            bar_sync(3, 256);
#pragma unroll 1
            for (int blk = 0; blk < 11; blk++) {
                const uint32_t o = stw + o128 + (blk & 1) * 8192;
#pragma unroll
                for (int q = 0; q < 4; q++) {
#pragma unroll 1
                    for (int rep = 0; rep < 2; rep++) {
                        post_kb<1>(sb, acc, pa, wg, lead, q == 0 && rep == 0 && blk < 6 && !(blk & 1), []() {});
                        if (rep != wg) {
                            vc[0] = lds2f(v3 + q * 64); vc[1] = lds2f(v3 + q * 64 + 32);
                            if (q == 2) wait_smem(bars + 8 * (PB_OUT + wg), 6 + min(blk, 7));
                            if ((q == 0 && wg && (uint32_t)(blk - 1) < 7) || (q == 3 && !wg && blk < 7)) { fence_async_smem(); signal(); }
                        } else if (blk < 7) {
                            asm volatile("" : F4(old, 8 * q), F4(old, 8 * q + 4));
                            float t[8];
#pragma unroll
                            for (int i = 0; i < 8; i++) {
                                const float4& c = rc[(i >> 1) & 1];
                                t[i] = gelu_s(fmaf(c.w, (i & 1) ? vc[i >> 2].y : vc[i >> 2].x, old[8 * q + i]), GeluK{c.x, c.y, c.z});
                                old[8 * q + i] = old[32 + 8 * q + i];
                                old[32 + 8 * q + i] = old[64 + 8 * q + i];
                            }
                            uint32_t r[4] = {pack2(t[0], t[1]), pack2(t[2], t[3]), pack2(t[4], t[5]), pack2(t[6], t[7])};
                            asm volatile("pmevent 0;" : F4(old, 8 * q), F4(old, 8 * q + 4), F4(old, 8 * q + 32), F4(old, 8 * q + 36), "+r"(r[0]), "+r"(r[1]), "+r"(r[2]), "+r"(r[3]));
                            stsm4(o ^ (q << 5), r[0], r[1], r[2], r[3]);
                        }
                    }
                }
                v3 += 256;
                if (blk != 1 && blk != 3) continue;
                post_end(sb, pa, lead);
                asm volatile("" : F16(acc, 0), F4(acc, 16), F4(acc, 20), F4(acc, 24));
                asm volatile("" : F16(acc, 28), F4(acc, 44), F4(acc, 48), F4(acc, 52));
                asm volatile("" : F4(acc, 56), F4(acc, 60));
#pragma unroll
                for (int i = 0; i < 64; i++) old[32 + i] = acc[i];
            }
            post_end(sb, pa, lead);
#pragma unroll
            for (int jn = 0; jn < 16; jn++) {
                const float2 gb = ldsv(vec + V_GB * 512 + jn * 32);
#pragma unroll
                for (int e = 0; e < 4; e++) acc[4 * jn + e] = fmaf((e & 1) ? gb.y : gb.x, acc[4 * jn + e], KEEP(jn, e));
                if ((jn & 7) == 7) put64(o128 + ((jn >> 3) ^ 1) * 8192, acc + 4 * jn - 28);
            }
        }
    }
}

typedef CUresult (*EncFn)(CUtensorMap*, CUtensorMapDataType, cuuint32_t, void*, const cuuint64_t*, const cuuint64_t*, const cuuint32_t*,
                          const cuuint32_t*, CUtensorMapInterleave, CUtensorMapSwizzle, CUtensorMapL2promotion, CUtensorMapFloatOOBfill);

static CUtensorMap make_map(EncFn enc, const void* p, uint64_t inner, uint64_t outer, uint32_t bi = 64) {
    CUtensorMap m;
    cuuint64_t dims[2] = {inner, outer};
    cuuint64_t str[1] = {inner * 2};
    cuuint32_t box[2] = {bi, bi == 64 ? 64u : 16u};
    cuuint32_t es[2] = {1, 1};
    enc(&m, CU_TENSOR_MAP_DATA_TYPE_BFLOAT16, 2, (void*)p, dims, str, box, es, CU_TENSOR_MAP_INTERLEAVE_NONE,
        bi == 64 ? CU_TENSOR_MAP_SWIZZLE_128B : CU_TENSOR_MAP_SWIZZLE_NONE, CU_TENSOR_MAP_L2_PROMOTION_L2_256B, CU_TENSOR_MAP_FLOAT_OOB_FILL_NONE);
    return m;
}
static CUtensorMap make_map_o(EncFn enc, const void* p) {
    CUtensorMap m;
    cuuint64_t dims[2] = {16384, 256};
    cuuint64_t str[1] = {65536};
    cuuint32_t box[2] = {256, 8};
    cuuint32_t es[2] = {1, 1};
    enc(&m, CU_TENSOR_MAP_DATA_TYPE_UINT32, 2, (void*)p, dims, str, box, es, CU_TENSOR_MAP_INTERLEAVE_NONE, CU_TENSOR_MAP_SWIZZLE_NONE,
        CU_TENSOR_MAP_L2_PROMOTION_L2_256B, CU_TENSOR_MAP_FLOAT_OOB_FILL_NONE);
    return m;
}
template <class T> static T* sym(T& s) { void* p = nullptr; cudaGetSymbolAddress(&p, s); return (T*)p; }
static uint8_t* arena_base() { return (uint8_t*)(((uintptr_t)sym(g_arena) + (2u << 20) - 1) & ~(uintptr_t)((2u << 20) - 1)); }

static const Delays h_dly = {D_NEAR, D_FAR, D_X2, D_V, D_W2, D_PA, D_MORE2, D_MORE};
extern "C" void kernel_launch(void* const* d_in, const int* in_sizes, int n_in, void* d_out, int out_size) {
    const bf16* x = (const bf16*)d_in[0];
    const bf16* mem0 = (const bf16*)d_in[1];
    const bf16 *Wq = (const bf16*)d_in[2], *Wk = (const bf16*)d_in[3], *Wv = (const bf16*)d_in[4], *Wo = (const bf16*)d_in[5];
    const bf16 *w1 = (const bf16*)d_in[8], *w2 = (const bf16*)d_in[9], *w3 = (const bf16*)d_in[10], *w4 = (const bf16*)d_in[11];
    const bf16 *c = (const bf16*)d_in[12], *wmod = (const bf16*)d_in[13];
    bf16* out = (bf16*)d_out;

    EncFn enc = nullptr;
    cudaDriverEntryPointQueryResult qr;
    cudaGetDriverEntryPoint("cuTensorMapEncodeTiled", (void**)&enc, cudaEnableDefault, &qr);
    CUtensorMap tWq = make_map(enc, Wq, NH * DH, DM), tWk = make_map(enc, Wk, NH * DH, DM), tWv = make_map(enc, Wv, NH * DH, DM);
    uint8_t* arena = arena_base();
    PostMaps mp;
    mp.o = make_map_o(enc, g_O); mp.wo = make_map(enc, Wo, DM, NH * DH);
    mp.y = make_map(enc, sym(g_y), DM, S_); mp.w1 = make_map(enc, w1, DM, DM);
    mp.g = make_map(enc, sym(g_g), DM, S_); mp.w2 = make_map(enc, w2, DM, DM);
    mp.x1 = make_map(enc, sym(g_x1), DM, S_); mp.w3 = make_map(enc, w3, FF, DM);
    mp.u = make_map(enc, sym(g_u), FF, S_); mp.w4 = make_map(enc, w4, DM, FF);
    mp.out = make_map(enc, out, DM, S_);
    cudaFuncSetAttribute(k_rec, cudaFuncAttributeMaxDynamicSharedMemorySize, SM_REC_TOTAL + 2048);
    cudaFuncSetAttribute(k_post, cudaFuncAttributeMaxDynamicSharedMemorySize, P_SMEM);

    const PostPtrs pp = {x, arena};
    const RecPtrs rp = {x, mem0, c, wmod, w1, w3, arena, 0u, w2, w4, Wo, h_dly};
    const RecMaps rm = {tWq, tWk, tWv, mp.wo, make_map(enc, wmod, 6 * DM, DM, 256), make_map(enc, w3, FF, DM, 256), make_map(enc, w1, DM, DM, 256)};
    k_rec<<<132, 384, SM_REC_TOTAL + 2048>>>(rm, rp);
    cudaLaunchConfig_t cfg = {};
    cfg.gridDim = dim3(132); cfg.blockDim = dim3(384); cfg.dynamicSmemBytes = P_SMEM; cfg.stream = cudaStreamPerThread;
    cudaLaunchAttribute at[1];
    at[0].id = cudaLaunchAttributeProgrammaticStreamSerialization; at[0].val.programmaticStreamSerializationAllowed = PDL;
    cfg.attrs = at; cfg.numAttrs = 1;
    cudaLaunchKernelEx(&cfg, k_post, mp, pp);
}
```
